```python
import torch

def _softmax(x, axis=-1):
    return torch.softmax(x, dim=axis)
def _gelu(x):
    return torch.nn.functional.gelu(x, approximate="tanh")
def _silu(x):
    return torch.nn.functional.silu(x)
def _sigmoid(x):
    return torch.sigmoid(x)
def _layernorm(x, axis=-1, eps=1e-5):
    m = x.mean(dim=axis, keepdim=True)
    v = x.var(dim=axis, keepdim=True, unbiased=False)
    return (x - m) / torch.sqrt(v + eps)
def _scatter_add(tgt, idx, src, axis=0):
    return tgt.clone().index_add_(axis, idx, src)
def _segment_sum(src, seg, n):
    out = torch.zeros((n,) + src.shape[1:], dtype=src.dtype)
    return out.index_add_(0, seg, src)
def _pad(x, pw):
    flat = tuple(v for pair in reversed(pw) for v in pair)
    return torch.nn.functional.pad(x, flat)

kernel_name = 'sequential_preLN__sliding_local_dilated__moe_arch_mod__prompt'

def setup_inputs():

    _w = (lambda a: (lambda t: t.to(torch.bfloat16) if t.is_floating_point() else t)(torch.as_tensor(a)))
    def _A_setup():
        B, S, D = 1, 2048, 640
        return {
            "x": _w((lambda *s: torch.randn(*s, dtype=torch.bfloat16) * 0.05)(B, S, D)),
            "wqkv": _w((lambda *s: torch.randn(*s, dtype=torch.bfloat16) * 0.05)(D, 3 * D)),
            "wo": _w((lambda *s: torch.randn(*s, dtype=torch.bfloat16) * 0.05)(D, D)),
        }
    _A_in = _A_setup()

    def _B_setup():
        B, S, D, F, C = 1, 2048, 640, 1536, 1
        return {
            "x": _w((lambda *s: torch.randn(*s, dtype=torch.bfloat16) * 0.05)(B, S, D)),
            "w_r": _w((lambda *s: torch.randn(*s, dtype=torch.bfloat16) * 0.05)(D)),
            "w_gate": _w((lambda *s: torch.randn(*s, dtype=torch.bfloat16) * 0.05)(D, F)),
            "w_up": _w((lambda *s: torch.randn(*s, dtype=torch.bfloat16) * 0.05)(D, F)),
            "w_down": _w((lambda *s: torch.randn(*s, dtype=torch.bfloat16) * 0.05)(F, D)),
        }
    _B_in = _B_setup()

    return {
        "A_x": _A_in["x"],
        "A_wqkv": _A_in["wqkv"],
        "A_wo": _A_in["wo"],
        "B_x": _B_in["x"],
        "B_w_r": _B_in["w_r"],
        "B_w_gate": _B_in["w_gate"],
        "B_w_up": _B_in["w_up"],
        "B_w_down": _B_in["w_down"],
    }

def reference(A_x, A_wqkv, A_wo, B_x, B_w_r, B_w_gate, B_w_up, B_w_down):
    def _A_ref(x, wqkv, wo):
        B, S, D = x.shape
        H = 32; Dh = D // H
        W, dil = 8, 2
        qkv = (lambda x, *d: x.permute(*d))((x @ wqkv).reshape(B, S, 3, H, Dh), 2, 0, 3, 1, 4)
        q, k, v = qkv[0], qkv[1], qkv[2]
        scale = Dh ** -0.5
        pos = torch.arange(S)
        off = torch.arange(W) * dil
        idx = pos[:, None] - off[None, :]
        mask = idx >= 0
        idx_c = torch.where(mask, idx, 0).reshape(-1)
        kg = k[:, :, idx_c, :].reshape(B, H, S, W, Dh)
        vg = v[:, :, idx_c, :].reshape(B, H, S, W, Dh)
        logits = torch.einsum("bhsd,bhswd->bhsw", q, kg) * scale
        logits = torch.where(mask[None, None, :, :], logits, -1e9)
        attn = _softmax(logits, axis=-1)
        o = torch.einsum("bhsw,bhswd->bhsd", attn, vg)
        return (lambda x, *d: x.permute(*d))(o, 0, 2, 1, 3).reshape(B, S, D) @ wo

    def _B_ref(x, w_r, w_gate, w_up, w_down):
        B, S, D = x.shape
        C = 1
        r = x @ w_r
        idx = torch.argsort(-r, axis=-1)[:, :C]
        idx_e = (lambda x, n, axis: torch.repeat_interleave(x, n, dim=axis))(idx.reshape(B, C, 1), D, axis=2)
        x_sel = (lambda x, i, axis: torch.take_along_dim(x, i, dim=axis))(x, idx_e, axis=1)
        g = _silu(x_sel @ w_gate)
        u = x_sel @ w_up
        y = (g * u) @ w_down
        r_sel = _sigmoid((lambda x, i, axis: torch.take_along_dim(x, i, dim=axis))(r, idx, axis=1))
        y = y * r_sel.reshape(B, C, 1)
        b_off = (torch.arange(B) * S).reshape(B, 1)
        flat_idx = (idx + b_off).reshape(B * C)
        zero = (x * 0.0).reshape(B * S, D)
        upd = _scatter_add(zero, flat_idx, y.reshape(B * C, D), axis=0)
        return x + upd.reshape(B, S, D)

    x = A_x
    h = x + _A_ref(_layernorm(x, axis=-1), A_wqkv, A_wo)
    h2 = h + _B_ref(_layernorm(h, axis=-1), B_w_r, B_w_gate, B_w_up, B_w_down)
    return h2
```

```cpp
#include <cuda_runtime.h>
#include <cuda_bf16.h>
#include <cuda.h>
#include <stdint.h>

#define PF0 1
#define PF_NS 160
#define PFX_IT 0
#define PFW_IT 99
#define FENCE_IT 6
#define REG_P 56
#define REG_C 224
#define EXP_H 0
#define F2_IT 7

namespace {

constexpr int SLOT    = 47104;
constexpr int OFF_W1  = 122880;
constexpr int OFF_W2  = 4 * SLOT;
constexpr int OFF_KV  = OFF_W2 + 24576;
constexpr int OFF_CS  = OFF_KV + 15360;
constexpr int OFF_ST  = OFF_CS + 960;
constexpr int OFF_WR  = OFF_ST + 1152;
constexpr int OFF_RED = OFF_CS;
constexpr int OFF_BAR = OFF_WR + 352;
constexpr int SMEM_BYTES = OFF_BAR + 96 + 288;
constexpr uint32_t SENT = 0xFFFFFFFFu;
constexpr int SPIN_MAX = 1 << 20;

struct Glob {
  uint4 cand[128][8][4][5];
  uint2 key[4][128];
  uint32_t act[768];
  uint32_t pad[288];
};
constexpr int GLOB_PER_CTA = sizeof(Glob) / 16 / 120;
static_assert(GLOB_PER_CTA * 120 * 16 == sizeof(Glob), "glob size");
struct Own {
  uint4 halo[2][5][32];
  uint4 st1[16];
  uint2 cs[16];
  uint32_t oflag[32];
  uint4 st2[16];
};
struct Scratch {
  Glob x;
  Own own[128];
  uint4 o[128][8][168];
  uint32_t epoch[128];
};
__device__ __align__(128) Scratch g_scratch;
#define g_x (sc->x)
#define g_own (sc->own)
#define g_o (sc->o)
#define g_epoch (sc->epoch)
#define TS(i)

__device__ __forceinline__ void mbar_init(uint32_t bar, uint32_t cnt) { asm volatile("mbarrier.init.shared::cta.b64 [%0], %1;" :: "r"(bar), "r"(cnt) : "memory"); }
__device__ __forceinline__ void mbar_expect_tx(uint32_t bar, uint32_t bytes) { asm volatile("mbarrier.arrive.expect_tx.shared::cta.b64 _, [%0], %1;" :: "r"(bar), "r"(bytes) : "memory"); }
__device__ __forceinline__ void mbar_arrive(uint32_t bar) { asm volatile("mbarrier.arrive.shared::cta.b64 _, [%0];" :: "r"(bar) : "memory"); }
__device__ __forceinline__ void mbar_arrive_cta(uint32_t bar, uint32_t cta) {
  asm volatile("{\n.reg .b32 ra;\nmapa.shared::cluster.u32 ra, %0, %1;\nmbarrier.arrive.shared::cluster.b64 _, [ra];\n}\n" :: "r"(bar), "r"(cta) : "memory");
}
__device__ __forceinline__ void mbar_wait(uint32_t bar, uint32_t parity) {
  uint32_t ok; int guard = SPIN_MAX;
  do {
    asm volatile("{\n.reg .pred p;\nmbarrier.try_wait.parity.shared::cta.b64 p, [%1], %2;\nselp.u32 %0, 1, 0, p;\n}\n" : "=r"(ok) : "r"(bar), "r"(parity) : "memory");
  } while (!ok && --guard);
}
__device__ __forceinline__ void tma_3d(uint32_t dst, const void* tm, uint32_t bar, int c0, int c1, int c2) {
  asm volatile("cp.async.bulk.tensor.3d.shared::cluster.global.mbarrier::complete_tx::bytes [%0], [%1, {%3, %4, %5}], [%2];" :: "r"(dst), "l"(tm), "r"(bar), "r"(c0), "r"(c1), "r"(c2) : "memory");
}
__device__ __forceinline__ void tma_3d_mc(uint32_t dst, const void* tm, uint32_t bar, int c0, int c1, int c2) {
  asm volatile("cp.async.bulk.tensor.3d.shared::cluster.global.mbarrier::complete_tx::bytes.multicast::cluster [%0], [%1, {%3, %4, %5}], [%2], %6;" :: "r"(dst), "l"(tm), "r"(bar), "r"(c0), "r"(c1), "r"(c2), "h"((uint16_t)3) : "memory");
}
__device__ __forceinline__ void wgmma_fence() { asm volatile("wgmma.fence.sync.aligned;" ::: "memory"); }
__device__ __forceinline__ void wgmma_commit() { asm volatile("wgmma.commit_group.sync.aligned;" ::: "memory"); }
template <int N> __device__ __forceinline__ void wgmma_wait() { asm volatile("wgmma.wait_group.sync.aligned %0;" :: "n"(N) : "memory"); }
__device__ __forceinline__ uint64_t make_desc(uint32_t addr, uint32_t lbo, uint32_t sbo, uint32_t swz) {
  return (uint64_t)(((addr & 0x3FFFF) >> 4) | ((lbo >> 4) << 16)) | ((uint64_t)((sbo >> 4) | (swz << 30)) << 32);
}
__device__ __forceinline__ void bar_sync(int id, int n) { asm volatile("bar.sync %0, %1;" :: "r"(id), "r"(n) : "memory"); }
__device__ __forceinline__ uint4 ld_pkt(const void* p) {
  uint4 v;
  asm volatile("{\n.reg .b128 t;\n.reg .b64 lo, hi;\nld.relaxed.gpu.b128 t, [%4];\nmov.b128 {lo, hi}, t;\nmov.b64 {%0, %1}, lo;\nmov.b64 {%2, %3}, hi;\n}\n"
               : "=r"(v.x), "=r"(v.y), "=r"(v.z), "=r"(v.w) : "l"(p) : "memory");
  return v;
}
__device__ __forceinline__ void st_pkt(void* p, uint32_t a, uint32_t b, uint32_t c, uint32_t d) {
  asm volatile("{\n.reg .b128 t;\n.reg .b64 lo, hi;\nmov.b64 lo, {%1, %2};\nmov.b64 hi, {%3, %4};\nmov.b128 t, {lo, hi};\nst.relaxed.gpu.b128 [%0], t;\n}\n"
               :: "l"(p), "r"(a), "r"(b), "r"(c), "r"(d) : "memory");
}
__device__ __forceinline__ uint4 ldg_pkt(const void* p) {
  uint4 v;
  asm volatile("{\n.reg .b128 t;\n.reg .b64 lo, hi;\nld.relaxed.gpu.global.b128 t, [%4];\nmov.b128 {lo, hi}, t;\nmov.b64 {%0, %1}, lo;\nmov.b64 {%2, %3}, hi;\n}\n"
               : "=r"(v.x), "=r"(v.y), "=r"(v.z), "=r"(v.w) : "l"(p) : "memory");
  return v;
}
__device__ __forceinline__ void stg_pkt(void* p, uint32_t a, uint32_t b, uint32_t c, uint32_t d) {
  asm volatile("{\n.reg .b128 t;\n.reg .b64 lo, hi;\nmov.b64 lo, {%1, %2};\nmov.b64 hi, {%3, %4};\nmov.b128 t, {lo, hi};\nst.relaxed.gpu.global.b128 [%0], t;\n}\n"
               :: "l"(p), "r"(a), "r"(b), "r"(c), "r"(d) : "memory");
}
__device__ __forceinline__ uint32_t ldg_rlx32(const void* p) { uint32_t v; asm volatile("ld.relaxed.gpu.global.u32 %0, [%1];" : "=r"(v) : "l"(p) : "memory"); return v; }
__device__ __forceinline__ void stg_rlx32(void* p, uint32_t v) { asm volatile("st.relaxed.gpu.global.u32 [%0], %1;" :: "l"(p), "r"(v) : "memory"); }
__device__ __forceinline__ void stg_rlx64(void* p, uint32_t a, uint32_t b) { asm volatile("st.relaxed.gpu.global.v2.u32 [%0], {%1, %2};" :: "l"(p), "r"(a), "r"(b) : "memory"); }
__device__ __forceinline__ uint4 ldsm4(uint32_t a) { uint4 v; asm volatile("ldmatrix.sync.aligned.m8n8.x4.shared.b16 {%0, %1, %2, %3}, [%4];" : "=r"(v.x), "=r"(v.y), "=r"(v.z), "=r"(v.w) : "r"(a) : "memory"); return v; }
__device__ __forceinline__ uint4 ldsm4t(uint32_t a) { uint4 v; asm volatile("ldmatrix.sync.aligned.m8n8.x4.trans.shared.b16 {%0, %1, %2, %3}, [%4];" : "=r"(v.x), "=r"(v.y), "=r"(v.z), "=r"(v.w) : "r"(a) : "memory"); return v; }
__device__ __forceinline__ void stsm4(uint32_t a, uint32_t x, uint32_t y, uint32_t z, uint32_t w) { asm volatile("stmatrix.sync.aligned.m8n8.x4.shared.b16 [%0], {%1, %2, %3, %4};" :: "r"(a), "r"(x), "r"(y), "r"(z), "r"(w) : "memory"); }
__device__ __forceinline__ void mma_acc(float (&c)[4], const uint4& a, uint32_t b0, uint32_t b1) {
  asm("mma.sync.aligned.m16n8k16.row.col.f32.bf16.bf16.f32 {%0,%1,%2,%3}, {%4,%5,%6,%7}, {%8,%9}, {%0,%1,%2,%3};"
      : "+f"(c[0]), "+f"(c[1]), "+f"(c[2]), "+f"(c[3]) : "r"(a.x), "r"(a.y), "r"(a.z), "r"(a.w), "r"(b0), "r"(b1));
}
__device__ __forceinline__ uint4 lds128(uint32_t a) { uint4 v; asm volatile("ld.shared.v4.u32 {%0, %1, %2, %3}, [%4];" : "=r"(v.x), "=r"(v.y), "=r"(v.z), "=r"(v.w) : "r"(a) : "memory"); return v; }
__device__ __forceinline__ float2 lds64f(uint32_t a) { float2 v; asm volatile("ld.shared.v2.f32 {%0, %1}, [%2];" : "=f"(v.x), "=f"(v.y) : "r"(a)); return v; }
__device__ __forceinline__ float lds32f(uint32_t a) { float v; asm volatile("ld.shared.f32 %0, [%1];" : "=f"(v) : "r"(a)); return v; }
__device__ __forceinline__ void sts32f(uint32_t a, float v) { asm volatile("st.shared.f32 [%0], %1;" :: "r"(a), "f"(v) : "memory"); }
__device__ __forceinline__ uint32_t pack_bf16(float lo, float hi) { uint32_t r; asm("cvt.rn.bf16x2.f32 %0, %1, %2;" : "=r"(r) : "f"(hi), "f"(lo)); return r; }
__device__ __forceinline__ float bf_lo(uint32_t v) { return __uint_as_float(v << 16); }
__device__ __forceinline__ float bf_hi(uint32_t v) { return __uint_as_float(v & 0xffff0000u); }
__device__ __forceinline__ uint32_t movm(uint32_t a) { uint32_t d; asm("movmatrix.sync.aligned.m8n8.trans.b16 %0, %1;" : "=r"(d) : "r"(a)); return d; }
__device__ __forceinline__ float ex2(float x) { float y; asm("ex2.approx.ftz.f32 %0, %1;" : "=f"(y) : "f"(x)); return y; }
__device__ __forceinline__ float rcp(float x) { float y; asm("rcp.approx.ftz.f32 %0, %1;" : "=f"(y) : "f"(x)); return y; }
__device__ __forceinline__ bool elect() { uint32_t p; asm volatile("{\n.reg .pred q;\nelect.sync _|q, 0xffffffff;\nselp.u32 %0, 1, 0, q;\n}\n" : "=r"(p)); return p; }
__device__ __forceinline__ void pf_l2(const void* p) { asm volatile("prefetch.global.L2 [%0];" :: "l"(p)); }
__device__ __forceinline__ bool anyw(bool p) { return __any_sync(0xffffffffu, p); }
__device__ __forceinline__ float shx(float v, int m) { return __shfl_xor_sync(0xffffffffu, v, m); }
__device__ __forceinline__ void mma_k24(float (&c)[4], uint32_t a0, uint32_t a1, uint32_t a2, uint32_t a3, uint32_t b0, uint32_t b1,
                                        uint32_t e0, uint32_t e1, uint32_t f0) {
  asm("mma.sync.aligned.m16n8k16.row.col.f32.bf16.bf16.f32 {%0,%1,%2,%3}, {%4,%5,%6,%7}, {%8,%9}, {%10,%10,%10,%10};"
      : "=f"(c[0]), "=f"(c[1]), "=f"(c[2]), "=f"(c[3]) : "r"(a0), "r"(a1), "r"(a2), "r"(a3), "r"(b0), "r"(b1), "f"(0.f));
  asm("mma.sync.aligned.m16n8k8.row.col.f32.bf16.bf16.f32 {%0,%1,%2,%3}, {%4,%5}, {%6}, {%0,%1,%2,%3};"
      : "+f"(c[0]), "+f"(c[1]), "+f"(c[2]), "+f"(c[3]) : "r"(e0), "r"(e1), "r"(f0));
}
__device__ __forceinline__ uint32_t ord_key(float r) { uint32_t u = __float_as_uint(r); return u ^ ((uint32_t)((int32_t)u >> 31) | 0x80000000u); }

__device__ __forceinline__ void wgmma_n192lo_ss(float (&d)[120], uint64_t da, uint64_t db, int scale_d) {
  asm volatile("{\n.reg .pred p;\nsetp.ne.b32 p, %98, 0;\n"
    "wgmma.mma_async.sync.aligned.m64n192k16.f32.bf16.bf16 "
    "{%0, %1, %2, %3, %4, %5, %6, %7, %8, %9, %10, %11, %12, %13, %14, %15, "
    "%16, %17, %18, %19, %20, %21, %22, %23, %24, %25, %26, %27, %28, %29, %30, %31, "
    "%32, %33, %34, %35, %36, %37, %38, %39, %40, %41, %42, %43, %44, %45, %46, %47, "
    "%48, %49, %50, %51, %52, %53, %54, %55, %56, %57, %58, %59, %60, %61, %62, %63, "
    "%64, %65, %66, %67, %68, %69, %70, %71, %72, %73, %74, %75, %76, %77, %78, %79, "
    "%80, %81, %82, %83, %84, %85, %86, %87, %88, %89, %90, %91, %92, %93, %94, %95}, "
    "%96, %97, p, 1, 1, 0, 1;\n}\n"
    : "+f"(d[0]), "+f"(d[1]), "+f"(d[2]), "+f"(d[3]), "+f"(d[4]), "+f"(d[5]), "+f"(d[6]), "+f"(d[7]),
      "+f"(d[8]), "+f"(d[9]), "+f"(d[10]), "+f"(d[11]), "+f"(d[12]), "+f"(d[13]), "+f"(d[14]), "+f"(d[15]),
      "+f"(d[16]), "+f"(d[17]), "+f"(d[18]), "+f"(d[19]), "+f"(d[20]), "+f"(d[21]), "+f"(d[22]), "+f"(d[23]),
      "+f"(d[24]), "+f"(d[25]), "+f"(d[26]), "+f"(d[27]), "+f"(d[28]), "+f"(d[29]), "+f"(d[30]), "+f"(d[31]),
      "+f"(d[32]), "+f"(d[33]), "+f"(d[34]), "+f"(d[35]), "+f"(d[36]), "+f"(d[37]), "+f"(d[38]), "+f"(d[39]),
      "+f"(d[40]), "+f"(d[41]), "+f"(d[42]), "+f"(d[43]), "+f"(d[44]), "+f"(d[45]), "+f"(d[46]), "+f"(d[47]),
      "+f"(d[48]), "+f"(d[49]), "+f"(d[50]), "+f"(d[51]), "+f"(d[52]), "+f"(d[53]), "+f"(d[54]), "+f"(d[55]),
      "+f"(d[56]), "+f"(d[57]), "+f"(d[58]), "+f"(d[59]), "+f"(d[60]), "+f"(d[61]), "+f"(d[62]), "+f"(d[63]),
      "+f"(d[64]), "+f"(d[65]), "+f"(d[66]), "+f"(d[67]), "+f"(d[68]), "+f"(d[69]), "+f"(d[70]), "+f"(d[71]),
      "+f"(d[72]), "+f"(d[73]), "+f"(d[74]), "+f"(d[75]), "+f"(d[76]), "+f"(d[77]), "+f"(d[78]), "+f"(d[79]),
      "+f"(d[80]), "+f"(d[81]), "+f"(d[82]), "+f"(d[83]), "+f"(d[84]), "+f"(d[85]), "+f"(d[86]), "+f"(d[87]),
      "+f"(d[88]), "+f"(d[89]), "+f"(d[90]), "+f"(d[91]), "+f"(d[92]), "+f"(d[93]), "+f"(d[94]), "+f"(d[95])
    : "l"(da), "l"(db), "r"(scale_d));
}
__device__ __forceinline__ void wgmma_n48hi_ss(float (&d)[120], uint64_t da, uint64_t db, int scale_d) {
  asm volatile("{\n.reg .pred p;\nsetp.ne.b32 p, %26, 0;\n"
    "wgmma.mma_async.sync.aligned.m64n48k16.f32.bf16.bf16 "
    "{%0, %1, %2, %3, %4, %5, %6, %7, %8, %9, %10, %11, %12, %13, %14, %15, "
    "%16, %17, %18, %19, %20, %21, %22, %23}, "
    "%24, %25, p, 1, 1, 0, 1;\n}\n"
    : "+f"(d[96]), "+f"(d[97]), "+f"(d[98]), "+f"(d[99]), "+f"(d[100]), "+f"(d[101]), "+f"(d[102]), "+f"(d[103]),
      "+f"(d[104]), "+f"(d[105]), "+f"(d[106]), "+f"(d[107]), "+f"(d[108]), "+f"(d[109]), "+f"(d[110]), "+f"(d[111]),
      "+f"(d[112]), "+f"(d[113]), "+f"(d[114]), "+f"(d[115]), "+f"(d[116]), "+f"(d[117]), "+f"(d[118]), "+f"(d[119])
    : "l"(da), "l"(db), "r"(scale_d));
}
__device__ __forceinline__ void wgmma_n80_rs(float (&d)[40], uint32_t a0, uint32_t a1, uint32_t a2, uint32_t a3, uint64_t db, int scale_d) {
  asm volatile("{\n.reg .pred p;\nsetp.ne.b32 p, %45, 0;\n"
    "wgmma.mma_async.sync.aligned.m64n80k16.f32.bf16.bf16 "
    "{%0, %1, %2, %3, %4, %5, %6, %7, %8, %9, %10, %11, %12, %13, %14, %15, "
    "%16, %17, %18, %19, %20, %21, %22, %23, %24, %25, %26, %27, %28, %29, %30, %31, "
    "%32, %33, %34, %35, %36, %37, %38, %39}, "
    "{%40, %41, %42, %43}, %44, p, 1, 1, 1;\n}\n"
    : "+f"(d[0]), "+f"(d[1]), "+f"(d[2]), "+f"(d[3]), "+f"(d[4]), "+f"(d[5]), "+f"(d[6]), "+f"(d[7]),
      "+f"(d[8]), "+f"(d[9]), "+f"(d[10]), "+f"(d[11]), "+f"(d[12]), "+f"(d[13]), "+f"(d[14]), "+f"(d[15]),
      "+f"(d[16]), "+f"(d[17]), "+f"(d[18]), "+f"(d[19]), "+f"(d[20]), "+f"(d[21]), "+f"(d[22]), "+f"(d[23]),
      "+f"(d[24]), "+f"(d[25]), "+f"(d[26]), "+f"(d[27]), "+f"(d[28]), "+f"(d[29]), "+f"(d[30]), "+f"(d[31]),
      "+f"(d[32]), "+f"(d[33]), "+f"(d[34]), "+f"(d[35]), "+f"(d[36]), "+f"(d[37]), "+f"(d[38]), "+f"(d[39])
    : "r"(a0), "r"(a1), "r"(a2), "r"(a3), "l"(db), "r"(scale_d));
}

__device__ __forceinline__ constexpr int QT(int t) { return t < 8 ? t : 16 + t; }
__device__ __forceinline__ constexpr int KT(int t) { return t < 8 ? 8 + t : 18 + t; }
__device__ __forceinline__ constexpr int VT(int t) { return t < 8 ? 16 + t : 20 + t; }

struct Maps { CUtensorMap x, w, wr, wo, wor, gate, up, down; };

__global__ void __cluster_dims__(2, 1, 1) __launch_bounds__(384, 1)
fused_kernel(const __nv_bfloat16* __restrict__ x, const __nv_bfloat16* __restrict__ wqkv,
             const __nv_bfloat16* __restrict__ wo, const __nv_bfloat16* __restrict__ w_r, const __nv_bfloat16* __restrict__ w_gate,
             const __nv_bfloat16* __restrict__ w_up, const __nv_bfloat16* __restrict__ w_down, __nv_bfloat16* __restrict__ out,
             Scratch* __restrict__ sc, const __grid_constant__ Maps tm) {
  extern __shared__ __align__(1024) uint8_t smem[];
  const int tid = threadIdx.x, warp = __shfl_sync(0xffffffffu, tid >> 5, 0), lane = tid & 31, bid = blockIdx.x;
  const uint32_t sb = (uint32_t)__cvta_generic_to_shared(smem);
  const uint32_t bar_full = sb + OFF_BAR, bar_empty = bar_full + 32, bar_aux = bar_full + 64, bar_ffn = bar_full + 72, bar_win = bar_full + 80;
  if (warp < 4 && elect()) {
    mbar_init(bar_full + 8 * (warp ^ 2), 1);
    mbar_init(bar_empty + 8 * warp, 8);
    mbar_init(bar_aux + 8 * warp, warp == 0 ? 64 : 1);
    asm volatile("fence.mbarrier_init.release.cluster;" ::: "memory");
  }
  asm volatile("barrier.cluster.arrive.relaxed.aligned;" ::: "memory");
  if (warp >= 8 && warp < 11 && elect()) asm volatile("prefetch.tensormap [%0];" :: "l"(&tm.x + (warp - 8)) : "memory");
  auto pf_slice = [&](int ks) {
    pf_l2(lane < 16 ? (const char*)x + ((bid * 16 + lane) * 1280 + ks * 128) : (const char*)wqkv + ((bid * 15 + min(lane, 30) - 16) * 128 + ks * 245760));
  };
  if (warp >= 4 && warp < 4 + PF0) {
    if (warp > 4) __nanosleep(300 + (warp - 4) * PF_NS);
    pf_slice(warp - 4);
  }
  const int rank = bid & 1, cl = bid >> 1;
  const int q7 = ((cl - 36) * 37) >> 8;
  const int P = cl < 4 ? 0 : cl < 36 ? (cl - 4) & 7 : cl - 35 - 7 * q7;
  const int g = cl < 4 ? 4 + cl : cl < 36 ? (cl - 4) >> 3 : 4 + q7;
  const int mt = 2 * P + rank, cid = mt * 8 + g;
  const bool ffn1 = g < 3;
  const int fj = ffn1 ? mt * 3 + g : (P * 5 + g - 3) * 2 + rank;
  auto load_w = [&](int it, uint32_t a, uint32_t full) {
    tma_3d_mc(a + 16384 + rank * 16384, &tm.w, full, g * 80, it * 64, rank * 2);
    tma_3d_mc(a + (rank ? 40960 : 24576), rank ? &tm.wr : &tm.w, full, g * 80 + rank * 64, it * 64, 1 - rank);
  };
  if (warp == 0 && elect()) {
    mbar_expect_tx(bar_full + 16, SLOT);
    tma_3d(sb + 2 * SLOT, &tm.x, bar_full + 16, 0, mt * 64, 0);
  }
  asm volatile("barrier.cluster.wait.aligned;" ::: "memory");
  if (warp == 0) {
    if (elect()) load_w(0, sb + 2 * SLOT, bar_full + 16);
    asm volatile("bar.arrive 4, 64;" ::: "memory");
  }

  if (warp >= 8) {
    asm volatile("setmaxnreg.dec.sync.aligned.u32 %0;" :: "n"(REG_P));
#define TS_T 0
    if (warp == 8) {
      TS(8);
      bar_sync(4, 64);
      if (elect()) {
        TS(10);
#pragma unroll 1
        for (int it = 1; it < 14; it++) {
          const int s = (it + 2) & 3;
          const uint32_t full = bar_full + 8 * s, a = sb + s * SLOT;
          if (it >= 4) mbar_wait(bar_empty + 8 * s, ((it >> 2) - 1) & 1);
          if (it < 10) {
            mbar_expect_tx(full, SLOT);
            tma_3d(a, &tm.x, full, it * 64, mt * 64, 0);
            load_w(it, a, full);
            if (it == 1) TS(9);
          } else if (it < 13) {
            const int g0 = 3 * (it - 10), g1 = min(g0 + 3, 8);
            mbar_expect_tx(full, (g1 - g0) * 12800);
#pragma unroll 1
            for (int gp = g0 + ((g0 ^ rank) & 1); gp < g1; gp += 2) {
              tma_3d_mc(sb + gp * 15360, &tm.wo, full, 0, gp * 80, g * 2);
              tma_3d_mc(sb + gp * 15360 + 10240, &tm.wor, full, 512 + g * 16, gp * 80, 0);
            }
          }
          if (it == 4) mbar_expect_tx(bar_ffn, ffn1 ? 81920 : 24576);
          const int j0 = ffn1 ? (it == 9 ? 8 : it == 12 ? 0 : 2) : 2 * (it - F2_IT);
          const int j1 = ffn1 ? (it == 9 ? 10 : it == 13 ? 8 : 2) : (it >= F2_IT && it < F2_IT + 3 ? j0 + 2 : j0);
#pragma unroll 1
          for (int j = j0; j < j1; j++) {
            if (ffn1) tma_3d(sb + OFF_W1 + j * 8192, j < 5 ? &tm.gate : &tm.up, bar_ffn, fj * 32, (j < 5 ? j : j - 5) * 128, 0);
            else tma_3d(sb + OFF_W2 + j * 4096, &tm.down, bar_ffn, fj * 8, j * 256, 0);
          }
        }
        TS(11);
      }
#undef TS_T
#define TS_T 32
    } else if (warp < 11) {
      Own* const own = g_own + cid;
      const int ch = min(mt, 14), r = lane >> 2, l7 = lane & 7, hb = (lane >> 3) & 1, hk = lane >> 4;
      const uint32_t off = warp == 9 ? (g * 16 + (lane & 15)) * 128 + ((hk ^ l7) * 16)
                         : ch < 12   ? 16384 + (ch >> 2) * 8192 + (l7 + hk * 8) * 128 + ((((ch & 3) * 2 + hb) ^ l7) * 16)
                                     : 40960 + (ch - 12) * 2048 + (l7 + hk * 8) * 32 + ((hb ^ (l7 >> 2)) * 16);
      const uint32_t step = ch < 12 ? 2048 : 512;
      float s0 = 0.f, s1 = 0.f, s2 = 0.f, s3 = 0.f, q0 = 0.f, q1 = 0.f, q2 = 0.f, q3 = 0.f;
#pragma unroll 1
      for (int it = 0; it < 10; it++) {
        const int sl = (it + 2) & 3;
        mbar_wait(bar_full + 8 * sl, (it >> 2) & 1);
        TS(13 + it);
        const uint32_t ad = sb + sl * SLOT + off;
        uint4 v[4];
        if (warp == 9) {
#pragma unroll
          for (int i = 0; i < 4; i++) v[i] = ldsm4(ad ^ (i * 32));
        } else {
#pragma unroll
          for (int i = 0; i < 4; i++) v[i] = ldsm4t(ad + i * step);
        }
        if (lane + (int)((v[0].x & v[1].x & v[2].x & v[3].x) == 0x7fc17fc1u && (v[0].x | v[1].x) == 0u) < 2) mbar_arrive_cta(bar_empty + 8 * sl, lane);
#pragma unroll
        for (int i = 0; i < 4; i++) {
          float d;
          d = bf_lo(v[i].x); s0 += d; q0 = fmaf(d, d, q0);  d = bf_hi(v[i].x); s2 += d; q2 = fmaf(d, d, q2);
          d = bf_lo(v[i].y); s1 += d; q1 = fmaf(d, d, q1);  d = bf_hi(v[i].y); s3 += d; q3 = fmaf(d, d, q3);
          d = bf_lo(v[i].z); s0 += d; q0 = fmaf(d, d, q0);  d = bf_hi(v[i].z); s2 += d; q2 = fmaf(d, d, q2);
          d = bf_lo(v[i].w); s1 += d; q1 = fmaf(d, d, q1);  d = bf_hi(v[i].w); s3 += d; q3 = fmaf(d, d, q3);
        }
      }
      TS(0);
      const bool odd = lane & 1;
      s0 += s2; s1 += s3; q0 += q2; q1 += q3;
      float t = (odd ? s1 : s0) + shx(odd ? s0 : s1, 1), sq = (odd ? q1 : q0) + shx(odd ? q0 : q1, 1);
      t += shx(t, 2); sq += shx(sq, 2);
      const int idx = r + (odd ? 8 : 0);
      bar_sync(2, 96);
      const uint32_t tag = __float_as_uint(lds32f(sb + OFF_WR + 324));
      int guard = SPIN_MAX;
      if (warp == 9) {
        t *= (1.f / 640.f);
        if (!(lane & 2)) stg_pkt(&own->st1[idx], __float_as_uint(t), __float_as_uint(rsqrtf(fmaxf(fmaf(-t, t, sq * (1.f / 640.f)), 0.f) + 1e-5f)), tag, 0u);
        TS(1);
        const uint4* sp = &g_own[mt * 8 + hk].st1[lane & 15];
        const uint4* hp = &g_own[max(mt - 1, 0) * 8 + hk * 4 + 3].st1[8 + l7];
        uint4 v[5];
        do {
#pragma unroll
          for (int i = 0; i < 4; i++) v[i] = ldg_pkt(sp + i * (2 * sizeof(Own) / 16));
          v[4] = ldg_pkt(hp);
        } while (anyw(v[0].z != tag || v[1].z != tag || v[2].z != tag || v[3].z != tag || v[4].z != tag) && --guard);
        uint2* const d = (uint2*)(smem + OFF_ST);
#pragma unroll
        for (int i = 0; i < 4; i++) d[8 + lane + 32 * i + 8 * (i >> 1)] = make_uint2(v[i].x, v[i].y);
        d[hk * 72 + l7] = make_uint2(v[4].x, v[4].y);
      } else {
        if (!(lane & 2)) stg_rlx64(&own->cs[idx], __float_as_uint(t), tag);
        const int j = min(lane, 29);
        const uint4* cp = (const uint4*)&g_own[(j >> 1) * 8 + g].cs[(j & 1) * 8];
        uint4 v[4];
        do {
#pragma unroll
          for (int i = 0; i < 4; i++) v[i] = ldg_pkt(cp + i);
        } while (anyw(v[0].y != tag || v[0].w != tag || v[1].y != tag || v[1].w != tag || v[2].y != tag || v[2].w != tag || v[3].y != tag || v[3].w != tag) && --guard);
#pragma unroll
        for (int i = 0; i < 4; i++) ((uint2*)(smem + OFF_CS))[j + 30 * i] = make_uint2(v[i].x, v[i].z);
      }
      mbar_arrive(bar_aux);
      TS(2);
#undef TS_T
#define TS_T 96
    } else {
#pragma unroll 1
      for (int i = lane; i < 960; i += 32) *(uint4*)(smem + OFF_KV + i * 16) = make_uint4(SENT, SENT, SENT, SENT);
      mbar_wait(bar_full + 16, 0);
      TS(4);
      const uint32_t epoch = ldg_rlx32(g_epoch + cid) + 1;
      uint32_t wv[10];
#pragma unroll
      for (int i = 0; i < 10; i++) wv[i] = __ldg((const uint32_t*)w_r + lane + 32 * i);
#pragma unroll 1
      for (int i = lane; i < 368; i += 32) {
        const uint32_t f = i >= 352 ? 0u : SENT;
        ((uint4*)(g_own + cid))[i] = make_uint4(f, f, f, f);
        if (i < GLOB_PER_CTA && mt < 15) ((uint4*)&g_x)[cid * GLOB_PER_CTA + i] = make_uint4(SENT, SENT, SENT, SENT);
      }
      float s = 0.f;
#pragma unroll
      for (int i = 0; i < 10; i++) {
        s += bf_lo(wv[i]) + bf_hi(wv[i]);
        const unsigned u = i < 8 ? lane + 32 * (i - g) : lane + 32 * (i - 7) - g * 8;
        if (i < 8 ? u < 32u : u - 32u < 8u) *(float2*)(smem + OFF_WR + ((u & 3) * 10 + (u >> 2)) * 8) = make_float2(bf_lo(wv[i]), bf_hi(wv[i]));
      }
#pragma unroll
      for (int m = 1; m < 32; m <<= 1) s += shx(s, m);
      *(float2*)(smem + OFF_WR + 320) = make_float2(s, __uint_as_float(epoch * 0x9E3779B8u));
      g_epoch[cid] = epoch;
      TS(3);
      asm volatile("fence.acq_rel.gpu;" ::: "memory");
      TS(5);
      bar_sync(2, 96);
      bar_sync(3, 64);
      const uint4* kp = (const uint4*)g_x.key[cid & 3] + lane;
      uint4 k0, k1;
      int guard = SPIN_MAX;
      do { k0 = ldg_pkt(kp); k1 = ldg_pkt(kp + 32); } while (anyw(k0.y == SENT || k0.w == SENT || k1.y == SENT || k1.w == SENT) && --guard);
      int i0 = 2 * lane, i1 = 2 * lane + 64;
      if (__uint_as_float(k0.z) > __uint_as_float(k0.x)) { k0.x = k0.z; k0.y = k0.w; i0++; }
      if (__uint_as_float(k1.z) > __uint_as_float(k1.x)) { k1.x = k1.z; k1.y = k1.w; i1++; }
      if (__uint_as_float(k1.x) > __uint_as_float(k0.x)) { k0.x = k1.x; k0.y = k1.y; i0 = i1; }
      const uint32_t kx = ord_key(__uint_as_float(k0.x));
      if (lane == __ffs(__ballot_sync(0xffffffffu, kx == __reduce_max_sync(0xffffffffu, kx))) - 1) {
        *(uint4*)(smem + OFF_WR + 336) = make_uint4(i0, k0.y, k0.x, 0);
        mbar_arrive(bar_win);
      }
      TS(7);
    }
#undef TS_T
  } else {
#define TS_T 0
    TS(23);
    asm volatile("setmaxnreg.inc.sync.aligned.u32 %0;" :: "n"(REG_C));
    const int wg = warp >> 2, w4 = warp & 3, r = lane >> 2, c = lane & 3;
    float acc[120];
    float s0 = 0.f, s1 = 0.f, s2 = 0.f, s3 = 0.f, q0 = 0.f, q1 = 0.f, q2 = 0.f, q3 = 0.f;
    uint4 xr[5];
    const uint32_t xa = (warp * 16 + (lane & 15)) * 128, xc = (lane >> 4) ^ (lane & 7);
    TS(0);
#pragma unroll 1
    for (int it = 0; it < 10; it++) {
      const int s = (it + 2) & 3;
      mbar_wait(bar_full + 8 * s, (it >> 2) & 1);
      TS(13 + it);
      const uint32_t a = sb + s * SLOT;
      const uint64_t da = make_desc(a + wg * 8192, 16, 1024, 1), db = make_desc(a + 16384, 8192, 1024, 1), dr = make_desc(a + 40960, 2048, 256, 3);
      wgmma_fence();
#pragma unroll
      for (int kk = 0; kk < 4; kk++) {
        wgmma_n192lo_ss(acc, da + kk * 2, db + kk * 128, (kk | it) != 0);
        wgmma_n48hi_ss(acc, da + kk * 2, dr + kk * 32, (kk | it) != 0);
      }
      wgmma_commit();
      if (it == PFX_IT && warp < 6) pf_slice(4 + warp);
      if (it >= PFW_IT && it < PFW_IT + 4) {
        const int n = it == PFW_IT + 1 ? 50 : 120;
        const char* b = (const char*)(it == PFW_IT ? w_down : it == PFW_IT + 1 ? wo : it == PFW_IT + 2 ? w_up : w_gate);
        if (tid < n) pf_l2(b + (bid * n + tid) * 128);
      }
      if (it == g) {
#pragma unroll
        for (int j = 0; j < 4; j++) xr[j] = ldsm4(a + xa + ((xc ^ (2 * j)) * 16));
      }
      if (it == 8 + (g >> 2)) xr[4] = ldsm4(a + xa + ((xc ^ (2 * (g & 3))) * 16));
      if (it > 0) {
        wgmma_wait<1>();
        if ((tid & 127) < 2) mbar_arrive_cta(bar_empty + 8 * ((it + 1) & 3), tid & 1);
      }
    }
    wgmma_wait<0>();
#pragma unroll
    for (int i = 0; i < 120; i++) asm volatile("" : "+f"(acc[i]) :: "memory");
    if ((tid & 127) < 2) mbar_arrive_cta(bar_empty + 24, tid & 1);
    if (s0 + s1 + s2 + s3 + q0 + q1 + q2 + q3 == 123.4567f) sts32f(sb + OFF_BAR + 96, 1.f);
    TS(2);
    mbar_wait(bar_aux, 0);
    TS(3);
    const uint32_t stb = sb + OFF_ST + (wg * 72 + 16 * w4) * 8;
    const float2 slo = lds64f(stb + (8 + r) * 8), shi = lds64f(stb + (16 + r) * 8);
    uint32_t Qlo[10], Qhi[10], Klo[10], Khi[10], Vlo[10], Vhi[10];
    {
      float cs[60];
#pragma unroll
      for (int j = 0; j < 15; j++) {
        const uint4 v = lds128(sb + OFF_CS + c * 240 + j * 16);
        cs[4 * j] = __uint_as_float(v.x); cs[4 * j + 1] = __uint_as_float(v.y); cs[4 * j + 2] = __uint_as_float(v.z); cs[4 * j + 3] = __uint_as_float(v.w);
      }
      const float ml = -slo.x, mh = -shi.x;
#pragma unroll
      for (int t = 0; t < 10; t++) {
        const int k = KT(t), v = VT(t);
        Khi[t] = pack_bf16(fmaf(mh, cs[2 * k], acc[4 * k + 2]), fmaf(mh, cs[2 * k + 1], acc[4 * k + 3]));
        Vhi[t] = movm(pack_bf16(fmaf(mh, cs[2 * v], acc[4 * v + 2]) * shi.y, fmaf(mh, cs[2 * v + 1], acc[4 * v + 3]) * shi.y));
      }
      {
        uint4* d = w4 < 3 ? (uint4*)(smem + OFF_KV + (wg * 3 + w4) * 2560) + lane : &g_own[cid].halo[wg][0][lane];
        st_pkt(d, Khi[0], Khi[1], Khi[2], Khi[3]);
        st_pkt(d + 32, Khi[4], Khi[5], Khi[6], Khi[7]);
        st_pkt(d + 64, Khi[8], Khi[9], Vhi[0], Vhi[1]);
        st_pkt(d + 96, Vhi[2], Vhi[3], Vhi[4], Vhi[5]);
        st_pkt(d + 128, Vhi[6], Vhi[7], Vhi[8], Vhi[9]);
      }
#pragma unroll
      for (int t = 0; t < 10; t++) {
        const int q = QT(t), k = KT(t), v = VT(t);
        Klo[t] = pack_bf16(fmaf(ml, cs[2 * k], acc[4 * k]), fmaf(ml, cs[2 * k + 1], acc[4 * k + 1]));
        Vlo[t] = movm(pack_bf16(fmaf(ml, cs[2 * v], acc[4 * v]) * slo.y, fmaf(ml, cs[2 * v + 1], acc[4 * v + 1]) * slo.y));
        Qlo[t] = pack_bf16(fmaf(ml, cs[2 * q], acc[4 * q]), fmaf(ml, cs[2 * q + 1], acc[4 * q + 1]));
        Qhi[t] = pack_bf16(fmaf(mh, cs[2 * q], acc[4 * q + 2]), fmaf(mh, cs[2 * q + 1], acc[4 * q + 3]));
      }
    }
    const bool first = (mt == 0) && (w4 == 0);
    uint4 pv[5];
#pragma unroll
    for (int j = 0; j < 5; j++) pv[j] = make_uint4(0, 0, 0, 0);
    if (!first) {
      const uint4* s = w4 > 0 ? (const uint4*)(smem + OFF_KV + (wg * 3 + w4 - 1) * 2560) + lane : &g_own[cid - 8].halo[wg][0][lane];
      int guard = SPIN_MAX;
      do {
#pragma unroll
        for (int j = 0; j < 5; j++) pv[j] = ld_pkt(s + 32 * j);
      } while (anyw(pv[0].x == SENT || pv[1].x == SENT || pv[2].x == SENT || pv[3].x == SENT || pv[4].x == SENT) && --guard);
    }
    TS(4);
    const uint32_t Kp[10] = {pv[0].x, pv[0].y, pv[0].z, pv[0].w, pv[1].x, pv[1].y, pv[1].z, pv[1].w, pv[2].x, pv[2].y};
    const uint32_t Vp[10] = {pv[2].z, pv[2].w, pv[3].x, pv[3].y, pv[3].z, pv[3].w, pv[4].x, pv[4].y, pv[4].z, pv[4].w};
    const bool in0 = 2 * c <= r, in1 = 2 * c + 1 <= r;
    const uint32_t mL = (in0 ? 0xffffu : 0u) | (in1 ? 0xffff0000u : 0u);
    const float qs = 0.22360679774997896f * 1.4426950408889634f;
    const uint32_t kb0 = stb + (2 * c + (in0 ? 8 : 0)) * 8 + 4, kb1 = stb + (2 * c + 1 + (in1 ? 8 : 0)) * 8 + 4;
    const float scl0 = lds32f(kb0) * slo.y * qs, scl1 = lds32f(kb1) * slo.y * qs;
    const float sch0 = lds32f(kb0 + 64) * shi.y * qs, sch1 = lds32f(kb1 + 64) * shi.y * qs;
    const float bias0 = (first && !in0) ? -INFINITY : 0.f, bias1 = (first && !in1) ? -INFINITY : 0.f;
    const bool cA = c < 2, nA = r < 4;
    const uint32_t ONES = 0x3f803f80u;
    uint32_t of[20];
#pragma unroll
    for (int hp = 0; hp < 2; hp++) {
      float o[6][4];
#pragma unroll
      for (int hh = 0; hh < 2; hh++) {
        const int ta = 5 * hp + 3 * hh, ts = 5 * hp + 2;
        const bool mine = hh == 0 ? cA : !cA;
        const uint32_t e0 = mine ? Qlo[ts] : 0u, e1 = mine ? Qhi[ts] : 0u;
        float sp[4], sl[4], sh[4];
        mma_k24(sp, Qlo[ta], Qhi[ta], Qlo[ta + 1], Qhi[ta + 1], Kp[ta], Kp[ta + 1], e0, e1, Kp[ts]);
        mma_k24(sl, Qlo[ta], Qhi[ta], Qlo[ta + 1], Qhi[ta + 1], Klo[ta], Klo[ta + 1], e0, e1, Klo[ts]);
        mma_k24(sh, Qlo[ta], Qhi[ta], Qlo[ta + 1], Qhi[ta + 1], Khi[ta], Khi[ta + 1], e0, e1, Khi[ts]);
        const float tl0 = fmaf(in0 ? sl[0] : sp[0], scl0, bias0), tl1 = fmaf(in1 ? sl[1] : sp[1], scl1, bias1);
        const float th0 = (in0 ? sh[2] : sl[2]) * sch0, th1 = (in1 ? sh[3] : sl[3]) * sch1;
        float ml = fmaxf(tl0, tl1), mh = fmaxf(th0, th1);
        ml = fmaxf(ml, shx(ml, 1)); mh = fmaxf(mh, shx(mh, 1));
        ml = fmaxf(ml, shx(ml, 2)); mh = fmaxf(mh, shx(mh, 2));
        const uint32_t Pl = pack_bf16(ex2(tl0 - ml), ex2(tl1 - ml)), Ph = pack_bf16(ex2(th0 - mh), ex2(th1 - mh));
        const uint32_t a0 = Pl & ~mL, a2 = Pl & mL, a3 = Ph & ~mL, a5 = Ph & mL;
        const bool vm = hh == 0 ? nA : !nA;
        mma_k24(o[3 * hh], a0, 0u, a2, a3, Vp[ta], Vlo[ta], 0u, a5, Vhi[ta]);
        mma_k24(o[3 * hh + 1], a0, 0u, a2, a3, Vp[ta + 1], Vlo[ta + 1], 0u, a5, Vhi[ta + 1]);
        mma_k24(o[3 * hh + 2], a0, 0u, a2, a3, vm ? Vp[ts] : ONES, vm ? Vlo[ts] : ONES, 0u, a5, vm ? Vhi[ts] : ONES);
      }
      const float il = rcp(cA ? o[5][0] : o[2][0]), ih = rcp(cA ? o[5][2] : o[2][2]);
      const float jl = shx(il, 2), jh = shx(ih, 2);
      const float al = cA ? jl : il, ah = cA ? jh : ih, bl = cA ? il : jl, bh = cA ? ih : jh;
      const int t0 = 5 * hp;
      of[2 * t0]     = pack_bf16(o[0][0] * al, o[0][1] * al); of[2 * t0 + 1] = pack_bf16(o[0][2] * ah, o[0][3] * ah);
      of[2 * t0 + 2] = pack_bf16(o[1][0] * al, o[1][1] * al); of[2 * t0 + 3] = pack_bf16(o[1][2] * ah, o[1][3] * ah);
      of[2 * t0 + 4] = pack_bf16((cA ? o[2][0] : o[5][0]) * jl, (cA ? o[2][1] : o[5][1]) * jl);
      of[2 * t0 + 5] = pack_bf16((cA ? o[2][2] : o[5][2]) * jh, (cA ? o[2][3] : o[5][3]) * jh);
      of[2 * t0 + 6] = pack_bf16(o[3][0] * bl, o[3][1] * bl); of[2 * t0 + 7] = pack_bf16(o[3][2] * bh, o[3][3] * bh);
      of[2 * t0 + 8] = pack_bf16(o[4][0] * bl, o[4][1] * bl); of[2 * t0 + 9] = pack_bf16(o[4][2] * bh, o[4][3] * bh);
    }
    const int slot = mt * 8 + warp;
    uint4* const ob = &g_o[slot][0][lane];
    const uint32_t tag = __float_as_uint(lds32f(sb + OFF_WR + 324));
    {
      uint32_t ck = tag;
#pragma unroll
      for (int s = 0; s < 5; s++) {
        stg_pkt(ob + g * 168 + s * 32, of[4 * s], of[4 * s + 1], of[4 * s + 2], of[4 * s + 3]);
        ck ^= of[4 * s] ^ of[4 * s + 1] ^ of[4 * s + 2] ^ of[4 * s + 3];
      }
      stg_rlx32((uint32_t*)&g_o[slot][g][160] + lane, ck);
      if (lane == 0) stg_rlx32(&g_own[slot].oflag[g], 0u);
    }
    TS(5);
    float h[40];
#pragma unroll
    for (int s = 0; s < 5; s++) {
      const uint4 v = xr[s];
      h[8 * s] = bf_lo(v.x); h[8 * s + 1] = bf_hi(v.x); h[8 * s + 2] = bf_lo(v.y); h[8 * s + 3] = bf_hi(v.y);
      h[8 * s + 4] = bf_lo(v.z); h[8 * s + 5] = bf_hi(v.z); h[8 * s + 6] = bf_lo(v.w); h[8 * s + 7] = bf_hi(v.w);
    }
    mbar_wait(bar_full, 0); mbar_wait(bar_full + 8, 0); mbar_wait(bar_full + 16, 1);
    bar_sync(1, 256);
    const uint64_t dwo = make_desc(sb, 5120, 512, 2);
    wgmma_fence();
#pragma unroll
    for (int s = 0; s < 5; s++) wgmma_n80_rs(h, of[4 * s], of[4 * s + 1], of[4 * s + 2], of[4 * s + 3], dwo + g * 960 + s * 64, 1);
    wgmma_commit();
    TS(6);
    {
      int guard = SPIN_MAX;
      while (anyw(ldg_rlx32(&g_own[slot].oflag[lane & 7]) == SENT) && --guard) {}
    }
    TS(1);
    uint4 af[4][5]; uint32_t ck[4];
#define LOAD_CHUNK(b, e) { const uint4* p_ = ob + ((e) + ((e) >= g)) * 168; _Pragma("unroll") for (int s = 0; s < 5; s++) af[b][s] = ldg_pkt(p_ + s * 32); \
                           ck[b] = ldg_rlx32((const uint32_t*)(p_ - lane + 160) + lane); }
#define CHUNK_BAD(b) anyw((af[b][0].x ^ af[b][0].y ^ af[b][0].z ^ af[b][0].w ^ af[b][1].x ^ af[b][1].y ^ af[b][1].z ^ af[b][1].w ^ af[b][2].x ^ af[b][2].y ^ \
                           af[b][2].z ^ af[b][2].w ^ af[b][3].x ^ af[b][3].y ^ af[b][3].z ^ af[b][3].w ^ af[b][4].x ^ af[b][4].y ^ af[b][4].z ^ af[b][4].w ^ ck[b]) != tag)
    LOAD_CHUNK(0, 0); LOAD_CHUNK(1, 1); LOAD_CHUNK(2, 2); LOAD_CHUNK(3, 3);
#pragma unroll 1
    for (int e0 = 0; e0 < 8; e0 += 4) {
#pragma unroll
      for (int b = 0; b < 4; b++) {
        const int e = e0 + b;
        if (e < 7) {
          int guard = SPIN_MAX;
          while (CHUNK_BAD(b) && --guard) LOAD_CHUNK(b, e);
          const uint64_t d = dwo + (e + (e >= g)) * 960;
          wgmma_fence();
#pragma unroll
          for (int s = 0; s < 5; s++) wgmma_n80_rs(h, af[b][s].x, af[b][s].y, af[b][s].z, af[b][s].w, d + s * 64, 1);
          wgmma_commit();
          if (b > 0 && e0 == 0) { wgmma_wait<1>(); LOAD_CHUNK(b - 1, e + 3); }
        }
      }
    }
    float wr[20];
#pragma unroll
    for (int j = 0; j < 5; j++) {
      const uint4 v = lds128(sb + OFF_WR + c * 80 + j * 16);
      wr[4 * j] = __uint_as_float(v.x); wr[4 * j + 1] = __uint_as_float(v.y); wr[4 * j + 2] = __uint_as_float(v.z); wr[4 * j + 3] = __uint_as_float(v.w);
    }
    const float wsum = lds32f(sb + OFF_WR + 320);
    wgmma_wait<0>();
#pragma unroll
    for (int i = 0; i < 40; i++) asm volatile("" : "+f"(h[i]) :: "memory");
    TS(7);
    const bool odd = c & 1;
    float mean, rstd, rr;
    {
      float l1 = 0.f, l2 = 0.f, l3 = 0.f, h1 = 0.f, h2 = 0.f, h3 = 0.f;
#pragma unroll
      for (int j = 0; j < 10; j++) {
        l1 += h[4 * j] + h[4 * j + 1]; h1 += h[4 * j + 2] + h[4 * j + 3];
        l2 = fmaf(h[4 * j], h[4 * j], l2); l2 = fmaf(h[4 * j + 1], h[4 * j + 1], l2);
        h2 = fmaf(h[4 * j + 2], h[4 * j + 2], h2); h2 = fmaf(h[4 * j + 3], h[4 * j + 3], h2);
        l3 = fmaf(h[4 * j], wr[2 * j], l3); l3 = fmaf(h[4 * j + 1], wr[2 * j + 1], l3);
        h3 = fmaf(h[4 * j + 2], wr[2 * j], h3); h3 = fmaf(h[4 * j + 3], wr[2 * j + 1], h3);
      }
      float s1 = (odd ? h1 : l1) + shx(odd ? l1 : h1, 1), s2 = (odd ? h2 : l2) + shx(odd ? l2 : h2, 1), s3 = (odd ? h3 : l3) + shx(odd ? l3 : h3, 1);
      s1 += shx(s1, 2); s2 += shx(s2, 2); s3 += shx(s3, 2);
      uint4* const sp = &g_own[slot].st2[r + (odd ? 8 : 0)];
      if (cA) asm volatile("red.relaxed.gpu.global.add.v4.f32 [%0], {%1, %2, %3, %4};" :: "l"(sp), "f"(s1), "f"(s2), "f"(s3), "f"(1.f) : "memory");
      uint4 p0;
      int guard = SPIN_MAX;
      do { p0 = ldg_pkt(sp); } while (anyw(p0.w != 0x41000000u) && --guard);
      s1 = __uint_as_float(p0.x); s2 = __uint_as_float(p0.y); s3 = __uint_as_float(p0.z);
      mean = s1 * (1.f / 640.f);
      rstd = rsqrtf(fmaxf(fmaf(-mean, mean, s2 * (1.f / 640.f)), 0.f) + 1e-5f);
      rr = fmaf(-mean, wsum, s3) * rstd;
    }
    TS(8);
    const int tok0 = mt * 128 + 32 * w4 + wg;
    const uint32_t stg = sb + (ffn1 ? 204800 : OFF_W1) + warp * 2560;
    const uint32_t fa = stg + (lane & 15) * 160 + (lane >> 4) * 16;
    const uint32_t kk = ord_key(rr);
    const int L = __ffs(__ballot_sync(0xffffffffu, kk == __reduce_max_sync(0xffffffffu, kk))) - 1;
    const int crow = (L >> 2) + 8 * (L & 1);
    if (warp == g) {
      const float rc = __shfl_sync(0xffffffffu, rr, L);
      if (lane < 4) stg_rlx64(&g_x.key[lane][slot], __float_as_uint(rc), tok0 + 2 * crow);
      asm volatile("bar.arrive 3, 64;" ::: "memory");
    }
    {
      const float om = shx(mean, 1), os = shx(rstd, 1);
      const float rl = odd ? os : rstd, rh = odd ? rstd : os;
      const float bl = -(odd ? om : mean) * rl, bh = -(odd ? mean : om) * rh, al = 1.f + rl, ah = 1.f + rh;
      uint32_t v[20];
#pragma unroll
      for (int j = 0; j < 10; j++) {
        v[2 * j] = pack_bf16(fmaf(h[4 * j], al, bl), fmaf(h[4 * j + 1], al, bl));
        v[2 * j + 1] = pack_bf16(fmaf(h[4 * j + 2], ah, bh), fmaf(h[4 * j + 3], ah, bh));
      }
      if ((L >> 2) == r) {
        const bool chi = L & 1;
        const float rc = chi ? rh : rl, bc = chi ? bh : bl;
        uint32_t n[10], b[10];
#pragma unroll
        for (int j = 0; j < 10; j++) {
          n[j] = pack_bf16(fmaf(chi ? h[4 * j + 2] : h[4 * j], rc, bc), fmaf(chi ? h[4 * j + 3] : h[4 * j + 1], rc, bc));
          b[j] = chi ? v[2 * j + 1] : v[2 * j];
        }
        uint4* d = g_x.cand[slot][g][c];
        stg_pkt(d, n[0], n[1], n[2], n[3]); stg_pkt(d + 1, n[4], n[5], n[6], n[7]); stg_pkt(d + 2, n[8], n[9], b[0], b[1]);
        stg_pkt(d + 3, b[2], b[3], b[4], b[5]); stg_pkt(d + 4, b[6], b[7], b[8], b[9]);
      }
      __syncwarp();
#pragma unroll
      for (int s = 0; s < 5; s++) stsm4(fa + s * 32, v[4 * s], v[4 * s + 1], v[4 * s + 2], v[4 * s + 3]);
      __syncwarp();
    }
    char* const ob2 = (char*)(out + tok0 * 640 + g * 64);
    const int remo = 896 - 96 * g;
#pragma unroll
    for (int s = 0; s < 5; s++) {
      const int row = s < 4 ? 4 * s + (lane >> 3) : lane >> 1, pc = s < 4 ? lane & 7 : 8 + (lane & 1);
      const uint4 v = lds128(stg + row * 160 + pc * 16);
      if (row != crow) *(uint4*)(ob2 + row * 2560 + pc * 16 + (s < 4 ? 0 : remo)) = v;
    }
    TS(9);
    mbar_wait(bar_ffn, 0);
    const uint32_t red = sb + OFF_RED;
    if (ffn1) {
      uint4 w1[4][5];
      {
        const int k = (lane & 7) + (lane >> 4) * 8;
        const uint32_t a1 = sb + OFF_W1 + k * 64, sw = ((lane >> 3) & 1) ^ ((lane >> 1) & 3);
#pragma unroll
        for (int s = 0; s < 5; s++)
#pragma unroll
          for (int u = 0; u < 4; u++)
            w1[u][s] = ldsm4t(a1 + (s < 4 ? warp * 4096 + s * 1024 : 32768 + warp * 1024) + (u >> 1) * 40960 + ((sw ^ (2 * (u & 1))) * 16));
      }
      mbar_wait(bar_win, 0);
      const uint4* p = g_x.cand[lds128(sb + OFF_WR + 336).x][warp][c];
      TS(10);
      uint4 c0, c1, c2;
      int guard = SPIN_MAX;
      do { c0 = ldg_pkt(p); c1 = ldg_pkt(p + 1); c2 = ldg_pkt(p + 2); } while (anyw(c0.x == SENT || c1.x == SENT || c2.x == SENT) && --guard);
      float a[4][4];
#pragma unroll
      for (int u = 0; u < 4; u++) {
        a[u][0] = a[u][1] = a[u][2] = a[u][3] = 0.f;
        mma_acc(a[u], w1[u][0], c0.x, c0.y); mma_acc(a[u], w1[u][1], c0.z, c0.w); mma_acc(a[u], w1[u][2], c1.x, c1.y);
        mma_acc(a[u], w1[u][3], c1.z, c1.w); mma_acc(a[u], w1[u][4], c2.x, c2.y);
      }
      asm volatile("st.shared.v2.f32 [%0], {%1, %2};" :: "r"(red + (warp * 32 + c * 8 + r) * 8),
                   "f"(cA ? (odd ? a[0][2] : a[0][0]) : (odd ? a[1][2] : a[1][0])), "f"(cA ? (odd ? a[2][2] : a[2][0]) : (odd ? a[3][2] : a[3][0])) : "memory");
      bar_sync(1, 256);
      if (warp == 0) {
        float s = 0.f, u = 0.f;
#pragma unroll
        for (int i = 0; i < 8; i++) { const float2 t = lds64f(red + (i * 32 + lane) * 8); s += t.x; u += t.y; }
        const float av = s * rcp(1.f + ex2(-1.4426950408889634f * s)) * u;
        const float an = shx(av, 1);
        if (!odd) stg_rlx32(g_x.act + fj * 16 + (lane >> 1), pack_bf16(av, an));
      }
      TS(11);
    }
    uint4 w2[6];
    if (!ffn1) {
      const uint32_t a2 = sb + OFF_W2 + (warp * 192 + 24 * (((lane >> 3) & 1) * 4 + ((lane & 7) >> 1)) + 2 * (lane >> 4) + (lane & 1)) * 16;
#pragma unroll
      for (int s = 0; s < 6; s++) w2[s] = ldsm4t(a2 + s * 64);
      mbar_wait(bar_win, 0);
      TS(10);
    }
    const uint4 win = lds128(sb + OFF_WR + 336);
    if (win.x != slot && lane < 10) *(uint4*)(ob2 + crow * 2560 + lane * 16 + (lane < 8 ? 0 : remo)) = lds128(stg + crow * 160 + lane * 16);
    if (!ffn1) {
      const uint4* p = (const uint4*)(g_x.act + warp * 96 + ((r & 1) * 4 + c) * 12);
      const uint32_t* pb = (const uint32_t*)g_x.cand[win.x][fj < 64 ? fj >> 3 : (fj - 64) >> 1][c] + (fj < 64 ? 10 + (fj & 7) : 18 + (fj & 1));
      uint4 c0, c1, c2; uint32_t bw;
      int guard = SPIN_MAX;
      do {
        c0 = ldg_pkt(p); c1 = ldg_pkt(p + 1); c2 = ldg_pkt(p + 2); bw = ldg_rlx32(pb);
      } while (anyw(max(max(max(max(c0.x, c0.y), max(c0.z, c0.w)), max(max(c1.x, c1.y), max(c1.z, c1.w))), max(max(max(c2.x, c2.y), max(c2.z, c2.w)), bw)) == SENT) && --guard);
      TS(11);
      float a[4] = {0.f, 0.f, 0.f, 0.f}, b[4] = {0.f, 0.f, 0.f, 0.f};
      mma_acc(a, w2[0], c0.x, c0.y); mma_acc(b, w2[1], c0.z, c0.w);
      mma_acc(a, w2[2], c1.x, c1.y); mma_acc(b, w2[3], c1.z, c1.w);
      mma_acc(a, w2[4], c2.x, c2.y); mma_acc(b, w2[5], c2.z, c2.w);
      if (c == 0) sts32f(red + (warp * 8 + r) * 4, (a[0] + b[0]) + (a[3] + b[3]));
      bar_sync(1, 256);
      if (tid < 4) {
        float y0 = 0.f, y1 = 0.f;
#pragma unroll
        for (int i = 0; i < 8; i++) { const float2 t = lds64f(red + (i * 4 + tid) * 8); y0 += t.x; y1 += t.y; }
        const float sg = rcp(1.f + ex2(-1.4426950408889634f * __uint_as_float(win.z)));
        *(uint32_t*)(out + win.y * 640 + fj * 8 + tid * 2) = pack_bf16(fmaf(y0, sg, bf_lo(bw)), fmaf(y1, sg, bf_hi(bw)));
      }
    }
    TS(12);
#undef TS_T
  }
}

typedef CUresult (*EncodeFn)(CUtensorMap*, CUtensorMapDataType, cuuint32_t, void*, const cuuint64_t*, const cuuint64_t*, const cuuint32_t*,
                             const cuuint32_t*, CUtensorMapInterleave, CUtensorMapSwizzle, CUtensorMapL2promotion, CUtensorMapFloatOOBfill);

void make_map(EncodeFn enc, CUtensorMap* m, const void* base, const cuuint64_t* dims, const cuuint64_t* strides, const cuuint32_t* box,
              CUtensorMapSwizzle swz) {
  const cuuint32_t es[3] = {1, 1, 1};
  enc(m, CU_TENSOR_MAP_DATA_TYPE_BFLOAT16, 3, (void*)base, dims, strides, box, es, CU_TENSOR_MAP_INTERLEAVE_NONE, swz,
      CU_TENSOR_MAP_L2_PROMOTION_L2_128B, CU_TENSOR_MAP_FLOAT_OOB_FILL_NONE);
}

}

extern "C" void kernel_launch(void* const* d_in, const int* in_sizes, int n_in, void* d_out, int out_size) {
  const __nv_bfloat16* x = (const __nv_bfloat16*)d_in[0];
  const __nv_bfloat16* wqkv = (const __nv_bfloat16*)d_in[1];
  const __nv_bfloat16* wo = (const __nv_bfloat16*)d_in[2];
  void* fn = nullptr;
  cudaDriverEntryPointQueryResult st;
  cudaGetDriverEntryPoint("cuTensorMapEncodeTiled", &fn, cudaEnableDefault, &st);
  EncodeFn enc = (EncodeFn)fn;
  void* scp = nullptr;
  cudaGetSymbolAddress(&scp, g_scratch);
  Maps tm;
  { const cuuint64_t d[3] = {640, 1024, 2}, s[2] = {2560, 1280}; const cuuint32_t b[3] = {64, 64, 2}; make_map(enc, &tm.x, x, d, s, b, CU_TENSOR_MAP_SWIZZLE_128B); }
  { const cuuint64_t d[3] = {640, 640, 3}, s[2] = {3840, 1280}; const cuuint32_t b[3] = {64, 64, 1}; make_map(enc, &tm.w, wqkv, d, s, b, CU_TENSOR_MAP_SWIZZLE_128B); }
  { const cuuint64_t d[3] = {640, 640, 3}, s[2] = {3840, 1280}; const cuuint32_t b[3] = {16, 64, 3}; make_map(enc, &tm.wr, wqkv, d, s, b, CU_TENSOR_MAP_SWIZZLE_32B); }
  { const cuuint64_t d[3] = {32, 640, 20}, s[2] = {1280, 64}; const cuuint32_t b[3] = {32, 80, 2}; make_map(enc, &tm.wo, wo, d, s, b, CU_TENSOR_MAP_SWIZZLE_64B); }
  { const cuuint64_t d[3] = {640, 640, 1}, s[2] = {1280, 819200}; const cuuint32_t b[3] = {16, 80, 1}; make_map(enc, &tm.wor, wo, d, s, b, CU_TENSOR_MAP_SWIZZLE_64B); }
  { const cuuint64_t d[3] = {1536, 640, 1}, s[2] = {3072, 1966080}; const cuuint32_t b[3] = {32, 128, 1};
    make_map(enc, &tm.gate, d_in[5], d, s, b, CU_TENSOR_MAP_SWIZZLE_64B); make_map(enc, &tm.up, d_in[6], d, s, b, CU_TENSOR_MAP_SWIZZLE_64B); }
  { const cuuint64_t d[3] = {640, 1536, 1}, s[2] = {1280, 1966080}; const cuuint32_t b[3] = {8, 256, 1}; make_map(enc, &tm.down, d_in[7], d, s, b, CU_TENSOR_MAP_SWIZZLE_NONE); }
  cudaFuncSetAttribute(fused_kernel, cudaFuncAttributeMaxDynamicSharedMemorySize, SMEM_BYTES);
  fused_kernel<<<128, 384, SMEM_BYTES, cudaStreamPerThread>>>(x, wqkv, wo, (const __nv_bfloat16*)d_in[4], (const __nv_bfloat16*)d_in[5],
                                                              (const __nv_bfloat16*)d_in[6], (const __nv_bfloat16*)d_in[7], (__nv_bfloat16*)d_out, (Scratch*)scp, tm);
}
```

```cpp
#include <cuda_runtime.h>
#include <cuda_bf16.h>
#include <cuda.h>
#include <stdint.h>

#define PF0 1
#define PF_NS 100
#define PFX_IT 1
#define PFW_IT 2
#define F_IT 5
#define F_MAX 5
#define F_NS 150
#define REG_P 72
#define REG_C 216
#define AUX_NS 200
#define PINGPONG 1

namespace {

constexpr int SLOT    = 47104;
constexpr int OFF_W1  = 122880;
constexpr int OFF_W2  = 4 * SLOT;
constexpr int OFF_KV  = OFF_W2 + 24576;
constexpr int OFF_CS  = OFF_KV + 15360;
constexpr int OFF_ST  = OFF_CS + 960;
constexpr int OFF_WR  = OFF_ST + 1152;
constexpr int OFF_RED = OFF_CS;
constexpr int OFF_PT  = OFF_WR + 352;
constexpr int OFF_BAR = OFF_PT + 768;
constexpr int SMEM_BYTES = OFF_BAR + 224 + 288;
constexpr uint32_t SENT = 0xFFFFFFFFu;
constexpr int SPIN_MAX = 1 << 20;

struct Glob {
  uint4 cand[128][8][22];
  uint2 key[4][128];
  uint32_t act[768];
  uint32_t pad[256];
};
constexpr int GLOB_PER_CTA = sizeof(Glob) / 16 / 128;
static_assert(GLOB_PER_CTA * 128 * 16 == sizeof(Glob), "glob size");
struct Own {
  uint4 halo[2][5][32];
  uint4 st1[32];
  uint2 cs[32];
  uint32_t oflag[32];
  uint4 st2[16];
};
struct Scratch {
  Glob x;
  Own own[128];
  uint4 o[32][8][640];
  uint32_t epoch[128];
};
__device__ __align__(128) Scratch g_scratch;
#define g_x (sc->x)
#define g_own (sc->own)
#define g_o (sc->o)
#define g_epoch (sc->epoch)
#define TS(i)

__device__ __forceinline__ void mbar_init(uint32_t bar, uint32_t cnt) { asm volatile("mbarrier.init.shared::cta.b64 [%0], %1;" :: "r"(bar), "r"(cnt) : "memory"); }
__device__ __forceinline__ void mbar_expect_tx(uint32_t bar, uint32_t bytes) { asm volatile("mbarrier.arrive.expect_tx.shared::cta.b64 _, [%0], %1;" :: "r"(bar), "r"(bytes) : "memory"); }
__device__ __forceinline__ void mbar_arrive(uint32_t bar) { asm volatile("mbarrier.arrive.shared::cta.b64 _, [%0];" :: "r"(bar) : "memory"); }
__device__ __forceinline__ void mbar_arrive_cta(uint32_t bar, uint32_t cta) {
  asm volatile("{\n.reg .b32 ra;\nmapa.shared::cluster.u32 ra, %0, %1;\nmbarrier.arrive.shared::cluster.b64 _, [ra];\n}\n" :: "r"(bar), "r"(cta) : "memory");
}
__device__ __forceinline__ void mbar_wait(uint32_t bar, uint32_t parity) {
  asm volatile("{\n.reg .pred p;\n.reg .u32 n;\nmov.u32 n, 0;\nW:\nmbarrier.try_wait.parity.shared::cta.b64 p, [%0], %1;\n@p bra.uni D;\n"
               "add.u32 n, n, 1;\nsetp.lt.u32 p, n, %2;\n@p bra.uni W;\nD:\n}\n" :: "r"(bar), "r"(parity), "n"(SPIN_MAX) : "memory");
}
__device__ __forceinline__ void tma_3d(uint32_t dst, const void* tm, uint32_t bar, int c0, int c1, int c2) {
  asm volatile("cp.async.bulk.tensor.3d.shared::cluster.global.mbarrier::complete_tx::bytes [%0], [%1, {%3, %4, %5}], [%2];" :: "r"(dst), "l"(tm), "r"(bar), "r"(c0), "r"(c1), "r"(c2) : "memory");
}
__device__ __forceinline__ void tma_3d_mc(uint32_t dst, const void* tm, uint32_t bar, int c0, int c1, int c2) {
  asm volatile("cp.async.bulk.tensor.3d.shared::cluster.global.mbarrier::complete_tx::bytes.multicast::cluster [%0], [%1, {%3, %4, %5}], [%2], %6;" :: "r"(dst), "l"(tm), "r"(bar), "r"(c0), "r"(c1), "r"(c2), "h"((uint16_t)3) : "memory");
}
__device__ __forceinline__ void wgmma_fence() { asm volatile("wgmma.fence.sync.aligned;" ::: "memory"); }
__device__ __forceinline__ void wgmma_commit() { asm volatile("wgmma.commit_group.sync.aligned;" ::: "memory"); }
template <int N> __device__ __forceinline__ void wgmma_wait() { asm volatile("wgmma.wait_group.sync.aligned %0;" :: "n"(N) : "memory"); }
__device__ __forceinline__ uint64_t make_desc(uint32_t addr, uint32_t lbo, uint32_t sbo, uint32_t swz) {
  return (uint64_t)(((addr & 0x3FFFF) >> 4) | ((lbo >> 4) << 16)) | ((uint64_t)((sbo >> 4) | (swz << 30)) << 32);
}
__device__ __forceinline__ void bar_sync(int id, int n) { asm volatile("bar.sync %0, %1;" :: "r"(id), "r"(n) : "memory"); }
__device__ __forceinline__ uint4 ld_pkt(const void* p) {
  uint4 v;
  asm volatile("{\n.reg .b128 t;\n.reg .b64 lo, hi;\nld.relaxed.gpu.b128 t, [%4];\nmov.b128 {lo, hi}, t;\nmov.b64 {%0, %1}, lo;\nmov.b64 {%2, %3}, hi;\n}\n"
               : "=r"(v.x), "=r"(v.y), "=r"(v.z), "=r"(v.w) : "l"(p) : "memory");
  return v;
}
__device__ __forceinline__ void st_pkt(void* p, uint32_t a, uint32_t b, uint32_t c, uint32_t d) {
  asm volatile("{\n.reg .b128 t;\n.reg .b64 lo, hi;\nmov.b64 lo, {%1, %2};\nmov.b64 hi, {%3, %4};\nmov.b128 t, {lo, hi};\nst.relaxed.gpu.b128 [%0], t;\n}\n"
               :: "l"(p), "r"(a), "r"(b), "r"(c), "r"(d) : "memory");
}
__device__ __forceinline__ uint4 ldg_pkt(const void* p) {
  uint4 v;
  asm volatile("{\n.reg .b128 t;\n.reg .b64 lo, hi;\nld.relaxed.gpu.global.b128 t, [%4];\nmov.b128 {lo, hi}, t;\nmov.b64 {%0, %1}, lo;\nmov.b64 {%2, %3}, hi;\n}\n"
               : "=r"(v.x), "=r"(v.y), "=r"(v.z), "=r"(v.w) : "l"(p) : "memory");
  return v;
}
__device__ __forceinline__ void stg_pkt(void* p, uint32_t a, uint32_t b, uint32_t c, uint32_t d) {
  asm volatile("{\n.reg .b128 t;\n.reg .b64 lo, hi;\nmov.b64 lo, {%1, %2};\nmov.b64 hi, {%3, %4};\nmov.b128 t, {lo, hi};\nst.relaxed.gpu.global.b128 [%0], t;\n}\n"
               :: "l"(p), "r"(a), "r"(b), "r"(c), "r"(d) : "memory");
}
__device__ __forceinline__ uint32_t ldg_rlx32(const void* p) { uint32_t v; asm volatile("ld.relaxed.gpu.global.u32 %0, [%1];" : "=r"(v) : "l"(p) : "memory"); return v; }
__device__ __forceinline__ uint2 ldg_rlx64(const void* p) { uint2 v; asm volatile("ld.relaxed.gpu.global.v2.u32 {%0, %1}, [%2];" : "=r"(v.x), "=r"(v.y) : "l"(p) : "memory"); return v; }
__device__ __forceinline__ void stg128(void* p, const uint4& v) { asm volatile("st.global.v4.u32 [%0], {%1, %2, %3, %4};" :: "l"(p), "r"(v.x), "r"(v.y), "r"(v.z), "r"(v.w) : "memory"); }
template <class T> __device__ __forceinline__ T* pin(T* p) { asm volatile("" : "+l"(p)); return p; }
__device__ __forceinline__ uint32_t pin(uint32_t v) { asm volatile("" : "+r"(v)); return v; }
__device__ __forceinline__ float pin(float v) { asm volatile("" : "+f"(v)); return v; }
__device__ __forceinline__ void stg_rlx32(void* p, uint32_t v) { asm volatile("st.relaxed.gpu.global.u32 [%0], %1;" :: "l"(p), "r"(v) : "memory"); }
__device__ __forceinline__ void stg_rlx64(void* p, uint32_t a, uint32_t b) { asm volatile("st.relaxed.gpu.global.v2.u32 [%0], {%1, %2};" :: "l"(p), "r"(a), "r"(b) : "memory"); }
__device__ __forceinline__ uint4 ldsm4(uint32_t a) { uint4 v; asm volatile("ldmatrix.sync.aligned.m8n8.x4.shared.b16 {%0, %1, %2, %3}, [%4];" : "=r"(v.x), "=r"(v.y), "=r"(v.z), "=r"(v.w) : "r"(a) : "memory"); return v; }
__device__ __forceinline__ uint4 ldsm4t(uint32_t a) { uint4 v; asm volatile("ldmatrix.sync.aligned.m8n8.x4.trans.shared.b16 {%0, %1, %2, %3}, [%4];" : "=r"(v.x), "=r"(v.y), "=r"(v.z), "=r"(v.w) : "r"(a) : "memory"); return v; }
__device__ __forceinline__ void stsm4(uint32_t a, uint32_t x, uint32_t y, uint32_t z, uint32_t w) { asm volatile("stmatrix.sync.aligned.m8n8.x4.shared.b16 [%0], {%1, %2, %3, %4};" :: "r"(a), "r"(x), "r"(y), "r"(z), "r"(w) : "memory"); }
__device__ __forceinline__ void mma_acc(float (&c)[4], const uint4& a, uint32_t b0, uint32_t b1) {
  asm("mma.sync.aligned.m16n8k16.row.col.f32.bf16.bf16.f32 {%0,%1,%2,%3}, {%4,%5,%6,%7}, {%8,%9}, {%0,%1,%2,%3};"
      : "+f"(c[0]), "+f"(c[1]), "+f"(c[2]), "+f"(c[3]) : "r"(a.x), "r"(a.y), "r"(a.z), "r"(a.w), "r"(b0), "r"(b1));
}
__device__ __forceinline__ uint4 lds128(uint32_t a) { uint4 v; asm volatile("ld.shared.v4.u32 {%0, %1, %2, %3}, [%4];" : "=r"(v.x), "=r"(v.y), "=r"(v.z), "=r"(v.w) : "r"(a) : "memory"); return v; }
__device__ __forceinline__ float2 lds64f(uint32_t a) { float2 v; asm volatile("ld.shared.v2.f32 {%0, %1}, [%2];" : "=f"(v.x), "=f"(v.y) : "r"(a)); return v; }
__device__ __forceinline__ float lds32f(uint32_t a) { float v; asm volatile("ld.shared.f32 %0, [%1];" : "=f"(v) : "r"(a)); return v; }
__device__ __forceinline__ void sts32f(uint32_t a, float v) { asm volatile("st.shared.f32 [%0], %1;" :: "r"(a), "f"(v) : "memory"); }
__device__ __forceinline__ uint32_t pack_bf16(float lo, float hi) { uint32_t r; asm("cvt.rn.bf16x2.f32 %0, %1, %2;" : "=r"(r) : "f"(hi), "f"(lo)); return r; }
__device__ __forceinline__ float bf_lo(uint32_t v) { return __uint_as_float(v << 16); }
__device__ __forceinline__ float bf_hi(uint32_t v) { return __uint_as_float(v & 0xffff0000u); }
__device__ __forceinline__ uint32_t movm(uint32_t a) { uint32_t d; asm("movmatrix.sync.aligned.m8n8.trans.b16 %0, %1;" : "=r"(d) : "r"(a)); return d; }
__device__ __forceinline__ float ex2(float x) { float y; asm("ex2.approx.ftz.f32 %0, %1;" : "=f"(y) : "f"(x)); return y; }
__device__ __forceinline__ float rsq(float x) { float y; asm("rsqrt.approx.ftz.f32 %0, %1;" : "=f"(y) : "f"(x)); return y; }
__device__ __forceinline__ float rcp(float x) { float y; asm("rcp.approx.ftz.f32 %0, %1;" : "=f"(y) : "f"(x)); return y; }
__device__ __forceinline__ bool elect() { uint32_t p; asm volatile("{\n.reg .pred q;\nelect.sync _|q, 0xffffffff;\nselp.u32 %0, 1, 0, q;\n}\n" : "=r"(p)); return p; }
__device__ __forceinline__ void pf_l2(const void* p) { asm volatile("prefetch.global.L2 [%0];" :: "l"(p)); }
__device__ __forceinline__ bool anyw(bool p) { return __any_sync(0xffffffffu, p); }
__device__ __forceinline__ float shx(float v, int m) { return __shfl_xor_sync(0xffffffffu, v, m); }
__device__ __forceinline__ void mma_k24(float (&c)[4], uint32_t a0, uint32_t a1, uint32_t a2, uint32_t a3, uint32_t b0, uint32_t b1,
                                        uint32_t e0, uint32_t e1, uint32_t f0) {
  asm("mma.sync.aligned.m16n8k16.row.col.f32.bf16.bf16.f32 {%0,%1,%2,%3}, {%4,%5,%6,%7}, {%8,%9}, {%10,%10,%10,%10};"
      : "=f"(c[0]), "=f"(c[1]), "=f"(c[2]), "=f"(c[3]) : "r"(a0), "r"(a1), "r"(a2), "r"(a3), "r"(b0), "r"(b1), "f"(0.f));
  asm("mma.sync.aligned.m16n8k8.row.col.f32.bf16.bf16.f32 {%0,%1,%2,%3}, {%4,%5}, {%6}, {%0,%1,%2,%3};"
      : "+f"(c[0]), "+f"(c[1]), "+f"(c[2]), "+f"(c[3]) : "r"(e0), "r"(e1), "r"(f0));
}
__device__ __forceinline__ uint32_t ord_key(float r) { uint32_t u = __float_as_uint(r); return u ^ ((uint32_t)((int32_t)u >> 31) | 0x80000000u); }

__device__ __forceinline__ void wgmma_n48hi_ss(float (&d)[120], uint64_t da, uint64_t db, int scale_d) {
  asm volatile("{\n.reg .pred p;\nsetp.ne.b32 p, %26, 0;\n"
    "wgmma.mma_async.sync.aligned.m64n48k16.f32.bf16.bf16 "
    "{%0, %1, %2, %3, %4, %5, %6, %7, %8, %9, %10, %11, %12, %13, %14, %15, "
    "%16, %17, %18, %19, %20, %21, %22, %23}, "
    "%24, %25, p, 1, 1, 0, 1;\n}\n"
    : "+f"(d[96]), "+f"(d[97]), "+f"(d[98]), "+f"(d[99]), "+f"(d[100]), "+f"(d[101]), "+f"(d[102]), "+f"(d[103]),
      "+f"(d[104]), "+f"(d[105]), "+f"(d[106]), "+f"(d[107]), "+f"(d[108]), "+f"(d[109]), "+f"(d[110]), "+f"(d[111]),
      "+f"(d[112]), "+f"(d[113]), "+f"(d[114]), "+f"(d[115]), "+f"(d[116]), "+f"(d[117]), "+f"(d[118]), "+f"(d[119])
    : "l"(da), "l"(db), "r"(scale_d));
}
__device__ __forceinline__ void wgmma_n192lo_ss(float (&d)[120], uint64_t da, uint64_t db, int scale_d) {
  asm volatile("{\n.reg .pred p;\nsetp.ne.b32 p, %98, 0;\n"
    "wgmma.mma_async.sync.aligned.m64n192k16.f32.bf16.bf16 "
    "{%0, %1, %2, %3, %4, %5, %6, %7, %8, %9, %10, %11, %12, %13, %14, %15, "
    "%16, %17, %18, %19, %20, %21, %22, %23, %24, %25, %26, %27, %28, %29, %30, %31, "
    "%32, %33, %34, %35, %36, %37, %38, %39, %40, %41, %42, %43, %44, %45, %46, %47, "
    "%48, %49, %50, %51, %52, %53, %54, %55, %56, %57, %58, %59, %60, %61, %62, %63, "
    "%64, %65, %66, %67, %68, %69, %70, %71, %72, %73, %74, %75, %76, %77, %78, %79, "
    "%80, %81, %82, %83, %84, %85, %86, %87, %88, %89, %90, %91, %92, %93, %94, %95}, "
    "%96, %97, p, 1, 1, 0, 1;\n}\n"
    : "+f"(d[0]), "+f"(d[1]), "+f"(d[2]), "+f"(d[3]), "+f"(d[4]), "+f"(d[5]), "+f"(d[6]), "+f"(d[7]),
      "+f"(d[8]), "+f"(d[9]), "+f"(d[10]), "+f"(d[11]), "+f"(d[12]), "+f"(d[13]), "+f"(d[14]), "+f"(d[15]),
      "+f"(d[16]), "+f"(d[17]), "+f"(d[18]), "+f"(d[19]), "+f"(d[20]), "+f"(d[21]), "+f"(d[22]), "+f"(d[23]),
      "+f"(d[24]), "+f"(d[25]), "+f"(d[26]), "+f"(d[27]), "+f"(d[28]), "+f"(d[29]), "+f"(d[30]), "+f"(d[31]),
      "+f"(d[32]), "+f"(d[33]), "+f"(d[34]), "+f"(d[35]), "+f"(d[36]), "+f"(d[37]), "+f"(d[38]), "+f"(d[39]),
      "+f"(d[40]), "+f"(d[41]), "+f"(d[42]), "+f"(d[43]), "+f"(d[44]), "+f"(d[45]), "+f"(d[46]), "+f"(d[47]),
      "+f"(d[48]), "+f"(d[49]), "+f"(d[50]), "+f"(d[51]), "+f"(d[52]), "+f"(d[53]), "+f"(d[54]), "+f"(d[55]),
      "+f"(d[56]), "+f"(d[57]), "+f"(d[58]), "+f"(d[59]), "+f"(d[60]), "+f"(d[61]), "+f"(d[62]), "+f"(d[63]),
      "+f"(d[64]), "+f"(d[65]), "+f"(d[66]), "+f"(d[67]), "+f"(d[68]), "+f"(d[69]), "+f"(d[70]), "+f"(d[71]),
      "+f"(d[72]), "+f"(d[73]), "+f"(d[74]), "+f"(d[75]), "+f"(d[76]), "+f"(d[77]), "+f"(d[78]), "+f"(d[79]),
      "+f"(d[80]), "+f"(d[81]), "+f"(d[82]), "+f"(d[83]), "+f"(d[84]), "+f"(d[85]), "+f"(d[86]), "+f"(d[87]),
      "+f"(d[88]), "+f"(d[89]), "+f"(d[90]), "+f"(d[91]), "+f"(d[92]), "+f"(d[93]), "+f"(d[94]), "+f"(d[95])
    : "l"(da), "l"(db), "r"(scale_d));
}
__device__ __forceinline__ void wgmma_n80_rs(float (&d)[40], uint32_t a0, uint32_t a1, uint32_t a2, uint32_t a3, uint64_t db, int scale_d) {
  asm volatile("{\n.reg .pred p;\nsetp.ne.b32 p, %45, 0;\n"
    "wgmma.mma_async.sync.aligned.m64n80k16.f32.bf16.bf16 "
    "{%0, %1, %2, %3, %4, %5, %6, %7, %8, %9, %10, %11, %12, %13, %14, %15, "
    "%16, %17, %18, %19, %20, %21, %22, %23, %24, %25, %26, %27, %28, %29, %30, %31, "
    "%32, %33, %34, %35, %36, %37, %38, %39}, "
    "{%40, %41, %42, %43}, %44, p, 1, 1, 1;\n}\n"
    : "+f"(d[0]), "+f"(d[1]), "+f"(d[2]), "+f"(d[3]), "+f"(d[4]), "+f"(d[5]), "+f"(d[6]), "+f"(d[7]),
      "+f"(d[8]), "+f"(d[9]), "+f"(d[10]), "+f"(d[11]), "+f"(d[12]), "+f"(d[13]), "+f"(d[14]), "+f"(d[15]),
      "+f"(d[16]), "+f"(d[17]), "+f"(d[18]), "+f"(d[19]), "+f"(d[20]), "+f"(d[21]), "+f"(d[22]), "+f"(d[23]),
      "+f"(d[24]), "+f"(d[25]), "+f"(d[26]), "+f"(d[27]), "+f"(d[28]), "+f"(d[29]), "+f"(d[30]), "+f"(d[31]),
      "+f"(d[32]), "+f"(d[33]), "+f"(d[34]), "+f"(d[35]), "+f"(d[36]), "+f"(d[37]), "+f"(d[38]), "+f"(d[39])
    : "r"(a0), "r"(a1), "r"(a2), "r"(a3), "l"(db), "r"(scale_d));
}
__device__ __forceinline__ void wgmma_n80_ss(float (&d)[40], uint64_t da, uint64_t db, int scale_d) {
  asm volatile("{\n.reg .pred p;\nsetp.ne.b32 p, %42, 0;\n"
    "wgmma.mma_async.sync.aligned.m64n80k16.f32.bf16.bf16 "
    "{%0, %1, %2, %3, %4, %5, %6, %7, %8, %9, %10, %11, %12, %13, %14, %15, "
    "%16, %17, %18, %19, %20, %21, %22, %23, %24, %25, %26, %27, %28, %29, %30, %31, "
    "%32, %33, %34, %35, %36, %37, %38, %39}, "
    "%40, %41, p, 1, 1, 0, 1;\n}\n"
    : "+f"(d[0]), "+f"(d[1]), "+f"(d[2]), "+f"(d[3]), "+f"(d[4]), "+f"(d[5]), "+f"(d[6]), "+f"(d[7]),
      "+f"(d[8]), "+f"(d[9]), "+f"(d[10]), "+f"(d[11]), "+f"(d[12]), "+f"(d[13]), "+f"(d[14]), "+f"(d[15]),
      "+f"(d[16]), "+f"(d[17]), "+f"(d[18]), "+f"(d[19]), "+f"(d[20]), "+f"(d[21]), "+f"(d[22]), "+f"(d[23]),
      "+f"(d[24]), "+f"(d[25]), "+f"(d[26]), "+f"(d[27]), "+f"(d[28]), "+f"(d[29]), "+f"(d[30]), "+f"(d[31]),
      "+f"(d[32]), "+f"(d[33]), "+f"(d[34]), "+f"(d[35]), "+f"(d[36]), "+f"(d[37]), "+f"(d[38]), "+f"(d[39])
    : "l"(da), "l"(db), "r"(scale_d));
}

__device__ __forceinline__ constexpr int QT(int t) { return t < 8 ? t : 16 + t; }
__device__ __forceinline__ constexpr int KT(int t) { return t < 8 ? 8 + t : 18 + t; }
__device__ __forceinline__ constexpr int VT(int t) { return t < 8 ? 16 + t : 20 + t; }

struct Maps { CUtensorMap x, w, wr, wo, wor, gate, up, down; };

__global__ void __cluster_dims__(2, 1, 1) __launch_bounds__(384, 1)
fused_kernel(const __nv_bfloat16* __restrict__ x, const __nv_bfloat16* __restrict__ wqkv,
             const __nv_bfloat16* __restrict__ wo, const __nv_bfloat16* __restrict__ w_r, const __nv_bfloat16* __restrict__ w_gate,
             const __nv_bfloat16* __restrict__ w_up, const __nv_bfloat16* __restrict__ w_down, __nv_bfloat16* __restrict__ out,
             Scratch* __restrict__ sc, const __grid_constant__ Maps tm) {
  extern __shared__ __align__(1024) uint8_t smem[];
  const int tid = threadIdx.x, warp = __shfl_sync(0xffffffffu, tid >> 5, 0), lane = tid & 31, bid = blockIdx.x;
  const uint32_t sb = (uint32_t)__cvta_generic_to_shared(smem);
  const uint32_t bar_full = sb + OFF_BAR, bar_empty = bar_full + 32, bar_aux = bar_full + 64, bar_ffn = bar_full + 72, bar_win = bar_full + 80,
                 bar_ssd = bar_full + 88, bar_o = bar_full + 96;
  if (warp < 4 && elect()) {
    mbar_init(bar_full + 8 * (warp ^ 2), 1);
    mbar_init(bar_empty + 8 * warp, 4);
    mbar_init(bar_aux + 8 * warp, warp == 0 ? 64 : warp == 3 ? 2 : 1);
    asm volatile("fence.mbarrier_init.release.cluster;" ::: "memory");
  }
  if (warp >= 4 && elect()) { mbar_init(bar_o + 16 * (warp - 4), 1); mbar_init(bar_o + 16 * (warp - 4) + 8, 1); }
  asm volatile("barrier.cluster.arrive.relaxed.aligned;" ::: "memory");
  if (warp >= 8 && warp < 11 && elect()) asm volatile("prefetch.tensormap [%0];" :: "l"(&tm.x + (warp - 8)) : "memory");
  auto pf_slice = [&](int ks) {
    pf_l2(lane < 16 ? (const char*)x + ((bid * 16 + lane) * 1280 + ks * 128) : (const char*)wqkv + ((bid * 15 + min(lane, 30) - 16) * 128 + ks * 245760));
  };
  if (warp >= 4 && warp < 4 + PF0) {
    if (warp > 4) __nanosleep(300 + (warp - 4) * PF_NS);
    pf_slice(warp == 6 ? 5 : warp - 4);
  }
  const int rank = bid & 1, cl = bid >> 1;
  const int q7 = ((cl - 36) * 37) >> 8;
  const int P = cl < 4 ? 0 : cl < 36 ? (cl - 4) & 7 : cl - 35 - 7 * q7;
  const int g = cl < 4 ? 4 + cl : cl < 36 ? (cl - 4) >> 3 : 4 + q7;
  const int mt = 2 * P + rank, cid = mt * 8 + g;
  const bool ffn1 = g < 3;
  const int fj = ffn1 ? mt * 3 + g : (P * 5 + g - 3) * 2 + rank;
  const int ord = ((g >> 2) ^ P) & 1;
  auto ks_of = [&](int it) { return ord == 0 || it == 0 ? it : it <= 5 ? it + 4 : it - 5; };
  auto load_w = [&](int it, uint32_t a, uint32_t full) {
    tma_3d_mc(a + 16384 + rank * 16384, &tm.w, full, g * 80, it * 64, rank * 2);
    tma_3d_mc(a + (rank ? 40960 : 24576), rank ? &tm.wr : &tm.w, full, g * 80 + rank * 64, it * 64, 1 - rank);
  };
  if (warp == 0 && elect()) {
    mbar_expect_tx(bar_full + 16, SLOT);
    tma_3d(sb + 2 * SLOT, &tm.x, bar_full + 16, 0, mt * 64, 0);
  }
  asm volatile("barrier.cluster.wait.aligned;" ::: "memory");
  if (warp == 0) {
    if (elect()) load_w(0, sb + 2 * SLOT, bar_full + 16);
    asm volatile("bar.arrive 4, 64;" ::: "memory");
  }

  if (warp >= 8) {
    asm volatile("setmaxnreg.dec.sync.aligned.u32 %0;" :: "n"(REG_P));
#define TS_T 0
    if (warp == 8) {
      TS(8);
      bar_sync(4, 64);
      if (elect()) {
        TS(10);
        int fjn = 0;
#pragma unroll 1
        for (int it = 1; it < 14; it++) {
          const int s = (it + 2) & 3;
          const uint32_t full = bar_full + 8 * s, a = sb + s * SLOT;
          if (it >= 4) mbar_wait(it == 13 ? bar_ssd : bar_empty + 8 * s, ((it >> 2) - 1) & 1);
          if (it < 10) {
            const int ks = ks_of(it);
            mbar_expect_tx(full, SLOT);
            tma_3d(a, &tm.x, full, ks * 64, mt * 64, 0);
            load_w(ks, a, full);
            if (it == 1) TS(9);
          } else if (it < 13) {
            const int g0 = 3 * (it - 10), g1 = min(g0 + 3, 8);
            mbar_expect_tx(full, (g1 - g0) * 12800);
#pragma unroll 1
            for (int gp = g0 + ((g0 ^ rank) & 1); gp < g1; gp += 2) {
              tma_3d_mc(sb + gp * 15360, &tm.wo, full, 0, gp * 80, g * 2);
              tma_3d_mc(sb + gp * 15360 + 10240, &tm.wor, full, 512 + g * 16, gp * 80, 0);
            }
          }
          if (it == 4) mbar_expect_tx(bar_ffn, ffn1 ? 81920 : 24576);
          const int j1 = it == 13 ? (ffn1 ? 10 : 12) : min(max(it - F_IT + 1, 0), ffn1 ? 2 : F_MAX);
#pragma unroll 1
          for (; fjn < j1; fjn++) {
            const int j = 9 - fjn;
            if (ffn1) tma_3d(sb + (j < 8 ? 0 : OFF_W1) + j * 8192, j < 5 ? &tm.gate : &tm.up, bar_ffn, fj * 32, (j < 5 ? j : j - 5) * 128, 0);
            else tma_3d(sb + OFF_W2 + fjn * 2048, &tm.down, bar_ffn, fj * 8, fjn * 128, 0);
          }
        }
        TS(11);
      }
#undef TS_T
#define TS_T 32
    } else if (warp < 11) {
      Own* const own = g_own + cid;
      const int r = lane >> 2, l7 = lane & 7, hk = lane >> 4, idx = lane;
      bar_sync(2, 352);
      TS(0);
      const uint32_t tag = __float_as_uint(lds32f(sb + OFF_WR + 324));
      const uint32_t pt = sb + OFF_PT + lane * 4 + (warp - 9) * 512;
      const float s0 = lds32f(pt) + lds32f(pt + 128), q0 = lds32f(sb + OFF_PT + 256 + lane * 4) + lds32f(sb + OFF_PT + 384 + lane * 4);
      int guard = SPIN_MAX;
      if (warp == 9) {
        stg_pkt(&own->st1[idx], __float_as_uint(s0), __float_as_uint(q0), tag, 0u);
        TS(1);
        const uint4* sp = &g_own[mt * 8].st1[lane];
        const uint4* hp = &g_own[max(mt - 1, 0) * 8 + hk * 2 + 1].st1[24 + l7];
        uint4 a[5], b[5];
        bool bad;
        do {
          __nanosleep(AUX_NS);
          bad = false;
#pragma unroll
          for (int i = 0; i < 5; i++) {
            const uint4* q = i < 4 ? sp + i * (sizeof(Own) / 16) : hp;
            a[i] = ldg_pkt(q); b[i] = ldg_pkt(q + 4 * sizeof(Own) / 16);
          }
#pragma unroll
          for (int i = 0; i < 5; i++) bad |= a[i].z != tag || b[i].z != tag;
        } while (anyw(bad) && --guard);
#pragma unroll
        for (int i = 0; i < 5; i++) {
          const float m = (__uint_as_float(a[i].x) + __uint_as_float(b[i].x)) * (1.f / 640.f);
          const float rs = rsq(fmaxf(fmaf(-m, m, (__uint_as_float(a[i].y) + __uint_as_float(b[i].y)) * (1.f / 640.f)), 0.f) + 1e-5f);
          ((float2*)(smem + OFF_ST))[i < 4 ? 8 + lane + 32 * i + 8 * (i >> 1) : hk * 72 + l7] = make_float2(m, rs);
        }
      } else {
        stg_rlx64(&own->cs[idx], __float_as_uint(s0), tag);
        const uint4* cp = (const uint4*)g_own[hk * 8 + g].cs + (lane & 15);
        uint4 a[4], b[4];
        bool bad;
        do {
          __nanosleep(AUX_NS);
          bad = false;
#pragma unroll
          for (int i = 0; i < 4; i++) { a[i] = ldg_pkt(cp + i * 32 * sizeof(Own) / 16); b[i] = ldg_pkt(cp + (i * 32 + 16) * sizeof(Own) / 16); }
#pragma unroll
          for (int i = 0; i < 4; i++) bad |= a[i].y != tag || a[i].w != tag || b[i].y != tag || b[i].w != tag;
        } while (anyw(bad) && --guard);
#pragma unroll
        for (int i = 0; i < 4; i++)
          if (i < 3 || lane < 24)
            ((float2*)(smem + OFF_CS))[(lane & 3) * 30 + r + 8 * i] = make_float2(__uint_as_float(a[i].x) + __uint_as_float(b[i].x), __uint_as_float(a[i].z) + __uint_as_float(b[i].z));
      }
      mbar_arrive(bar_aux);
      TS(2);
      const int wq = warp - 9;
      const uint32_t* const fp = pin(&g_own[mt * 8 + wq * 4].oflag[lane]);
      const char* const src = (const char*)g_o[mt * 2 + wq];
      bar_sync(5 + wq, 160);
      while (anyw(ldg_rlx32(fp) != tag) && --guard > 0) {}
      if (elect()) {
        asm volatile("fence.proxy.async.global;" ::: "memory");
        TS(6);
#pragma unroll 1
        for (int i = 0, sl = 0; i < 7; i++) {
          const uint32_t full = bar_o + wq * 64 + 8 * sl;
          if (i >= 3) mbar_wait(full + 32, i == 6);
          mbar_expect_tx(full, 10240);
          asm volatile("cp.async.bulk.shared::cluster.global.mbarrier::complete_tx::bytes [%0], [%1], 10240, [%2];"
                       :: "r"(sb + OFF_W1 + sl * 20480 + wq * 10240), "l"(src + (i + (i >= g)) * 10240), "r"(full) : "memory");
          sl = sl == 2 ? 0 : sl + 1;
        }
      }
#undef TS_T
#define TS_T 96
    } else {
#pragma unroll 1
      for (int i = lane; i < 960; i += 32) *(uint4*)(smem + OFF_KV + i * 16) = make_uint4(SENT, SENT, SENT, SENT);
      mbar_wait(bar_full + 16, 0);
      TS(4);
      const uint32_t epoch = ldg_rlx32(g_epoch + cid) + 1;
      uint32_t wv[10];
#pragma unroll
      for (int i = 0; i < 10; i++) wv[i] = __ldg((const uint32_t*)w_r + lane + 32 * i);
#pragma unroll 1
      for (int i = lane; i < 392; i += 32) {
        const uint32_t f = i >= 376 ? 0u : SENT;
        ((uint4*)(g_own + cid))[i] = make_uint4(f, f, f, f);
        if (i < GLOB_PER_CTA) ((uint4*)&g_x)[cid * GLOB_PER_CTA + i] = make_uint4(SENT, SENT, SENT, SENT);
      }
      float s = 0.f;
#pragma unroll
      for (int i = 0; i < 10; i++) {
        s += bf_lo(wv[i]) + bf_hi(wv[i]);
        const unsigned u = i < 8 ? lane + 32 * (i - g) : lane + 32 * (i - 7) - g * 8;
        if (i < 8 ? u < 32u : u - 32u < 8u) *(float2*)(smem + OFF_WR + ((u & 3) * 10 + (u >> 2)) * 8) = make_float2(bf_lo(wv[i]), bf_hi(wv[i]));
      }
#pragma unroll
      for (int m = 1; m < 32; m <<= 1) s += shx(s, m);
      *(float2*)(smem + OFF_WR + 320) = make_float2(s, __uint_as_float(epoch * 0x9E3779B8u));
      g_epoch[cid] = epoch;
      TS(3);
      asm volatile("fence.acq_rel.gpu;" ::: "memory");
      TS(5);
      asm volatile("bar.arrive 2, 352;" ::: "memory");
      bar_sync(3, 64);
      const uint4* kp = (const uint4*)g_x.key[cid & 3] + lane;
      uint4 k0, k1;
      int guard = SPIN_MAX;
      do { k0 = ldg_pkt(kp); k1 = ldg_pkt(kp + 32); } while (anyw(k0.y == SENT || k0.w == SENT || k1.y == SENT || k1.w == SENT) && --guard);
      int i0 = 2 * lane, i1 = 2 * lane + 64;
      if (k0.z > k0.x) { k0.x = k0.z; k0.y = k0.w; i0++; }
      if (k1.z > k1.x) { k1.x = k1.z; k1.y = k1.w; i1++; }
      if (k1.x > k0.x) { k0.x = k1.x; k0.y = k1.y; i0 = i1; }
      const float rw = __uint_as_float(k0.x ^ ((uint32_t)((int32_t)~k0.x >> 31) | 0x80000000u));
      const float sg = rcp(1.f + ex2(-1.4426950408889634f * rw));
      if (lane == __ffs(__ballot_sync(0xffffffffu, k0.x == __reduce_max_sync(0xffffffffu, k0.x))) - 1) {
        *(uint4*)(smem + OFF_WR + 336) = make_uint4(i0, k0.y, __float_as_uint(sg), i0 * (8 * 22 * 16));
        mbar_arrive(bar_win);
      }
      TS(7);
    }
#undef TS_T
  } else {
#define TS_T 0
    TS(23);
    asm volatile("setmaxnreg.inc.sync.aligned.u32 %0;" :: "n"(REG_C));
    const int wg = warp >> 2, w4 = warp & 3, r = lane >> 2, c = lane & 3;
    float acc[120];
    uint4 xr[5];
    const uint32_t xa = (warp * 16 + (lane & 15)) * 128, xc = (lane >> 4) ^ (lane & 7);
    float ps = 0.f, pq = 0.f, pc_ = 0.f;
    uint32_t sxo, swo;
    {
      const int l7 = lane & 7, j = warp >> 1, k = (warp & 1) * 32 + lane, ch = min((P >> 1) * 4 + rank * 2 + (j >> 1), 14);
      sxo = ((g & 3) * 32 + j * 8 + l7) * 128 + ((((warp & 1) * 4 + (lane >> 3)) ^ l7) * 16);
      swo = ch < 12 ? 16384 + (ch >> 2) * 8192 + k * 128 + ((((ch & 3) * 2 + (j & 1)) ^ l7) * 16) : 40960 + (ch - 12) * 2048 + k * 32 + (((j & 1) ^ (l7 >> 2)) * 16);
    }
    TS(0);
#pragma unroll 1
    for (int it = 0; it < 10; it++) {
      const int s = (it + 2) & 3;
      mbar_wait(bar_full + 8 * s, (it >> 2) & 1);
      TS(13 + it);
      const uint32_t a = sb + s * SLOT;
      const uint64_t da = make_desc(a + wg * 8192, 16, 1024, 1), db = make_desc(a + 16384, 8192, 1024, 1), dr = make_desc(a + 40960, 2048, 256, 3);
      if (PINGPONG && (it | wg)) bar_sync(7 + wg, 256);
      wgmma_fence();
#pragma unroll
      for (int kk = 0; kk < 4; kk++) {
        wgmma_n48hi_ss(acc, da + kk * 2, dr + kk * 32, (kk | it) != 0);
        if (PINGPONG == 2 && kk == 3 && (it < 9 || wg == 0)) asm volatile("bar.arrive %0, 256;" :: "r"(8 - wg) : "memory");
        wgmma_n192lo_ss(acc, da + kk * 2, db + kk * 128, (kk | it) != 0);
      }
      wgmma_commit();
      if (PINGPONG == 1 && (it < 9 || wg == 0)) asm volatile("bar.arrive %0, 256;" :: "r"(8 - wg) : "memory");
      if (it == PFX_IT && warp < 3) pf_slice(warp == 0 ? 4 : 7 + warp);
      if (it >= PFW_IT && it < PFW_IT + 4) {
        const int n = it == PFW_IT + 1 ? 50 : 120;
        const char* b = (const char*)(it == PFW_IT ? w_down : it == PFW_IT + 1 ? wo : it == PFW_IT + 2 ? w_up : w_gate);
        if (tid < n) pf_l2(b + (bid * n + tid) * 128);
      }
      const int ks = ks_of(it);
      if (ks == g) {
#pragma unroll
        for (int j = 0; j < 4; j++) xr[j] = ldsm4(a + xa + ((xc ^ (2 * j)) * 16));
      }
      if (ks == 8 + (g >> 2)) xr[4] = ldsm4(a + xa + ((xc ^ (2 * (g & 3))) * 16));
      if ((unsigned)(it - ord) < 5u) {
        const uint4 v = ldsm4(a + sxo), w = ldsm4t(a + swo);
        const uint32_t vv[4] = {v.x, v.y, v.z, v.w}, ww[4] = {w.x, w.y, w.z, w.w};
#pragma unroll
        for (int i = 0; i < 4; i++) {
          const float d = bf_lo(vv[i]), e = bf_hi(vv[i]);
          ps += d + e; pq = fmaf(d, d, pq); pq = fmaf(e, e, pq); pc_ += bf_lo(ww[i]) + bf_hi(ww[i]);
        }
        if (it - ord == 4) {
          ps += shx(ps, 1); pq += shx(pq, 1); pc_ += shx(pc_, 1);
          ps += shx(ps, 2); pq += shx(pq, 2); pc_ += shx(pc_, 2);
          if (c < 3) sts32f(sb + OFF_PT + (c * 64 + (warp & 1) * 32 + (warp >> 1) * 8 + r) * 4, c == 0 ? ps : c == 1 ? pq : pc_);
          asm volatile("bar.arrive 2, 352;" ::: "memory");
        }
      }
      if (it > 0 && it < 9) {
        wgmma_wait<1>();
        if ((tid & 127) < 2) mbar_arrive_cta(bar_empty + 8 * ((it + 1) & 3), tid & 1);
      }
    }
    mbar_wait(bar_aux, 0);
    TS(3);
    const uint32_t stb = sb + OFF_ST + (wg * 72 + 16 * w4) * 8;
    const float2 slo = lds64f(stb + (8 + r) * 8), shi = lds64f(stb + (16 + r) * 8);
    float cs[60];
#pragma unroll
    for (int j = 0; j < 15; j++) {
      const uint4 v = lds128(sb + OFF_CS + c * 240 + j * 16);
      cs[4 * j] = __uint_as_float(v.x); cs[4 * j + 1] = __uint_as_float(v.y); cs[4 * j + 2] = __uint_as_float(v.z); cs[4 * j + 3] = __uint_as_float(v.w);
    }
    const bool first = (mt == 0) && (w4 == 0);
    uint4* const kvd = pin(w4 < 3 ? (uint4*)(smem + OFF_KV + (wg * 3 + w4) * 2560) + lane : &g_own[cid].halo[wg][0][lane]);
    wgmma_wait<1>();
    if ((tid & 127) < 2) mbar_arrive_cta(bar_empty + 16, tid & 1);
    wgmma_wait<0>();
#pragma unroll
    for (int i = 0; i < 120; i++) asm volatile("" : "+f"(acc[i]) :: "memory");
    TS(2);
    uint32_t Qlo[10], Qhi[10], Klo[10], Khi[10], Vlo[10], Vhi[10];
    const float ml_ = -slo.x, mh_ = -shi.x;
#pragma unroll
    for (int t = 0; t < 10; t++) {
      const int k = KT(t), v = VT(t);
      Khi[t] = pack_bf16(fmaf(mh_, cs[2 * k], acc[4 * k + 2]), fmaf(mh_, cs[2 * k + 1], acc[4 * k + 3]));
      Vhi[t] = pack_bf16(fmaf(mh_, cs[2 * v], acc[4 * v + 2]) * shi.y, fmaf(mh_, cs[2 * v + 1], acc[4 * v + 3]) * shi.y);
    }
    st_pkt(kvd, Khi[0], Khi[1], Khi[3], Khi[4]);
    st_pkt(kvd + 32, Khi[5], Khi[6], Khi[8], Khi[9]);
    st_pkt(kvd + 64, Khi[2], Khi[7], Vhi[0], Vhi[1]);
    st_pkt(kvd + 96, Vhi[2], Vhi[3], Vhi[4], Vhi[5]);
    st_pkt(kvd + 128, Vhi[6], Vhi[7], Vhi[8], Vhi[9]);
#pragma unroll
    for (int t = 0; t < 10; t++) {
      const int q = QT(t), k = KT(t), v = VT(t);
      Vhi[t] = movm(Vhi[t]);
      Klo[t] = pack_bf16(fmaf(ml_, cs[2 * k], acc[4 * k]), fmaf(ml_, cs[2 * k + 1], acc[4 * k + 1]));
      Vlo[t] = movm(pack_bf16(fmaf(ml_, cs[2 * v], acc[4 * v]) * slo.y, fmaf(ml_, cs[2 * v + 1], acc[4 * v + 1]) * slo.y));
      Qlo[t] = pack_bf16(fmaf(ml_, cs[2 * q], acc[4 * q]), fmaf(ml_, cs[2 * q + 1], acc[4 * q + 1]));
      Qhi[t] = pack_bf16(fmaf(mh_, cs[2 * q], acc[4 * q + 2]), fmaf(mh_, cs[2 * q + 1], acc[4 * q + 3]));
    }
    const bool in0 = 2 * c <= r, in1 = 2 * c + 1 <= r;
    const uint32_t mL = (in0 ? 0xffffu : 0u) | (in1 ? 0xffff0000u : 0u);
    const float qs = 0.22360679774997896f * 1.4426950408889634f;
    const uint32_t kb0 = stb + (2 * c + (in0 ? 8 : 0)) * 8 + 4, kb1 = stb + (2 * c + 1 + (in1 ? 8 : 0)) * 8 + 4;
    const float scl0 = lds32f(kb0) * slo.y * qs, scl1 = lds32f(kb1) * slo.y * qs;
    const float sch0 = lds32f(kb0 + 64) * shi.y * qs, sch1 = lds32f(kb1 + 64) * shi.y * qs;
    const float bias0 = (first && !in0) ? -INFINITY : 0.f, bias1 = (first && !in1) ? -INFINITY : 0.f;
    const uint32_t tag = __float_as_uint(lds32f(sb + OFF_WR + 324));
    const int slot = mt * 8 + warp;
    int guard = SPIN_MAX;
    uint4 pv[5];
    {
      const uint4* s = first ? kvd : w4 > 0 ? (const uint4*)(smem + OFF_KV + (wg * 3 + w4 - 1) * 2560) + lane : &g_own[cid - 8].halo[wg][0][lane];
      do {
#pragma unroll
        for (int j = 0; j < 5; j++) pv[j] = ld_pkt(s + 32 * j);
      } while (anyw(pv[0].x == SENT || pv[1].x == SENT || pv[2].x == SENT || pv[3].x == SENT || pv[4].x == SENT) && --guard);
    }
    TS(4);
    const uint32_t Kp[10] = {pv[0].x, pv[0].y, pv[2].x, pv[0].z, pv[0].w, pv[1].x, pv[1].y, pv[2].y, pv[1].z, pv[1].w};
    const uint32_t Vp[10] = {movm(pv[2].z), movm(pv[2].w), movm(pv[3].x), movm(pv[3].y), movm(pv[3].z), movm(pv[3].w), movm(pv[4].x), movm(pv[4].y), movm(pv[4].z), movm(pv[4].w)};
    const bool cA = c < 2, nA = r < 4;
    const uint32_t ONES = 0x3f803f80u;
    uint32_t of[20];
#pragma unroll
    for (int hp = 0; hp < 2; hp++) {
      float o[6][4];
#pragma unroll
      for (int hh = 0; hh < 2; hh++) {
        const int ta = 5 * hp + 3 * hh, ts = 5 * hp + 2;
        const bool mine = hh == 0 ? cA : !cA;
        const uint32_t e0 = mine ? Qlo[ts] : 0u, e1 = mine ? Qhi[ts] : 0u;
        float sp[4], sl[4], sh[4];
        mma_k24(sp, Qlo[ta], Qhi[ta], Qlo[ta + 1], Qhi[ta + 1], Kp[ta], Kp[ta + 1], e0, e1, Kp[ts]);
        mma_k24(sl, Qlo[ta], Qhi[ta], Qlo[ta + 1], Qhi[ta + 1], Klo[ta], Klo[ta + 1], e0, e1, Klo[ts]);
        mma_k24(sh, Qlo[ta], Qhi[ta], Qlo[ta + 1], Qhi[ta + 1], Khi[ta], Khi[ta + 1], e0, e1, Khi[ts]);
        const float tl0 = fmaf(in0 ? sl[0] : sp[0], scl0, bias0), tl1 = fmaf(in1 ? sl[1] : sp[1], scl1, bias1);
        const float th0 = (in0 ? sh[2] : sl[2]) * sch0, th1 = (in1 ? sh[3] : sl[3]) * sch1;
        float ml = fmaxf(tl0, tl1), mh = fmaxf(th0, th1);
        ml = fmaxf(ml, shx(ml, 1)); mh = fmaxf(mh, shx(mh, 1));
        ml = fmaxf(ml, shx(ml, 2)); mh = fmaxf(mh, shx(mh, 2));
        const uint32_t Pl = pack_bf16(ex2(tl0 - ml), ex2(tl1 - ml)), Ph = pack_bf16(ex2(th0 - mh), ex2(th1 - mh));
        const uint32_t a0 = Pl & mL, a1 = Ph & ~mL, a3 = Ph & mL, ap = Pl & ~mL;
        const bool vm = hh == 0 ? nA : !nA;
        mma_k24(o[3 * hh], a0, a1, 0u, a3, Vlo[ta], Vhi[ta], ap, 0u, Vp[ta]);
        mma_k24(o[3 * hh + 1], a0, a1, 0u, a3, Vlo[ta + 1], Vhi[ta + 1], ap, 0u, Vp[ta + 1]);
        mma_k24(o[3 * hh + 2], a0, a1, 0u, a3, vm ? Vlo[ts] : ONES, vm ? Vhi[ts] : ONES, ap, 0u, vm ? Vp[ts] : ONES);
      }
      const float il = rcp(cA ? o[5][0] : o[2][0]), ih = rcp(cA ? o[5][2] : o[2][2]);
      const float jl = shx(il, 2), jh = shx(ih, 2);
      const float al = cA ? jl : il, ah = cA ? jh : ih, bl = cA ? il : jl, bh = cA ? ih : jh;
      const int t0 = 5 * hp;
      of[2 * t0]     = pack_bf16(o[0][0] * al, o[0][1] * al); of[2 * t0 + 1] = pack_bf16(o[0][2] * ah, o[0][3] * ah);
      of[2 * t0 + 2] = pack_bf16(o[1][0] * al, o[1][1] * al); of[2 * t0 + 3] = pack_bf16(o[1][2] * ah, o[1][3] * ah);
      of[2 * t0 + 4] = pack_bf16((cA ? o[2][0] : o[5][0]) * jl, (cA ? o[2][1] : o[5][1]) * jl);
      of[2 * t0 + 5] = pack_bf16((cA ? o[2][2] : o[5][2]) * jh, (cA ? o[2][3] : o[5][3]) * jh);
      of[2 * t0 + 6] = pack_bf16(o[3][0] * bl, o[3][1] * bl); of[2 * t0 + 7] = pack_bf16(o[3][2] * bh, o[3][3] * bh);
      of[2 * t0 + 8] = pack_bf16(o[4][0] * bl, o[4][1] * bl); of[2 * t0 + 9] = pack_bf16(o[4][2] * bh, o[4][3] * bh);
    }
    bar_sync(1, 256);
    {
      const uint32_t os = sb + OFF_W1 + warp * 2560, oa = os + ((lane >> 3) & 1) * 1280 + (lane >> 4) * 128 + (lane & 7) * 16;
#pragma unroll
      for (int s = 0; s < 5; s++) stsm4(oa + s * 256, of[4 * s], of[4 * s + 1], of[4 * s + 2], of[4 * s + 3]);
      asm volatile("fence.proxy.async.shared::cta;" ::: "memory");
      __syncwarp();
      if (elect()) {
        asm volatile("cp.async.bulk.global.shared::cta.bulk_group [%0], [%1], 2560;\ncp.async.bulk.commit_group;" :: "l"(&g_o[mt * 2 + wg][g][w4 * 160]), "r"(os) : "memory");
      }
    }
    TS(5);
    float h[40];
#pragma unroll
    for (int s = 0; s < 5; s++) {
      const uint4 v = xr[s];
      h[8 * s] = bf_lo(v.x); h[8 * s + 1] = bf_hi(v.x); h[8 * s + 2] = bf_lo(v.y); h[8 * s + 3] = bf_hi(v.y);
      h[8 * s + 4] = bf_lo(v.z); h[8 * s + 5] = bf_hi(v.z); h[8 * s + 6] = bf_lo(v.w); h[8 * s + 7] = bf_hi(v.w);
    }
    mbar_wait(bar_full, 0); mbar_wait(bar_full + 8, 0); mbar_wait(bar_full + 16, 1);
    uint64_t dwo = make_desc(sb, 5120, 512, 2);
    wgmma_fence();
#pragma unroll
    for (int s = 0; s < 5; s++) wgmma_n80_rs(h, of[4 * s], of[4 * s + 1], of[4 * s + 2], of[4 * s + 3], dwo + g * 960 + s * 64, 1);
    wgmma_commit();
    if (elect()) {
      asm volatile("cp.async.bulk.wait_group 0;" ::: "memory");
      stg_rlx32(&g_own[mt * 8 + wg * 4].oflag[g * 4 + w4], tag);
    }
    asm volatile("bar.arrive %0, 160;" :: "r"(5 + wg) : "memory");
    TS(6);
#pragma unroll 1
    for (int i = 0, sl = 0; i < 7; i++) {
      mbar_wait(bar_o + wg * 64 + 8 * sl, i >= 3 && i < 6);
      if (i == 0) TS(1);
      const uint64_t da = make_desc(sb + OFF_W1 + sl * 20480 + wg * 10240, 128, 1280, 0), db = dwo + (i + (i >= g)) * 960;
      wgmma_fence();
#pragma unroll
      for (int s = 0; s < 5; s++) wgmma_n80_ss(h, da + s * 16, db + s * 64, 1);
      wgmma_commit();
      wgmma_wait<1>();
      if ((tid & 127) == 0 && i > 0 && i < 6) mbar_arrive(i == 5 ? bar_ssd : bar_o + wg * 64 + 32 + 8 * (sl == 0 ? 2 : sl - 1));
      sl = sl == 2 ? 0 : sl + 1;
    }
    const bool odd = c & 1;
    float wr[20];
#pragma unroll
    for (int j = 0; j < 5; j++) {
      const uint4 v = lds128(sb + OFF_WR + c * 80 + j * 16);
      wr[4 * j] = __uint_as_float(v.x); wr[4 * j + 1] = __uint_as_float(v.y); wr[4 * j + 2] = __uint_as_float(v.z); wr[4 * j + 3] = __uint_as_float(v.w);
    }
    const float wsum = lds32f(sb + OFF_WR + 320);
    uint4* const sp = pin(&g_own[slot].st2[r + (odd ? 8 : 0)]);
    uint2* const kp = pin(&g_x.key[c][slot]);
    uint4* const cdp = pin(&g_x.cand[slot][g][0]);
    const int tok0 = mt * 128 + 32 * w4 + wg;
    wgmma_wait<0>();
#pragma unroll
    for (int i = 0; i < 40; i++) asm volatile("" : "+f"(h[i]) :: "memory");
    TS(7);
    float mean, rstd, rr;
    {
      float l1 = 0.f, l2 = 0.f, l3 = 0.f, h1 = 0.f, h2 = 0.f, h3 = 0.f;
#pragma unroll
      for (int j = 0; j < 10; j++) {
        l1 += h[4 * j] + h[4 * j + 1]; h1 += h[4 * j + 2] + h[4 * j + 3];
        l2 = fmaf(h[4 * j], h[4 * j], l2); l2 = fmaf(h[4 * j + 1], h[4 * j + 1], l2);
        h2 = fmaf(h[4 * j + 2], h[4 * j + 2], h2); h2 = fmaf(h[4 * j + 3], h[4 * j + 3], h2);
        l3 = fmaf(h[4 * j], wr[2 * j], l3); l3 = fmaf(h[4 * j + 1], wr[2 * j + 1], l3);
        h3 = fmaf(h[4 * j + 2], wr[2 * j], h3); h3 = fmaf(h[4 * j + 3], wr[2 * j + 1], h3);
      }
      float s1 = (odd ? h1 : l1) + shx(odd ? l1 : h1, 1), s2 = (odd ? h2 : l2) + shx(odd ? l2 : h2, 1), s3 = (odd ? h3 : l3) + shx(odd ? l3 : h3, 1);
      s1 += shx(s1, 2); s2 += shx(s2, 2); s3 += shx(s3, 2);
      if (cA) asm volatile("red.relaxed.gpu.global.add.v4.f32 [%0], {%1, %2, %3, %4};" :: "l"(sp), "f"(s1), "f"(s2), "f"(s3), "f"(1.f) : "memory");
      uint4 p0;
      do { p0 = ldg_pkt(sp); } while (anyw(p0.w != 0x41000000u) && --guard > 0);
      mean = __uint_as_float(p0.x) * (1.f / 640.f);
      rstd = rsq(fmaxf(fmaf(-mean, mean, __uint_as_float(p0.y) * (1.f / 640.f)), 0.f) + 1e-5f);
      rr = fmaf(-mean, wsum, __uint_as_float(p0.z)) * rstd;
    }
    TS(8);
    const uint32_t kk = ord_key(rr), kmax = __reduce_max_sync(0xffffffffu, kk);
    const int L = __ffs(__ballot_sync(0xffffffffu, kk == kmax)) - 1;
    const int crow = (L >> 2) + 8 * (L & 1);
    if (warp == g) {
      if (lane < 4) stg_rlx64(kp, kmax, tok0 + 2 * crow);
      asm volatile("bar.arrive 3, 64;" ::: "memory");
    }
    const uint32_t stg = sb + OFF_W1 + warp * 2560;
    uint4 held;
    {
      const float om = shx(mean, 1), os = shx(rstd, 1);
      const float rl = odd ? os : rstd, rh = odd ? rstd : os;
      const float bl = -(odd ? om : mean) * rl, bh = -(odd ? mean : om) * rh, al = 1.f + rl, ah = 1.f + rh;
      if ((L >> 2) == r) {
        const bool chi = L & 1;
        const float rc = chi ? rh : rl, bc = chi ? bh : bl;
        uint32_t n[10];
#pragma unroll
        for (int j = 0; j < 10; j++) n[j] = pack_bf16(fmaf(chi ? h[4 * j + 2] : h[4 * j], rc, bc), fmaf(chi ? h[4 * j + 3] : h[4 * j + 1], rc, bc));
        uint4* d = cdp + 3 * c;
        stg_pkt(d, n[0], n[1], n[2], n[3]); stg_pkt(d + 1, n[4], n[5], n[6], n[7]); stg_rlx64(d + 2, n[8], n[9]);
      }
      __syncwarp();
      const uint32_t fa = stg + (lane & 15) * 160 + (lane >> 4) * 16;
#pragma unroll
      for (int s = 0; s < 5; s++)
        stsm4(fa + s * 32, pack_bf16(fmaf(h[8 * s], al, bl), fmaf(h[8 * s + 1], al, bl)), pack_bf16(fmaf(h[8 * s + 2], ah, bh), fmaf(h[8 * s + 3], ah, bh)),
              pack_bf16(fmaf(h[8 * s + 4], al, bl), fmaf(h[8 * s + 5], al, bl)), pack_bf16(fmaf(h[8 * s + 6], ah, bh), fmaf(h[8 * s + 7], ah, bh)));
      __syncwarp();
      held = lds128(stg + crow * 160 + min(lane, 9) * 16);
      if (lane < 10) stg_pkt(cdp + 12 + lane, held.x, held.y, held.z, held.w);
    }
    TS(9);
    mbar_wait(bar_ffn, 0);
    const uint32_t red = sb + OFF_RED;
    if (ffn1) {
      uint4 w1[4][5];
      {
        const int k = (lane & 7) + (lane >> 4) * 8;
        const uint32_t a1 = sb + k * 64, sw = ((lane >> 3) & 1) ^ ((lane >> 1) & 3);
#pragma unroll
        for (int s = 0; s < 5; s++)
#pragma unroll
          for (int u = 0; u < 4; u++)
            w1[u][s] = ldsm4t(a1 + (s < 4 ? warp * 4096 + s * 1024 : 32768 + warp * 1024) + (u >> 1) * (40960 + (s == 4 || warp >= 6 ? OFF_W1 : 0)) + ((sw ^ (2 * (u & 1))) * 16));
      }
      const char* p = pin((const char*)&g_x.cand[0][warp][3 * c]);
      uint32_t* const ap = pin(g_x.act + fj * 16 + (lane >> 1));
      mbar_wait(bar_win, 0);
      p += lds128(sb + OFF_WR + 336).w;
      TS(10);
      uint4 c0, c1; uint2 c2;
      do { c0 = ldg_pkt(p); c1 = ldg_pkt(p + 16); c2 = ldg_rlx64(p + 32); } while (anyw(c0.x == SENT || c1.x == SENT || c2.x == SENT) && --guard > 0);
      float a[4][4];
#pragma unroll
      for (int u = 0; u < 4; u++) {
        a[u][0] = a[u][1] = a[u][2] = a[u][3] = 0.f;
        mma_acc(a[u], w1[u][0], c0.x, c0.y); mma_acc(a[u], w1[u][1], c0.z, c0.w); mma_acc(a[u], w1[u][2], c1.x, c1.y);
        mma_acc(a[u], w1[u][3], c1.z, c1.w); mma_acc(a[u], w1[u][4], c2.x, c2.y);
      }
      asm volatile("st.shared.v2.f32 [%0], {%1, %2};" :: "r"(red + (warp * 32 + c * 8 + r) * 8),
                   "f"(cA ? (odd ? a[0][2] : a[0][0]) : (odd ? a[1][2] : a[1][0])), "f"(cA ? (odd ? a[2][2] : a[2][0]) : (odd ? a[3][2] : a[3][0])) : "memory");
      bar_sync(1, 256);
      if (warp == 0) {
        float2 t[8];
#pragma unroll
        for (int i = 0; i < 8; i++) t[i] = lds64f(red + (i * 32 + lane) * 8);
        const float s = ((t[0].x + t[1].x) + (t[2].x + t[3].x)) + ((t[4].x + t[5].x) + (t[6].x + t[7].x));
        const float u = ((t[0].y + t[1].y) + (t[2].y + t[3].y)) + ((t[4].y + t[5].y) + (t[6].y + t[7].y));
        const float av = s * u * rcp(1.f + ex2(-1.4426950408889634f * s));
        const float an = shx(av, 1);
        if (!odd) stg_rlx32(ap, pack_bf16(av, an));
      }
      bar_sync(1, 256);
      TS(11);
    }
    char* const ob2 = (char*)(out + tok0 * 640 + g * 64);
    const int remo = 896 - 96 * g;
#pragma unroll
    for (int s = 0; s < 5; s++) {
      const int row = s < 4 ? 4 * s + (lane >> 3) : lane >> 1, pc = s < 4 ? lane & 7 : 8 + (lane & 1);
      const uint4 v = lds128(stg + row * 160 + pc * 16);
      if (row != crow) stg128(ob2 + row * 2560 + pc * 16 + (s < 4 ? 0 : remo), v);
    }
    mbar_wait(bar_win, 0);
    const uint4 win = lds128(sb + OFF_WR + 336);
    if (win.x != slot && lane < 10) stg128(ob2 + crow * 2560 + lane * 16 + (lane < 8 ? 0 : remo), held);
    if (!ffn1) {
      TS(10);
      uint4 w2[6];
      const uint32_t a2 = sb + OFF_W2 + (warp * 192 + 24 * (((lane >> 3) & 1) * 4 + ((lane & 7) >> 1)) + 2 * (lane >> 4) + (lane & 1)) * 16;
#pragma unroll
      for (int s = 0; s < 6; s++) w2[s] = ldsm4t(a2 + s * 64);
      const uint4* p = (const uint4*)(g_x.act + warp * 96 + ((r & 1) * 4 + c) * 12);
      const uint32_t* pb = (const uint32_t*)&g_x.cand[win.x][fj < 64 ? fj >> 3 : (fj - 64) >> 1][fj < 64 ? 12 + (fj & 7) : 20 + (fj & 1)] + c;
      uint32_t* const op = pin((uint32_t*)(out + win.y * 640 + fj * 8) + c);
      uint4 c0, c1, c2; uint32_t bw;
      do {
        c0 = ldg_pkt(p); c1 = ldg_pkt(p + 1); c2 = ldg_pkt(p + 2); bw = ldg_rlx32(pb);
      } while (anyw(max(max(max(max(c0.x, c0.y), max(c0.z, c0.w)), max(max(c1.x, c1.y), max(c1.z, c1.w))), max(max(max(c2.x, c2.y), max(c2.z, c2.w)), bw)) == SENT) && --guard > 0);
      TS(11);
      float a[4] = {0.f, 0.f, 0.f, 0.f}, b[4] = {0.f, 0.f, 0.f, 0.f}, d[4] = {0.f, 0.f, 0.f, 0.f};
      mma_acc(a, w2[0], c0.x, c0.y); mma_acc(b, w2[2], c1.x, c1.y); mma_acc(d, w2[4], c2.x, c2.y);
      mma_acc(a, w2[1], c0.z, c0.w); mma_acc(b, w2[3], c1.z, c1.w); mma_acc(d, w2[5], c2.z, c2.w);
      if (c == 0) sts32f(red + (warp * 8 + r) * 4, ((a[0] + a[3]) + (b[0] + b[3])) + (d[0] + d[3]));
      bar_sync(1, 256);
      if (tid < 4) {
        float2 t[8];
#pragma unroll
        for (int i = 0; i < 8; i++) t[i] = lds64f(red + (i * 4 + tid) * 8);
        const float y0 = ((t[0].x + t[1].x) + (t[2].x + t[3].x)) + ((t[4].x + t[5].x) + (t[6].x + t[7].x));
        const float y1 = ((t[0].y + t[1].y) + (t[2].y + t[3].y)) + ((t[4].y + t[5].y) + (t[6].y + t[7].y));
        const float sg = __uint_as_float(win.z);
        *op = pack_bf16(fmaf(y0, sg, bf_lo(bw)), fmaf(y1, sg, bf_hi(bw)));
      }
    }
    TS(12);
#undef TS_T
  }
}

typedef CUresult (*EncodeFn)(CUtensorMap*, CUtensorMapDataType, cuuint32_t, void*, const cuuint64_t*, const cuuint64_t*, const cuuint32_t*,
                             const cuuint32_t*, CUtensorMapInterleave, CUtensorMapSwizzle, CUtensorMapL2promotion, CUtensorMapFloatOOBfill);

void make_map(EncodeFn enc, CUtensorMap* m, const void* base, const cuuint64_t* dims, const cuuint64_t* strides, const cuuint32_t* box,
              CUtensorMapSwizzle swz) {
  const cuuint32_t es[3] = {1, 1, 1};
  enc(m, CU_TENSOR_MAP_DATA_TYPE_BFLOAT16, 3, (void*)base, dims, strides, box, es, CU_TENSOR_MAP_INTERLEAVE_NONE, swz,
      CU_TENSOR_MAP_L2_PROMOTION_L2_128B, CU_TENSOR_MAP_FLOAT_OOB_FILL_NONE);
}

}

extern "C" void kernel_launch(void* const* d_in, const int* in_sizes, int n_in, void* d_out, int out_size) {
  const __nv_bfloat16* x = (const __nv_bfloat16*)d_in[0];
  const __nv_bfloat16* wqkv = (const __nv_bfloat16*)d_in[1];
  const __nv_bfloat16* wo = (const __nv_bfloat16*)d_in[2];
  void* fn = nullptr;
  cudaDriverEntryPointQueryResult st;
  cudaGetDriverEntryPoint("cuTensorMapEncodeTiled", &fn, cudaEnableDefault, &st);
  EncodeFn enc = (EncodeFn)fn;
  void* scp = nullptr;
  cudaGetSymbolAddress(&scp, g_scratch);
  Maps tm;
  { const cuuint64_t d[3] = {640, 1024, 2}, s[2] = {2560, 1280}; const cuuint32_t b[3] = {64, 64, 2}; make_map(enc, &tm.x, x, d, s, b, CU_TENSOR_MAP_SWIZZLE_128B); }
  { const cuuint64_t d[3] = {640, 640, 3}, s[2] = {3840, 1280}; const cuuint32_t b[3] = {64, 64, 1}; make_map(enc, &tm.w, wqkv, d, s, b, CU_TENSOR_MAP_SWIZZLE_128B); }
  { const cuuint64_t d[3] = {640, 640, 3}, s[2] = {3840, 1280}; const cuuint32_t b[3] = {16, 64, 3}; make_map(enc, &tm.wr, wqkv, d, s, b, CU_TENSOR_MAP_SWIZZLE_32B); }
  { const cuuint64_t d[3] = {32, 640, 20}, s[2] = {1280, 64}; const cuuint32_t b[3] = {32, 80, 2}; make_map(enc, &tm.wo, wo, d, s, b, CU_TENSOR_MAP_SWIZZLE_64B); }
  { const cuuint64_t d[3] = {640, 640, 1}, s[2] = {1280, 819200}; const cuuint32_t b[3] = {16, 80, 1}; make_map(enc, &tm.wor, wo, d, s, b, CU_TENSOR_MAP_SWIZZLE_64B); }
  { const cuuint64_t d[3] = {1536, 640, 1}, s[2] = {3072, 1966080}; const cuuint32_t b[3] = {32, 128, 1};
    make_map(enc, &tm.gate, d_in[5], d, s, b, CU_TENSOR_MAP_SWIZZLE_64B); make_map(enc, &tm.up, d_in[6], d, s, b, CU_TENSOR_MAP_SWIZZLE_64B); }
  { const cuuint64_t d[3] = {640, 1536, 1}, s[2] = {1280, 1966080}; const cuuint32_t b[3] = {8, 128, 1}; make_map(enc, &tm.down, d_in[7], d, s, b, CU_TENSOR_MAP_SWIZZLE_NONE); }
  cudaFuncSetAttribute(fused_kernel, cudaFuncAttributeMaxDynamicSharedMemorySize, SMEM_BYTES);
  fused_kernel<<<128, 384, SMEM_BYTES, cudaStreamPerThread>>>(x, wqkv, wo, (const __nv_bfloat16*)d_in[4], (const __nv_bfloat16*)d_in[5],
                                                              (const __nv_bfloat16*)d_in[6], (const __nv_bfloat16*)d_in[7], (__nv_bfloat16*)d_out, (Scratch*)scp, tm);
}
```

```cpp
#include <cuda_runtime.h>
#include <cuda_bf16.h>
#include <cuda.h>
#include <stdint.h>

#define PF0 1
#define PF_NS 100
#define PFX_IT 1
#define PFW_IT 2
#define F_IT 5
#define F_MAX 12
#define F_PER 2
#define OUT_LATE 0
#define REG_P 72
#define REG_C 216
#define AUX_NS 50
#define PINGPONG 1

namespace {

constexpr int SLOT    = 47104;
constexpr int OFF_O   = 122880;
constexpr int OFF_W2  = 4 * SLOT;
constexpr int OFF_CS  = OFF_W2 + 32768;
constexpr int OFF_RS  = OFF_CS + 3840;
constexpr int OFF_MN  = OFF_RS + 576;
constexpr int OFF_WR  = OFF_MN + 1024;
constexpr int OFF_RED = OFF_CS;
constexpr int OFF_PT  = OFF_WR + 352;
constexpr int OFF_BAR = OFF_PT + 768;
constexpr int SMEM_BYTES = OFF_BAR + 240 + 288;
constexpr uint32_t SENT = 0xFFFFFFFFu;
constexpr int SPIN_MAX = 1 << 20;

struct Glob {
  uint4 cand[128][8][24];
  uint2 key[4][128];
  uint32_t act[768];
  uint32_t pad[256];
};
constexpr int GLOB_PER_CTA = sizeof(Glob) / 16 / 128;
static_assert(GLOB_PER_CTA * 128 * 16 == sizeof(Glob), "glob size");
struct Own {
  uint4 halo[2][5][32];
  uint4 st1[32];
  uint2 cs[32];
  uint32_t oflag[32];
  uint4 st2[16];
};
struct Scratch {
  Glob x;
  Own own[128];
  uint4 o[32][8][640];
  uint32_t epoch[128];
};
__device__ __align__(128) Scratch g_scratch;
#define g_x (sc->x)
#define g_own (sc->own)
#define g_o (sc->o)
#define g_epoch (sc->epoch)
#define TS(i)

__device__ __forceinline__ void mbar_init(uint32_t bar, uint32_t cnt) { asm volatile("mbarrier.init.shared::cta.b64 [%0], %1;" :: "r"(bar), "r"(cnt) : "memory"); }
__device__ __forceinline__ void mbar_expect_tx(uint32_t bar, uint32_t bytes) { asm volatile("mbarrier.arrive.expect_tx.shared::cta.b64 _, [%0], %1;" :: "r"(bar), "r"(bytes) : "memory"); }
__device__ __forceinline__ void mbar_arrive(uint32_t bar) { asm volatile("mbarrier.arrive.shared::cta.b64 _, [%0];" :: "r"(bar) : "memory"); }
__device__ __forceinline__ void mbar_arrive_cta(uint32_t bar, uint32_t cta) {
  asm volatile("{\n.reg .b32 ra;\nmapa.shared::cluster.u32 ra, %0, %1;\nmbarrier.arrive.shared::cluster.b64 _, [ra];\n}\n" :: "r"(bar), "r"(cta) : "memory");
}
__device__ __forceinline__ void mbar_wait(uint32_t bar, uint32_t parity) {
  asm volatile("{\n.reg .pred p;\n.reg .u32 n;\nmov.u32 n, 0;\nW:\nmbarrier.try_wait.parity.shared::cta.b64 p, [%0], %1;\n@p bra.uni D;\n"
               "add.u32 n, n, 1;\nsetp.lt.u32 p, n, %2;\n@p bra.uni W;\nD:\n}\n" :: "r"(bar), "r"(parity), "n"(SPIN_MAX) : "memory");
}
__device__ __forceinline__ void tma_3d(uint32_t dst, const void* tm, uint32_t bar, int c0, int c1, int c2) {
  asm volatile("cp.async.bulk.tensor.3d.shared::cluster.global.mbarrier::complete_tx::bytes [%0], [%1, {%3, %4, %5}], [%2];" :: "r"(dst), "l"(tm), "r"(bar), "r"(c0), "r"(c1), "r"(c2) : "memory");
}
__device__ __forceinline__ void tma_3d_mc(uint32_t dst, const void* tm, uint32_t bar, int c0, int c1, int c2) {
  asm volatile("cp.async.bulk.tensor.3d.shared::cluster.global.mbarrier::complete_tx::bytes.multicast::cluster [%0], [%1, {%3, %4, %5}], [%2], %6;" :: "r"(dst), "l"(tm), "r"(bar), "r"(c0), "r"(c1), "r"(c2), "h"((uint16_t)3) : "memory");
}
__device__ __forceinline__ void wgmma_fence() { asm volatile("wgmma.fence.sync.aligned;" ::: "memory"); }
__device__ __forceinline__ void wgmma_commit() { asm volatile("wgmma.commit_group.sync.aligned;" ::: "memory"); }
template <int N> __device__ __forceinline__ void wgmma_wait() { asm volatile("wgmma.wait_group.sync.aligned %0;" :: "n"(N) : "memory"); }
__device__ __forceinline__ uint64_t make_desc(uint32_t addr, uint32_t lbo, uint32_t sbo, uint32_t swz) {
  return (uint64_t)(((addr & 0x3FFFF) >> 4) | ((lbo >> 4) << 16)) | ((uint64_t)((sbo >> 4) | (swz << 30)) << 32);
}
__device__ __forceinline__ void bar_sync(int id, int n) { asm volatile("bar.sync %0, %1;" :: "r"(id), "r"(n) : "memory"); }
__device__ __forceinline__ uint4 ld_pkt(const void* p) {
  uint4 v;
  asm volatile("{\n.reg .b128 t;\n.reg .b64 lo, hi;\nld.relaxed.gpu.b128 t, [%4];\nmov.b128 {lo, hi}, t;\nmov.b64 {%0, %1}, lo;\nmov.b64 {%2, %3}, hi;\n}\n"
               : "=r"(v.x), "=r"(v.y), "=r"(v.z), "=r"(v.w) : "l"(p) : "memory");
  return v;
}
__device__ __forceinline__ void st_pkt(void* p, uint32_t a, uint32_t b, uint32_t c, uint32_t d) {
  asm volatile("{\n.reg .b128 t;\n.reg .b64 lo, hi;\nmov.b64 lo, {%1, %2};\nmov.b64 hi, {%3, %4};\nmov.b128 t, {lo, hi};\nst.relaxed.gpu.b128 [%0], t;\n}\n"
               :: "l"(p), "r"(a), "r"(b), "r"(c), "r"(d) : "memory");
}
__device__ __forceinline__ uint4 ldg_pkt(const void* p) {
  uint4 v;
  asm volatile("{\n.reg .b128 t;\n.reg .b64 lo, hi;\nld.relaxed.gpu.global.b128 t, [%4];\nmov.b128 {lo, hi}, t;\nmov.b64 {%0, %1}, lo;\nmov.b64 {%2, %3}, hi;\n}\n"
               : "=r"(v.x), "=r"(v.y), "=r"(v.z), "=r"(v.w) : "l"(p) : "memory");
  return v;
}
__device__ __forceinline__ void stg_pkt(void* p, uint32_t a, uint32_t b, uint32_t c, uint32_t d) {
  asm volatile("{\n.reg .b128 t;\n.reg .b64 lo, hi;\nmov.b64 lo, {%1, %2};\nmov.b64 hi, {%3, %4};\nmov.b128 t, {lo, hi};\nst.relaxed.gpu.global.b128 [%0], t;\n}\n"
               :: "l"(p), "r"(a), "r"(b), "r"(c), "r"(d) : "memory");
}
__device__ __forceinline__ uint32_t ldg_rlx32(const void* p) { uint32_t v; asm volatile("ld.relaxed.gpu.global.u32 %0, [%1];" : "=r"(v) : "l"(p) : "memory"); return v; }
__device__ __forceinline__ uint2 ldg_rlx64(const void* p) { uint2 v; asm volatile("ld.relaxed.gpu.global.v2.u32 {%0, %1}, [%2];" : "=r"(v.x), "=r"(v.y) : "l"(p) : "memory"); return v; }
__device__ __forceinline__ void stg128(void* p, const uint4& v) { asm volatile("st.global.v4.u32 [%0], {%1, %2, %3, %4};" :: "l"(p), "r"(v.x), "r"(v.y), "r"(v.z), "r"(v.w) : "memory"); }
template <class T> __device__ __forceinline__ T* pin(T* p) { asm volatile("" : "+l"(p)); return p; }
__device__ __forceinline__ void stg_rlx32(void* p, uint32_t v) { asm volatile("st.relaxed.gpu.global.u32 [%0], %1;" :: "l"(p), "r"(v) : "memory"); }
__device__ __forceinline__ void stg_rlx64(void* p, uint32_t a, uint32_t b) { asm volatile("st.relaxed.gpu.global.v2.u32 [%0], {%1, %2};" :: "l"(p), "r"(a), "r"(b) : "memory"); }
__device__ __forceinline__ uint4 ldsm4(uint32_t a) { uint4 v; asm volatile("ldmatrix.sync.aligned.m8n8.x4.shared.b16 {%0, %1, %2, %3}, [%4];" : "=r"(v.x), "=r"(v.y), "=r"(v.z), "=r"(v.w) : "r"(a) : "memory"); return v; }
__device__ __forceinline__ uint4 ldsm4t(uint32_t a) { uint4 v; asm volatile("ldmatrix.sync.aligned.m8n8.x4.trans.shared.b16 {%0, %1, %2, %3}, [%4];" : "=r"(v.x), "=r"(v.y), "=r"(v.z), "=r"(v.w) : "r"(a) : "memory"); return v; }
__device__ __forceinline__ void stsm4(uint32_t a, uint32_t x, uint32_t y, uint32_t z, uint32_t w) { asm volatile("stmatrix.sync.aligned.m8n8.x4.shared.b16 [%0], {%1, %2, %3, %4};" :: "r"(a), "r"(x), "r"(y), "r"(z), "r"(w) : "memory"); }
__device__ __forceinline__ void mma_acc(float (&c)[4], const uint4& a, uint32_t b0, uint32_t b1) {
  asm("mma.sync.aligned.m16n8k16.row.col.f32.bf16.bf16.f32 {%0,%1,%2,%3}, {%4,%5,%6,%7}, {%8,%9}, {%0,%1,%2,%3};"
      : "+f"(c[0]), "+f"(c[1]), "+f"(c[2]), "+f"(c[3]) : "r"(a.x), "r"(a.y), "r"(a.z), "r"(a.w), "r"(b0), "r"(b1));
}
__device__ __forceinline__ uint4 lds128(uint32_t a) { uint4 v; asm volatile("ld.shared.v4.u32 {%0, %1, %2, %3}, [%4];" : "=r"(v.x), "=r"(v.y), "=r"(v.z), "=r"(v.w) : "r"(a) : "memory"); return v; }
__device__ __forceinline__ float2 lds64f(uint32_t a) { float2 v; asm volatile("ld.shared.v2.f32 {%0, %1}, [%2];" : "=f"(v.x), "=f"(v.y) : "r"(a)); return v; }
__device__ __forceinline__ float lds32f(uint32_t a) { float v; asm volatile("ld.shared.f32 %0, [%1];" : "=f"(v) : "r"(a)); return v; }
__device__ __forceinline__ void sts32f(uint32_t a, float v) { asm volatile("st.shared.f32 [%0], %1;" :: "r"(a), "f"(v) : "memory"); }
__device__ __forceinline__ uint32_t pack_bf16(float lo, float hi) { uint32_t r; asm("cvt.rn.bf16x2.f32 %0, %1, %2;" : "=r"(r) : "f"(hi), "f"(lo)); return r; }
__device__ __forceinline__ float bf_lo(uint32_t v) { return __uint_as_float(v << 16); }
__device__ __forceinline__ float bf_hi(uint32_t v) { return __uint_as_float(v & 0xffff0000u); }
__device__ __forceinline__ uint32_t movm(uint32_t a) { uint32_t d; asm("movmatrix.sync.aligned.m8n8.trans.b16 %0, %1;" : "=r"(d) : "r"(a)); return d; }
__device__ __forceinline__ float ex2(float x) { float y; asm("ex2.approx.ftz.f32 %0, %1;" : "=f"(y) : "f"(x)); return y; }
__device__ __forceinline__ float rsq(float x) { float y; asm("rsqrt.approx.ftz.f32 %0, %1;" : "=f"(y) : "f"(x)); return y; }
__device__ __forceinline__ float rcp(float x) { float y; asm("rcp.approx.ftz.f32 %0, %1;" : "=f"(y) : "f"(x)); return y; }
__device__ __forceinline__ bool elect() { uint32_t p; asm volatile("{\n.reg .pred q;\nelect.sync _|q, 0xffffffff;\nselp.u32 %0, 1, 0, q;\n}\n" : "=r"(p)); return p; }
__device__ __forceinline__ void pf_l2(const void* p) { asm volatile("prefetch.global.L2 [%0];" :: "l"(p)); }
__device__ __forceinline__ bool anyw(bool p) { return __any_sync(0xffffffffu, p); }
__device__ __forceinline__ float shx(float v, int m) { return __shfl_xor_sync(0xffffffffu, v, m); }
__device__ __forceinline__ void mma_k24(float (&c)[4], uint32_t a0, uint32_t a1, uint32_t a2, uint32_t a3, uint32_t b0, uint32_t b1,
                                        uint32_t e0, uint32_t e1, uint32_t f0) {
  asm("mma.sync.aligned.m16n8k16.row.col.f32.bf16.bf16.f32 {%0,%1,%2,%3}, {%4,%5,%6,%7}, {%8,%9}, {%10,%10,%10,%10};"
      : "=f"(c[0]), "=f"(c[1]), "=f"(c[2]), "=f"(c[3]) : "r"(a0), "r"(a1), "r"(a2), "r"(a3), "r"(b0), "r"(b1), "f"(0.f));
  asm("mma.sync.aligned.m16n8k8.row.col.f32.bf16.bf16.f32 {%0,%1,%2,%3}, {%4,%5}, {%6}, {%0,%1,%2,%3};"
      : "+f"(c[0]), "+f"(c[1]), "+f"(c[2]), "+f"(c[3]) : "r"(e0), "r"(e1), "r"(f0));
}
__device__ __forceinline__ uint32_t ord_key(float r) { uint32_t u = __float_as_uint(r); return u ^ ((uint32_t)((int32_t)u >> 31) | 0x80000000u); }

__device__ __forceinline__ void wgmma_n48hi_rk(float (&d)[120], uint32_t a0, uint32_t a1, uint32_t a2, uint32_t a3, uint64_t db, int scale_d) {
  asm volatile("{\n.reg .pred p;\nsetp.ne.b32 p, %29, 0;\n"
    "wgmma.mma_async.sync.aligned.m64n48k16.f32.bf16.bf16 "
    "{%0, %1, %2, %3, %4, %5, %6, %7, %8, %9, %10, %11, %12, %13, %14, %15, "
    "%16, %17, %18, %19, %20, %21, %22, %23}, "
    "{%24, %25, %26, %27}, %28, p, 1, 1, 0;\n}\n"
    : "+f"(d[96]), "+f"(d[97]), "+f"(d[98]), "+f"(d[99]), "+f"(d[100]), "+f"(d[101]), "+f"(d[102]), "+f"(d[103]),
      "+f"(d[104]), "+f"(d[105]), "+f"(d[106]), "+f"(d[107]), "+f"(d[108]), "+f"(d[109]), "+f"(d[110]), "+f"(d[111]),
      "+f"(d[112]), "+f"(d[113]), "+f"(d[114]), "+f"(d[115]), "+f"(d[116]), "+f"(d[117]), "+f"(d[118]), "+f"(d[119])
    : "r"(a0), "r"(a1), "r"(a2), "r"(a3), "l"(db), "r"(scale_d));
}
__device__ __forceinline__ void wgmma_n192lo_rk(float (&d)[120], uint32_t a0, uint32_t a1, uint32_t a2, uint32_t a3, uint64_t db, int scale_d) {
  asm volatile("{\n.reg .pred p;\nsetp.ne.b32 p, %101, 0;\n"
    "wgmma.mma_async.sync.aligned.m64n192k16.f32.bf16.bf16 "
    "{%0, %1, %2, %3, %4, %5, %6, %7, %8, %9, %10, %11, %12, %13, %14, %15, "
    "%16, %17, %18, %19, %20, %21, %22, %23, %24, %25, %26, %27, %28, %29, %30, %31, "
    "%32, %33, %34, %35, %36, %37, %38, %39, %40, %41, %42, %43, %44, %45, %46, %47, "
    "%48, %49, %50, %51, %52, %53, %54, %55, %56, %57, %58, %59, %60, %61, %62, %63, "
    "%64, %65, %66, %67, %68, %69, %70, %71, %72, %73, %74, %75, %76, %77, %78, %79, "
    "%80, %81, %82, %83, %84, %85, %86, %87, %88, %89, %90, %91, %92, %93, %94, %95}, "
    "{%96, %97, %98, %99}, %100, p, 1, 1, 0;\n}\n"
    : "+f"(d[0]), "+f"(d[1]), "+f"(d[2]), "+f"(d[3]), "+f"(d[4]), "+f"(d[5]), "+f"(d[6]), "+f"(d[7]),
      "+f"(d[8]), "+f"(d[9]), "+f"(d[10]), "+f"(d[11]), "+f"(d[12]), "+f"(d[13]), "+f"(d[14]), "+f"(d[15]),
      "+f"(d[16]), "+f"(d[17]), "+f"(d[18]), "+f"(d[19]), "+f"(d[20]), "+f"(d[21]), "+f"(d[22]), "+f"(d[23]),
      "+f"(d[24]), "+f"(d[25]), "+f"(d[26]), "+f"(d[27]), "+f"(d[28]), "+f"(d[29]), "+f"(d[30]), "+f"(d[31]),
      "+f"(d[32]), "+f"(d[33]), "+f"(d[34]), "+f"(d[35]), "+f"(d[36]), "+f"(d[37]), "+f"(d[38]), "+f"(d[39]),
      "+f"(d[40]), "+f"(d[41]), "+f"(d[42]), "+f"(d[43]), "+f"(d[44]), "+f"(d[45]), "+f"(d[46]), "+f"(d[47]),
      "+f"(d[48]), "+f"(d[49]), "+f"(d[50]), "+f"(d[51]), "+f"(d[52]), "+f"(d[53]), "+f"(d[54]), "+f"(d[55]),
      "+f"(d[56]), "+f"(d[57]), "+f"(d[58]), "+f"(d[59]), "+f"(d[60]), "+f"(d[61]), "+f"(d[62]), "+f"(d[63]),
      "+f"(d[64]), "+f"(d[65]), "+f"(d[66]), "+f"(d[67]), "+f"(d[68]), "+f"(d[69]), "+f"(d[70]), "+f"(d[71]),
      "+f"(d[72]), "+f"(d[73]), "+f"(d[74]), "+f"(d[75]), "+f"(d[76]), "+f"(d[77]), "+f"(d[78]), "+f"(d[79]),
      "+f"(d[80]), "+f"(d[81]), "+f"(d[82]), "+f"(d[83]), "+f"(d[84]), "+f"(d[85]), "+f"(d[86]), "+f"(d[87]),
      "+f"(d[88]), "+f"(d[89]), "+f"(d[90]), "+f"(d[91]), "+f"(d[92]), "+f"(d[93]), "+f"(d[94]), "+f"(d[95])
    : "r"(a0), "r"(a1), "r"(a2), "r"(a3), "l"(db), "r"(scale_d));
}
__device__ __forceinline__ void wgmma_n48hi_ss(float (&d)[120], uint64_t da, uint64_t db, int scale_d) {
  asm volatile("{\n.reg .pred p;\nsetp.ne.b32 p, %26, 0;\n"
    "wgmma.mma_async.sync.aligned.m64n48k16.f32.bf16.bf16 "
    "{%0, %1, %2, %3, %4, %5, %6, %7, %8, %9, %10, %11, %12, %13, %14, %15, "
    "%16, %17, %18, %19, %20, %21, %22, %23}, "
    "%24, %25, p, 1, 1, 0, 1;\n}\n"
    : "+f"(d[96]), "+f"(d[97]), "+f"(d[98]), "+f"(d[99]), "+f"(d[100]), "+f"(d[101]), "+f"(d[102]), "+f"(d[103]),
      "+f"(d[104]), "+f"(d[105]), "+f"(d[106]), "+f"(d[107]), "+f"(d[108]), "+f"(d[109]), "+f"(d[110]), "+f"(d[111]),
      "+f"(d[112]), "+f"(d[113]), "+f"(d[114]), "+f"(d[115]), "+f"(d[116]), "+f"(d[117]), "+f"(d[118]), "+f"(d[119])
    : "l"(da), "l"(db), "r"(scale_d));
}
__device__ __forceinline__ void wgmma_n192lo_ss(float (&d)[120], uint64_t da, uint64_t db, int scale_d) {
  asm volatile("{\n.reg .pred p;\nsetp.ne.b32 p, %98, 0;\n"
    "wgmma.mma_async.sync.aligned.m64n192k16.f32.bf16.bf16 "
    "{%0, %1, %2, %3, %4, %5, %6, %7, %8, %9, %10, %11, %12, %13, %14, %15, "
    "%16, %17, %18, %19, %20, %21, %22, %23, %24, %25, %26, %27, %28, %29, %30, %31, "
    "%32, %33, %34, %35, %36, %37, %38, %39, %40, %41, %42, %43, %44, %45, %46, %47, "
    "%48, %49, %50, %51, %52, %53, %54, %55, %56, %57, %58, %59, %60, %61, %62, %63, "
    "%64, %65, %66, %67, %68, %69, %70, %71, %72, %73, %74, %75, %76, %77, %78, %79, "
    "%80, %81, %82, %83, %84, %85, %86, %87, %88, %89, %90, %91, %92, %93, %94, %95}, "
    "%96, %97, p, 1, 1, 0, 1;\n}\n"
    : "+f"(d[0]), "+f"(d[1]), "+f"(d[2]), "+f"(d[3]), "+f"(d[4]), "+f"(d[5]), "+f"(d[6]), "+f"(d[7]),
      "+f"(d[8]), "+f"(d[9]), "+f"(d[10]), "+f"(d[11]), "+f"(d[12]), "+f"(d[13]), "+f"(d[14]), "+f"(d[15]),
      "+f"(d[16]), "+f"(d[17]), "+f"(d[18]), "+f"(d[19]), "+f"(d[20]), "+f"(d[21]), "+f"(d[22]), "+f"(d[23]),
      "+f"(d[24]), "+f"(d[25]), "+f"(d[26]), "+f"(d[27]), "+f"(d[28]), "+f"(d[29]), "+f"(d[30]), "+f"(d[31]),
      "+f"(d[32]), "+f"(d[33]), "+f"(d[34]), "+f"(d[35]), "+f"(d[36]), "+f"(d[37]), "+f"(d[38]), "+f"(d[39]),
      "+f"(d[40]), "+f"(d[41]), "+f"(d[42]), "+f"(d[43]), "+f"(d[44]), "+f"(d[45]), "+f"(d[46]), "+f"(d[47]),
      "+f"(d[48]), "+f"(d[49]), "+f"(d[50]), "+f"(d[51]), "+f"(d[52]), "+f"(d[53]), "+f"(d[54]), "+f"(d[55]),
      "+f"(d[56]), "+f"(d[57]), "+f"(d[58]), "+f"(d[59]), "+f"(d[60]), "+f"(d[61]), "+f"(d[62]), "+f"(d[63]),
      "+f"(d[64]), "+f"(d[65]), "+f"(d[66]), "+f"(d[67]), "+f"(d[68]), "+f"(d[69]), "+f"(d[70]), "+f"(d[71]),
      "+f"(d[72]), "+f"(d[73]), "+f"(d[74]), "+f"(d[75]), "+f"(d[76]), "+f"(d[77]), "+f"(d[78]), "+f"(d[79]),
      "+f"(d[80]), "+f"(d[81]), "+f"(d[82]), "+f"(d[83]), "+f"(d[84]), "+f"(d[85]), "+f"(d[86]), "+f"(d[87]),
      "+f"(d[88]), "+f"(d[89]), "+f"(d[90]), "+f"(d[91]), "+f"(d[92]), "+f"(d[93]), "+f"(d[94]), "+f"(d[95])
    : "l"(da), "l"(db), "r"(scale_d));
}
__device__ __forceinline__ void wgmma_n80_rs(float (&d)[40], uint32_t a0, uint32_t a1, uint32_t a2, uint32_t a3, uint64_t db, int scale_d) {
  asm volatile("{\n.reg .pred p;\nsetp.ne.b32 p, %45, 0;\n"
    "wgmma.mma_async.sync.aligned.m64n80k16.f32.bf16.bf16 "
    "{%0, %1, %2, %3, %4, %5, %6, %7, %8, %9, %10, %11, %12, %13, %14, %15, "
    "%16, %17, %18, %19, %20, %21, %22, %23, %24, %25, %26, %27, %28, %29, %30, %31, "
    "%32, %33, %34, %35, %36, %37, %38, %39}, "
    "{%40, %41, %42, %43}, %44, p, 1, 1, 1;\n}\n"
    : "+f"(d[0]), "+f"(d[1]), "+f"(d[2]), "+f"(d[3]), "+f"(d[4]), "+f"(d[5]), "+f"(d[6]), "+f"(d[7]),
      "+f"(d[8]), "+f"(d[9]), "+f"(d[10]), "+f"(d[11]), "+f"(d[12]), "+f"(d[13]), "+f"(d[14]), "+f"(d[15]),
      "+f"(d[16]), "+f"(d[17]), "+f"(d[18]), "+f"(d[19]), "+f"(d[20]), "+f"(d[21]), "+f"(d[22]), "+f"(d[23]),
      "+f"(d[24]), "+f"(d[25]), "+f"(d[26]), "+f"(d[27]), "+f"(d[28]), "+f"(d[29]), "+f"(d[30]), "+f"(d[31]),
      "+f"(d[32]), "+f"(d[33]), "+f"(d[34]), "+f"(d[35]), "+f"(d[36]), "+f"(d[37]), "+f"(d[38]), "+f"(d[39])
    : "r"(a0), "r"(a1), "r"(a2), "r"(a3), "l"(db), "r"(scale_d));
}
__device__ __forceinline__ void wgmma_n80_ss(float (&d)[40], uint64_t da, uint64_t db, int scale_d) {
  asm volatile("{\n.reg .pred p;\nsetp.ne.b32 p, %42, 0;\n"
    "wgmma.mma_async.sync.aligned.m64n80k16.f32.bf16.bf16 "
    "{%0, %1, %2, %3, %4, %5, %6, %7, %8, %9, %10, %11, %12, %13, %14, %15, "
    "%16, %17, %18, %19, %20, %21, %22, %23, %24, %25, %26, %27, %28, %29, %30, %31, "
    "%32, %33, %34, %35, %36, %37, %38, %39}, "
    "%40, %41, p, 1, 1, 0, 1;\n}\n"
    : "+f"(d[0]), "+f"(d[1]), "+f"(d[2]), "+f"(d[3]), "+f"(d[4]), "+f"(d[5]), "+f"(d[6]), "+f"(d[7]),
      "+f"(d[8]), "+f"(d[9]), "+f"(d[10]), "+f"(d[11]), "+f"(d[12]), "+f"(d[13]), "+f"(d[14]), "+f"(d[15]),
      "+f"(d[16]), "+f"(d[17]), "+f"(d[18]), "+f"(d[19]), "+f"(d[20]), "+f"(d[21]), "+f"(d[22]), "+f"(d[23]),
      "+f"(d[24]), "+f"(d[25]), "+f"(d[26]), "+f"(d[27]), "+f"(d[28]), "+f"(d[29]), "+f"(d[30]), "+f"(d[31]),
      "+f"(d[32]), "+f"(d[33]), "+f"(d[34]), "+f"(d[35]), "+f"(d[36]), "+f"(d[37]), "+f"(d[38]), "+f"(d[39])
    : "l"(da), "l"(db), "r"(scale_d));
}

__device__ __forceinline__ constexpr int QT(int t) { return t < 8 ? t : 16 + t; }
__device__ __forceinline__ constexpr int KT(int t) { return t < 8 ? 8 + t : 18 + t; }
__device__ __forceinline__ constexpr int VT(int t) { return t < 8 ? 16 + t : 20 + t; }

struct Maps { CUtensorMap x, w, wr, wo, wor, gate, up, down; };

__global__ void __cluster_dims__(2, 1, 1) __launch_bounds__(384, 1)
fused_kernel(const __nv_bfloat16* __restrict__ x, const __nv_bfloat16* __restrict__ wqkv,
             const __nv_bfloat16* __restrict__ wo, const __nv_bfloat16* __restrict__ w_r, const __nv_bfloat16* __restrict__ w_gate,
             const __nv_bfloat16* __restrict__ w_up, const __nv_bfloat16* __restrict__ w_down, __nv_bfloat16* __restrict__ out,
             Scratch* __restrict__ sc, const __grid_constant__ Maps tm) {
  extern __shared__ __align__(1024) uint8_t smem[];
  const int tid = threadIdx.x, warp = __shfl_sync(0xffffffffu, tid >> 5, 0), lane = tid & 31, bid = blockIdx.x;
  const uint32_t sb = (uint32_t)__cvta_generic_to_shared(smem);
  const uint32_t bar_full = sb + OFF_BAR, bar_empty = bar_full + 32, bar_aux = bar_full + 64, bar_ffn = bar_full + 72, bar_win = bar_full + 80,
                 bar_o = bar_full + 96;
  if (warp < 4 && elect()) {
    mbar_init(bar_full + 8 * (warp ^ 2), 1);
    mbar_init(bar_empty + 8 * warp, 4);
    mbar_init(bar_aux + 8 * warp, warp == 0 ? 64 : 1);
    asm volatile("fence.mbarrier_init.release.cluster;" ::: "memory");
  }
  if (warp >= 4 && elect()) { mbar_init(bar_o + 16 * (warp - 4), 1); mbar_init(bar_o + 16 * (warp - 4) + 8, (warp & 3) == 1 ? 128 : 1); }
  asm volatile("barrier.cluster.arrive.relaxed.aligned;" ::: "memory");
  if (warp >= 8 && warp < 11 && elect()) asm volatile("prefetch.tensormap [%0];" :: "l"(&tm.x + (warp - 8)) : "memory");
  auto pf_slice = [&](int ks) {
    pf_l2(lane < 16 ? (const char*)x + ((bid * 16 + lane) * 1280 + ks * 128) : (const char*)wqkv + ((bid * 15 + min(lane, 30) - 16) * 128 + ks * 245760));
  };
  if (warp >= 4 && warp < 4 + PF0) {
    if (warp > 4) __nanosleep(300 + (warp - 4) * PF_NS);
    pf_slice(warp == 6 ? 5 : warp - 4);
  }
  const int rank = bid & 1, cl = bid >> 1;
  const int q7 = ((cl - 36) * 37) >> 8;
  const int P = cl < 4 ? 0 : cl < 36 ? (cl - 4) & 7 : cl - 35 - 7 * q7;
  const int g = cl < 4 ? 4 + cl : cl < 36 ? (cl - 4) >> 3 : 4 + q7;
  const int mt = 2 * P + rank, cid = mt * 8 + g;
  const bool ffn1 = g < 3;
  const int fj = ffn1 ? mt * 3 + g : (P * 5 + g - 3) * 2 + rank;
  const int ord = ((g >> 2) ^ P) & 1;
  auto ks_of = [&](int it) { return ord == 0 || it == 0 ? it : it <= 5 ? it + 4 : it - 5; };
  auto load_w = [&](int it, uint32_t a, uint32_t full) {
    tma_3d_mc(a + 16384 + rank * 16384, &tm.w, full, g * 80, it * 64, rank * 2);
    tma_3d_mc(a + (rank ? 40960 : 24576), rank ? &tm.wr : &tm.w, full, g * 80 + rank * 64, it * 64, 1 - rank);
  };
  if (warp == 0 && elect()) {
    mbar_expect_tx(bar_full + 16, SLOT);
    tma_3d(sb + 2 * SLOT, &tm.x, bar_full + 16, 0, mt * 64, 0);
  }
  asm volatile("barrier.cluster.wait.aligned;" ::: "memory");
  if (warp == 0) {
    if (elect()) load_w(0, sb + 2 * SLOT, bar_full + 16);
    asm volatile("bar.arrive 4, 64;" ::: "memory");
  }

  if (warp >= 8) {
    asm volatile("setmaxnreg.dec.sync.aligned.u32 %0;" :: "n"(REG_P));
#define TS_T 0
    if (warp == 8) {
      TS(8);
      bar_sync(4, 64);
      if (elect()) {
        TS(10);
        int fjn = 0;
#pragma unroll 1
        for (int it = 1; it < 17; it++) {
          const int s = (it + 2) & 3;
          const uint32_t full = bar_full + 8 * s, a = sb + s * SLOT;
          if (it >= 13) { mbar_wait(bar_o + 32 + 8 * (it - 13), 0); mbar_wait(bar_o + 96 + 8 * (it - 13), 0); }
          else if (it >= 4) mbar_wait(bar_empty + 8 * s, ((it >> 2) - 1) & 1);
          if (it < 10) {
            const int ks = ks_of(it);
            mbar_expect_tx(full, SLOT);
            tma_3d(a, &tm.x, full, ks * 64, mt * 64, 0);
            load_w(ks, a, full);
            if (it == 1) TS(9);
          } else if (it < 13) {
            const int g0 = 3 * (it - 10), g1 = min(g0 + 3, 8);
            mbar_expect_tx(full, (g1 - g0) * 12800);
#pragma unroll 1
            for (int gp = g0 + ((g0 ^ rank) & 1); gp < g1; gp += 2) {
              tma_3d_mc(sb + gp * 15360, &tm.wo, full, 0, gp * 80, g * 2);
              tma_3d_mc(sb + gp * 15360 + 10240, &tm.wor, full, 512 + g * 16, gp * 80, 0);
            }
          }
          if (it == 4) mbar_expect_tx(bar_ffn, ffn1 ? 81920 : 24576);
          const int j1 = ffn1 ? (it >= 13 ? min(2 * it - 21, 10) : min(max(it - F_IT + 1, 0), 4)) : (it >= 13 ? 12 : min(max((it - F_IT + 1) * F_PER, 0), F_MAX));
#pragma unroll 1
          for (; fjn < j1; fjn++) {
            const int j = fjn < 4 ? fjn + 6 : fjn - 4;
            if (ffn1) tma_3d(sb + (j < 6 ? 0 : OFF_W2 - 49152) + j * 8192, j < 5 ? &tm.gate : &tm.up, bar_ffn, fj * 32, (j < 5 ? j : j - 5) * 128, 0);
            else tma_3d(sb + OFF_W2 + fjn * 2048, &tm.down, bar_ffn, fj * 8, fjn * 128, 0);
          }
        }
        TS(11);
      }
#undef TS_T
#define TS_T 32
    } else if (warp < 11) {
      Own* const own = g_own + cid;
      const int r = lane >> 2, l7 = lane & 7, hk = lane >> 4, idx = lane;
      bar_sync(2, 352);
      TS(0);
      const uint32_t tag = __float_as_uint(lds32f(sb + OFF_WR + 324));
      const uint32_t pt = sb + OFF_PT + lane * 4 + (warp - 9) * 512;
      const float s0 = lds32f(pt) + lds32f(pt + 128), q0 = lds32f(sb + OFF_PT + 256 + lane * 4) + lds32f(sb + OFF_PT + 384 + lane * 4);
      int guard = SPIN_MAX;
      if (warp == 9) {
        stg_pkt(&own->st1[idx], __float_as_uint(s0), __float_as_uint(q0), tag, 0u);
        TS(1);
        const uint4* sp = &g_own[mt * 8].st1[lane];
        const uint4* hp = &g_own[max(mt - 1, 0) * 8 + hk * 2 + 1].st1[24 + l7];
        uint4 a[5], b[5];
        bool bad;
        do {
          __nanosleep(AUX_NS);
          bad = false;
#pragma unroll
          for (int i = 0; i < 5; i++) {
            const uint4* q = i < 4 ? sp + i * (sizeof(Own) / 16) : hp;
            a[i] = ldg_pkt(q); b[i] = ldg_pkt(q + 4 * sizeof(Own) / 16);
          }
#pragma unroll
          for (int i = 0; i < 5; i++) bad |= a[i].z != tag || b[i].z != tag;
        } while (anyw(bad) && --guard);
#pragma unroll
        for (int i = 0; i < 5; i++) {
          const float m = (__uint_as_float(a[i].x) + __uint_as_float(b[i].x)) * (1.f / 640.f);
          const float rs = rsq(fmaxf(fmaf(-m, m, (__uint_as_float(a[i].y) + __uint_as_float(b[i].y)) * (1.f / 640.f)), 0.f) + 1e-5f);
          ((float*)(smem + OFF_RS))[i < 4 ? 8 + lane + 32 * i + 8 * (i >> 1) : hk * 72 + l7] = rs;
          const uint32_t mh = pack_bf16(-m, -m);
          const float ml = -m - bf_lo(mh);
          if (i < 4) ((uint2*)(smem + OFF_MN))[lane + 32 * i] = make_uint2(mh, pack_bf16(ml, ml));
        }
      } else {
        stg_rlx64(&own->cs[idx], __float_as_uint(s0), tag);
        const uint4* cp = (const uint4*)g_own[hk * 8 + g].cs + (lane & 15);
        uint4 a[4], b[4];
        bool bad;
        do {
          __nanosleep(AUX_NS);
          bad = false;
#pragma unroll
          for (int i = 0; i < 4; i++) { a[i] = ldg_pkt(cp + i * 32 * sizeof(Own) / 16); b[i] = ldg_pkt(cp + (i * 32 + 16) * sizeof(Own) / 16); }
#pragma unroll
          for (int i = 0; i < 4; i++) bad |= a[i].y != tag || a[i].w != tag || b[i].y != tag || b[i].w != tag;
        } while (anyw(bad) && --guard);
#pragma unroll
        for (int i = 0; i < 4; i++)
          if (i < 3 || lane < 24) {
            const float c0 = __uint_as_float(a[i].x) + __uint_as_float(b[i].x), c1 = __uint_as_float(a[i].z) + __uint_as_float(b[i].z);
            const uint32_t hi = pack_bf16(c0, c1), w0 = pack_bf16(c0, c0 - bf_lo(hi)), w1 = pack_bf16(c1, c1 - bf_hi(hi));
            uint4* const d = (uint4*)(smem + OFF_CS) + 2 * (lane + 32 * i);
            d[0] = make_uint4(w0, w0, 0, 0); d[1] = make_uint4(w1, w1, 0, 0);
          }
        asm volatile("fence.proxy.async.shared::cta;" ::: "memory");
      }
      mbar_arrive(bar_aux);
      TS(2);
      const int wq = warp - 9;
      const uint32_t* const fp = pin(&g_own[mt * 8 + wq * 4].oflag[lane]);
      const char* const src = (const char*)g_o[mt * 2 + wq];
      bar_sync(5 + wq, 160);
      while (anyw(ldg_rlx32(fp) != tag) && --guard > 0) {}
      if (elect()) {
        asm volatile("fence.proxy.async.global;" ::: "memory");
        TS(6);
#pragma unroll 1
        for (int i = 0, sl = 0; i < 7; i++) {
          const uint32_t full = bar_o + wq * 64 + 8 * sl;
          if (i >= 3) mbar_wait(bar_o + wq * 64 + 8 + 8 * i, 0);
          mbar_expect_tx(full, 10240);
          asm volatile("cp.async.bulk.shared::cluster.global.mbarrier::complete_tx::bytes [%0], [%1], 10240, [%2];"
                       :: "r"(sb + OFF_O + sl * 20480 + wq * 10240), "l"(src + (i + (i >= g)) * 10240), "r"(full) : "memory");
          sl = sl == 2 ? 0 : sl + 1;
        }
      }
#undef TS_T
#define TS_T 96
    } else {
      mbar_wait(bar_full + 16, 0);
      TS(4);
      const uint32_t epoch = ldg_rlx32(g_epoch + cid) + 1;
      uint32_t wv[10];
#pragma unroll
      for (int i = 0; i < 10; i++) wv[i] = __ldg((const uint32_t*)w_r + lane + 32 * i);
#pragma unroll 1
      for (int i = lane; i < 392; i += 32) {
        const uint32_t f = i >= 376 ? 0u : SENT;
        ((uint4*)(g_own + cid))[i] = make_uint4(f, f, f, f);
        if (i < GLOB_PER_CTA) ((uint4*)&g_x)[cid * GLOB_PER_CTA + i] = make_uint4(SENT, SENT, SENT, SENT);
      }
      float s = 0.f;
#pragma unroll
      for (int i = 0; i < 10; i++) {
        s += bf_lo(wv[i]) + bf_hi(wv[i]);
        const unsigned u = i < 8 ? lane + 32 * (i - g) : lane + 32 * (i - 7) - g * 8;
        if (i < 8 ? u < 32u : u - 32u < 8u) *(float2*)(smem + OFF_WR + ((u & 3) * 10 + (u >> 2)) * 8) = make_float2(bf_lo(wv[i]), bf_hi(wv[i]));
      }
#pragma unroll
      for (int m = 1; m < 32; m <<= 1) s += shx(s, m);
      *(float2*)(smem + OFF_WR + 320) = make_float2(s, __uint_as_float(epoch * 0x9E3779B8u));
      g_epoch[cid] = epoch;
      TS(3);
      asm volatile("fence.acq_rel.gpu;" ::: "memory");
      TS(5);
      asm volatile("bar.arrive 2, 352;" ::: "memory");
      bar_sync(3, 64);
      const uint4* kp = (const uint4*)g_x.key[cid & 3] + lane;
      uint4 k0, k1;
      int guard = SPIN_MAX;
      do { k0 = ldg_pkt(kp); k1 = ldg_pkt(kp + 32); } while (anyw(k0.y == SENT || k0.w == SENT || k1.y == SENT || k1.w == SENT) && --guard);
      int i0 = 2 * lane, i1 = 2 * lane + 64;
      if (k0.z > k0.x) { k0.x = k0.z; k0.y = k0.w; i0++; }
      if (k1.z > k1.x) { k1.x = k1.z; k1.y = k1.w; i1++; }
      if (k1.x > k0.x) { k0.x = k1.x; k0.y = k1.y; i0 = i1; }
      const float rw = __uint_as_float(k0.x ^ ((uint32_t)((int32_t)~k0.x >> 31) | 0x80000000u));
      const float sg = rcp(1.f + ex2(-1.4426950408889634f * rw));
      if (lane == __ffs(__ballot_sync(0xffffffffu, k0.x == __reduce_max_sync(0xffffffffu, k0.x))) - 1) {
        *(uint4*)(smem + OFF_WR + 336) = make_uint4(i0, k0.y, __float_as_uint(sg), i0 * (8 * 24 * 16));
        mbar_arrive(bar_win);
      }
      TS(7);
    }
#undef TS_T
  } else {
#define TS_T 0
    TS(23);
    asm volatile("setmaxnreg.inc.sync.aligned.u32 %0;" :: "n"(REG_C));
    const int wg = warp >> 2, w4 = warp & 3, r = lane >> 2, c = lane & 3;
    float acc[120];
    uint4 xr[5];
    const uint32_t xa = (warp * 16 + (lane & 15)) * 128, xc = (lane >> 4) ^ (lane & 7);
    float ps = 0.f, pq = 0.f, pc_ = 0.f;
    uint32_t sxo, swo;
    {
      const int l7 = lane & 7, j = warp >> 1, k = (warp & 1) * 32 + lane, ch = min((P >> 1) * 4 + rank * 2 + (j >> 1), 14);
      sxo = ((g & 3) * 32 + j * 8 + l7) * 128 + ((((warp & 1) * 4 + (lane >> 3)) ^ l7) * 16);
      swo = ch < 12 ? 16384 + (ch >> 2) * 8192 + k * 128 + ((((ch & 3) * 2 + (j & 1)) ^ l7) * 16) : 40960 + (ch - 12) * 2048 + k * 32 + (((j & 1) ^ (l7 >> 2)) * 16);
    }
    const bool first = (mt == 0) && (w4 == 0);
    uint4* const kvd = pin(w4 < 3 ? (uint4*)(smem + OFF_O + (wg * 3 + w4) * 2560) + lane : &g_own[cid].halo[wg][0][lane]);
    const uint4* const kvs = pin(first ? kvd : w4 > 0 ? (const uint4*)(smem + OFF_O + (wg * 3 + w4 - 1) * 2560) + lane : &g_own[cid - 8].halo[wg][0][lane]);
    TS(0);
#pragma unroll 1
    for (int it = 0; it < 10; it++) {
      const int s = (it + 2) & 3;
      mbar_wait(bar_full + 8 * s, (it >> 2) & 1);
      TS(13 + it);
      const uint32_t a = sb + s * SLOT;
      const uint64_t da = make_desc(a + wg * 8192, 16, 1024, 1), db = make_desc(a + 16384, 8192, 1024, 1), dr = make_desc(a + 40960, 2048, 256, 3);
      uint32_t m0 = 0, m1 = 0;
      if (it == 9) {
        mbar_wait(bar_aux, 0);
        TS(3);
        if (c < 2) { m0 = __float_as_uint(lds32f(sb + OFF_MN + (warp * 16 + r) * 8 + c * 4)); m1 = __float_as_uint(lds32f(sb + OFF_MN + (warp * 16 + r) * 8 + c * 4 + 64)); }
      }
      if (PINGPONG && (it | wg)) bar_sync(7 + wg, 256);
      wgmma_fence();
      if (it == 9) {
        const uint64_t dc = make_desc(sb + OFF_CS, 0, 128, 0);
        wgmma_n48hi_rk(acc, m0, m1, 0u, 0u, dc + 192, 1);
        wgmma_n192lo_rk(acc, m0, m1, 0u, 0u, dc, 1);
      }
#pragma unroll
      for (int kk = 0; kk < 4; kk++) {
        wgmma_n48hi_ss(acc, da + kk * 2, dr + kk * 32, (kk | it) != 0);
        if (PINGPONG == 2 && kk == 3 && (it < 9 || wg == 0)) asm volatile("bar.arrive %0, 256;" :: "r"(8 - wg) : "memory");
        wgmma_n192lo_ss(acc, da + kk * 2, db + kk * 128, (kk | it) != 0);
      }
      wgmma_commit();
      if (PINGPONG == 1 && (it < 9 || wg == 0)) asm volatile("bar.arrive %0, 256;" :: "r"(8 - wg) : "memory");
      if (it == PFX_IT && warp < 3) pf_slice(warp == 0 ? 4 : 7 + warp);
      if (it >= PFW_IT && it < PFW_IT + 4) {
        const int n = it == PFW_IT + 1 ? 50 : 120;
        const char* b = (const char*)(it == PFW_IT ? w_down : it == PFW_IT + 1 ? wo : it == PFW_IT + 2 ? w_up : w_gate);
        if (tid < n) pf_l2(b + (bid * n + tid) * 128);
      }
      const int ks = ks_of(it);
      if (ks == g) {
#pragma unroll
        for (int j = 0; j < 4; j++) xr[j] = ldsm4(a + xa + ((xc ^ (2 * j)) * 16));
      }
      if (ks == 8 + (g >> 2)) xr[4] = ldsm4(a + xa + ((xc ^ (2 * (g & 3))) * 16));
      if ((unsigned)(it - ord) < 5u) {
        const uint4 v = ldsm4(a + sxo), w = ldsm4t(a + swo);
        const uint32_t vv[4] = {v.x, v.y, v.z, v.w}, ww[4] = {w.x, w.y, w.z, w.w};
#pragma unroll
        for (int i = 0; i < 4; i++) {
          const float d = bf_lo(vv[i]), e = bf_hi(vv[i]);
          ps += d + e; pq = fmaf(d, d, pq); pq = fmaf(e, e, pq); pc_ += bf_lo(ww[i]) + bf_hi(ww[i]);
        }
        if (it - ord == 4) {
          ps += shx(ps, 1); pq += shx(pq, 1); pc_ += shx(pc_, 1);
          ps += shx(ps, 2); pq += shx(pq, 2); pc_ += shx(pc_, 2);
          if (c < 3) sts32f(sb + OFF_PT + (c * 64 + (warp & 1) * 32 + (warp >> 1) * 8 + r) * 4, c == 0 ? ps : c == 1 ? pq : pc_);
          asm volatile("bar.arrive 2, 352;" ::: "memory");
        }
      }
      if (it > 0) {
        wgmma_wait<1>();
        if ((tid & 127) < 2) mbar_arrive_cta(bar_empty + 8 * ((it + 1) & 3), tid & 1);
      }
    }
    const uint32_t stb = sb + OFF_RS + (wg * 72 + 16 * w4) * 4;
    const float rlo = lds32f(stb + (8 + r) * 4), rhi = lds32f(stb + (16 + r) * 4);
    wgmma_wait<0>();
#pragma unroll
    for (int i = 0; i < 120; i++) asm volatile("" : "+f"(acc[i]) :: "memory");
    TS(2);
    uint32_t Qlo[10], Qhi[10], Klo[10], Khi[10], Vlo[10], Vhi[10];
#pragma unroll
    for (int t = 0; t < 10; t++) {
      const int k = KT(t), v = VT(t);
      Khi[t] = pack_bf16(acc[4 * k + 2], acc[4 * k + 3]);
      Vhi[t] = pack_bf16(acc[4 * v + 2] * rhi, acc[4 * v + 3] * rhi);
    }
    st_pkt(kvd, Khi[0], Khi[1], Khi[3], Khi[4]);
    st_pkt(kvd + 32, Khi[5], Khi[6], Khi[8], Khi[9]);
    st_pkt(kvd + 64, Khi[2], Khi[7], Vhi[0], Vhi[1]);
    st_pkt(kvd + 96, Vhi[2], Vhi[3], Vhi[4], Vhi[5]);
    st_pkt(kvd + 128, Vhi[6], Vhi[7], Vhi[8], Vhi[9]);
    mbar_arrive(bar_o + wg * 64 + 24);
#pragma unroll
    for (int t = 0; t < 10; t++) {
      const int q = QT(t), k = KT(t), v = VT(t);
      Vhi[t] = movm(Vhi[t]);
      Klo[t] = pack_bf16(acc[4 * k], acc[4 * k + 1]);
      Vlo[t] = movm(pack_bf16(acc[4 * v] * rlo, acc[4 * v + 1] * rlo));
      Qlo[t] = pack_bf16(acc[4 * q], acc[4 * q + 1]);
      Qhi[t] = pack_bf16(acc[4 * q + 2], acc[4 * q + 3]);
    }
    const bool in0 = 2 * c <= r, in1 = 2 * c + 1 <= r;
    const uint32_t mL = (in0 ? 0xffffu : 0u) | (in1 ? 0xffff0000u : 0u);
    const float qs = 0.22360679774997896f * 1.4426950408889634f;
    const uint32_t kb0 = stb + (2 * c + (in0 ? 8 : 0)) * 4, kb1 = stb + (2 * c + 1 + (in1 ? 8 : 0)) * 4;
    const float scl0 = lds32f(kb0) * rlo * qs, scl1 = lds32f(kb1) * rlo * qs;
    const float sch0 = lds32f(kb0 + 32) * rhi * qs, sch1 = lds32f(kb1 + 32) * rhi * qs;
    const float bias0 = (first && !in0) ? -INFINITY : 0.f, bias1 = (first && !in1) ? -INFINITY : 0.f;
    const uint32_t tag = __float_as_uint(lds32f(sb + OFF_WR + 324));
    const int slot = mt * 8 + warp;
    int guard = SPIN_MAX;
    uint4 pv[5];
    mbar_wait(bar_o + wg * 64 + 24, 0);
    do {
#pragma unroll
      for (int j = 0; j < 5; j++) pv[j] = ld_pkt(kvs + 32 * j);
    } while (anyw(pv[0].x == SENT || pv[1].x == SENT || pv[2].x == SENT || pv[3].x == SENT || pv[4].x == SENT) && --guard);
    TS(4);
    const uint32_t Kp[10] = {pv[0].x, pv[0].y, pv[2].x, pv[0].z, pv[0].w, pv[1].x, pv[1].y, pv[2].y, pv[1].z, pv[1].w};
    const uint32_t Vp[10] = {movm(pv[2].z), movm(pv[2].w), movm(pv[3].x), movm(pv[3].y), movm(pv[3].z), movm(pv[3].w), movm(pv[4].x), movm(pv[4].y), movm(pv[4].z), movm(pv[4].w)};
    const bool cA = c < 2, nA = r < 4;
    const uint32_t ONES = 0x3f803f80u;
    uint32_t of[20];
#pragma unroll
    for (int hp = 0; hp < 2; hp++) {
      float o[6][4];
#pragma unroll
      for (int hh = 0; hh < 2; hh++) {
        const int ta = 5 * hp + 3 * hh, ts = 5 * hp + 2;
        const bool mine = hh == 0 ? cA : !cA;
        const uint32_t e0 = mine ? Qlo[ts] : 0u, e1 = mine ? Qhi[ts] : 0u;
        float sp[4], sl[4], sh[4];
        mma_k24(sp, Qlo[ta], Qhi[ta], Qlo[ta + 1], Qhi[ta + 1], Kp[ta], Kp[ta + 1], e0, e1, Kp[ts]);
        mma_k24(sl, Qlo[ta], Qhi[ta], Qlo[ta + 1], Qhi[ta + 1], Klo[ta], Klo[ta + 1], e0, e1, Klo[ts]);
        mma_k24(sh, Qlo[ta], Qhi[ta], Qlo[ta + 1], Qhi[ta + 1], Khi[ta], Khi[ta + 1], e0, e1, Khi[ts]);
        const float tl0 = fmaf(in0 ? sl[0] : sp[0], scl0, bias0), tl1 = fmaf(in1 ? sl[1] : sp[1], scl1, bias1);
        const float th0 = (in0 ? sh[2] : sl[2]) * sch0, th1 = (in1 ? sh[3] : sl[3]) * sch1;
        float ml = fmaxf(tl0, tl1), mh = fmaxf(th0, th1);
        ml = fmaxf(ml, shx(ml, 1)); mh = fmaxf(mh, shx(mh, 1));
        ml = fmaxf(ml, shx(ml, 2)); mh = fmaxf(mh, shx(mh, 2));
        const uint32_t Pl = pack_bf16(ex2(tl0 - ml), ex2(tl1 - ml)), Ph = pack_bf16(ex2(th0 - mh), ex2(th1 - mh));
        const uint32_t a0 = Pl & mL, a1 = Ph & ~mL, a3 = Ph & mL, ap = Pl & ~mL;
        const bool vm = hh == 0 ? nA : !nA;
        mma_k24(o[3 * hh], a0, a1, 0u, a3, Vlo[ta], Vhi[ta], ap, 0u, Vp[ta]);
        mma_k24(o[3 * hh + 1], a0, a1, 0u, a3, Vlo[ta + 1], Vhi[ta + 1], ap, 0u, Vp[ta + 1]);
        mma_k24(o[3 * hh + 2], a0, a1, 0u, a3, vm ? Vlo[ts] : ONES, vm ? Vhi[ts] : ONES, ap, 0u, vm ? Vp[ts] : ONES);
      }
      const float il = rcp(cA ? o[5][0] : o[2][0]), ih = rcp(cA ? o[5][2] : o[2][2]);
      const float jl = shx(il, 2), jh = shx(ih, 2);
      const float al = cA ? jl : il, ah = cA ? jh : ih, bl = cA ? il : jl, bh = cA ? ih : jh;
      const int t0 = 5 * hp;
      of[2 * t0]     = pack_bf16(o[0][0] * al, o[0][1] * al); of[2 * t0 + 1] = pack_bf16(o[0][2] * ah, o[0][3] * ah);
      of[2 * t0 + 2] = pack_bf16(o[1][0] * al, o[1][1] * al); of[2 * t0 + 3] = pack_bf16(o[1][2] * ah, o[1][3] * ah);
      of[2 * t0 + 4] = pack_bf16((cA ? o[2][0] : o[5][0]) * jl, (cA ? o[2][1] : o[5][1]) * jl);
      of[2 * t0 + 5] = pack_bf16((cA ? o[2][2] : o[5][2]) * jh, (cA ? o[2][3] : o[5][3]) * jh);
      of[2 * t0 + 6] = pack_bf16(o[3][0] * bl, o[3][1] * bl); of[2 * t0 + 7] = pack_bf16(o[3][2] * bh, o[3][3] * bh);
      of[2 * t0 + 8] = pack_bf16(o[4][0] * bl, o[4][1] * bl); of[2 * t0 + 9] = pack_bf16(o[4][2] * bh, o[4][3] * bh);
    }
    bar_sync(1, 256);
    {
      const uint32_t os = sb + OFF_O + warp * 2560, oa = os + ((lane >> 3) & 1) * 1280 + (lane >> 4) * 128 + (lane & 7) * 16;
#pragma unroll
      for (int s = 0; s < 5; s++) stsm4(oa + s * 256, of[4 * s], of[4 * s + 1], of[4 * s + 2], of[4 * s + 3]);
      asm volatile("fence.proxy.async.shared::cta;" ::: "memory");
      __syncwarp();
      if (elect()) {
        asm volatile("cp.async.bulk.global.shared::cta.bulk_group [%0], [%1], 2560;\ncp.async.bulk.commit_group;" :: "l"(&g_o[mt * 2 + wg][g][w4 * 160]), "r"(os) : "memory");
      }
    }
    TS(5);
    float h[40];
#pragma unroll
    for (int s = 0; s < 5; s++) {
      const uint4 v = xr[s];
      h[8 * s] = bf_lo(v.x); h[8 * s + 1] = bf_hi(v.x); h[8 * s + 2] = bf_lo(v.y); h[8 * s + 3] = bf_hi(v.y);
      h[8 * s + 4] = bf_lo(v.z); h[8 * s + 5] = bf_hi(v.z); h[8 * s + 6] = bf_lo(v.w); h[8 * s + 7] = bf_hi(v.w);
    }
    mbar_wait(bar_full, 0); mbar_wait(bar_full + 8, 0); mbar_wait(bar_full + 16, 1);
    uint64_t dwo = make_desc(sb, 5120, 512, 2);
    wgmma_fence();
#pragma unroll
    for (int s = 0; s < 5; s++) wgmma_n80_rs(h, of[4 * s], of[4 * s + 1], of[4 * s + 2], of[4 * s + 3], dwo + g * 960 + s * 64, 1);
    wgmma_commit();
    if (elect()) {
      asm volatile("cp.async.bulk.wait_group 0;" ::: "memory");
      stg_rlx32(&g_own[mt * 8 + wg * 4].oflag[g * 4 + w4], tag);
    }
    asm volatile("bar.arrive %0, 160;" :: "r"(5 + wg) : "memory");
    TS(6);
#pragma unroll 1
    for (int i = 0, sl = 0; i < 7; i++) {
      mbar_wait(bar_o + wg * 64 + 8 * sl, i >= 3 && i < 6);
      if (i == 0) TS(1);
      const uint64_t da = make_desc(sb + OFF_O + sl * 20480 + wg * 10240, 128, 1280, 0), db = dwo + (i + (i >= g)) * 960;
      wgmma_fence();
#pragma unroll
      for (int s = 0; s < 5; s++) wgmma_n80_ss(h, da + s * 16, db + s * 64, 1);
      wgmma_commit();
      wgmma_wait<1>();
      if ((tid & 127) == 0 && i > 0 && i < 5) mbar_arrive(bar_o + wg * 64 + 24 + 8 * i);
      sl = sl == 2 ? 0 : sl + 1;
    }
    const bool odd = c & 1;
    float wr[20];
#pragma unroll
    for (int j = 0; j < 5; j++) {
      const uint4 v = lds128(sb + OFF_WR + c * 80 + j * 16);
      wr[4 * j] = __uint_as_float(v.x); wr[4 * j + 1] = __uint_as_float(v.y); wr[4 * j + 2] = __uint_as_float(v.z); wr[4 * j + 3] = __uint_as_float(v.w);
    }
    const float wsum = lds32f(sb + OFF_WR + 320);
    uint4* const sp = pin(&g_own[slot].st2[r + (odd ? 8 : 0)]);
    uint2* const kp = pin(&g_x.key[c][slot]);
    uint4* const cdp = pin(&g_x.cand[slot][g][0]);
    const int tok0 = mt * 128 + 32 * w4 + wg;
    wgmma_wait<0>();
#pragma unroll
    for (int i = 0; i < 40; i++) asm volatile("" : "+f"(h[i]) :: "memory");
    TS(7);
    float mean, rstd, rr;
    {
      float l1 = 0.f, l2 = 0.f, l3 = 0.f, h1 = 0.f, h2 = 0.f, h3 = 0.f;
#pragma unroll
      for (int j = 0; j < 10; j++) {
        l1 += h[4 * j] + h[4 * j + 1]; h1 += h[4 * j + 2] + h[4 * j + 3];
        l2 = fmaf(h[4 * j], h[4 * j], l2); l2 = fmaf(h[4 * j + 1], h[4 * j + 1], l2);
        h2 = fmaf(h[4 * j + 2], h[4 * j + 2], h2); h2 = fmaf(h[4 * j + 3], h[4 * j + 3], h2);
        l3 = fmaf(h[4 * j], wr[2 * j], l3); l3 = fmaf(h[4 * j + 1], wr[2 * j + 1], l3);
        h3 = fmaf(h[4 * j + 2], wr[2 * j], h3); h3 = fmaf(h[4 * j + 3], wr[2 * j + 1], h3);
      }
      float s1 = (odd ? h1 : l1) + shx(odd ? l1 : h1, 1), s2 = (odd ? h2 : l2) + shx(odd ? l2 : h2, 1), s3 = (odd ? h3 : l3) + shx(odd ? l3 : h3, 1);
      s1 += shx(s1, 2); s2 += shx(s2, 2); s3 += shx(s3, 2);
      if (cA) asm volatile("red.relaxed.gpu.global.add.v4.f32 [%0], {%1, %2, %3, %4};" :: "l"(sp), "f"(s1), "f"(s2), "f"(s3), "f"(1.f) : "memory");
      uint4 p0;
      do { p0 = ldg_pkt(sp); } while (anyw(p0.w != 0x41000000u) && --guard > 0);
      mean = __uint_as_float(p0.x) * (1.f / 640.f);
      rstd = rsq(fmaxf(fmaf(-mean, mean, __uint_as_float(p0.y) * (1.f / 640.f)), 0.f) + 1e-5f);
      rr = fmaf(-mean, wsum, __uint_as_float(p0.z)) * rstd;
    }
    TS(8);
    const uint32_t kk = ord_key(rr), kmax = __reduce_max_sync(0xffffffffu, kk);
    const int L = __ffs(__ballot_sync(0xffffffffu, kk == kmax)) - 1;
    const int crow = (L >> 2) + 8 * (L & 1);
    if (warp == g) {
      if (lane < 4) stg_rlx64(kp, kmax, tok0 + 2 * crow);
      asm volatile("bar.arrive 3, 64;" ::: "memory");
    }
    const uint32_t stg = sb + OFF_O + warp * 2560;
    uint4 held;
    {
      const float om = shx(mean, 1), os = shx(rstd, 1);
      const float rl = odd ? os : rstd, rh = odd ? rstd : os;
      const float bl = -(odd ? om : mean) * rl, bh = -(odd ? mean : om) * rh, al = 1.f + rl, ah = 1.f + rh;
      if ((L >> 2) == r) {
        const bool chi = L & 1;
        const float rc = chi ? rh : rl, bc = chi ? bh : bl;
        uint32_t n[10];
#pragma unroll
        for (int j = 0; j < 10; j++) n[j] = pack_bf16(fmaf(chi ? h[4 * j + 2] : h[4 * j], rc, bc), fmaf(chi ? h[4 * j + 3] : h[4 * j + 1], rc, bc));
        uint4* d = cdp + c;
        stg_pkt(d, n[0], n[1], n[2], n[3]); stg_pkt(d + 4, n[4], n[5], n[6], n[7]); stg_rlx64(d + 8, n[8], n[9]);
      }
      __syncwarp();
      const uint32_t fa = stg + (lane & 15) * 160 + (lane >> 4) * 16;
#pragma unroll
      for (int s = 0; s < 5; s++)
        stsm4(fa + s * 32, pack_bf16(fmaf(h[8 * s], al, bl), fmaf(h[8 * s + 1], al, bl)), pack_bf16(fmaf(h[8 * s + 2], ah, bh), fmaf(h[8 * s + 3], ah, bh)),
              pack_bf16(fmaf(h[8 * s + 4], al, bl), fmaf(h[8 * s + 5], al, bl)), pack_bf16(fmaf(h[8 * s + 6], ah, bh), fmaf(h[8 * s + 7], ah, bh)));
      __syncwarp();
      held = lds128(stg + crow * 160 + min(lane, 9) * 16);
      if (lane < 10) stg_pkt(cdp + 12 + lane, held.x, held.y, held.z, held.w);
    }
    TS(9);
    mbar_wait(bar_ffn, 0);
    const uint32_t red = sb + OFF_RED;
    if (ffn1) {
      uint4 w1[4][5];
      {
        const int k = (lane & 7) + (lane >> 4) * 8;
        const uint32_t a1 = sb + k * 64, sw = ((lane >> 3) & 1) ^ ((lane >> 1) & 3);
#pragma unroll
        for (int s = 0; s < 5; s++)
#pragma unroll
          for (int u = 0; u < 4; u++)
            w1[u][s] = ldsm4t(a1 + (s < 4 ? warp * 4096 + s * 1024 : 32768 + warp * 1024) + (u >> 1) * (40960 + (s == 4 || warp >= 2 ? OFF_W2 - 49152 : 0)) + ((sw ^ (2 * (u & 1))) * 16));
      }
      const char* p = pin((const char*)&g_x.cand[0][warp][c]);
      uint32_t* const ap = pin(g_x.act + fj * 16 + (lane >> 1));
      mbar_wait(bar_win, 0);
      p += lds128(sb + OFF_WR + 336).w;
      TS(10);
      uint4 c0, c1; uint2 c2;
      do { c0 = ldg_pkt(p); c1 = ldg_pkt(p + 64); c2 = ldg_rlx64(p + 128); } while (anyw(c0.x == SENT || c1.x == SENT || c2.x == SENT) && --guard > 0);
      float a[4][4];
#pragma unroll
      for (int u = 0; u < 4; u++) {
        a[u][0] = a[u][1] = a[u][2] = a[u][3] = 0.f;
        mma_acc(a[u], w1[u][0], c0.x, c0.y); mma_acc(a[u], w1[u][1], c0.z, c0.w); mma_acc(a[u], w1[u][2], c1.x, c1.y);
        mma_acc(a[u], w1[u][3], c1.z, c1.w); mma_acc(a[u], w1[u][4], c2.x, c2.y);
      }
      asm volatile("st.shared.v2.f32 [%0], {%1, %2};" :: "r"(red + (warp * 32 + c * 8 + r) * 8),
                   "f"(cA ? (odd ? a[0][2] : a[0][0]) : (odd ? a[1][2] : a[1][0])), "f"(cA ? (odd ? a[2][2] : a[2][0]) : (odd ? a[3][2] : a[3][0])) : "memory");
      bar_sync(1, 256);
      if (warp == 0) {
        float2 t[8];
#pragma unroll
        for (int i = 0; i < 8; i++) t[i] = lds64f(red + (i * 32 + lane) * 8);
        const float s = ((t[0].x + t[1].x) + (t[2].x + t[3].x)) + ((t[4].x + t[5].x) + (t[6].x + t[7].x));
        const float u = ((t[0].y + t[1].y) + (t[2].y + t[3].y)) + ((t[4].y + t[5].y) + (t[6].y + t[7].y));
        const float av = s * u * rcp(1.f + ex2(-1.4426950408889634f * s));
        const float an = shx(av, 1);
        if (!odd) stg_rlx32(ap, pack_bf16(av, an));
      }
      bar_sync(1, 256);
      TS(11);
    }
    if (OUT_LATE) mbar_wait(bar_win, 0);
    char* const ob2 = (char*)(out + tok0 * 640 + g * 64);
    const int remo = 896 - 96 * g;
#pragma unroll
    for (int s = 0; s < 5; s++) {
      const int row = s < 4 ? 4 * s + (lane >> 3) : lane >> 1, pc = s < 4 ? lane & 7 : 8 + (lane & 1);
      const uint4 v = lds128(stg + row * 160 + pc * 16);
      if (row != crow) stg128(ob2 + row * 2560 + pc * 16 + (s < 4 ? 0 : remo), v);
    }
    mbar_wait(bar_win, 0);
    const uint4 win = lds128(sb + OFF_WR + 336);
    if (win.x != slot && lane < 10) stg128(ob2 + crow * 2560 + lane * 16 + (lane < 8 ? 0 : remo), held);
    if (!ffn1) {
      TS(10);
      uint4 w2[6];
      const uint32_t a2 = sb + OFF_W2 + (warp * 192 + 8 * (((lane >> 3) & 1) * 4 + ((lane & 7) >> 1)) + 2 * (lane >> 4) + (lane & 1)) * 16;
#pragma unroll
      for (int s = 0; s < 6; s++) w2[s] = ldsm4t(a2 + (s >> 1) * 1024 + (s & 1) * 64);
      const uint4* p = (const uint4*)(g_x.act + warp * 96) + (r & 1) * 4 + c;
      const uint32_t* pb = (const uint32_t*)&g_x.cand[win.x][fj < 64 ? fj >> 3 : (fj - 64) >> 1][fj < 64 ? 12 + (fj & 7) : 20 + (fj & 1)] + c;
      uint32_t* const op = pin((uint32_t*)(out + win.y * 640 + fj * 8) + c);
      uint4 c0, c1, c2; uint32_t bw;
      do {
        c0 = ldg_pkt(p); c1 = ldg_pkt(p + 8); c2 = ldg_pkt(p + 16); bw = ldg_rlx32(pb);
      } while (anyw(max(max(max(max(c0.x, c0.y), max(c0.z, c0.w)), max(max(c1.x, c1.y), max(c1.z, c1.w))), max(max(max(c2.x, c2.y), max(c2.z, c2.w)), bw)) == SENT) && --guard > 0);
      TS(11);
      float a[4] = {0.f, 0.f, 0.f, 0.f}, b[4] = {0.f, 0.f, 0.f, 0.f}, d[4] = {0.f, 0.f, 0.f, 0.f};
      mma_acc(a, w2[0], c0.x, c0.y); mma_acc(b, w2[2], c1.x, c1.y); mma_acc(d, w2[4], c2.x, c2.y);
      mma_acc(a, w2[1], c0.z, c0.w); mma_acc(b, w2[3], c1.z, c1.w); mma_acc(d, w2[5], c2.z, c2.w);
      if (c == 0) sts32f(red + (warp * 8 + r) * 4, ((a[0] + a[3]) + (b[0] + b[3])) + (d[0] + d[3]));
      bar_sync(1, 256);
      if (tid < 4) {
        float2 t[8];
#pragma unroll
        for (int i = 0; i < 8; i++) t[i] = lds64f(red + (i * 4 + tid) * 8);
        const float y0 = ((t[0].x + t[1].x) + (t[2].x + t[3].x)) + ((t[4].x + t[5].x) + (t[6].x + t[7].x));
        const float y1 = ((t[0].y + t[1].y) + (t[2].y + t[3].y)) + ((t[4].y + t[5].y) + (t[6].y + t[7].y));
        const float sg = __uint_as_float(win.z);
        *op = pack_bf16(fmaf(y0, sg, bf_lo(bw)), fmaf(y1, sg, bf_hi(bw)));
      }
    }
    TS(12);
#undef TS_T
  }
}

typedef CUresult (*EncodeFn)(CUtensorMap*, CUtensorMapDataType, cuuint32_t, void*, const cuuint64_t*, const cuuint64_t*, const cuuint32_t*,
                             const cuuint32_t*, CUtensorMapInterleave, CUtensorMapSwizzle, CUtensorMapL2promotion, CUtensorMapFloatOOBfill);

void make_map(EncodeFn enc, CUtensorMap* m, const void* base, const cuuint64_t* dims, const cuuint64_t* strides, const cuuint32_t* box,
              CUtensorMapSwizzle swz) {
  const cuuint32_t es[3] = {1, 1, 1};
  enc(m, CU_TENSOR_MAP_DATA_TYPE_BFLOAT16, 3, (void*)base, dims, strides, box, es, CU_TENSOR_MAP_INTERLEAVE_NONE, swz,
      CU_TENSOR_MAP_L2_PROMOTION_L2_128B, CU_TENSOR_MAP_FLOAT_OOB_FILL_NONE);
}

}

extern "C" void kernel_launch(void* const* d_in, const int* in_sizes, int n_in, void* d_out, int out_size) {
  const __nv_bfloat16* x = (const __nv_bfloat16*)d_in[0];
  const __nv_bfloat16* wqkv = (const __nv_bfloat16*)d_in[1];
  const __nv_bfloat16* wo = (const __nv_bfloat16*)d_in[2];
  void* fn = nullptr;
  cudaDriverEntryPointQueryResult st;
  cudaGetDriverEntryPoint("cuTensorMapEncodeTiled", &fn, cudaEnableDefault, &st);
  EncodeFn enc = (EncodeFn)fn;
  void* scp = nullptr;
  cudaGetSymbolAddress(&scp, g_scratch);
  Maps tm;
  { const cuuint64_t d[3] = {640, 1024, 2}, s[2] = {2560, 1280}; const cuuint32_t b[3] = {64, 64, 2}; make_map(enc, &tm.x, x, d, s, b, CU_TENSOR_MAP_SWIZZLE_128B); }
  { const cuuint64_t d[3] = {640, 640, 3}, s[2] = {3840, 1280}; const cuuint32_t b[3] = {64, 64, 1}; make_map(enc, &tm.w, wqkv, d, s, b, CU_TENSOR_MAP_SWIZZLE_128B); }
  { const cuuint64_t d[3] = {640, 640, 3}, s[2] = {3840, 1280}; const cuuint32_t b[3] = {16, 64, 3}; make_map(enc, &tm.wr, wqkv, d, s, b, CU_TENSOR_MAP_SWIZZLE_32B); }
  { const cuuint64_t d[3] = {32, 640, 20}, s[2] = {1280, 64}; const cuuint32_t b[3] = {32, 80, 2}; make_map(enc, &tm.wo, wo, d, s, b, CU_TENSOR_MAP_SWIZZLE_64B); }
  { const cuuint64_t d[3] = {640, 640, 1}, s[2] = {1280, 819200}; const cuuint32_t b[3] = {16, 80, 1}; make_map(enc, &tm.wor, wo, d, s, b, CU_TENSOR_MAP_SWIZZLE_64B); }
  { const cuuint64_t d[3] = {1536, 640, 1}, s[2] = {3072, 1966080}; const cuuint32_t b[3] = {32, 128, 1};
    make_map(enc, &tm.gate, d_in[5], d, s, b, CU_TENSOR_MAP_SWIZZLE_64B); make_map(enc, &tm.up, d_in[6], d, s, b, CU_TENSOR_MAP_SWIZZLE_64B); }
  { const cuuint64_t d[3] = {640, 1536, 1}, s[2] = {1280, 1966080}; const cuuint32_t b[3] = {8, 128, 1}; make_map(enc, &tm.down, d_in[7], d, s, b, CU_TENSOR_MAP_SWIZZLE_NONE); }
  cudaFuncSetAttribute(fused_kernel, cudaFuncAttributeMaxDynamicSharedMemorySize, SMEM_BYTES);
  fused_kernel<<<128, 384, SMEM_BYTES, cudaStreamPerThread>>>(x, wqkv, wo, (const __nv_bfloat16*)d_in[4], (const __nv_bfloat16*)d_in[5],
                                                              (const __nv_bfloat16*)d_in[6], (const __nv_bfloat16*)d_in[7], (__nv_bfloat16*)d_out, (Scratch*)scp, tm);
}
```

```cpp
#include <cuda_runtime.h>
#include <cuda_bf16.h>
#include <cuda.h>
#include <stdint.h>

#define PF0 1
#define PF_NS 100
#define PFX_IT 1
#define PFW_NS 400
#define ACT_NS 0
#define F_IT 4
#define F_MAX 9
#define F_PER 1
#define OUT_LATE 1
#define REG_P 72
#define REG_C 216
#define AUX_NS 50

namespace {

constexpr int SLOT    = 47104;
constexpr int OFF_O   = 122880;
constexpr int OFF_W2  = 4 * SLOT;
constexpr int OFF_CS  = OFF_W2 + 32768;
constexpr int OFF_RS  = OFF_CS + 3840;
constexpr int OFF_MN  = OFF_RS + 576;
constexpr int OFF_WR  = OFF_MN + 1024;
constexpr int OFF_RED = OFF_CS;
constexpr int OFF_HN  = OFF_CS + 2048;
constexpr int OFF_PT  = OFF_WR + 352;
constexpr int OFF_BAR = OFF_PT + 768;
constexpr int SMEM_BYTES = OFF_BAR + 240 + 288;
constexpr uint32_t SENT = 0xFFFFFFFFu;
constexpr int SPIN_MAX = 1 << 20;

struct Glob {
  uint4 cand[128][8][24];
  uint32_t act[768];
  uint32_t pad[256];
};
constexpr int GLOB_PER_CTA = sizeof(Glob) / 16 / 128;
static_assert(GLOB_PER_CTA * 128 * 16 == sizeof(Glob), "glob size");
struct Own {
  uint4 halo[2][5][32];
  uint4 st1[32];
  uint2 cs[32];
  uint4 st2[16];
  uint4 cnt[8];
};
struct Scratch {
  Glob x;
  Own own[128];
  uint4 o[32][8][640];
  uint32_t epoch[128];
};
__device__ __align__(128) Scratch g_scratch;
#define g_x (sc->x)
#define g_own (sc->own)
#define g_o (sc->o)
#define g_epoch (sc->epoch)
#define TS(i)

__device__ __forceinline__ void mbar_init(uint32_t bar, uint32_t cnt) { asm volatile("mbarrier.init.shared::cta.b64 [%0], %1;" :: "r"(bar), "r"(cnt) : "memory"); }
__device__ __forceinline__ void mbar_expect_tx(uint32_t bar, uint32_t bytes) { asm volatile("mbarrier.arrive.expect_tx.shared::cta.b64 _, [%0], %1;" :: "r"(bar), "r"(bytes) : "memory"); }
__device__ __forceinline__ void mbar_arrive(uint32_t bar) { asm volatile("mbarrier.arrive.shared::cta.b64 _, [%0];" :: "r"(bar) : "memory"); }
__device__ __forceinline__ void mbar_arrive_cta(uint32_t bar, uint32_t cta) {
  asm volatile("{\n.reg .b32 ra;\nmapa.shared::cluster.u32 ra, %0, %1;\nmbarrier.arrive.shared::cluster.b64 _, [ra];\n}\n" :: "r"(bar), "r"(cta) : "memory");
}
__device__ __forceinline__ void mbar_wait(uint32_t bar, uint32_t parity) {
  asm volatile("{\n.reg .pred p;\n.reg .u32 n;\nmov.u32 n, 0;\nW:\nmbarrier.try_wait.parity.shared::cta.b64 p, [%0], %1;\n@p bra.uni D;\n"
               "add.u32 n, n, 1;\nsetp.lt.u32 p, n, %2;\n@p bra.uni W;\nD:\n}\n" :: "r"(bar), "r"(parity), "n"(SPIN_MAX) : "memory");
}
__device__ __forceinline__ void tma_3d(uint32_t dst, const void* tm, uint32_t bar, int c0, int c1, int c2) {
  asm volatile("cp.async.bulk.tensor.3d.shared::cluster.global.mbarrier::complete_tx::bytes [%0], [%1, {%3, %4, %5}], [%2];" :: "r"(dst), "l"(tm), "r"(bar), "r"(c0), "r"(c1), "r"(c2) : "memory");
}
__device__ __forceinline__ void tma_3d_mc(uint32_t dst, const void* tm, uint32_t bar, int c0, int c1, int c2) {
  asm volatile("cp.async.bulk.tensor.3d.shared::cluster.global.mbarrier::complete_tx::bytes.multicast::cluster [%0], [%1, {%3, %4, %5}], [%2], %6;" :: "r"(dst), "l"(tm), "r"(bar), "r"(c0), "r"(c1), "r"(c2), "h"((uint16_t)3) : "memory");
}
__device__ __forceinline__ void wgmma_fence() { asm volatile("wgmma.fence.sync.aligned;" ::: "memory"); }
__device__ __forceinline__ void wgmma_commit() { asm volatile("wgmma.commit_group.sync.aligned;" ::: "memory"); }
template <int N> __device__ __forceinline__ void wgmma_wait() { asm volatile("wgmma.wait_group.sync.aligned %0;" :: "n"(N) : "memory"); }
__device__ __forceinline__ uint64_t make_desc(uint32_t addr, uint32_t lbo, uint32_t sbo, uint32_t swz) {
  return (uint64_t)(((addr & 0x3FFFF) >> 4) | ((lbo >> 4) << 16)) | ((uint64_t)((sbo >> 4) | (swz << 30)) << 32);
}
__device__ __forceinline__ void bar_sync(int id, int n) { asm volatile("bar.sync %0, %1;" :: "r"(id), "r"(n) : "memory"); }
__device__ __forceinline__ uint4 ld_pkt(const void* p) {
  uint4 v;
  asm volatile("{\n.reg .b128 t;\n.reg .b64 lo, hi;\nld.relaxed.gpu.b128 t, [%4];\nmov.b128 {lo, hi}, t;\nmov.b64 {%0, %1}, lo;\nmov.b64 {%2, %3}, hi;\n}\n"
               : "=r"(v.x), "=r"(v.y), "=r"(v.z), "=r"(v.w) : "l"(p) : "memory");
  return v;
}
__device__ __forceinline__ void st_pkt(void* p, uint32_t a, uint32_t b, uint32_t c, uint32_t d) {
  asm volatile("{\n.reg .b128 t;\n.reg .b64 lo, hi;\nmov.b64 lo, {%1, %2};\nmov.b64 hi, {%3, %4};\nmov.b128 t, {lo, hi};\nst.relaxed.gpu.b128 [%0], t;\n}\n"
               :: "l"(p), "r"(a), "r"(b), "r"(c), "r"(d) : "memory");
}
__device__ __forceinline__ uint4 ldg_pkt(const void* p) {
  uint4 v;
  asm volatile("{\n.reg .b128 t;\n.reg .b64 lo, hi;\nld.relaxed.gpu.global.b128 t, [%4];\nmov.b128 {lo, hi}, t;\nmov.b64 {%0, %1}, lo;\nmov.b64 {%2, %3}, hi;\n}\n"
               : "=r"(v.x), "=r"(v.y), "=r"(v.z), "=r"(v.w) : "l"(p) : "memory");
  return v;
}
__device__ __forceinline__ void stg_pkt(void* p, uint32_t a, uint32_t b, uint32_t c, uint32_t d) {
  asm volatile("{\n.reg .b128 t;\n.reg .b64 lo, hi;\nmov.b64 lo, {%1, %2};\nmov.b64 hi, {%3, %4};\nmov.b128 t, {lo, hi};\nst.relaxed.gpu.global.b128 [%0], t;\n}\n"
               :: "l"(p), "r"(a), "r"(b), "r"(c), "r"(d) : "memory");
}
__device__ __forceinline__ uint32_t ldg_rlx32(const void* p) { uint32_t v; asm volatile("ld.relaxed.gpu.global.u32 %0, [%1];" : "=r"(v) : "l"(p) : "memory"); return v; }
__device__ __forceinline__ uint2 ldg_rlx64(const void* p) { uint2 v; asm volatile("ld.relaxed.gpu.global.v2.u32 {%0, %1}, [%2];" : "=r"(v.x), "=r"(v.y) : "l"(p) : "memory"); return v; }
__device__ __forceinline__ void stg128(void* p, const uint4& v) { asm volatile("st.global.v4.u32 [%0], {%1, %2, %3, %4};" :: "l"(p), "r"(v.x), "r"(v.y), "r"(v.z), "r"(v.w) : "memory"); }
template <class T> __device__ __forceinline__ T* pin(T* p) { asm volatile("" : "+l"(p)); return p; }
__device__ __forceinline__ void stg_rlx32(void* p, uint32_t v) { asm volatile("st.relaxed.gpu.global.u32 [%0], %1;" :: "l"(p), "r"(v) : "memory"); }
__device__ __forceinline__ void stg_rlx64(void* p, uint32_t a, uint32_t b) { asm volatile("st.relaxed.gpu.global.v2.u32 [%0], {%1, %2};" :: "l"(p), "r"(a), "r"(b) : "memory"); }
__device__ __forceinline__ uint4 ldsm4(uint32_t a) { uint4 v; asm volatile("ldmatrix.sync.aligned.m8n8.x4.shared.b16 {%0, %1, %2, %3}, [%4];" : "=r"(v.x), "=r"(v.y), "=r"(v.z), "=r"(v.w) : "r"(a) : "memory"); return v; }
__device__ __forceinline__ uint4 ldsm4t(uint32_t a) { uint4 v; asm volatile("ldmatrix.sync.aligned.m8n8.x4.trans.shared.b16 {%0, %1, %2, %3}, [%4];" : "=r"(v.x), "=r"(v.y), "=r"(v.z), "=r"(v.w) : "r"(a) : "memory"); return v; }
__device__ __forceinline__ void stsm4(uint32_t a, uint32_t x, uint32_t y, uint32_t z, uint32_t w) { asm volatile("stmatrix.sync.aligned.m8n8.x4.shared.b16 [%0], {%1, %2, %3, %4};" :: "r"(a), "r"(x), "r"(y), "r"(z), "r"(w) : "memory"); }
__device__ __forceinline__ void mma_acc(float (&c)[4], const uint4& a, uint32_t b0, uint32_t b1) {
  asm("mma.sync.aligned.m16n8k16.row.col.f32.bf16.bf16.f32 {%0,%1,%2,%3}, {%4,%5,%6,%7}, {%8,%9}, {%0,%1,%2,%3};"
      : "+f"(c[0]), "+f"(c[1]), "+f"(c[2]), "+f"(c[3]) : "r"(a.x), "r"(a.y), "r"(a.z), "r"(a.w), "r"(b0), "r"(b1));
}
__device__ __forceinline__ uint4 lds128(uint32_t a) { uint4 v; asm volatile("ld.shared.v4.u32 {%0, %1, %2, %3}, [%4];" : "=r"(v.x), "=r"(v.y), "=r"(v.z), "=r"(v.w) : "r"(a) : "memory"); return v; }
__device__ __forceinline__ float2 lds64f(uint32_t a) { float2 v; asm volatile("ld.shared.v2.f32 {%0, %1}, [%2];" : "=f"(v.x), "=f"(v.y) : "r"(a)); return v; }
__device__ __forceinline__ float lds32f(uint32_t a) { float v; asm volatile("ld.shared.f32 %0, [%1];" : "=f"(v) : "r"(a)); return v; }
__device__ __forceinline__ void sts32f(uint32_t a, float v) { asm volatile("st.shared.f32 [%0], %1;" :: "r"(a), "f"(v) : "memory"); }
__device__ __forceinline__ uint32_t pack_bf16(float lo, float hi) { uint32_t r; asm("cvt.rn.bf16x2.f32 %0, %1, %2;" : "=r"(r) : "f"(hi), "f"(lo)); return r; }
__device__ __forceinline__ float bf_lo(uint32_t v) { return __uint_as_float(v << 16); }
__device__ __forceinline__ float bf_hi(uint32_t v) { return __uint_as_float(v & 0xffff0000u); }
__device__ __forceinline__ uint32_t movm(uint32_t a) { uint32_t d; asm("movmatrix.sync.aligned.m8n8.trans.b16 %0, %1;" : "=r"(d) : "r"(a)); return d; }
__device__ __forceinline__ float ex2(float x) { float y; asm("ex2.approx.ftz.f32 %0, %1;" : "=f"(y) : "f"(x)); return y; }
__device__ __forceinline__ float rsq(float x) { float y; asm("rsqrt.approx.ftz.f32 %0, %1;" : "=f"(y) : "f"(x)); return y; }
__device__ __forceinline__ float rcp(float x) { float y; asm("rcp.approx.ftz.f32 %0, %1;" : "=f"(y) : "f"(x)); return y; }
__device__ __forceinline__ bool elect() { uint32_t p; asm volatile("{\n.reg .pred q;\nelect.sync _|q, 0xffffffff;\nselp.u32 %0, 1, 0, q;\n}\n" : "=r"(p)); return p; }
__device__ __forceinline__ void pf_l2(const void* p) { asm volatile("prefetch.global.L2 [%0];" :: "l"(p)); }
__device__ __forceinline__ bool anyw(bool p) { return __any_sync(0xffffffffu, p); }
__device__ __forceinline__ float shx(float v, int m) { return __shfl_xor_sync(0xffffffffu, v, m); }
__device__ __forceinline__ void mma_k24(float (&c)[4], uint32_t a0, uint32_t a1, uint32_t a2, uint32_t a3, uint32_t b0, uint32_t b1,
                                        uint32_t e0, uint32_t e1, uint32_t f0) {
  asm("mma.sync.aligned.m16n8k16.row.col.f32.bf16.bf16.f32 {%0,%1,%2,%3}, {%4,%5,%6,%7}, {%8,%9}, {%10,%10,%10,%10};"
      : "=f"(c[0]), "=f"(c[1]), "=f"(c[2]), "=f"(c[3]) : "r"(a0), "r"(a1), "r"(a2), "r"(a3), "r"(b0), "r"(b1), "f"(0.f));
  asm("mma.sync.aligned.m16n8k8.row.col.f32.bf16.bf16.f32 {%0,%1,%2,%3}, {%4,%5}, {%6}, {%0,%1,%2,%3};"
      : "+f"(c[0]), "+f"(c[1]), "+f"(c[2]), "+f"(c[3]) : "r"(e0), "r"(e1), "r"(f0));
}
__device__ __forceinline__ uint32_t ord_key(float r) { uint32_t u = __float_as_uint(r); return u ^ ((uint32_t)((int32_t)u >> 31) | 0x80000000u); }

__device__ __forceinline__ void wgmma_n48hi_rk(float (&d)[120], uint32_t a0, uint32_t a1, uint32_t a2, uint32_t a3, uint64_t db, int scale_d) {
  asm volatile("{\n.reg .pred p;\nsetp.ne.b32 p, %29, 0;\n"
    "wgmma.mma_async.sync.aligned.m64n48k16.f32.bf16.bf16 "
    "{%0, %1, %2, %3, %4, %5, %6, %7, %8, %9, %10, %11, %12, %13, %14, %15, "
    "%16, %17, %18, %19, %20, %21, %22, %23}, "
    "{%24, %25, %26, %27}, %28, p, 1, 1, 0;\n}\n"
    : "+f"(d[96]), "+f"(d[97]), "+f"(d[98]), "+f"(d[99]), "+f"(d[100]), "+f"(d[101]), "+f"(d[102]), "+f"(d[103]),
      "+f"(d[104]), "+f"(d[105]), "+f"(d[106]), "+f"(d[107]), "+f"(d[108]), "+f"(d[109]), "+f"(d[110]), "+f"(d[111]),
      "+f"(d[112]), "+f"(d[113]), "+f"(d[114]), "+f"(d[115]), "+f"(d[116]), "+f"(d[117]), "+f"(d[118]), "+f"(d[119])
    : "r"(a0), "r"(a1), "r"(a2), "r"(a3), "l"(db), "r"(scale_d));
}
__device__ __forceinline__ void wgmma_n192lo_rk(float (&d)[120], uint32_t a0, uint32_t a1, uint32_t a2, uint32_t a3, uint64_t db, int scale_d) {
  asm volatile("{\n.reg .pred p;\nsetp.ne.b32 p, %101, 0;\n"
    "wgmma.mma_async.sync.aligned.m64n192k16.f32.bf16.bf16 "
    "{%0, %1, %2, %3, %4, %5, %6, %7, %8, %9, %10, %11, %12, %13, %14, %15, "
    "%16, %17, %18, %19, %20, %21, %22, %23, %24, %25, %26, %27, %28, %29, %30, %31, "
    "%32, %33, %34, %35, %36, %37, %38, %39, %40, %41, %42, %43, %44, %45, %46, %47, "
    "%48, %49, %50, %51, %52, %53, %54, %55, %56, %57, %58, %59, %60, %61, %62, %63, "
    "%64, %65, %66, %67, %68, %69, %70, %71, %72, %73, %74, %75, %76, %77, %78, %79, "
    "%80, %81, %82, %83, %84, %85, %86, %87, %88, %89, %90, %91, %92, %93, %94, %95}, "
    "{%96, %97, %98, %99}, %100, p, 1, 1, 0;\n}\n"
    : "+f"(d[0]), "+f"(d[1]), "+f"(d[2]), "+f"(d[3]), "+f"(d[4]), "+f"(d[5]), "+f"(d[6]), "+f"(d[7]),
      "+f"(d[8]), "+f"(d[9]), "+f"(d[10]), "+f"(d[11]), "+f"(d[12]), "+f"(d[13]), "+f"(d[14]), "+f"(d[15]),
      "+f"(d[16]), "+f"(d[17]), "+f"(d[18]), "+f"(d[19]), "+f"(d[20]), "+f"(d[21]), "+f"(d[22]), "+f"(d[23]),
      "+f"(d[24]), "+f"(d[25]), "+f"(d[26]), "+f"(d[27]), "+f"(d[28]), "+f"(d[29]), "+f"(d[30]), "+f"(d[31]),
      "+f"(d[32]), "+f"(d[33]), "+f"(d[34]), "+f"(d[35]), "+f"(d[36]), "+f"(d[37]), "+f"(d[38]), "+f"(d[39]),
      "+f"(d[40]), "+f"(d[41]), "+f"(d[42]), "+f"(d[43]), "+f"(d[44]), "+f"(d[45]), "+f"(d[46]), "+f"(d[47]),
      "+f"(d[48]), "+f"(d[49]), "+f"(d[50]), "+f"(d[51]), "+f"(d[52]), "+f"(d[53]), "+f"(d[54]), "+f"(d[55]),
      "+f"(d[56]), "+f"(d[57]), "+f"(d[58]), "+f"(d[59]), "+f"(d[60]), "+f"(d[61]), "+f"(d[62]), "+f"(d[63]),
      "+f"(d[64]), "+f"(d[65]), "+f"(d[66]), "+f"(d[67]), "+f"(d[68]), "+f"(d[69]), "+f"(d[70]), "+f"(d[71]),
      "+f"(d[72]), "+f"(d[73]), "+f"(d[74]), "+f"(d[75]), "+f"(d[76]), "+f"(d[77]), "+f"(d[78]), "+f"(d[79]),
      "+f"(d[80]), "+f"(d[81]), "+f"(d[82]), "+f"(d[83]), "+f"(d[84]), "+f"(d[85]), "+f"(d[86]), "+f"(d[87]),
      "+f"(d[88]), "+f"(d[89]), "+f"(d[90]), "+f"(d[91]), "+f"(d[92]), "+f"(d[93]), "+f"(d[94]), "+f"(d[95])
    : "r"(a0), "r"(a1), "r"(a2), "r"(a3), "l"(db), "r"(scale_d));
}
__device__ __forceinline__ void wgmma_n48hi_ss(float (&d)[120], uint64_t da, uint64_t db, int scale_d) {
  asm volatile("{\n.reg .pred p;\nsetp.ne.b32 p, %26, 0;\n"
    "wgmma.mma_async.sync.aligned.m64n48k16.f32.bf16.bf16 "
    "{%0, %1, %2, %3, %4, %5, %6, %7, %8, %9, %10, %11, %12, %13, %14, %15, "
    "%16, %17, %18, %19, %20, %21, %22, %23}, "
    "%24, %25, p, 1, 1, 0, 1;\n}\n"
    : "+f"(d[96]), "+f"(d[97]), "+f"(d[98]), "+f"(d[99]), "+f"(d[100]), "+f"(d[101]), "+f"(d[102]), "+f"(d[103]),
      "+f"(d[104]), "+f"(d[105]), "+f"(d[106]), "+f"(d[107]), "+f"(d[108]), "+f"(d[109]), "+f"(d[110]), "+f"(d[111]),
      "+f"(d[112]), "+f"(d[113]), "+f"(d[114]), "+f"(d[115]), "+f"(d[116]), "+f"(d[117]), "+f"(d[118]), "+f"(d[119])
    : "l"(da), "l"(db), "r"(scale_d));
}
__device__ __forceinline__ void wgmma_n192lo_ss(float (&d)[120], uint64_t da, uint64_t db, int scale_d) {
  asm volatile("{\n.reg .pred p;\nsetp.ne.b32 p, %98, 0;\n"
    "wgmma.mma_async.sync.aligned.m64n192k16.f32.bf16.bf16 "
    "{%0, %1, %2, %3, %4, %5, %6, %7, %8, %9, %10, %11, %12, %13, %14, %15, "
    "%16, %17, %18, %19, %20, %21, %22, %23, %24, %25, %26, %27, %28, %29, %30, %31, "
    "%32, %33, %34, %35, %36, %37, %38, %39, %40, %41, %42, %43, %44, %45, %46, %47, "
    "%48, %49, %50, %51, %52, %53, %54, %55, %56, %57, %58, %59, %60, %61, %62, %63, "
    "%64, %65, %66, %67, %68, %69, %70, %71, %72, %73, %74, %75, %76, %77, %78, %79, "
    "%80, %81, %82, %83, %84, %85, %86, %87, %88, %89, %90, %91, %92, %93, %94, %95}, "
    "%96, %97, p, 1, 1, 0, 1;\n}\n"
    : "+f"(d[0]), "+f"(d[1]), "+f"(d[2]), "+f"(d[3]), "+f"(d[4]), "+f"(d[5]), "+f"(d[6]), "+f"(d[7]),
      "+f"(d[8]), "+f"(d[9]), "+f"(d[10]), "+f"(d[11]), "+f"(d[12]), "+f"(d[13]), "+f"(d[14]), "+f"(d[15]),
      "+f"(d[16]), "+f"(d[17]), "+f"(d[18]), "+f"(d[19]), "+f"(d[20]), "+f"(d[21]), "+f"(d[22]), "+f"(d[23]),
      "+f"(d[24]), "+f"(d[25]), "+f"(d[26]), "+f"(d[27]), "+f"(d[28]), "+f"(d[29]), "+f"(d[30]), "+f"(d[31]),
      "+f"(d[32]), "+f"(d[33]), "+f"(d[34]), "+f"(d[35]), "+f"(d[36]), "+f"(d[37]), "+f"(d[38]), "+f"(d[39]),
      "+f"(d[40]), "+f"(d[41]), "+f"(d[42]), "+f"(d[43]), "+f"(d[44]), "+f"(d[45]), "+f"(d[46]), "+f"(d[47]),
      "+f"(d[48]), "+f"(d[49]), "+f"(d[50]), "+f"(d[51]), "+f"(d[52]), "+f"(d[53]), "+f"(d[54]), "+f"(d[55]),
      "+f"(d[56]), "+f"(d[57]), "+f"(d[58]), "+f"(d[59]), "+f"(d[60]), "+f"(d[61]), "+f"(d[62]), "+f"(d[63]),
      "+f"(d[64]), "+f"(d[65]), "+f"(d[66]), "+f"(d[67]), "+f"(d[68]), "+f"(d[69]), "+f"(d[70]), "+f"(d[71]),
      "+f"(d[72]), "+f"(d[73]), "+f"(d[74]), "+f"(d[75]), "+f"(d[76]), "+f"(d[77]), "+f"(d[78]), "+f"(d[79]),
      "+f"(d[80]), "+f"(d[81]), "+f"(d[82]), "+f"(d[83]), "+f"(d[84]), "+f"(d[85]), "+f"(d[86]), "+f"(d[87]),
      "+f"(d[88]), "+f"(d[89]), "+f"(d[90]), "+f"(d[91]), "+f"(d[92]), "+f"(d[93]), "+f"(d[94]), "+f"(d[95])
    : "l"(da), "l"(db), "r"(scale_d));
}
__device__ __forceinline__ void wgmma_n80_rs(float (&d)[40], uint32_t a0, uint32_t a1, uint32_t a2, uint32_t a3, uint64_t db, int scale_d) {
  asm volatile("{\n.reg .pred p;\nsetp.ne.b32 p, %45, 0;\n"
    "wgmma.mma_async.sync.aligned.m64n80k16.f32.bf16.bf16 "
    "{%0, %1, %2, %3, %4, %5, %6, %7, %8, %9, %10, %11, %12, %13, %14, %15, "
    "%16, %17, %18, %19, %20, %21, %22, %23, %24, %25, %26, %27, %28, %29, %30, %31, "
    "%32, %33, %34, %35, %36, %37, %38, %39}, "
    "{%40, %41, %42, %43}, %44, p, 1, 1, 1;\n}\n"
    : "+f"(d[0]), "+f"(d[1]), "+f"(d[2]), "+f"(d[3]), "+f"(d[4]), "+f"(d[5]), "+f"(d[6]), "+f"(d[7]),
      "+f"(d[8]), "+f"(d[9]), "+f"(d[10]), "+f"(d[11]), "+f"(d[12]), "+f"(d[13]), "+f"(d[14]), "+f"(d[15]),
      "+f"(d[16]), "+f"(d[17]), "+f"(d[18]), "+f"(d[19]), "+f"(d[20]), "+f"(d[21]), "+f"(d[22]), "+f"(d[23]),
      "+f"(d[24]), "+f"(d[25]), "+f"(d[26]), "+f"(d[27]), "+f"(d[28]), "+f"(d[29]), "+f"(d[30]), "+f"(d[31]),
      "+f"(d[32]), "+f"(d[33]), "+f"(d[34]), "+f"(d[35]), "+f"(d[36]), "+f"(d[37]), "+f"(d[38]), "+f"(d[39])
    : "r"(a0), "r"(a1), "r"(a2), "r"(a3), "l"(db), "r"(scale_d));
}
__device__ __forceinline__ void wgmma_n80_ss(float (&d)[40], uint64_t da, uint64_t db, int scale_d) {
  asm volatile("{\n.reg .pred p;\nsetp.ne.b32 p, %42, 0;\n"
    "wgmma.mma_async.sync.aligned.m64n80k16.f32.bf16.bf16 "
    "{%0, %1, %2, %3, %4, %5, %6, %7, %8, %9, %10, %11, %12, %13, %14, %15, "
    "%16, %17, %18, %19, %20, %21, %22, %23, %24, %25, %26, %27, %28, %29, %30, %31, "
    "%32, %33, %34, %35, %36, %37, %38, %39}, "
    "%40, %41, p, 1, 1, 0, 1;\n}\n"
    : "+f"(d[0]), "+f"(d[1]), "+f"(d[2]), "+f"(d[3]), "+f"(d[4]), "+f"(d[5]), "+f"(d[6]), "+f"(d[7]),
      "+f"(d[8]), "+f"(d[9]), "+f"(d[10]), "+f"(d[11]), "+f"(d[12]), "+f"(d[13]), "+f"(d[14]), "+f"(d[15]),
      "+f"(d[16]), "+f"(d[17]), "+f"(d[18]), "+f"(d[19]), "+f"(d[20]), "+f"(d[21]), "+f"(d[22]), "+f"(d[23]),
      "+f"(d[24]), "+f"(d[25]), "+f"(d[26]), "+f"(d[27]), "+f"(d[28]), "+f"(d[29]), "+f"(d[30]), "+f"(d[31]),
      "+f"(d[32]), "+f"(d[33]), "+f"(d[34]), "+f"(d[35]), "+f"(d[36]), "+f"(d[37]), "+f"(d[38]), "+f"(d[39])
    : "l"(da), "l"(db), "r"(scale_d));
}

__device__ __forceinline__ constexpr int QT(int t) { return t < 8 ? t : 16 + t; }
__device__ __forceinline__ constexpr int KT(int t) { return t < 8 ? 8 + t : 18 + t; }
__device__ __forceinline__ constexpr int VT(int t) { return t < 8 ? 16 + t : 20 + t; }

struct Maps { CUtensorMap x, w, wr, wo, wor, gate, up, down; };

__global__ void __cluster_dims__(2, 1, 1) __launch_bounds__(384, 1)
fused_kernel(const __nv_bfloat16* __restrict__ x, const __nv_bfloat16* __restrict__ wqkv,
             const __nv_bfloat16* __restrict__ wo, const __nv_bfloat16* __restrict__ w_r, const __nv_bfloat16* __restrict__ w_gate,
             const __nv_bfloat16* __restrict__ w_up, const __nv_bfloat16* __restrict__ w_down, __nv_bfloat16* __restrict__ out,
             Scratch* __restrict__ sc, const __grid_constant__ Maps tm) {
  extern __shared__ __align__(1024) uint8_t smem[];
  const int tid = threadIdx.x, warp = __shfl_sync(0xffffffffu, tid >> 5, 0), lane = tid & 31, bid = blockIdx.x;
  const uint32_t sb = (uint32_t)__cvta_generic_to_shared(smem);
  const uint32_t bar_full = sb + OFF_BAR, bar_empty = bar_full + 32, bar_aux = bar_full + 64, bar_ffn = bar_full + 72, bar_win = bar_full + 80,
                 bar_o = bar_full + 96;
  if (warp < 4 && elect()) {
    mbar_init(bar_full + 8 * (warp ^ 2), 1);
    mbar_init(bar_empty + 8 * warp, 4);
    mbar_init(bar_aux + 8 * warp, warp == 0 ? 64 : warp == 2 ? 32 : 1);
    asm volatile("fence.mbarrier_init.release.cluster;" ::: "memory");
  }
  if (warp >= 4 && elect()) { mbar_init(bar_o + 16 * (warp - 4), 1); mbar_init(bar_o + 16 * (warp - 4) + 8, (warp & 3) == 1 ? 128 : 1); }
  asm volatile("barrier.cluster.arrive.relaxed.aligned;" ::: "memory");
  if (warp >= 8 && warp < 11 && elect()) asm volatile("prefetch.tensormap [%0];" :: "l"(&tm.x + (warp - 8)) : "memory");
  auto pf_slice = [&](int ks) {
    pf_l2(lane < 16 ? (const char*)x + ((bid * 16 + lane) * 1280 + ks * 128) : (const char*)wqkv + ((bid * 15 + min(lane, 30) - 16) * 128 + ks * 245760));
  };
  if (warp >= 4 && warp < 4 + PF0) {
    if (warp > 4) __nanosleep(300 + (warp - 4) * PF_NS);
    pf_slice(warp == 6 ? 5 : warp - 4);
  }
  const int rank = bid & 1, cl = bid >> 1;
  const int q7 = ((cl - 36) * 37) >> 8;
  const int P = cl < 4 ? 0 : cl < 36 ? (cl - 4) & 7 : cl - 35 - 7 * q7;
  const int g = cl < 4 ? 4 + cl : cl < 36 ? (cl - 4) >> 3 : 4 + q7;
  const int mt = 2 * P + rank, cid = mt * 8 + g;
  const bool ffn1 = g < 3;
  const int fj = ffn1 ? mt * 3 + g : (P * 5 + g - 3) * 2 + rank;
  const int ord = ((g >> 2) ^ P) & 1;
  auto ks_of = [&](int it) { return ord == 0 || it == 0 ? it : it <= 5 ? it + 4 : it - 5; };
  auto load_w = [&](int it, uint32_t a, uint32_t full) {
    tma_3d_mc(a + 16384 + rank * 16384, &tm.w, full, g * 80, it * 64, rank * 2);
    tma_3d_mc(a + (rank ? 40960 : 24576), rank ? &tm.wr : &tm.w, full, g * 80 + rank * 64, it * 64, 1 - rank);
  };
  if (warp == 0 && elect()) {
    mbar_expect_tx(bar_full + 16, SLOT);
    tma_3d(sb + 2 * SLOT, &tm.x, bar_full + 16, 0, mt * 64, 0);
  }
  asm volatile("barrier.cluster.wait.aligned;" ::: "memory");
  if (warp == 0) {
    if (elect()) load_w(0, sb + 2 * SLOT, bar_full + 16);
    asm volatile("bar.arrive 4, 64;" ::: "memory");
  }

  if (warp >= 8) {
    asm volatile("setmaxnreg.dec.sync.aligned.u32 %0;" :: "n"(REG_P));
#define TS_T 0
    if (warp == 8) {
      TS(8);
      bar_sync(4, 64);
      if (elect()) {
        TS(10);
        int fjn = 0;
#pragma unroll 1
        for (int it = 1; it < 17; it++) {
          const int s = (it + 2) & 3;
          const uint32_t full = bar_full + 8 * s, a = sb + s * SLOT;
          if (it >= 13) { mbar_wait(bar_o + 32 + 8 * (it - 13), 0); mbar_wait(bar_o + 96 + 8 * (it - 13), 0); }
          else if (it >= 4) mbar_wait(bar_empty + 8 * s, ((it >> 2) - 1) & 1);
          if (it < 10) {
            const int ks = ks_of(it);
            mbar_expect_tx(full, SLOT);
            tma_3d(a, &tm.x, full, ks * 64, mt * 64, 0);
            load_w(ks, a, full);
            if (it == 1) TS(9);
          } else if (it < 13) {
            const int g0 = 3 * (it - 10), g1 = min(g0 + 3, 8);
            mbar_expect_tx(full, (g1 - g0) * 12800);
#pragma unroll 1
            for (int gp = g0 + ((g0 ^ rank) & 1); gp < g1; gp += 2) {
              tma_3d_mc(sb + gp * 15360, &tm.wo, full, 0, gp * 80, g * 2);
              tma_3d_mc(sb + gp * 15360 + 10240, &tm.wor, full, 512 + g * 16, gp * 80, 0);
            }
          }
          if (it == 4) mbar_expect_tx(bar_ffn, ffn1 ? 81920 : 24576);
          const int j1 = ffn1 ? (it >= 13 ? min(2 * it - 21, 10) : min(max(it - F_IT + 1, 0), 4)) : (it >= 13 ? 12 : min(max((it - F_IT + 1) * F_PER, 0), F_MAX));
#pragma unroll 1
          for (; fjn < j1; fjn++) {
            const int j = fjn < 4 ? fjn + 6 : fjn - 4;
            if (ffn1) tma_3d(sb + (j < 6 ? 0 : OFF_W2 - 49152) + j * 8192, j < 5 ? &tm.gate : &tm.up, bar_ffn, fj * 32, (j < 5 ? j : j - 5) * 128, 0);
            else tma_3d(sb + OFF_W2 + fjn * 2048, &tm.down, bar_ffn, fj * 8, fjn * 128, 0);
          }
        }
        TS(11);
      }
#undef TS_T
#define TS_T 32
    } else if (warp < 11) {
      Own* const own = g_own + cid;
      const int l7 = lane & 7, hk = lane >> 4, idx = lane;
      mbar_wait(bar_full + 8 * ((PFX_IT + 2) & 3), 0);
      pf_slice(warp == 9 ? 4 : 8);
      if (warp == 9) pf_slice(9);
#pragma unroll 1
      for (int i = 0; i < 4; i++) {
        __nanosleep(PFW_NS);
        const char* b = (const char*)(i == 0 ? w_down : i == 1 ? w_up : i == 2 ? wo : w_gate);
        const int n = i == 2 ? 50 : 120, t = tid - 288;
        if (t < n) pf_l2(b + (bid * n + t) * 128);
        if (t + 64 < n) pf_l2(b + (bid * n + t + 64) * 128);
      }
      bar_sync(2, 352);
      TS(0);
      const uint32_t tag = __float_as_uint(lds32f(sb + OFF_WR + 324));
      const uint32_t pt = sb + OFF_PT + lane * 4 + (warp - 9) * 512;
      const float s0 = lds32f(pt) + lds32f(pt + 128), q0 = lds32f(sb + OFF_PT + 256 + lane * 4) + lds32f(sb + OFF_PT + 384 + lane * 4);
      int guard = SPIN_MAX;
      if (warp == 9) {
        stg_pkt(&own->st1[idx], __float_as_uint(s0), __float_as_uint(q0), tag, 0u);
        TS(1);
        const uint4* sp = &g_own[mt * 8].st1[lane];
        const uint4* hp = &g_own[max(mt - 1, 0) * 8 + hk * 2 + 1].st1[24 + l7];
        uint4 a[5], b[5];
        bool bad;
        do {
          __nanosleep(AUX_NS);
          bad = false;
#pragma unroll
          for (int i = 0; i < 5; i++) {
            const uint4* q = i < 4 ? sp + i * (sizeof(Own) / 16) : hp;
            a[i] = ldg_pkt(q); b[i] = ldg_pkt(q + 4 * sizeof(Own) / 16);
          }
#pragma unroll
          for (int i = 0; i < 5; i++) bad |= a[i].z != tag || b[i].z != tag;
        } while (anyw(bad) && --guard);
#pragma unroll
        for (int i = 0; i < 5; i++) {
          const float m = (__uint_as_float(a[i].x) + __uint_as_float(b[i].x)) * (1.f / 640.f);
          const float rs = rsq(fmaxf(fmaf(-m, m, (__uint_as_float(a[i].y) + __uint_as_float(b[i].y)) * (1.f / 640.f)), 0.f) + 1e-5f);
          ((float*)(smem + OFF_RS))[i < 4 ? 8 + lane + 32 * i + 8 * (i >> 1) : hk * 72 + l7] = rs;
          const uint32_t mh = pack_bf16(-m, -m);
          const float ml = -m - bf_lo(mh);
          if (i < 4) ((uint2*)(smem + OFF_MN))[lane + 32 * i] = make_uint2(mh, pack_bf16(ml, ml));
        }
      } else {
        stg_rlx64(&own->cs[idx], __float_as_uint(s0), tag);
        const uint4* cp = (const uint4*)g_own[hk * 8 + g].cs + (lane & 15);
        uint4 a[4], b[4];
        bool bad;
        do {
          __nanosleep(AUX_NS);
          bad = false;
#pragma unroll
          for (int i = 0; i < 4; i++) { a[i] = ldg_pkt(cp + i * 32 * sizeof(Own) / 16); b[i] = ldg_pkt(cp + (i * 32 + 16) * sizeof(Own) / 16); }
#pragma unroll
          for (int i = 0; i < 4; i++) bad |= a[i].y != tag || a[i].w != tag || b[i].y != tag || b[i].w != tag;
        } while (anyw(bad) && --guard);
#pragma unroll
        for (int i = 0; i < 4; i++)
          if (i < 3 || lane < 24) {
            const float c0 = __uint_as_float(a[i].x) + __uint_as_float(b[i].x), c1 = __uint_as_float(a[i].z) + __uint_as_float(b[i].z);
            const uint32_t hi = pack_bf16(c0, c1), w0 = pack_bf16(c0, c0 - bf_lo(hi)), w1 = pack_bf16(c1, c1 - bf_hi(hi));
            uint4* const d = (uint4*)(smem + OFF_CS) + 2 * (lane + 32 * i);
            d[0] = make_uint4(w0, w0, 0, 0); d[1] = make_uint4(w1, w1, 0, 0);
          }
        asm volatile("fence.proxy.async.shared::cta;" ::: "memory");
      }
      mbar_arrive(bar_aux);
      TS(2);
      const int wq = warp - 9;
      const uint4* const fp = pin(g_own[mt * 8 + wq * 4].cnt);
      const char* const src = (const char*)g_o[mt * 2 + wq];
      bar_sync(5 + wq, 160);
      if (elect()) {
        while (ldg_rlx32(fp) != 32u && --guard > 0) {}
        asm volatile("fence.proxy.async.global;" ::: "memory");
        TS(6);
#pragma unroll 1
        for (int i = 0, sl = 0; i < 7; i++) {
          const uint32_t full = bar_o + wq * 64 + 8 * sl;
          if (i >= 3) mbar_wait(bar_o + wq * 64 + 8 + 8 * i, 0);
          mbar_expect_tx(full, 10240);
          asm volatile("cp.async.bulk.shared::cluster.global.mbarrier::complete_tx::bytes [%0], [%1], 10240, [%2];"
                       :: "r"(sb + OFF_O + sl * 20480 + wq * 10240), "l"(src + (i + (i >= g)) * 10240), "r"(full) : "memory");
          sl = sl == 2 ? 0 : sl + 1;
        }
      }
#undef TS_T
#define TS_T 96
    } else {
      mbar_wait(bar_full + 16, 0);
      TS(4);
      const uint32_t epoch = ldg_rlx32(g_epoch + cid) + 1;
      uint32_t wv[10];
#pragma unroll
      for (int i = 0; i < 10; i++) wv[i] = __ldg((const uint32_t*)w_r + lane + 32 * i);
#pragma unroll 1
      for (int i = lane; i < 392; i += 32) {
        const uint32_t f = i >= 368 ? 0u : SENT;
        ((uint4*)(g_own + cid))[i] = make_uint4(f, f, f, f);
        if (i < GLOB_PER_CTA) ((uint4*)&g_x)[cid * GLOB_PER_CTA + i] = make_uint4(SENT, SENT, SENT, SENT);
      }
      float s = 0.f;
#pragma unroll
      for (int i = 0; i < 10; i++) {
        s += bf_lo(wv[i]) + bf_hi(wv[i]);
        const unsigned u = i < 8 ? lane + 32 * (i - g) : lane + 32 * (i - 7) - g * 8;
        if (i < 8 ? u < 32u : u - 32u < 8u) *(float2*)(smem + OFF_WR + ((u & 3) * 10 + (u >> 2)) * 8) = make_float2(bf_lo(wv[i]), bf_hi(wv[i]));
      }
#pragma unroll
      for (int m = 1; m < 32; m <<= 1) s += shx(s, m);
      *(float2*)(smem + OFF_WR + 320) = make_float2(s, __uint_as_float(epoch * 0x9E3779B8u));
      g_epoch[cid] = epoch;
      TS(3);
      asm volatile("fence.acq_rel.gpu;" ::: "memory");
      TS(5);
      asm volatile("bar.arrive 2, 352;" ::: "memory");
      bar_sync(3, 64);
      const uint4* const kp = g_own[1].cnt;
      const uint4* const cb = &g_x.cand[0][lane >> 2][lane & 3];
      uint4 k = ldg_pkt(kp), c0 = make_uint4(0, 0, 0, 0), c1 = c0; uint2 c2 = make_uint2(0, 0);
      int guard = SPIN_MAX, ws;
      while (true) {
        const uint32_t tk = 2047u - (k.x & 2047u);
        ws = (tk >> 7) * 8 + (tk & 1) * 4 + ((tk >> 5) & 3);
        const uint32_t prev = k.x;
        if (ffn1) { const uint4* q = cb + ws * 192; c0 = ldg_pkt(q); c1 = ldg_pkt(q + 4); c2 = ldg_rlx64(q + 8); }
        if (k.z != 128u) k = ldg_pkt(kp);
        if ((k.z == 128u && k.x == prev && !anyw(c0.x == SENT || c1.x == SENT || c2.x == SENT)) || --guard <= 0) break;
      }
      *(uint4*)(smem + OFF_HN + lane * 16) = c0; *(uint4*)(smem + OFF_HN + 512 + lane * 16) = c1; *(uint2*)(smem + OFF_HN + 1024 + lane * 16) = c2;
      const float rw = __uint_as_float(k.y ^ ((uint32_t)((int32_t)~k.y >> 31) | 0x80000000u));
      *(uint4*)(smem + OFF_WR + 336) = make_uint4(ws, 2047u - (k.x & 2047u), __float_as_uint(rcp(1.f + ex2(-1.4426950408889634f * rw))), 0);
      mbar_arrive(bar_win);
      TS(7);
    }
#undef TS_T
  } else {
#define TS_T 0
    TS(23);
    asm volatile("setmaxnreg.inc.sync.aligned.u32 %0;" :: "n"(REG_C));
    const int wg = warp >> 2, w4 = warp & 3, r = lane >> 2, c = lane & 3;
    float acc[120];
    uint4 xr[5];
    const uint32_t xa = (warp * 16 + (lane & 15)) * 128, xc = (lane >> 4) ^ (lane & 7);
    float ps = 0.f, pq = 0.f, pc_ = 0.f;
    uint32_t sxo, swo;
    {
      const int l7 = lane & 7, j = warp >> 1, k = (warp & 1) * 32 + lane, ch = min((P >> 1) * 4 + rank * 2 + (j >> 1), 14);
      sxo = ((g & 3) * 32 + j * 8 + l7) * 128 + ((((warp & 1) * 4 + (lane >> 3)) ^ l7) * 16);
      swo = ch < 12 ? 16384 + (ch >> 2) * 8192 + k * 128 + ((((ch & 3) * 2 + (j & 1)) ^ l7) * 16) : 40960 + (ch - 12) * 2048 + k * 32 + (((j & 1) ^ (l7 >> 2)) * 16);
    }
    const bool first = (mt == 0) && (w4 == 0);
    uint4* const kvd = pin(w4 < 3 ? (uint4*)(smem + OFF_O + warp * 2560) + lane : &g_own[cid].halo[wg][0][lane]);
    const uint4* const kvs = pin(first ? kvd : w4 > 0 ? (const uint4*)(smem + OFF_O + (warp - 1) * 2560) + lane : &g_own[cid - 8].halo[wg][0][lane]);
    TS(0);
#pragma unroll 1
    for (int it = 0; it < 10; it++) {
      const int s = (it + 2) & 3;
      mbar_wait(bar_full + 8 * s, (it >> 2) & 1);
      TS(13 + it);
      const uint32_t a = sb + s * SLOT;
      const uint64_t da = make_desc(a + wg * 8192, 16, 1024, 1), db = make_desc(a + 16384, 8192, 1024, 1), dr = make_desc(a + 40960, 2048, 256, 3);
      const int ks = ks_of(it);
      if (ks == g) {
#pragma unroll
        for (int j = 0; j < 4; j++) xr[j] = ldsm4(a + xa + ((xc ^ (2 * j)) * 16));
      }
      if (ks == 8 + (g >> 2)) xr[4] = ldsm4(a + xa + ((xc ^ (2 * (g & 3))) * 16));
      uint4 sv, sw;
      if ((unsigned)(it - ord) < 5u) { sv = ldsm4(a + sxo); sw = ldsm4t(a + swo); }
      uint32_t m0 = 0, m1 = 0;
      if (it == 9) {
        mbar_wait(bar_aux, 0);
        TS(3);
        if (c < 2) { m0 = __float_as_uint(lds32f(sb + OFF_MN + (warp * 16 + r) * 8 + c * 4)); m1 = __float_as_uint(lds32f(sb + OFF_MN + (warp * 16 + r) * 8 + c * 4 + 64)); }
      }
      if (it | wg) bar_sync(7 + wg, 256);
      wgmma_fence();
      if (it == 9) {
        const uint64_t dc = make_desc(sb + OFF_CS, 0, 128, 0);
        wgmma_n48hi_rk(acc, m0, m1, 0u, 0u, dc + 192, 1);
        wgmma_n192lo_rk(acc, m0, m1, 0u, 0u, dc, 1);
      }
#pragma unroll
      for (int kk = 0; kk < 4; kk++) {
        wgmma_n48hi_ss(acc, da + kk * 2, dr + kk * 32, (kk | it) != 0);
        wgmma_n192lo_ss(acc, da + kk * 2, db + kk * 128, (kk | it) != 0);
      }
      wgmma_commit();
      if (it < 9 || wg == 0) asm volatile("bar.arrive %0, 256;" :: "r"(8 - wg) : "memory");
      if (it < 9) {
        wgmma_wait<0>();
        if ((tid & 127) < 2) mbar_arrive_cta(bar_empty + 8 * s, tid & 1);
      }
      if ((unsigned)(it - ord) < 5u) {
        const uint32_t vv[4] = {sv.x, sv.y, sv.z, sv.w}, ww[4] = {sw.x, sw.y, sw.z, sw.w};
#pragma unroll
        for (int i = 0; i < 4; i++) {
          const float d = bf_lo(vv[i]), e = bf_hi(vv[i]);
          ps += d + e; pq = fmaf(d, d, pq); pq = fmaf(e, e, pq); pc_ += bf_lo(ww[i]) + bf_hi(ww[i]);
        }
        if (it - ord == 4) {
          ps += shx(ps, 1); pq += shx(pq, 1); pc_ += shx(pc_, 1);
          ps += shx(ps, 2); pq += shx(pq, 2); pc_ += shx(pc_, 2);
          if (c < 3) sts32f(sb + OFF_PT + (c * 64 + (warp & 1) * 32 + (warp >> 1) * 8 + r) * 4, c == 0 ? ps : c == 1 ? pq : pc_);
          asm volatile("bar.arrive 2, 352;" ::: "memory");
        }
      }
    }
    const uint32_t stb = sb + OFF_RS + (wg * 72 + 16 * w4) * 4;
    const float rlo = lds32f(stb + (8 + r) * 4), rhi = lds32f(stb + (16 + r) * 4);
    wgmma_wait<0>();
#pragma unroll
    for (int i = 0; i < 120; i++) asm volatile("" : "+f"(acc[i]) :: "memory");
    if (wg == 1) asm volatile("bar.arrive 7, 256;" ::: "memory");
    TS(2);
    uint32_t Qlo[10], Qhi[10], Klo[10], Khi[10], Vlo[10], Vhi[10];
#pragma unroll
    for (int t = 0; t < 10; t++) {
      const int k = KT(t), v = VT(t);
      Khi[t] = pack_bf16(acc[4 * k + 2], acc[4 * k + 3]);
      Vhi[t] = pack_bf16(acc[4 * v + 2] * rhi, acc[4 * v + 3] * rhi);
    }
    st_pkt(kvd, Khi[0], Khi[1], Khi[3], Khi[4]);
    st_pkt(kvd + 32, Khi[5], Khi[6], Khi[8], Khi[9]);
    st_pkt(kvd + 64, Khi[2], Khi[7], Vhi[0], Vhi[1]);
    st_pkt(kvd + 96, Vhi[2], Vhi[3], Vhi[4], Vhi[5]);
    st_pkt(kvd + 128, Vhi[6], Vhi[7], Vhi[8], Vhi[9]);
    mbar_arrive(bar_o + wg * 64 + 24);
#pragma unroll
    for (int t = 0; t < 10; t++) {
      const int q = QT(t), k = KT(t), v = VT(t);
      Vhi[t] = movm(Vhi[t]);
      Klo[t] = pack_bf16(acc[4 * k], acc[4 * k + 1]);
      Vlo[t] = movm(pack_bf16(acc[4 * v] * rlo, acc[4 * v + 1] * rlo));
      Qlo[t] = pack_bf16(acc[4 * q], acc[4 * q + 1]);
      Qhi[t] = pack_bf16(acc[4 * q + 2], acc[4 * q + 3]);
    }
    const bool in0 = 2 * c <= r, in1 = 2 * c + 1 <= r;
    const uint32_t mL = (in0 ? 0xffffu : 0u) | (in1 ? 0xffff0000u : 0u);
    const float qs = 0.22360679774997896f * 1.4426950408889634f;
    const uint32_t kb0 = stb + (2 * c + (in0 ? 8 : 0)) * 4, kb1 = stb + (2 * c + 1 + (in1 ? 8 : 0)) * 4;
    const float scl0 = lds32f(kb0) * rlo * qs, scl1 = lds32f(kb1) * rlo * qs;
    const float sch0 = lds32f(kb0 + 32) * rhi * qs, sch1 = lds32f(kb1 + 32) * rhi * qs;
    const float bias0 = (first && !in0) ? -INFINITY : 0.f, bias1 = (first && !in1) ? -INFINITY : 0.f;
    const int slot = mt * 8 + warp;
    int guard = SPIN_MAX;
    uint4 pv[5];
    mbar_wait(bar_o + wg * 64 + 24, 0);
    do {
#pragma unroll
      for (int j = 0; j < 5; j++) pv[j] = ld_pkt(kvs + 32 * j);
    } while (anyw(pv[0].x == SENT || pv[1].x == SENT || pv[2].x == SENT || pv[3].x == SENT || pv[4].x == SENT) && --guard);
    if (wg == 0) bar_sync(7, 256);
    TS(4);
    const uint32_t Kp[10] = {pv[0].x, pv[0].y, pv[2].x, pv[0].z, pv[0].w, pv[1].x, pv[1].y, pv[2].y, pv[1].z, pv[1].w};
    const uint32_t Vp[10] = {movm(pv[2].z), movm(pv[2].w), movm(pv[3].x), movm(pv[3].y), movm(pv[3].z), movm(pv[3].w), movm(pv[4].x), movm(pv[4].y), movm(pv[4].z), movm(pv[4].w)};
    const bool cA = c < 2, nA = r < 4;
    const uint32_t ONES = 0x3f803f80u;
    uint32_t of[20];
#pragma unroll
    for (int hp = 0; hp < 2; hp++) {
      float o[6][4];
#pragma unroll
      for (int hh = 0; hh < 2; hh++) {
        const int ta = 5 * hp + 3 * hh, ts = 5 * hp + 2;
        const bool mine = hh == 0 ? cA : !cA;
        const uint32_t e0 = mine ? Qlo[ts] : 0u, e1 = mine ? Qhi[ts] : 0u;
        float sp[4], sl[4], sh[4];
        mma_k24(sp, Qlo[ta], Qhi[ta], Qlo[ta + 1], Qhi[ta + 1], Kp[ta], Kp[ta + 1], e0, e1, Kp[ts]);
        mma_k24(sl, Qlo[ta], Qhi[ta], Qlo[ta + 1], Qhi[ta + 1], Klo[ta], Klo[ta + 1], e0, e1, Klo[ts]);
        mma_k24(sh, Qlo[ta], Qhi[ta], Qlo[ta + 1], Qhi[ta + 1], Khi[ta], Khi[ta + 1], e0, e1, Khi[ts]);
        const float tl0 = fmaf(in0 ? sl[0] : sp[0], scl0, bias0), tl1 = fmaf(in1 ? sl[1] : sp[1], scl1, bias1);
        const float th0 = (in0 ? sh[2] : sl[2]) * sch0, th1 = (in1 ? sh[3] : sl[3]) * sch1;
        float ml = fmaxf(tl0, tl1), mh = fmaxf(th0, th1);
        ml = fmaxf(ml, shx(ml, 1)); mh = fmaxf(mh, shx(mh, 1));
        ml = fmaxf(ml, shx(ml, 2)); mh = fmaxf(mh, shx(mh, 2));
        const uint32_t Pl = pack_bf16(ex2(tl0 - ml), ex2(tl1 - ml)), Ph = pack_bf16(ex2(th0 - mh), ex2(th1 - mh));
        const uint32_t a0 = Pl & mL, a1 = Ph & ~mL, a3 = Ph & mL, ap = Pl & ~mL;
        const bool vm = hh == 0 ? nA : !nA;
        mma_k24(o[3 * hh], a0, a1, 0u, a3, Vlo[ta], Vhi[ta], ap, 0u, Vp[ta]);
        mma_k24(o[3 * hh + 1], a0, a1, 0u, a3, Vlo[ta + 1], Vhi[ta + 1], ap, 0u, Vp[ta + 1]);
        mma_k24(o[3 * hh + 2], a0, a1, 0u, a3, vm ? Vlo[ts] : ONES, vm ? Vhi[ts] : ONES, ap, 0u, vm ? Vp[ts] : ONES);
      }
      const float il = rcp(cA ? o[5][0] : o[2][0]), ih = rcp(cA ? o[5][2] : o[2][2]);
      const float jl = shx(il, 2), jh = shx(ih, 2);
      const float al = cA ? jl : il, ah = cA ? jh : ih, bl = cA ? il : jl, bh = cA ? ih : jh;
      const int t0 = 5 * hp;
      of[2 * t0]     = pack_bf16(o[0][0] * al, o[0][1] * al); of[2 * t0 + 1] = pack_bf16(o[0][2] * ah, o[0][3] * ah);
      of[2 * t0 + 2] = pack_bf16(o[1][0] * al, o[1][1] * al); of[2 * t0 + 3] = pack_bf16(o[1][2] * ah, o[1][3] * ah);
      of[2 * t0 + 4] = pack_bf16((cA ? o[2][0] : o[5][0]) * jl, (cA ? o[2][1] : o[5][1]) * jl);
      of[2 * t0 + 5] = pack_bf16((cA ? o[2][2] : o[5][2]) * jh, (cA ? o[2][3] : o[5][3]) * jh);
      of[2 * t0 + 6] = pack_bf16(o[3][0] * bl, o[3][1] * bl); of[2 * t0 + 7] = pack_bf16(o[3][2] * bh, o[3][3] * bh);
      of[2 * t0 + 8] = pack_bf16(o[4][0] * bl, o[4][1] * bl); of[2 * t0 + 9] = pack_bf16(o[4][2] * bh, o[4][3] * bh);
    }
    {
      const uint32_t os = sb + OFF_O + 20480 + warp * 2560, oa = os + ((lane >> 3) & 1) * 1280 + (lane >> 4) * 128 + (lane & 7) * 16;
#pragma unroll
      for (int s = 0; s < 5; s++) stsm4(oa + s * 256, of[4 * s], of[4 * s + 1], of[4 * s + 2], of[4 * s + 3]);
      asm volatile("fence.proxy.async.shared::cta;" ::: "memory");
      __syncwarp();
      if (elect()) {
        asm volatile("cp.async.bulk.global.shared::cta.bulk_group [%0], [%1], 2560;\ncp.async.bulk.commit_group;" :: "l"(&g_o[mt * 2 + wg][g][w4 * 160]), "r"(os) : "memory");
      }
    }
    TS(5);
    float h[40];
#pragma unroll
    for (int s = 0; s < 5; s++) {
      const uint4 v = xr[s];
      h[8 * s] = bf_lo(v.x); h[8 * s + 1] = bf_hi(v.x); h[8 * s + 2] = bf_lo(v.y); h[8 * s + 3] = bf_hi(v.y);
      h[8 * s + 4] = bf_lo(v.z); h[8 * s + 5] = bf_hi(v.z); h[8 * s + 6] = bf_lo(v.w); h[8 * s + 7] = bf_hi(v.w);
    }
    mbar_wait(bar_full, 0); mbar_wait(bar_full + 8, 0); mbar_wait(bar_full + 16, 1);
    if (elect()) {
      asm volatile("cp.async.bulk.wait_group 0;" ::: "memory");
      asm volatile("red.relaxed.gpu.global.add.u32 [%0], 1;" :: "l"(g_own[mt * 8 + wg * 4].cnt) : "memory");
    }
    asm volatile("bar.arrive %0, 160;" :: "r"(5 + wg) : "memory");
    bar_sync(1, 256);
    const uint64_t dwo = make_desc(sb, 5120, 512, 2);
    wgmma_fence();
#pragma unroll
    for (int s = 0; s < 5; s++) wgmma_n80_rs(h, of[4 * s], of[4 * s + 1], of[4 * s + 2], of[4 * s + 3], dwo + g * 960 + s * 64, 1);
    wgmma_commit();
    TS(6);
#pragma unroll 1
    for (int i = 0, sl = 0; i < 7; i++) {
      mbar_wait(bar_o + wg * 64 + 8 * sl, i >= 3 && i < 6);
      if (i == 0) TS(1);
      const uint64_t da = make_desc(sb + OFF_O + sl * 20480 + wg * 10240, 128, 1280, 0), db = dwo + (i + (i >= g)) * 960;
      wgmma_fence();
#pragma unroll
      for (int s = 0; s < 5; s++) wgmma_n80_ss(h, da + s * 16, db + s * 64, 1);
      wgmma_commit();
      wgmma_wait<1>();
      if ((tid & 127) == 0 && i > 0 && i < 5) mbar_arrive(bar_o + wg * 64 + 24 + 8 * i);
      sl = sl == 2 ? 0 : sl + 1;
    }
    const bool odd = c & 1;
    float wr[20];
#pragma unroll
    for (int j = 0; j < 5; j++) {
      const uint4 v = lds128(sb + OFF_WR + c * 80 + j * 16);
      wr[4 * j] = __uint_as_float(v.x); wr[4 * j + 1] = __uint_as_float(v.y); wr[4 * j + 2] = __uint_as_float(v.z); wr[4 * j + 3] = __uint_as_float(v.w);
    }
    const float wsum = lds32f(sb + OFF_WR + 320);
    uint4* const sp = pin(&g_own[slot].st2[r + (odd ? 8 : 0)]);
    uint4* const cdp = pin(&g_x.cand[slot][g][0]);
    const int tok0 = mt * 128 + 32 * w4 + wg;
    wgmma_wait<0>();
#pragma unroll
    for (int i = 0; i < 40; i++) asm volatile("" : "+f"(h[i]) :: "memory");
    TS(7);
    float mean, rstd, rr;
    {
      float l1 = 0.f, l2 = 0.f, l3 = 0.f, h1 = 0.f, h2 = 0.f, h3 = 0.f;
#pragma unroll
      for (int j = 0; j < 10; j++) {
        l1 += h[4 * j] + h[4 * j + 1]; h1 += h[4 * j + 2] + h[4 * j + 3];
        l2 = fmaf(h[4 * j], h[4 * j], l2); l2 = fmaf(h[4 * j + 1], h[4 * j + 1], l2);
        h2 = fmaf(h[4 * j + 2], h[4 * j + 2], h2); h2 = fmaf(h[4 * j + 3], h[4 * j + 3], h2);
        l3 = fmaf(h[4 * j], wr[2 * j], l3); l3 = fmaf(h[4 * j + 1], wr[2 * j + 1], l3);
        h3 = fmaf(h[4 * j + 2], wr[2 * j], h3); h3 = fmaf(h[4 * j + 3], wr[2 * j + 1], h3);
      }
      float s1 = (odd ? h1 : l1) + shx(odd ? l1 : h1, 1), s2 = (odd ? h2 : l2) + shx(odd ? l2 : h2, 1), s3 = (odd ? h3 : l3) + shx(odd ? l3 : h3, 1);
      s1 += shx(s1, 2); s2 += shx(s2, 2); s3 += shx(s3, 2);
      if (cA) asm volatile("red.relaxed.gpu.global.add.v4.f32 [%0], {%1, %2, %3, %4};" :: "l"(sp), "f"(s1), "f"(s2), "f"(s3), "f"(1.f) : "memory");
      uint4 p0;
      do { p0 = ldg_pkt(sp); } while (anyw(p0.w != 0x41000000u) && --guard > 0);
      mean = __uint_as_float(p0.x) * (1.f / 640.f);
      rstd = rsq(fmaxf(fmaf(-mean, mean, __uint_as_float(p0.y) * (1.f / 640.f)), 0.f) + 1e-5f);
      rr = fmaf(-mean, wsum, __uint_as_float(p0.z)) * rstd;
    }
    TS(8);
    const uint32_t kk = ord_key(rr), kmax = __reduce_max_sync(0xffffffffu, kk);
    const int L = __ffs(__ballot_sync(0xffffffffu, kk == kmax)) - 1;
    const int crow = (L >> 2) + 8 * (L & 1);
    if (warp == g) {
      if (elect()) {
        asm volatile("red.relaxed.gpu.global.max.u64 [%0], %1;" :: "l"(g_own[1].cnt), "l"(((uint64_t)kmax << 32) | (uint32_t)(2047 - tok0 - 2 * crow)) : "memory");
        asm volatile("red.relaxed.gpu.global.add.u32 [%0], 1;" :: "l"(&g_own[1].cnt[0].z) : "memory");
      }
      asm volatile("bar.arrive 3, 64;" ::: "memory");
    }
    const uint32_t stg = sb + OFF_O + warp * 2560;
    uint4 held;
    {
      const float om = shx(mean, 1), os = shx(rstd, 1);
      const float rl = odd ? os : rstd, rh = odd ? rstd : os;
      const float bl = -(odd ? om : mean) * rl, bh = -(odd ? mean : om) * rh, al = 1.f + rl, ah = 1.f + rh;
      if ((L >> 2) == r) {
        const bool chi = L & 1;
        const float rc = chi ? rh : rl, bc = chi ? bh : bl;
        uint32_t n[10];
#pragma unroll
        for (int j = 0; j < 10; j++) n[j] = pack_bf16(fmaf(chi ? h[4 * j + 2] : h[4 * j], rc, bc), fmaf(chi ? h[4 * j + 3] : h[4 * j + 1], rc, bc));
        uint4* d = cdp + c;
        stg_pkt(d, n[0], n[1], n[2], n[3]); stg_pkt(d + 4, n[4], n[5], n[6], n[7]); stg_rlx64(d + 8, n[8], n[9]);
      }
      __syncwarp();
      const uint32_t fa = stg + (lane & 15) * 160 + (lane >> 4) * 16;
#pragma unroll
      for (int s = 0; s < 5; s++)
        stsm4(fa + s * 32, pack_bf16(fmaf(h[8 * s], al, bl), fmaf(h[8 * s + 1], al, bl)), pack_bf16(fmaf(h[8 * s + 2], ah, bh), fmaf(h[8 * s + 3], ah, bh)),
              pack_bf16(fmaf(h[8 * s + 4], al, bl), fmaf(h[8 * s + 5], al, bl)), pack_bf16(fmaf(h[8 * s + 6], ah, bh), fmaf(h[8 * s + 7], ah, bh)));
      __syncwarp();
      held = lds128(stg + crow * 160 + min(lane, 9) * 16);
      if (lane < 10) stg_pkt(cdp + 12 + lane, held.x, held.y, held.z, held.w);
    }
    TS(9);
    mbar_wait(bar_ffn, 0);
    const uint32_t red = sb + OFF_RED;
    if (ffn1) {
      uint4 w1[4][5];
      {
        const int k = (lane & 7) + (lane >> 4) * 8;
        const uint32_t a1 = sb + k * 64, sw = ((lane >> 3) & 1) ^ ((lane >> 1) & 3);
#pragma unroll
        for (int s = 0; s < 5; s++)
#pragma unroll
          for (int u = 0; u < 4; u++)
            w1[u][s] = ldsm4t(a1 + (s < 4 ? warp * 4096 + s * 1024 : 32768 + warp * 1024) + (u >> 1) * (40960 + (s == 4 || warp >= 2 ? OFF_W2 - 49152 : 0)) + ((sw ^ (2 * (u & 1))) * 16));
      }
      uint32_t* const ap = pin(g_x.act + fj * 16 + (lane >> 1));
      mbar_wait(bar_win, 0);
      const uint32_t hp = sb + OFF_HN + (warp * 4 + c) * 16;
      const uint4 c0 = lds128(hp), c1 = lds128(hp + 512), c2 = lds128(hp + 1024);
      TS(10);
      float a[4][4];
#pragma unroll
      for (int u = 0; u < 4; u++) {
        a[u][0] = a[u][1] = a[u][2] = a[u][3] = 0.f;
        mma_acc(a[u], w1[u][0], c0.x, c0.y); mma_acc(a[u], w1[u][1], c0.z, c0.w); mma_acc(a[u], w1[u][2], c1.x, c1.y);
        mma_acc(a[u], w1[u][3], c1.z, c1.w); mma_acc(a[u], w1[u][4], c2.x, c2.y);
      }
      asm volatile("st.shared.v2.f32 [%0], {%1, %2};" :: "r"(red + (warp * 32 + c * 8 + r) * 8),
                   "f"(cA ? (odd ? a[0][2] : a[0][0]) : (odd ? a[1][2] : a[1][0])), "f"(cA ? (odd ? a[2][2] : a[2][0]) : (odd ? a[3][2] : a[3][0])) : "memory");
      bar_sync(1, 256);
      if (warp == 0) {
        float2 t[8];
#pragma unroll
        for (int i = 0; i < 8; i++) t[i] = lds64f(red + (i * 32 + lane) * 8);
        const float s = ((t[0].x + t[1].x) + (t[2].x + t[3].x)) + ((t[4].x + t[5].x) + (t[6].x + t[7].x));
        const float u = ((t[0].y + t[1].y) + (t[2].y + t[3].y)) + ((t[4].y + t[5].y) + (t[6].y + t[7].y));
        const float av = s * u * rcp(1.f + ex2(-1.4426950408889634f * s));
        const float an = shx(av, 1);
        if (!odd) stg_rlx32(ap, pack_bf16(av, an));
      }
      bar_sync(1, 256);
      TS(11);
    }
    if (OUT_LATE) mbar_wait(bar_win, 0);
    char* const ob2 = (char*)(out + tok0 * 640 + g * 64);
    const int remo = 896 - 96 * g;
#pragma unroll
    for (int s = 0; s < 5; s++) {
      const int row = s < 4 ? 4 * s + (lane >> 3) : lane >> 1, pc = s < 4 ? lane & 7 : 8 + (lane & 1);
      const uint4 v = lds128(stg + row * 160 + pc * 16);
      if (row != crow) stg128(ob2 + row * 2560 + pc * 16 + (s < 4 ? 0 : remo), v);
    }
    mbar_wait(bar_win, 0);
    const uint4 win = lds128(sb + OFF_WR + 336);
    if (win.x != slot && lane < 10) stg128(ob2 + crow * 2560 + lane * 16 + (lane < 8 ? 0 : remo), held);
    if (!ffn1) {
      TS(10);
      uint4 w2[6];
      const uint32_t a2 = sb + OFF_W2 + (warp * 192 + 8 * (((lane >> 3) & 1) * 4 + ((lane & 7) >> 1)) + 2 * (lane >> 4) + (lane & 1)) * 16;
#pragma unroll
      for (int s = 0; s < 6; s++) w2[s] = ldsm4t(a2 + (s >> 1) * 1024 + (s & 1) * 64);
      const uint4* p = (const uint4*)(g_x.act + warp * 96) + (r & 1) * 4 + c;
      const uint32_t* pb = (const uint32_t*)&g_x.cand[win.x][fj < 64 ? fj >> 3 : (fj - 64) >> 1][fj < 64 ? 12 + (fj & 7) : 20 + (fj & 1)] + c;
      uint32_t* const op = pin((uint32_t*)(out + win.y * 640 + fj * 8) + c);
      uint4 c0, c1, c2; uint32_t bw;
      if (ACT_NS) __nanosleep(ACT_NS);
      do {
        c0 = ldg_pkt(p); c1 = ldg_pkt(p + 8); c2 = ldg_pkt(p + 16); bw = ldg_rlx32(pb);
      } while (anyw(max(max(max(max(c0.x, c0.y), max(c0.z, c0.w)), max(max(c1.x, c1.y), max(c1.z, c1.w))), max(max(max(c2.x, c2.y), max(c2.z, c2.w)), bw)) == SENT) && --guard > 0);
      TS(11);
      float a[4] = {0.f, 0.f, 0.f, 0.f}, b[4] = {0.f, 0.f, 0.f, 0.f}, d[4] = {0.f, 0.f, 0.f, 0.f};
      mma_acc(a, w2[0], c0.x, c0.y); mma_acc(b, w2[2], c1.x, c1.y); mma_acc(d, w2[4], c2.x, c2.y);
      mma_acc(a, w2[1], c0.z, c0.w); mma_acc(b, w2[3], c1.z, c1.w); mma_acc(d, w2[5], c2.z, c2.w);
      if (c == 0) sts32f(red + (warp * 8 + r) * 4, ((a[0] + a[3]) + (b[0] + b[3])) + (d[0] + d[3]));
      bar_sync(1, 256);
      if (tid < 4) {
        float2 t[8];
#pragma unroll
        for (int i = 0; i < 8; i++) t[i] = lds64f(red + (i * 4 + tid) * 8);
        const float y0 = ((t[0].x + t[1].x) + (t[2].x + t[3].x)) + ((t[4].x + t[5].x) + (t[6].x + t[7].x));
        const float y1 = ((t[0].y + t[1].y) + (t[2].y + t[3].y)) + ((t[4].y + t[5].y) + (t[6].y + t[7].y));
        const float sg = __uint_as_float(win.z);
        *op = pack_bf16(fmaf(y0, sg, bf_lo(bw)), fmaf(y1, sg, bf_hi(bw)));
      }
    }
    TS(12);
#undef TS_T
  }
}

typedef CUresult (*EncodeFn)(CUtensorMap*, CUtensorMapDataType, cuuint32_t, void*, const cuuint64_t*, const cuuint64_t*, const cuuint32_t*,
                             const cuuint32_t*, CUtensorMapInterleave, CUtensorMapSwizzle, CUtensorMapL2promotion, CUtensorMapFloatOOBfill);

void make_map(EncodeFn enc, CUtensorMap* m, const void* base, const cuuint64_t* dims, const cuuint64_t* strides, const cuuint32_t* box,
              CUtensorMapSwizzle swz) {
  const cuuint32_t es[3] = {1, 1, 1};
  enc(m, CU_TENSOR_MAP_DATA_TYPE_BFLOAT16, 3, (void*)base, dims, strides, box, es, CU_TENSOR_MAP_INTERLEAVE_NONE, swz,
      CU_TENSOR_MAP_L2_PROMOTION_L2_128B, CU_TENSOR_MAP_FLOAT_OOB_FILL_NONE);
}

}

extern "C" void kernel_launch(void* const* d_in, const int* in_sizes, int n_in, void* d_out, int out_size) {
  const __nv_bfloat16* x = (const __nv_bfloat16*)d_in[0];
  const __nv_bfloat16* wqkv = (const __nv_bfloat16*)d_in[1];
  const __nv_bfloat16* wo = (const __nv_bfloat16*)d_in[2];
  void* fn = nullptr;
  cudaDriverEntryPointQueryResult st;
  cudaGetDriverEntryPoint("cuTensorMapEncodeTiled", &fn, cudaEnableDefault, &st);
  EncodeFn enc = (EncodeFn)fn;
  void* scp = nullptr;
  cudaGetSymbolAddress(&scp, g_scratch);
  Maps tm;
  { const cuuint64_t d[3] = {640, 1024, 2}, s[2] = {2560, 1280}; const cuuint32_t b[3] = {64, 64, 2}; make_map(enc, &tm.x, x, d, s, b, CU_TENSOR_MAP_SWIZZLE_128B); }
  { const cuuint64_t d[3] = {640, 640, 3}, s[2] = {3840, 1280}; const cuuint32_t b[3] = {64, 64, 1}; make_map(enc, &tm.w, wqkv, d, s, b, CU_TENSOR_MAP_SWIZZLE_128B); }
  { const cuuint64_t d[3] = {640, 640, 3}, s[2] = {3840, 1280}; const cuuint32_t b[3] = {16, 64, 3}; make_map(enc, &tm.wr, wqkv, d, s, b, CU_TENSOR_MAP_SWIZZLE_32B); }
  { const cuuint64_t d[3] = {32, 640, 20}, s[2] = {1280, 64}; const cuuint32_t b[3] = {32, 80, 2}; make_map(enc, &tm.wo, wo, d, s, b, CU_TENSOR_MAP_SWIZZLE_64B); }
  { const cuuint64_t d[3] = {640, 640, 1}, s[2] = {1280, 819200}; const cuuint32_t b[3] = {16, 80, 1}; make_map(enc, &tm.wor, wo, d, s, b, CU_TENSOR_MAP_SWIZZLE_64B); }
  { const cuuint64_t d[3] = {1536, 640, 1}, s[2] = {3072, 1966080}; const cuuint32_t b[3] = {32, 128, 1};
    make_map(enc, &tm.gate, d_in[5], d, s, b, CU_TENSOR_MAP_SWIZZLE_64B); make_map(enc, &tm.up, d_in[6], d, s, b, CU_TENSOR_MAP_SWIZZLE_64B); }
  { const cuuint64_t d[3] = {640, 1536, 1}, s[2] = {1280, 1966080}; const cuuint32_t b[3] = {8, 128, 1}; make_map(enc, &tm.down, d_in[7], d, s, b, CU_TENSOR_MAP_SWIZZLE_NONE); }
  cudaFuncSetAttribute(fused_kernel, cudaFuncAttributeMaxDynamicSharedMemorySize, SMEM_BYTES);
  fused_kernel<<<128, 384, SMEM_BYTES, cudaStreamPerThread>>>(x, wqkv, wo, (const __nv_bfloat16*)d_in[4], (const __nv_bfloat16*)d_in[5],
                                                              (const __nv_bfloat16*)d_in[6], (const __nv_bfloat16*)d_in[7], (__nv_bfloat16*)d_out, (Scratch*)scp, tm);
}
```

```cpp
#include <cuda_runtime.h>
#include <cuda_bf16.h>
#include <cuda.h>
#include <stdint.h>

#define PF0 1
#define PF_NS 100
#define PFX_IT 1
#define PFW_NS 100
#define ACT_NS 0
#define F_IT 7
#define F_MAX 6
#define F_PER 1
#define OUT_LATE 1
#define REG_P 72
#define REG_C 184
#define AUX_NS 50
#define PP 1
#define PPK 4

namespace {

constexpr int SLOT    = 47104;
constexpr int OFF_O   = 122880;
constexpr int OFF_W2  = 4 * SLOT;
constexpr int OFF_CS  = OFF_W2 + 32768;
constexpr int OFF_RS  = OFF_CS + 3840;
constexpr int OFF_MN  = OFF_RS + 576;
constexpr int OFF_WR  = OFF_MN + 1024;
constexpr int OFF_RED = OFF_CS;
constexpr int OFF_HN  = OFF_CS + 2048;
constexpr int OFF_PT  = OFF_WR + 352;
constexpr int OFF_BAR = OFF_PT + 768;
constexpr int SMEM_BYTES = OFF_BAR + 240 + 288;
constexpr uint32_t SENT = 0xFFFFFFFFu;
constexpr int SPIN_MAX = 1 << 20;

struct Glob {
  uint4 cand[128][8][24];
  uint32_t act[768];
  uint32_t pad[256];
};
constexpr int GLOB_PER_CTA = sizeof(Glob) / 16 / 128;
static_assert(GLOB_PER_CTA * 128 * 16 == sizeof(Glob), "glob size");
struct Own {
  uint4 halo[2][5][32];
  uint4 st1[32];
  uint2 cs[32];
  uint4 st2[16];
  uint4 cnt[8];
};
struct Scratch {
  Glob x;
  Own own[128];
  uint4 o[32][8][640];
  uint32_t epoch[128];
};
__device__ __align__(128) Scratch g_scratch;
#define g_x (sc->x)
#define g_own (sc->own)
#define g_o (sc->o)
#define g_epoch (sc->epoch)
#define TS(i)

__device__ __forceinline__ void mbar_init(uint32_t bar, uint32_t cnt) { asm volatile("mbarrier.init.shared::cta.b64 [%0], %1;" :: "r"(bar), "r"(cnt) : "memory"); }
__device__ __forceinline__ void mbar_expect_tx(uint32_t bar, uint32_t bytes) { asm volatile("mbarrier.arrive.expect_tx.shared::cta.b64 _, [%0], %1;" :: "r"(bar), "r"(bytes) : "memory"); }
__device__ __forceinline__ void mbar_arrive(uint32_t bar) { asm volatile("mbarrier.arrive.shared::cta.b64 _, [%0];" :: "r"(bar) : "memory"); }
__device__ __forceinline__ void mbar_arrive_cta(uint32_t bar, uint32_t cta) {
  asm volatile("{\n.reg .b32 ra;\nmapa.shared::cluster.u32 ra, %0, %1;\nmbarrier.arrive.shared::cluster.b64 _, [ra];\n}\n" :: "r"(bar), "r"(cta) : "memory");
}
__device__ __forceinline__ void mbar_wait(uint32_t bar, uint32_t parity) {
  asm volatile("{\n.reg .pred p;\n.reg .u32 n;\nmov.u32 n, 0;\nW:\nmbarrier.try_wait.parity.shared::cta.b64 p, [%0], %1;\n@p bra.uni D;\n"
               "add.u32 n, n, 1;\nsetp.lt.u32 p, n, %2;\n@p bra.uni W;\nD:\n}\n" :: "r"(bar), "r"(parity), "n"(SPIN_MAX) : "memory");
}
__device__ __forceinline__ void tma_3d(uint32_t dst, const void* tm, uint32_t bar, int c0, int c1, int c2) {
  asm volatile("cp.async.bulk.tensor.3d.shared::cluster.global.mbarrier::complete_tx::bytes [%0], [%1, {%3, %4, %5}], [%2];" :: "r"(dst), "l"(tm), "r"(bar), "r"(c0), "r"(c1), "r"(c2) : "memory");
}
__device__ __forceinline__ void tma_3d_mc(uint32_t dst, const void* tm, uint32_t bar, int c0, int c1, int c2) {
  asm volatile("cp.async.bulk.tensor.3d.shared::cluster.global.mbarrier::complete_tx::bytes.multicast::cluster [%0], [%1, {%3, %4, %5}], [%2], %6;" :: "r"(dst), "l"(tm), "r"(bar), "r"(c0), "r"(c1), "r"(c2), "h"((uint16_t)3) : "memory");
}
__device__ __forceinline__ void wgmma_fence() { asm volatile("wgmma.fence.sync.aligned;" ::: "memory"); }
__device__ __forceinline__ void wgmma_commit() { asm volatile("wgmma.commit_group.sync.aligned;" ::: "memory"); }
template <int N> __device__ __forceinline__ void wgmma_wait() { asm volatile("wgmma.wait_group.sync.aligned %0;" :: "n"(N) : "memory"); }
__device__ __forceinline__ uint64_t make_desc(uint32_t addr, uint32_t lbo, uint32_t sbo, uint32_t swz) {
  return (uint64_t)(((addr & 0x3FFFF) >> 4) | ((lbo >> 4) << 16)) | ((uint64_t)((sbo >> 4) | (swz << 30)) << 32);
}
__device__ __forceinline__ void bar_sync(int id, int n) { asm volatile("bar.sync %0, %1;" :: "r"(id), "r"(n) : "memory"); }
__device__ __forceinline__ uint4 ld_pkt(const void* p) {
  uint4 v;
  asm volatile("{\n.reg .b128 t;\n.reg .b64 lo, hi;\nld.relaxed.gpu.b128 t, [%4];\nmov.b128 {lo, hi}, t;\nmov.b64 {%0, %1}, lo;\nmov.b64 {%2, %3}, hi;\n}\n"
               : "=r"(v.x), "=r"(v.y), "=r"(v.z), "=r"(v.w) : "l"(p) : "memory");
  return v;
}
__device__ __forceinline__ void st_pkt(void* p, uint32_t a, uint32_t b, uint32_t c, uint32_t d) {
  asm volatile("{\n.reg .b128 t;\n.reg .b64 lo, hi;\nmov.b64 lo, {%1, %2};\nmov.b64 hi, {%3, %4};\nmov.b128 t, {lo, hi};\nst.relaxed.gpu.b128 [%0], t;\n}\n"
               :: "l"(p), "r"(a), "r"(b), "r"(c), "r"(d) : "memory");
}
__device__ __forceinline__ uint4 ldg_pkt(const void* p) {
  uint4 v;
  asm volatile("{\n.reg .b128 t;\n.reg .b64 lo, hi;\nld.relaxed.gpu.global.b128 t, [%4];\nmov.b128 {lo, hi}, t;\nmov.b64 {%0, %1}, lo;\nmov.b64 {%2, %3}, hi;\n}\n"
               : "=r"(v.x), "=r"(v.y), "=r"(v.z), "=r"(v.w) : "l"(p) : "memory");
  return v;
}
__device__ __forceinline__ void stg_pkt(void* p, uint32_t a, uint32_t b, uint32_t c, uint32_t d) {
  asm volatile("{\n.reg .b128 t;\n.reg .b64 lo, hi;\nmov.b64 lo, {%1, %2};\nmov.b64 hi, {%3, %4};\nmov.b128 t, {lo, hi};\nst.relaxed.gpu.global.b128 [%0], t;\n}\n"
               :: "l"(p), "r"(a), "r"(b), "r"(c), "r"(d) : "memory");
}
__device__ __forceinline__ uint32_t ldg_rlx32(const void* p) { uint32_t v; asm volatile("ld.relaxed.gpu.global.u32 %0, [%1];" : "=r"(v) : "l"(p) : "memory"); return v; }
__device__ __forceinline__ uint2 ldg_rlx64(const void* p) { uint2 v; asm volatile("ld.relaxed.gpu.global.v2.u32 {%0, %1}, [%2];" : "=r"(v.x), "=r"(v.y) : "l"(p) : "memory"); return v; }
__device__ __forceinline__ void stg128(void* p, const uint4& v) { asm volatile("st.global.v4.u32 [%0], {%1, %2, %3, %4};" :: "l"(p), "r"(v.x), "r"(v.y), "r"(v.z), "r"(v.w) : "memory"); }
template <class T> __device__ __forceinline__ T* pin(T* p) { asm volatile("" : "+l"(p)); return p; }
__device__ __forceinline__ void stg_rlx32(void* p, uint32_t v) { asm volatile("st.relaxed.gpu.global.u32 [%0], %1;" :: "l"(p), "r"(v) : "memory"); }
__device__ __forceinline__ void stg_rlx64(void* p, uint32_t a, uint32_t b) { asm volatile("st.relaxed.gpu.global.v2.u32 [%0], {%1, %2};" :: "l"(p), "r"(a), "r"(b) : "memory"); }
__device__ __forceinline__ uint4 ldsm4(uint32_t a) { uint4 v; asm volatile("ldmatrix.sync.aligned.m8n8.x4.shared.b16 {%0, %1, %2, %3}, [%4];" : "=r"(v.x), "=r"(v.y), "=r"(v.z), "=r"(v.w) : "r"(a) : "memory"); return v; }
__device__ __forceinline__ uint4 ldsm4t(uint32_t a) { uint4 v; asm volatile("ldmatrix.sync.aligned.m8n8.x4.trans.shared.b16 {%0, %1, %2, %3}, [%4];" : "=r"(v.x), "=r"(v.y), "=r"(v.z), "=r"(v.w) : "r"(a) : "memory"); return v; }
__device__ __forceinline__ void stsm4(uint32_t a, uint32_t x, uint32_t y, uint32_t z, uint32_t w) { asm volatile("stmatrix.sync.aligned.m8n8.x4.shared.b16 [%0], {%1, %2, %3, %4};" :: "r"(a), "r"(x), "r"(y), "r"(z), "r"(w) : "memory"); }
__device__ __forceinline__ void mma_acc(float (&c)[4], const uint4& a, uint32_t b0, uint32_t b1) {
  asm("mma.sync.aligned.m16n8k16.row.col.f32.bf16.bf16.f32 {%0,%1,%2,%3}, {%4,%5,%6,%7}, {%8,%9}, {%0,%1,%2,%3};"
      : "+f"(c[0]), "+f"(c[1]), "+f"(c[2]), "+f"(c[3]) : "r"(a.x), "r"(a.y), "r"(a.z), "r"(a.w), "r"(b0), "r"(b1));
}
__device__ __forceinline__ uint4 lds128(uint32_t a) { uint4 v; asm volatile("ld.shared.v4.u32 {%0, %1, %2, %3}, [%4];" : "=r"(v.x), "=r"(v.y), "=r"(v.z), "=r"(v.w) : "r"(a) : "memory"); return v; }
__device__ __forceinline__ float2 lds64f(uint32_t a) { float2 v; asm volatile("ld.shared.v2.f32 {%0, %1}, [%2];" : "=f"(v.x), "=f"(v.y) : "r"(a)); return v; }
__device__ __forceinline__ float lds32f(uint32_t a) { float v; asm volatile("ld.shared.f32 %0, [%1];" : "=f"(v) : "r"(a)); return v; }
__device__ __forceinline__ void sts32f(uint32_t a, float v) { asm volatile("st.shared.f32 [%0], %1;" :: "r"(a), "f"(v) : "memory"); }
__device__ __forceinline__ uint32_t pack_bf16(float lo, float hi) { uint32_t r; asm("cvt.rn.bf16x2.f32 %0, %1, %2;" : "=r"(r) : "f"(hi), "f"(lo)); return r; }
__device__ __forceinline__ float bf_lo(uint32_t v) { return __uint_as_float(v << 16); }
__device__ __forceinline__ float bf_hi(uint32_t v) { return __uint_as_float(v & 0xffff0000u); }
__device__ __forceinline__ uint32_t movm(uint32_t a) { uint32_t d; asm("movmatrix.sync.aligned.m8n8.trans.b16 %0, %1;" : "=r"(d) : "r"(a)); return d; }
__device__ __forceinline__ float ex2(float x) { float y; asm("ex2.approx.ftz.f32 %0, %1;" : "=f"(y) : "f"(x)); return y; }
__device__ __forceinline__ float rsq(float x) { float y; asm("rsqrt.approx.ftz.f32 %0, %1;" : "=f"(y) : "f"(x)); return y; }
__device__ __forceinline__ float rcp(float x) { float y; asm("rcp.approx.ftz.f32 %0, %1;" : "=f"(y) : "f"(x)); return y; }
__device__ __forceinline__ bool elect() { uint32_t p; asm volatile("{\n.reg .pred q;\nelect.sync _|q, 0xffffffff;\nselp.u32 %0, 1, 0, q;\n}\n" : "=r"(p)); return p; }
__device__ __forceinline__ void pf_l2(const void* p) { asm volatile("prefetch.global.L2 [%0];" :: "l"(p)); }
__device__ __forceinline__ bool anyw(bool p) { return __any_sync(0xffffffffu, p); }
__device__ __forceinline__ float shx(float v, int m) { return __shfl_xor_sync(0xffffffffu, v, m); }
__device__ __forceinline__ void mma_k24(float (&c)[4], uint32_t a0, uint32_t a1, uint32_t a2, uint32_t a3, uint32_t b0, uint32_t b1,
                                        uint32_t e0, uint32_t e1, uint32_t f0) {
  asm("mma.sync.aligned.m16n8k16.row.col.f32.bf16.bf16.f32 {%0,%1,%2,%3}, {%4,%5,%6,%7}, {%8,%9}, {%10,%10,%10,%10};"
      : "=f"(c[0]), "=f"(c[1]), "=f"(c[2]), "=f"(c[3]) : "r"(a0), "r"(a1), "r"(a2), "r"(a3), "r"(b0), "r"(b1), "f"(0.f));
  asm("mma.sync.aligned.m16n8k8.row.col.f32.bf16.bf16.f32 {%0,%1,%2,%3}, {%4,%5}, {%6}, {%0,%1,%2,%3};"
      : "+f"(c[0]), "+f"(c[1]), "+f"(c[2]), "+f"(c[3]) : "r"(e0), "r"(e1), "r"(f0));
}
__device__ __forceinline__ uint32_t ord_key(float r) { uint32_t u = __float_as_uint(r); return u ^ ((uint32_t)((int32_t)u >> 31) | 0x80000000u); }

__device__ __forceinline__ void wgmma_n48hi_rk(float (&d)[120], uint32_t a0, uint32_t a1, uint32_t a2, uint32_t a3, uint64_t db, int scale_d) {
  asm volatile("{\n.reg .pred p;\nsetp.ne.b32 p, %29, 0;\n"
    "wgmma.mma_async.sync.aligned.m64n48k16.f32.bf16.bf16 "
    "{%0, %1, %2, %3, %4, %5, %6, %7, %8, %9, %10, %11, %12, %13, %14, %15, "
    "%16, %17, %18, %19, %20, %21, %22, %23}, "
    "{%24, %25, %26, %27}, %28, p, 1, 1, 0;\n}\n"
    : "+f"(d[96]), "+f"(d[97]), "+f"(d[98]), "+f"(d[99]), "+f"(d[100]), "+f"(d[101]), "+f"(d[102]), "+f"(d[103]),
      "+f"(d[104]), "+f"(d[105]), "+f"(d[106]), "+f"(d[107]), "+f"(d[108]), "+f"(d[109]), "+f"(d[110]), "+f"(d[111]),
      "+f"(d[112]), "+f"(d[113]), "+f"(d[114]), "+f"(d[115]), "+f"(d[116]), "+f"(d[117]), "+f"(d[118]), "+f"(d[119])
    : "r"(a0), "r"(a1), "r"(a2), "r"(a3), "l"(db), "r"(scale_d));
}
__device__ __forceinline__ void wgmma_n192lo_rk(float (&d)[120], uint32_t a0, uint32_t a1, uint32_t a2, uint32_t a3, uint64_t db, int scale_d) {
  asm volatile("{\n.reg .pred p;\nsetp.ne.b32 p, %101, 0;\n"
    "wgmma.mma_async.sync.aligned.m64n192k16.f32.bf16.bf16 "
    "{%0, %1, %2, %3, %4, %5, %6, %7, %8, %9, %10, %11, %12, %13, %14, %15, "
    "%16, %17, %18, %19, %20, %21, %22, %23, %24, %25, %26, %27, %28, %29, %30, %31, "
    "%32, %33, %34, %35, %36, %37, %38, %39, %40, %41, %42, %43, %44, %45, %46, %47, "
    "%48, %49, %50, %51, %52, %53, %54, %55, %56, %57, %58, %59, %60, %61, %62, %63, "
    "%64, %65, %66, %67, %68, %69, %70, %71, %72, %73, %74, %75, %76, %77, %78, %79, "
    "%80, %81, %82, %83, %84, %85, %86, %87, %88, %89, %90, %91, %92, %93, %94, %95}, "
    "{%96, %97, %98, %99}, %100, p, 1, 1, 0;\n}\n"
    : "+f"(d[0]), "+f"(d[1]), "+f"(d[2]), "+f"(d[3]), "+f"(d[4]), "+f"(d[5]), "+f"(d[6]), "+f"(d[7]),
      "+f"(d[8]), "+f"(d[9]), "+f"(d[10]), "+f"(d[11]), "+f"(d[12]), "+f"(d[13]), "+f"(d[14]), "+f"(d[15]),
      "+f"(d[16]), "+f"(d[17]), "+f"(d[18]), "+f"(d[19]), "+f"(d[20]), "+f"(d[21]), "+f"(d[22]), "+f"(d[23]),
      "+f"(d[24]), "+f"(d[25]), "+f"(d[26]), "+f"(d[27]), "+f"(d[28]), "+f"(d[29]), "+f"(d[30]), "+f"(d[31]),
      "+f"(d[32]), "+f"(d[33]), "+f"(d[34]), "+f"(d[35]), "+f"(d[36]), "+f"(d[37]), "+f"(d[38]), "+f"(d[39]),
      "+f"(d[40]), "+f"(d[41]), "+f"(d[42]), "+f"(d[43]), "+f"(d[44]), "+f"(d[45]), "+f"(d[46]), "+f"(d[47]),
      "+f"(d[48]), "+f"(d[49]), "+f"(d[50]), "+f"(d[51]), "+f"(d[52]), "+f"(d[53]), "+f"(d[54]), "+f"(d[55]),
      "+f"(d[56]), "+f"(d[57]), "+f"(d[58]), "+f"(d[59]), "+f"(d[60]), "+f"(d[61]), "+f"(d[62]), "+f"(d[63]),
      "+f"(d[64]), "+f"(d[65]), "+f"(d[66]), "+f"(d[67]), "+f"(d[68]), "+f"(d[69]), "+f"(d[70]), "+f"(d[71]),
      "+f"(d[72]), "+f"(d[73]), "+f"(d[74]), "+f"(d[75]), "+f"(d[76]), "+f"(d[77]), "+f"(d[78]), "+f"(d[79]),
      "+f"(d[80]), "+f"(d[81]), "+f"(d[82]), "+f"(d[83]), "+f"(d[84]), "+f"(d[85]), "+f"(d[86]), "+f"(d[87]),
      "+f"(d[88]), "+f"(d[89]), "+f"(d[90]), "+f"(d[91]), "+f"(d[92]), "+f"(d[93]), "+f"(d[94]), "+f"(d[95])
    : "r"(a0), "r"(a1), "r"(a2), "r"(a3), "l"(db), "r"(scale_d));
}
__device__ __forceinline__ void wgmma_n48hi_ss(float (&d)[120], uint64_t da, uint64_t db, int scale_d) {
  asm volatile("{\n.reg .pred p;\nsetp.ne.b32 p, %26, 0;\n"
    "wgmma.mma_async.sync.aligned.m64n48k16.f32.bf16.bf16 "
    "{%0, %1, %2, %3, %4, %5, %6, %7, %8, %9, %10, %11, %12, %13, %14, %15, "
    "%16, %17, %18, %19, %20, %21, %22, %23}, "
    "%24, %25, p, 1, 1, 0, 1;\n}\n"
    : "+f"(d[96]), "+f"(d[97]), "+f"(d[98]), "+f"(d[99]), "+f"(d[100]), "+f"(d[101]), "+f"(d[102]), "+f"(d[103]),
      "+f"(d[104]), "+f"(d[105]), "+f"(d[106]), "+f"(d[107]), "+f"(d[108]), "+f"(d[109]), "+f"(d[110]), "+f"(d[111]),
      "+f"(d[112]), "+f"(d[113]), "+f"(d[114]), "+f"(d[115]), "+f"(d[116]), "+f"(d[117]), "+f"(d[118]), "+f"(d[119])
    : "l"(da), "l"(db), "r"(scale_d));
}
__device__ __forceinline__ void wgmma_n192lo_ss(float (&d)[120], uint64_t da, uint64_t db, int scale_d) {
  asm volatile("{\n.reg .pred p;\nsetp.ne.b32 p, %98, 0;\n"
    "wgmma.mma_async.sync.aligned.m64n192k16.f32.bf16.bf16 "
    "{%0, %1, %2, %3, %4, %5, %6, %7, %8, %9, %10, %11, %12, %13, %14, %15, "
    "%16, %17, %18, %19, %20, %21, %22, %23, %24, %25, %26, %27, %28, %29, %30, %31, "
    "%32, %33, %34, %35, %36, %37, %38, %39, %40, %41, %42, %43, %44, %45, %46, %47, "
    "%48, %49, %50, %51, %52, %53, %54, %55, %56, %57, %58, %59, %60, %61, %62, %63, "
    "%64, %65, %66, %67, %68, %69, %70, %71, %72, %73, %74, %75, %76, %77, %78, %79, "
    "%80, %81, %82, %83, %84, %85, %86, %87, %88, %89, %90, %91, %92, %93, %94, %95}, "
    "%96, %97, p, 1, 1, 0, 1;\n}\n"
    : "+f"(d[0]), "+f"(d[1]), "+f"(d[2]), "+f"(d[3]), "+f"(d[4]), "+f"(d[5]), "+f"(d[6]), "+f"(d[7]),
      "+f"(d[8]), "+f"(d[9]), "+f"(d[10]), "+f"(d[11]), "+f"(d[12]), "+f"(d[13]), "+f"(d[14]), "+f"(d[15]),
      "+f"(d[16]), "+f"(d[17]), "+f"(d[18]), "+f"(d[19]), "+f"(d[20]), "+f"(d[21]), "+f"(d[22]), "+f"(d[23]),
      "+f"(d[24]), "+f"(d[25]), "+f"(d[26]), "+f"(d[27]), "+f"(d[28]), "+f"(d[29]), "+f"(d[30]), "+f"(d[31]),
      "+f"(d[32]), "+f"(d[33]), "+f"(d[34]), "+f"(d[35]), "+f"(d[36]), "+f"(d[37]), "+f"(d[38]), "+f"(d[39]),
      "+f"(d[40]), "+f"(d[41]), "+f"(d[42]), "+f"(d[43]), "+f"(d[44]), "+f"(d[45]), "+f"(d[46]), "+f"(d[47]),
      "+f"(d[48]), "+f"(d[49]), "+f"(d[50]), "+f"(d[51]), "+f"(d[52]), "+f"(d[53]), "+f"(d[54]), "+f"(d[55]),
      "+f"(d[56]), "+f"(d[57]), "+f"(d[58]), "+f"(d[59]), "+f"(d[60]), "+f"(d[61]), "+f"(d[62]), "+f"(d[63]),
      "+f"(d[64]), "+f"(d[65]), "+f"(d[66]), "+f"(d[67]), "+f"(d[68]), "+f"(d[69]), "+f"(d[70]), "+f"(d[71]),
      "+f"(d[72]), "+f"(d[73]), "+f"(d[74]), "+f"(d[75]), "+f"(d[76]), "+f"(d[77]), "+f"(d[78]), "+f"(d[79]),
      "+f"(d[80]), "+f"(d[81]), "+f"(d[82]), "+f"(d[83]), "+f"(d[84]), "+f"(d[85]), "+f"(d[86]), "+f"(d[87]),
      "+f"(d[88]), "+f"(d[89]), "+f"(d[90]), "+f"(d[91]), "+f"(d[92]), "+f"(d[93]), "+f"(d[94]), "+f"(d[95])
    : "l"(da), "l"(db), "r"(scale_d));
}
__device__ __forceinline__ void wgmma_n80_rs(float (&d)[40], uint32_t a0, uint32_t a1, uint32_t a2, uint32_t a3, uint64_t db, int scale_d) {
  asm volatile("{\n.reg .pred p;\nsetp.ne.b32 p, %45, 0;\n"
    "wgmma.mma_async.sync.aligned.m64n80k16.f32.bf16.bf16 "
    "{%0, %1, %2, %3, %4, %5, %6, %7, %8, %9, %10, %11, %12, %13, %14, %15, "
    "%16, %17, %18, %19, %20, %21, %22, %23, %24, %25, %26, %27, %28, %29, %30, %31, "
    "%32, %33, %34, %35, %36, %37, %38, %39}, "
    "{%40, %41, %42, %43}, %44, p, 1, 1, 1;\n}\n"
    : "+f"(d[0]), "+f"(d[1]), "+f"(d[2]), "+f"(d[3]), "+f"(d[4]), "+f"(d[5]), "+f"(d[6]), "+f"(d[7]),
      "+f"(d[8]), "+f"(d[9]), "+f"(d[10]), "+f"(d[11]), "+f"(d[12]), "+f"(d[13]), "+f"(d[14]), "+f"(d[15]),
      "+f"(d[16]), "+f"(d[17]), "+f"(d[18]), "+f"(d[19]), "+f"(d[20]), "+f"(d[21]), "+f"(d[22]), "+f"(d[23]),
      "+f"(d[24]), "+f"(d[25]), "+f"(d[26]), "+f"(d[27]), "+f"(d[28]), "+f"(d[29]), "+f"(d[30]), "+f"(d[31]),
      "+f"(d[32]), "+f"(d[33]), "+f"(d[34]), "+f"(d[35]), "+f"(d[36]), "+f"(d[37]), "+f"(d[38]), "+f"(d[39])
    : "r"(a0), "r"(a1), "r"(a2), "r"(a3), "l"(db), "r"(scale_d));
}
__device__ __forceinline__ void wgmma_n80_ss(float (&d)[40], uint64_t da, uint64_t db, int scale_d) {
  asm volatile("{\n.reg .pred p;\nsetp.ne.b32 p, %42, 0;\n"
    "wgmma.mma_async.sync.aligned.m64n80k16.f32.bf16.bf16 "
    "{%0, %1, %2, %3, %4, %5, %6, %7, %8, %9, %10, %11, %12, %13, %14, %15, "
    "%16, %17, %18, %19, %20, %21, %22, %23, %24, %25, %26, %27, %28, %29, %30, %31, "
    "%32, %33, %34, %35, %36, %37, %38, %39}, "
    "%40, %41, p, 1, 1, 0, 1;\n}\n"
    : "+f"(d[0]), "+f"(d[1]), "+f"(d[2]), "+f"(d[3]), "+f"(d[4]), "+f"(d[5]), "+f"(d[6]), "+f"(d[7]),
      "+f"(d[8]), "+f"(d[9]), "+f"(d[10]), "+f"(d[11]), "+f"(d[12]), "+f"(d[13]), "+f"(d[14]), "+f"(d[15]),
      "+f"(d[16]), "+f"(d[17]), "+f"(d[18]), "+f"(d[19]), "+f"(d[20]), "+f"(d[21]), "+f"(d[22]), "+f"(d[23]),
      "+f"(d[24]), "+f"(d[25]), "+f"(d[26]), "+f"(d[27]), "+f"(d[28]), "+f"(d[29]), "+f"(d[30]), "+f"(d[31]),
      "+f"(d[32]), "+f"(d[33]), "+f"(d[34]), "+f"(d[35]), "+f"(d[36]), "+f"(d[37]), "+f"(d[38]), "+f"(d[39])
    : "l"(da), "l"(db), "r"(scale_d));
}

__device__ __forceinline__ constexpr int QT(int t) { return t < 8 ? t : 16 + t; }
__device__ __forceinline__ constexpr int KT(int t) { return t < 8 ? 8 + t : 18 + t; }
__device__ __forceinline__ constexpr int VT(int t) { return t < 8 ? 16 + t : 20 + t; }

struct Maps { CUtensorMap x, w, wr, wo, wor, gate, up, down; };

__global__ void __cluster_dims__(2, 1, 1) __launch_bounds__(512, 1)
fused_kernel(const __nv_bfloat16* __restrict__ x, const __nv_bfloat16* __restrict__ wqkv,
             const __nv_bfloat16* __restrict__ wo, const __nv_bfloat16* __restrict__ w_r, const __nv_bfloat16* __restrict__ w_gate,
             const __nv_bfloat16* __restrict__ w_up, const __nv_bfloat16* __restrict__ w_down, __nv_bfloat16* __restrict__ out,
             Scratch* __restrict__ sc, const __grid_constant__ Maps tm) {
  extern __shared__ __align__(1024) uint8_t smem[];
  const int tid = threadIdx.x, warp = __shfl_sync(0xffffffffu, tid >> 5, 0), lane = tid & 31, bid = blockIdx.x;
  const uint32_t sb = (uint32_t)__cvta_generic_to_shared(smem);
  const uint32_t bar_full = sb + OFF_BAR, bar_empty = bar_full + 32, bar_aux = bar_full + 64, bar_ffn = bar_full + 72, bar_win = bar_full + 80,
                 bar_o = bar_full + 96;
  if (warp < 4 && elect()) {
    mbar_init(bar_full + 8 * (warp ^ 2), 1);
    mbar_init(bar_empty + 8 * warp, 12);
    mbar_init(bar_aux + 8 * warp, warp == 0 ? 64 : warp == 2 ? 32 : 1);
    asm volatile("fence.mbarrier_init.release.cluster;" ::: "memory");
  }
  if (warp >= 4 && warp < 12 && elect()) { mbar_init(bar_o + 16 * (warp - 4), 1); mbar_init(bar_o + 16 * (warp - 4) + 8, (warp & 3) == 1 ? 128 : 1); }
  asm volatile("barrier.cluster.arrive.relaxed.aligned;" ::: "memory");
  if (warp >= 8 && warp < 11 && elect()) asm volatile("prefetch.tensormap [%0];" :: "l"(&tm.x + (warp - 8)) : "memory");
  auto pf_slice = [&](int ks) {
    pf_l2(lane < 16 ? (const char*)x + ((bid * 16 + lane) * 1280 + ks * 128) : (const char*)wqkv + ((bid * 15 + min(lane, 30) - 16) * 128 + ks * 245760));
  };
  if (warp >= 4 && warp < 4 + PF0) {
    if (warp > 4) __nanosleep(300 + (warp - 4) * PF_NS);
    pf_slice(warp == 6 ? 5 : warp - 4);
  }
  const int rank = bid & 1, cl = bid >> 1;
  const int q7 = ((cl - 36) * 37) >> 8;
  const int P = cl < 4 ? 0 : cl < 36 ? (cl - 4) & 7 : cl - 35 - 7 * q7;
  const int g = cl < 4 ? 4 + cl : cl < 36 ? (cl - 4) >> 3 : 4 + q7;
  const int mt = 2 * P + rank, cid = mt * 8 + g;
  const bool ffn1 = g < 3;
  const int fj = ffn1 ? mt * 3 + g : (P * 5 + g - 3) * 2 + rank;
  const int ord = ((g >> 2) ^ P) & 1;
  auto ks_of = [&](int it) { return ord == 0 || it == 0 ? it : it <= 5 ? it + 4 : it - 5; };
  auto load_w = [&](int it, uint32_t a, uint32_t full) {
    tma_3d_mc(a + 16384 + rank * 16384, &tm.w, full, g * 80, it * 64, rank * 2);
    tma_3d_mc(a + (rank ? 40960 : 24576), rank ? &tm.wr : &tm.w, full, g * 80 + rank * 64, it * 64, 1 - rank);
  };
  if (warp == 0 && elect()) {
    mbar_expect_tx(bar_full + 16, SLOT);
    tma_3d(sb + 2 * SLOT, &tm.x, bar_full + 16, 0, mt * 64, 0);
  }
  asm volatile("barrier.cluster.wait.aligned;" ::: "memory");
  if (warp == 0) {
    if (elect()) load_w(0, sb + 2 * SLOT, bar_full + 16);
    asm volatile("bar.arrive 4, 64;" ::: "memory");
  }

  if (warp >= 8) {
    asm volatile("setmaxnreg.dec.sync.aligned.u32 %0;" :: "n"(REG_P));
#define TS_T 0
    if (warp == 8) {
      TS(8);
      bar_sync(4, 64);
      if (elect()) {
        TS(10);
        int fjn = 0;
#pragma unroll 1
        for (int it = 1; it < 17; it++) {
          const int s = (it + 2) & 3;
          const uint32_t full = bar_full + 8 * s, a = sb + s * SLOT;
          if (it >= 13) { mbar_wait(bar_o + 32 + 8 * (it - 13), 0); mbar_wait(bar_o + 96 + 8 * (it - 13), 0); }
          else if (it >= 4) mbar_wait(bar_empty + 8 * s, ((it >> 2) - 1) & 1);
          if (it < 10) {
            const int ks = ks_of(it);
            mbar_expect_tx(full, SLOT);
            tma_3d(a, &tm.x, full, ks * 64, mt * 64, 0);
            load_w(ks, a, full);
            if (it == 1) TS(9);
          } else if (it < 13) {
            const int g0 = 3 * (it - 10), g1 = min(g0 + 3, 8);
            mbar_expect_tx(full, (g1 - g0) * 12800);
#pragma unroll 1
            for (int gp = g0 + ((g0 ^ rank) & 1); gp < g1; gp += 2) {
              tma_3d_mc(sb + gp * 15360, &tm.wo, full, 0, gp * 80, g * 2);
              tma_3d_mc(sb + gp * 15360 + 10240, &tm.wor, full, 512 + g * 16, gp * 80, 0);
            }
          }
          if (it == 4) mbar_expect_tx(bar_ffn, ffn1 ? 81920 : 24576);
          const int j1 = ffn1 ? (it >= 13 ? min(2 * it - 21, 10) : min(max(it - F_IT + 1, 0), 4)) : (it >= 13 ? 12 : min(max((it - F_IT + 1) * F_PER, 0), F_MAX));
#pragma unroll 1
          for (; fjn < j1; fjn++) {
            const int j = fjn < 4 ? fjn + 6 : fjn - 4;
            if (ffn1) tma_3d(sb + (j < 6 ? 0 : OFF_W2 - 49152) + j * 8192, j < 5 ? &tm.gate : &tm.up, bar_ffn, fj * 32, (j < 5 ? j : j - 5) * 128, 0);
            else tma_3d(sb + OFF_W2 + fjn * 2048, &tm.down, bar_ffn, fj * 8, fjn * 128, 0);
          }
        }
        TS(11);
      }
#undef TS_T
    } else if (warp >= 12) {
      const int l7 = lane & 7, j = warp - 12, ch = min((P >> 1) * 4 + rank * 2 + (j >> 1), 14);
      const uint32_t sxo = ((g & 3) * 32 + j * 8 + l7) * 128 + (((lane >> 3) ^ l7) * 16);
      const uint32_t swo = ch < 12 ? 16384 + (ch >> 2) * 8192 + lane * 128 + ((((ch & 3) * 2 + (j & 1)) ^ l7) * 16)
                                   : 40960 + (ch - 12) * 2048 + lane * 32 + (((j & 1) ^ (l7 >> 2)) * 16);
      float ps = 0.f, pq = 0.f, pq1 = 0.f, pc = 0.f;
#pragma unroll 1
      for (int it = ord; it < ord + 5; it++) {
        const int sl = (it + 2) & 3;
        mbar_wait(bar_full + 8 * sl, (it >> 2) & 1);
        const uint32_t a = sb + sl * SLOT;
        const uint4 v0 = ldsm4(a + sxo), v1 = ldsm4((a + sxo) ^ 64), w0 = ldsm4t(a + swo), w1 = ldsm4t(a + swo + (ch < 12 ? 4096 : 1024));
        if (lane + (int)((v0.x & v1.x & w0.x & w1.x) == 0x7fc17fc1u && (v0.x | v1.x) == 0u) < 2) mbar_arrive_cta(bar_empty + 8 * sl, lane);
        const uint32_t vv[8] = {v0.x, v0.y, v0.z, v0.w, v1.x, v1.y, v1.z, v1.w}, ww[8] = {w0.x, w0.y, w0.z, w0.w, w1.x, w1.y, w1.z, w1.w};
#pragma unroll
        for (int i = 0; i < 8; i++) {
          const float d = bf_lo(vv[i]), e = bf_hi(vv[i]);
          ps += d + e; pq = fmaf(d, d, pq); pq1 = fmaf(e, e, pq1); pc += bf_lo(ww[i]) + bf_hi(ww[i]);
        }
      }
      pq += pq1;
      ps += shx(ps, 1); pq += shx(pq, 1); pc += shx(pc, 1);
      ps += shx(ps, 2); pq += shx(pq, 2); pc += shx(pc, 2);
      const int c = lane & 3;
      if (c < 3) sts32f(sb + OFF_PT + (c * 32 + j * 8 + (lane >> 2)) * 4, c == 0 ? ps : c == 1 ? pq : pc);
      asm volatile("bar.arrive 2, 224;" ::: "memory");
#define TS_T 32
    } else if (warp < 11) {
      Own* const own = g_own + cid;
      const int l7 = lane & 7, hk = lane >> 4, idx = lane;
      mbar_wait(bar_full + 8 * ((PFX_IT + 2) & 3), 0);
      pf_slice(warp == 9 ? 4 : 8);
      if (warp == 9) pf_slice(9);
      bar_sync(2, 224);
      TS(0);
      const uint32_t tag = __float_as_uint(lds32f(sb + OFF_WR + 324));
      const float s0 = lds32f(sb + OFF_PT + lane * 4 + (warp - 9) * 256), q0 = lds32f(sb + OFF_PT + 128 + lane * 4);
      int guard = SPIN_MAX;
      if (warp == 9) {
        stg_pkt(&own->st1[idx], __float_as_uint(s0), __float_as_uint(q0), tag, 0u);
        TS(1);
        const uint4* sp = &g_own[mt * 8].st1[lane];
        const uint4* hp = &g_own[max(mt - 1, 0) * 8 + hk * 2 + 1].st1[24 + l7];
        uint4 a[5], b[5];
        bool bad;
        do {
          __nanosleep(AUX_NS);
          bad = false;
#pragma unroll
          for (int i = 0; i < 5; i++) {
            const uint4* q = i < 4 ? sp + i * (sizeof(Own) / 16) : hp;
            a[i] = ldg_pkt(q); b[i] = ldg_pkt(q + 4 * sizeof(Own) / 16);
          }
#pragma unroll
          for (int i = 0; i < 5; i++) bad |= a[i].z != tag || b[i].z != tag;
        } while (anyw(bad) && --guard);
#pragma unroll
        for (int i = 0; i < 5; i++) {
          const float m = (__uint_as_float(a[i].x) + __uint_as_float(b[i].x)) * (1.f / 640.f);
          const float rs = rsq(fmaxf(fmaf(-m, m, (__uint_as_float(a[i].y) + __uint_as_float(b[i].y)) * (1.f / 640.f)), 0.f) + 1e-5f);
          ((float*)(smem + OFF_RS))[i < 4 ? 8 + lane + 32 * i + 8 * (i >> 1) : hk * 72 + l7] = rs;
          const uint32_t mh = pack_bf16(-m, -m);
          const float ml = -m - bf_lo(mh);
          if (i < 4) ((uint2*)(smem + OFF_MN))[lane + 32 * i] = make_uint2(mh, pack_bf16(ml, ml));
        }
      } else {
        stg_rlx64(&own->cs[idx], __float_as_uint(s0), tag);
        const uint4* cp = (const uint4*)g_own[hk * 8 + g].cs + (lane & 15);
        uint4 a[4], b[4];
        bool bad;
        do {
          __nanosleep(AUX_NS);
          bad = false;
#pragma unroll
          for (int i = 0; i < 4; i++) { a[i] = ldg_pkt(cp + i * 32 * sizeof(Own) / 16); b[i] = ldg_pkt(cp + (i * 32 + 16) * sizeof(Own) / 16); }
#pragma unroll
          for (int i = 0; i < 4; i++) bad |= a[i].y != tag || a[i].w != tag || b[i].y != tag || b[i].w != tag;
        } while (anyw(bad) && --guard);
#pragma unroll
        for (int i = 0; i < 4; i++)
          if (i < 3 || lane < 24) {
            const float c0 = __uint_as_float(a[i].x) + __uint_as_float(b[i].x), c1 = __uint_as_float(a[i].z) + __uint_as_float(b[i].z);
            const uint32_t hi = pack_bf16(c0, c1), w0 = pack_bf16(c0, c0 - bf_lo(hi)), w1 = pack_bf16(c1, c1 - bf_hi(hi));
            uint4* const d = (uint4*)(smem + OFF_CS) + 2 * (lane + 32 * i);
            d[0] = make_uint4(w0, w0, 0, 0); d[1] = make_uint4(w1, w1, 0, 0);
          }
        asm volatile("fence.proxy.async.shared::cta;" ::: "memory");
      }
      mbar_arrive(bar_aux);
      TS(2);
      const int wq = warp - 9;
      const uint4* const fp = pin(g_own[mt * 8 + wq * 4].cnt);
      const char* const src = (const char*)g_o[mt * 2 + wq];
      bar_sync(5 + wq, 160);
      if (elect()) {
        while (ldg_rlx32(fp) != 32u && --guard > 0) {}
        asm volatile("fence.proxy.async.global;" ::: "memory");
        TS(6);
#pragma unroll 1
        for (int i = 0, sl = 0; i < 7; i++) {
          const uint32_t full = bar_o + wq * 64 + 8 * sl;
          if (i >= 3) mbar_wait(bar_o + wq * 64 + 8 + 8 * i, 0);
          mbar_expect_tx(full, 10240);
          asm volatile("cp.async.bulk.shared::cluster.global.mbarrier::complete_tx::bytes [%0], [%1], 10240, [%2];"
                       :: "r"(sb + OFF_O + sl * 20480 + wq * 10240), "l"(src + (i + (i >= g)) * 10240), "r"(full) : "memory");
          sl = sl == 2 ? 0 : sl + 1;
        }
      }
#undef TS_T
#define TS_T 96
    } else {
      mbar_wait(bar_full + 16, 0);
      TS(4);
      const uint32_t epoch = ldg_rlx32(g_epoch + cid) + 1;
      uint32_t wv[10];
#pragma unroll
      for (int i = 0; i < 10; i++) wv[i] = __ldg((const uint32_t*)w_r + lane + 32 * i);
#pragma unroll 1
      for (int i = lane; i < 392; i += 32) {
        const uint32_t f = i >= 368 ? 0u : SENT;
        ((uint4*)(g_own + cid))[i] = make_uint4(f, f, f, f);
        if (i < GLOB_PER_CTA) ((uint4*)&g_x)[cid * GLOB_PER_CTA + i] = make_uint4(SENT, SENT, SENT, SENT);
      }
      float s = 0.f;
#pragma unroll
      for (int i = 0; i < 10; i++) {
        s += bf_lo(wv[i]) + bf_hi(wv[i]);
        const unsigned u = i < 8 ? lane + 32 * (i - g) : lane + 32 * (i - 7) - g * 8;
        if (i < 8 ? u < 32u : u - 32u < 8u) *(float2*)(smem + OFF_WR + ((u & 3) * 10 + (u >> 2)) * 8) = make_float2(bf_lo(wv[i]), bf_hi(wv[i]));
      }
#pragma unroll
      for (int m = 1; m < 32; m <<= 1) s += shx(s, m);
      *(float2*)(smem + OFF_WR + 320) = make_float2(s, __uint_as_float(epoch * 0x9E3779B8u));
      g_epoch[cid] = epoch;
      TS(3);
      asm volatile("fence.acq_rel.gpu;" ::: "memory");
      TS(5);
      asm volatile("bar.arrive 2, 224;" ::: "memory");
#pragma unroll 1
      for (int i = 0; i < 14; i++) {
        const int m = (i + 2) >> 2, n = m == 0 ? 50 : 120, t = (m == 0 ? i : (i + 2) & 3) * 32 + lane;
        const char* b = (const char*)(m == 0 ? wo : m == 1 ? w_up : m == 2 ? w_down : w_gate);
        if (t < n) pf_l2(b + (bid * n + t) * 128);
        __nanosleep(PFW_NS);
      }
      bar_sync(3, 64);
      const uint4* const kp = g_own[1].cnt;
      const uint4* const cb = &g_x.cand[0][lane >> 2][lane & 3];
      uint4 k = ldg_pkt(kp), c0 = make_uint4(0, 0, 0, 0), c1 = c0; uint2 c2 = make_uint2(0, 0);
      int guard = SPIN_MAX, ws;
      while (true) {
        const uint32_t tk = 2047u - (k.x & 2047u);
        ws = (tk >> 7) * 8 + (tk & 1) * 4 + ((tk >> 5) & 3);
        const uint32_t prev = k.x;
        if (ffn1) { const uint4* q = cb + ws * 192; c0 = ldg_pkt(q); c1 = ldg_pkt(q + 4); c2 = ldg_rlx64(q + 8); }
        if (k.z != 128u) k = ldg_pkt(kp);
        if ((k.z == 128u && k.x == prev && !anyw(c0.x == SENT || c1.x == SENT || c2.x == SENT)) || --guard <= 0) break;
      }
      *(uint4*)(smem + OFF_HN + lane * 16) = c0; *(uint4*)(smem + OFF_HN + 512 + lane * 16) = c1; *(uint2*)(smem + OFF_HN + 1024 + lane * 16) = c2;
      const float rw = __uint_as_float(k.y ^ ((uint32_t)((int32_t)~k.y >> 31) | 0x80000000u));
      *(uint4*)(smem + OFF_WR + 336) = make_uint4(ws, 2047u - (k.x & 2047u), __float_as_uint(rcp(1.f + ex2(-1.4426950408889634f * rw))), 0);
      mbar_arrive(bar_win);
      TS(7);
    }
#undef TS_T
  } else {
#define TS_T 0
    TS(23);
    asm volatile("setmaxnreg.inc.sync.aligned.u32 %0;" :: "n"(REG_C));
    const int wg = warp >> 2, w4 = warp & 3, r = lane >> 2, c = lane & 3;
    float acc[120];
    uint4 xr[5];
    const uint32_t xa = (warp * 16 + (lane & 15)) * 128, xc = (lane >> 4) ^ (lane & 7);
    const bool first = (mt == 0) && (w4 == 0);
    uint4* const kvd = pin(w4 < 3 ? (uint4*)(smem + OFF_O + warp * 2560) + lane : &g_own[cid].halo[wg][0][lane]);
    const uint4* const kvs = pin(first ? kvd : w4 > 0 ? (const uint4*)(smem + OFF_O + (warp - 1) * 2560) + lane : &g_own[cid - 8].halo[wg][0][lane]);
    TS(0);
#pragma unroll 1
    for (int it = 0; it < 10; it++) {
      const int s = (it + 2) & 3;
      mbar_wait(bar_full + 8 * s, (it >> 2) & 1);
      TS(13 + it);
      const uint32_t a = sb + s * SLOT;
      const uint64_t da = make_desc(a + wg * 8192, 16, 1024, 1), db = make_desc(a + 16384, 8192, 1024, 1), dr = make_desc(a + 40960, 2048, 256, 3);
      const int ks = ks_of(it);
      if (ks == g) {
#pragma unroll
        for (int j = 0; j < 4; j++) xr[j] = ldsm4(a + xa + ((xc ^ (2 * j)) * 16));
      }
      if (ks == 8 + (g >> 2)) xr[4] = ldsm4(a + xa + ((xc ^ (2 * (g & 3))) * 16));
      uint32_t m0 = 0, m1 = 0;
      if (it == 9) {
        mbar_wait(bar_aux, 0);
        TS(3);
        if (c < 2) { m0 = __float_as_uint(lds32f(sb + OFF_MN + (warp * 16 + r) * 8 + c * 4)); m1 = __float_as_uint(lds32f(sb + OFF_MN + (warp * 16 + r) * 8 + c * 4 + 64)); }
      }
      if (PP ? (it | wg) != 0 : it == 9) bar_sync(7 + wg, 256);
      wgmma_fence();
      if (it == 9) {
        const uint64_t dc = make_desc(sb + OFF_CS, 0, 128, 0);
        wgmma_n48hi_rk(acc, m0, m1, 0u, 0u, dc + 192, 1);
        wgmma_n192lo_rk(acc, m0, m1, 0u, 0u, dc, 1);
      }
#pragma unroll
      for (int kk = 0; kk < 4; kk++) {
        if (kk == PPK && (PP ? it < 9 || wg == 0 : it == 9 - wg)) asm volatile("bar.arrive %0, 256;" :: "r"(8 - wg) : "memory");
        wgmma_n48hi_ss(acc, da + kk * 2, dr + kk * 32, (kk | it) != 0);
        wgmma_n192lo_ss(acc, da + kk * 2, db + kk * 128, (kk | it) != 0);
      }
      wgmma_commit();
      if (PPK == 4 && (PP ? it < 9 || wg == 0 : it == 9 - wg)) asm volatile("bar.arrive %0, 256;" :: "r"(8 - wg) : "memory");
      if (PP) {
        if (it < 9) {
          wgmma_wait<0>();
          if ((tid & 127) < ((unsigned)(it - ord) < 5u ? 2 : 6)) mbar_arrive_cta(bar_empty + 8 * s, tid & 1);
        }
      } else if (it > 0) {
        wgmma_wait<1>();
        if ((tid & 127) < ((unsigned)(it - 1 - ord) < 5u ? 2 : 6)) mbar_arrive_cta(bar_empty + 8 * ((it + 1) & 3), tid & 1);
      }
    }
    const uint32_t stb = sb + OFF_RS + (wg * 72 + 16 * w4) * 4;
    const float rlo = lds32f(stb + (8 + r) * 4), rhi = lds32f(stb + (16 + r) * 4);
    wgmma_wait<0>();
#pragma unroll
    for (int i = 0; i < 120; i++) asm volatile("" : "+f"(acc[i]) :: "memory");
    if (wg == 1) asm volatile("bar.arrive 7, 256;" ::: "memory");
    TS(2);
    uint32_t Qlo[10], Qhi[10], Klo[10], Khi[10], Vlo[10], Vhi[10];
#pragma unroll
    for (int t = 0; t < 10; t++) {
      const int k = KT(t), v = VT(t);
      Khi[t] = pack_bf16(acc[4 * k + 2], acc[4 * k + 3]);
      Vhi[t] = pack_bf16(acc[4 * v + 2] * rhi, acc[4 * v + 3] * rhi);
    }
    st_pkt(kvd, Khi[0], Khi[1], Khi[3], Khi[4]);
    st_pkt(kvd + 32, Khi[5], Khi[6], Khi[8], Khi[9]);
    st_pkt(kvd + 64, Khi[2], Khi[7], Vhi[0], Vhi[1]);
    st_pkt(kvd + 96, Vhi[2], Vhi[3], Vhi[4], Vhi[5]);
    st_pkt(kvd + 128, Vhi[6], Vhi[7], Vhi[8], Vhi[9]);
    mbar_arrive(bar_o + wg * 64 + 24);
#pragma unroll
    for (int t = 0; t < 10; t++) {
      const int q = QT(t), k = KT(t), v = VT(t);
      Vhi[t] = movm(Vhi[t]);
      Klo[t] = pack_bf16(acc[4 * k], acc[4 * k + 1]);
      Vlo[t] = movm(pack_bf16(acc[4 * v] * rlo, acc[4 * v + 1] * rlo));
      Qlo[t] = pack_bf16(acc[4 * q], acc[4 * q + 1]);
      Qhi[t] = pack_bf16(acc[4 * q + 2], acc[4 * q + 3]);
    }
    const bool in0 = 2 * c <= r, in1 = 2 * c + 1 <= r;
    const uint32_t mL = (in0 ? 0xffffu : 0u) | (in1 ? 0xffff0000u : 0u);
    const float qs = 0.22360679774997896f * 1.4426950408889634f;
    const uint32_t kb0 = stb + (2 * c + (in0 ? 8 : 0)) * 4, kb1 = stb + (2 * c + 1 + (in1 ? 8 : 0)) * 4;
    const float scl0 = lds32f(kb0) * rlo * qs, scl1 = lds32f(kb1) * rlo * qs;
    const float sch0 = lds32f(kb0 + 32) * rhi * qs, sch1 = lds32f(kb1 + 32) * rhi * qs;
    const float bias0 = (first && !in0) ? -INFINITY : 0.f, bias1 = (first && !in1) ? -INFINITY : 0.f;
    const int slot = mt * 8 + warp;
    int guard = SPIN_MAX;
    uint4 pv[5];
    mbar_wait(bar_o + wg * 64 + 24, 0);
    do {
#pragma unroll
      for (int j = 0; j < 5; j++) pv[j] = ld_pkt(kvs + 32 * j);
    } while (anyw(pv[0].x == SENT || pv[1].x == SENT || pv[2].x == SENT || pv[3].x == SENT || pv[4].x == SENT) && --guard);
    if (wg == 0) bar_sync(7, 256);
    TS(4);
    const uint32_t Kp[10] = {pv[0].x, pv[0].y, pv[2].x, pv[0].z, pv[0].w, pv[1].x, pv[1].y, pv[2].y, pv[1].z, pv[1].w};
    const uint32_t Vp[10] = {movm(pv[2].z), movm(pv[2].w), movm(pv[3].x), movm(pv[3].y), movm(pv[3].z), movm(pv[3].w), movm(pv[4].x), movm(pv[4].y), movm(pv[4].z), movm(pv[4].w)};
    const bool cA = c < 2, nA = r < 4;
    const uint32_t ONES = 0x3f803f80u;
    uint32_t of[20];
#pragma unroll
    for (int hp = 0; hp < 2; hp++) {
      float o[6][4];
#pragma unroll
      for (int hh = 0; hh < 2; hh++) {
        const int ta = 5 * hp + 3 * hh, ts = 5 * hp + 2;
        const bool mine = hh == 0 ? cA : !cA;
        const uint32_t e0 = mine ? Qlo[ts] : 0u, e1 = mine ? Qhi[ts] : 0u;
        float sp[4], sl[4], sh[4];
        mma_k24(sp, Qlo[ta], Qhi[ta], Qlo[ta + 1], Qhi[ta + 1], Kp[ta], Kp[ta + 1], e0, e1, Kp[ts]);
        mma_k24(sl, Qlo[ta], Qhi[ta], Qlo[ta + 1], Qhi[ta + 1], Klo[ta], Klo[ta + 1], e0, e1, Klo[ts]);
        mma_k24(sh, Qlo[ta], Qhi[ta], Qlo[ta + 1], Qhi[ta + 1], Khi[ta], Khi[ta + 1], e0, e1, Khi[ts]);
        const float tl0 = fmaf(in0 ? sl[0] : sp[0], scl0, bias0), tl1 = fmaf(in1 ? sl[1] : sp[1], scl1, bias1);
        const float th0 = (in0 ? sh[2] : sl[2]) * sch0, th1 = (in1 ? sh[3] : sl[3]) * sch1;
        float ml = fmaxf(tl0, tl1), mh = fmaxf(th0, th1);
        ml = fmaxf(ml, shx(ml, 1)); mh = fmaxf(mh, shx(mh, 1));
        ml = fmaxf(ml, shx(ml, 2)); mh = fmaxf(mh, shx(mh, 2));
        const uint32_t Pl = pack_bf16(ex2(tl0 - ml), ex2(tl1 - ml)), Ph = pack_bf16(ex2(th0 - mh), ex2(th1 - mh));
        const uint32_t a0 = Pl & mL, a1 = Ph & ~mL, a3 = Ph & mL, ap = Pl & ~mL;
        const bool vm = hh == 0 ? nA : !nA;
        mma_k24(o[3 * hh], a0, a1, 0u, a3, Vlo[ta], Vhi[ta], ap, 0u, Vp[ta]);
        mma_k24(o[3 * hh + 1], a0, a1, 0u, a3, Vlo[ta + 1], Vhi[ta + 1], ap, 0u, Vp[ta + 1]);
        mma_k24(o[3 * hh + 2], a0, a1, 0u, a3, vm ? Vlo[ts] : ONES, vm ? Vhi[ts] : ONES, ap, 0u, vm ? Vp[ts] : ONES);
      }
      const float il = rcp(cA ? o[5][0] : o[2][0]), ih = rcp(cA ? o[5][2] : o[2][2]);
      const float jl = shx(il, 2), jh = shx(ih, 2);
      const float al = cA ? jl : il, ah = cA ? jh : ih, bl = cA ? il : jl, bh = cA ? ih : jh;
      const int t0 = 5 * hp;
      of[2 * t0]     = pack_bf16(o[0][0] * al, o[0][1] * al); of[2 * t0 + 1] = pack_bf16(o[0][2] * ah, o[0][3] * ah);
      of[2 * t0 + 2] = pack_bf16(o[1][0] * al, o[1][1] * al); of[2 * t0 + 3] = pack_bf16(o[1][2] * ah, o[1][3] * ah);
      of[2 * t0 + 4] = pack_bf16((cA ? o[2][0] : o[5][0]) * jl, (cA ? o[2][1] : o[5][1]) * jl);
      of[2 * t0 + 5] = pack_bf16((cA ? o[2][2] : o[5][2]) * jh, (cA ? o[2][3] : o[5][3]) * jh);
      of[2 * t0 + 6] = pack_bf16(o[3][0] * bl, o[3][1] * bl); of[2 * t0 + 7] = pack_bf16(o[3][2] * bh, o[3][3] * bh);
      of[2 * t0 + 8] = pack_bf16(o[4][0] * bl, o[4][1] * bl); of[2 * t0 + 9] = pack_bf16(o[4][2] * bh, o[4][3] * bh);
    }
    {
      const uint32_t os = sb + OFF_O + 20480 + warp * 2560, oa = os + ((lane >> 3) & 1) * 1280 + (lane >> 4) * 128 + (lane & 7) * 16;
#pragma unroll
      for (int s = 0; s < 5; s++) stsm4(oa + s * 256, of[4 * s], of[4 * s + 1], of[4 * s + 2], of[4 * s + 3]);
      asm volatile("fence.proxy.async.shared::cta;" ::: "memory");
      __syncwarp();
      if (elect()) {
        asm volatile("cp.async.bulk.global.shared::cta.bulk_group [%0], [%1], 2560;\ncp.async.bulk.commit_group;" :: "l"(&g_o[mt * 2 + wg][g][w4 * 160]), "r"(os) : "memory");
      }
    }
    TS(5);
    float h[40];
#pragma unroll
    for (int s = 0; s < 5; s++) {
      const uint4 v = xr[s];
      h[8 * s] = bf_lo(v.x); h[8 * s + 1] = bf_hi(v.x); h[8 * s + 2] = bf_lo(v.y); h[8 * s + 3] = bf_hi(v.y);
      h[8 * s + 4] = bf_lo(v.z); h[8 * s + 5] = bf_hi(v.z); h[8 * s + 6] = bf_lo(v.w); h[8 * s + 7] = bf_hi(v.w);
    }
    mbar_wait(bar_full, 0); mbar_wait(bar_full + 8, 0); mbar_wait(bar_full + 16, 1);
    if (elect()) {
      asm volatile("cp.async.bulk.wait_group 0;" ::: "memory");
      asm volatile("red.relaxed.gpu.global.add.u32 [%0], 1;" :: "l"(g_own[mt * 8 + wg * 4].cnt) : "memory");
    }
    asm volatile("bar.arrive %0, 160;" :: "r"(5 + wg) : "memory");
    bar_sync(1, 256);
    const uint64_t dwo = make_desc(sb, 5120, 512, 2);
    wgmma_fence();
#pragma unroll
    for (int s = 0; s < 5; s++) wgmma_n80_rs(h, of[4 * s], of[4 * s + 1], of[4 * s + 2], of[4 * s + 3], dwo + g * 960 + s * 64, 1);
    wgmma_commit();
    TS(6);
#pragma unroll 1
    for (int i = 0, sl = 0; i < 7; i++) {
      mbar_wait(bar_o + wg * 64 + 8 * sl, i >= 3 && i < 6);
      if (i == 0) TS(1);
      const uint64_t da = make_desc(sb + OFF_O + sl * 20480 + wg * 10240, 128, 1280, 0), db = dwo + (i + (i >= g)) * 960;
      wgmma_fence();
#pragma unroll
      for (int s = 0; s < 5; s++) wgmma_n80_ss(h, da + s * 16, db + s * 64, 1);
      wgmma_commit();
      wgmma_wait<1>();
      if ((tid & 127) == 0 && i > 0 && i < 5) mbar_arrive(bar_o + wg * 64 + 24 + 8 * i);
      sl = sl == 2 ? 0 : sl + 1;
    }
    const bool odd = c & 1;
    float wr[20];
#pragma unroll
    for (int j = 0; j < 5; j++) {
      const uint4 v = lds128(sb + OFF_WR + c * 80 + j * 16);
      wr[4 * j] = __uint_as_float(v.x); wr[4 * j + 1] = __uint_as_float(v.y); wr[4 * j + 2] = __uint_as_float(v.z); wr[4 * j + 3] = __uint_as_float(v.w);
    }
    const float wsum = lds32f(sb + OFF_WR + 320);
    uint4* const sp = pin(&g_own[slot].st2[r + (odd ? 8 : 0)]);
    uint4* const cdp = pin(&g_x.cand[slot][g][0]);
    const int tok0 = mt * 128 + 32 * w4 + wg;
    wgmma_wait<0>();
#pragma unroll
    for (int i = 0; i < 40; i++) asm volatile("" : "+f"(h[i]) :: "memory");
    TS(7);
    float mean, rstd, rr;
    {
      float l1 = 0.f, l2 = 0.f, l3 = 0.f, h1 = 0.f, h2 = 0.f, h3 = 0.f;
#pragma unroll
      for (int j = 0; j < 10; j++) {
        l1 += h[4 * j] + h[4 * j + 1]; h1 += h[4 * j + 2] + h[4 * j + 3];
        l2 = fmaf(h[4 * j], h[4 * j], l2); l2 = fmaf(h[4 * j + 1], h[4 * j + 1], l2);
        h2 = fmaf(h[4 * j + 2], h[4 * j + 2], h2); h2 = fmaf(h[4 * j + 3], h[4 * j + 3], h2);
        l3 = fmaf(h[4 * j], wr[2 * j], l3); l3 = fmaf(h[4 * j + 1], wr[2 * j + 1], l3);
        h3 = fmaf(h[4 * j + 2], wr[2 * j], h3); h3 = fmaf(h[4 * j + 3], wr[2 * j + 1], h3);
      }
      float s1 = (odd ? h1 : l1) + shx(odd ? l1 : h1, 1), s2 = (odd ? h2 : l2) + shx(odd ? l2 : h2, 1), s3 = (odd ? h3 : l3) + shx(odd ? l3 : h3, 1);
      s1 += shx(s1, 2); s2 += shx(s2, 2); s3 += shx(s3, 2);
      if (cA) asm volatile("red.relaxed.gpu.global.add.v4.f32 [%0], {%1, %2, %3, %4};" :: "l"(sp), "f"(s1), "f"(s2), "f"(s3), "f"(1.f) : "memory");
      uint4 p0;
      do { p0 = ldg_pkt(sp); } while (anyw(p0.w != 0x41000000u) && --guard > 0);
      mean = __uint_as_float(p0.x) * (1.f / 640.f);
      rstd = rsq(fmaxf(fmaf(-mean, mean, __uint_as_float(p0.y) * (1.f / 640.f)), 0.f) + 1e-5f);
      rr = fmaf(-mean, wsum, __uint_as_float(p0.z)) * rstd;
    }
    TS(8);
    const uint32_t kk = ord_key(rr), kmax = __reduce_max_sync(0xffffffffu, kk);
    const int L = __ffs(__ballot_sync(0xffffffffu, kk == kmax)) - 1;
    const int crow = (L >> 2) + 8 * (L & 1);
    if (warp == g) {
      if (elect()) {
        asm volatile("red.relaxed.gpu.global.max.u64 [%0], %1;" :: "l"(g_own[1].cnt), "l"(((uint64_t)kmax << 32) | (uint32_t)(2047 - tok0 - 2 * crow)) : "memory");
        asm volatile("red.relaxed.gpu.global.add.u32 [%0], 1;" :: "l"(&g_own[1].cnt[0].z) : "memory");
      }
      asm volatile("bar.arrive 3, 64;" ::: "memory");
    }
    const uint32_t stg = sb + OFF_O + warp * 2560;
    uint4 held;
    {
      const float om = shx(mean, 1), os = shx(rstd, 1);
      const float rl = odd ? os : rstd, rh = odd ? rstd : os;
      const float bl = -(odd ? om : mean) * rl, bh = -(odd ? mean : om) * rh, al = 1.f + rl, ah = 1.f + rh;
      if ((L >> 2) == r) {
        const bool chi = L & 1;
        const float rc = chi ? rh : rl, bc = chi ? bh : bl;
        uint32_t n[10];
#pragma unroll
        for (int j = 0; j < 10; j++) n[j] = pack_bf16(fmaf(chi ? h[4 * j + 2] : h[4 * j], rc, bc), fmaf(chi ? h[4 * j + 3] : h[4 * j + 1], rc, bc));
        uint4* d = cdp + c;
        stg_pkt(d, n[0], n[1], n[2], n[3]); stg_pkt(d + 4, n[4], n[5], n[6], n[7]); stg_rlx64(d + 8, n[8], n[9]);
      }
      __syncwarp();
      const uint32_t fa = stg + (lane & 15) * 160 + (lane >> 4) * 16;
#pragma unroll
      for (int s = 0; s < 5; s++)
        stsm4(fa + s * 32, pack_bf16(fmaf(h[8 * s], al, bl), fmaf(h[8 * s + 1], al, bl)), pack_bf16(fmaf(h[8 * s + 2], ah, bh), fmaf(h[8 * s + 3], ah, bh)),
              pack_bf16(fmaf(h[8 * s + 4], al, bl), fmaf(h[8 * s + 5], al, bl)), pack_bf16(fmaf(h[8 * s + 6], ah, bh), fmaf(h[8 * s + 7], ah, bh)));
      __syncwarp();
      held = lds128(stg + crow * 160 + min(lane, 9) * 16);
      if (lane < 10) stg_pkt(cdp + 12 + lane, held.x, held.y, held.z, held.w);
    }
    TS(9);
    mbar_wait(bar_ffn, 0);
    const uint32_t red = sb + OFF_RED;
    if (ffn1) {
      uint4 w1[4][5];
      {
        const int k = (lane & 7) + (lane >> 4) * 8;
        const uint32_t a1 = sb + k * 64, sw = ((lane >> 3) & 1) ^ ((lane >> 1) & 3);
#pragma unroll
        for (int s = 0; s < 5; s++)
#pragma unroll
          for (int u = 0; u < 4; u++)
            w1[u][s] = ldsm4t(a1 + (s < 4 ? warp * 4096 + s * 1024 : 32768 + warp * 1024) + (u >> 1) * (40960 + (s == 4 || warp >= 2 ? OFF_W2 - 49152 : 0)) + ((sw ^ (2 * (u & 1))) * 16));
      }
      uint32_t* const ap = pin(g_x.act + fj * 16 + (lane >> 1));
      mbar_wait(bar_win, 0);
      const uint32_t hp = sb + OFF_HN + (warp * 4 + c) * 16;
      const uint4 c0 = lds128(hp), c1 = lds128(hp + 512), c2 = lds128(hp + 1024);
      TS(10);
      float a[4][4];
#pragma unroll
      for (int u = 0; u < 4; u++) {
        a[u][0] = a[u][1] = a[u][2] = a[u][3] = 0.f;
        mma_acc(a[u], w1[u][0], c0.x, c0.y); mma_acc(a[u], w1[u][1], c0.z, c0.w); mma_acc(a[u], w1[u][2], c1.x, c1.y);
        mma_acc(a[u], w1[u][3], c1.z, c1.w); mma_acc(a[u], w1[u][4], c2.x, c2.y);
      }
      asm volatile("st.shared.v2.f32 [%0], {%1, %2};" :: "r"(red + (warp * 32 + c * 8 + r) * 8),
                   "f"(cA ? (odd ? a[0][2] : a[0][0]) : (odd ? a[1][2] : a[1][0])), "f"(cA ? (odd ? a[2][2] : a[2][0]) : (odd ? a[3][2] : a[3][0])) : "memory");
      bar_sync(1, 256);
      if (warp == 0) {
        float2 t[8];
#pragma unroll
        for (int i = 0; i < 8; i++) t[i] = lds64f(red + (i * 32 + lane) * 8);
        const float s = ((t[0].x + t[1].x) + (t[2].x + t[3].x)) + ((t[4].x + t[5].x) + (t[6].x + t[7].x));
        const float u = ((t[0].y + t[1].y) + (t[2].y + t[3].y)) + ((t[4].y + t[5].y) + (t[6].y + t[7].y));
        const float av = s * u * rcp(1.f + ex2(-1.4426950408889634f * s));
        const float an = shx(av, 1);
        if (!odd) stg_rlx32(ap, pack_bf16(av, an));
      }
      bar_sync(1, 256);
      TS(11);
    }
    if (OUT_LATE) mbar_wait(bar_win, 0);
    char* const ob2 = (char*)(out + tok0 * 640 + g * 64);
    const int remo = 896 - 96 * g;
#pragma unroll
    for (int s = 0; s < 5; s++) {
      const int row = s < 4 ? 4 * s + (lane >> 3) : lane >> 1, pc = s < 4 ? lane & 7 : 8 + (lane & 1);
      const uint4 v = lds128(stg + row * 160 + pc * 16);
      if (row != crow) stg128(ob2 + row * 2560 + pc * 16 + (s < 4 ? 0 : remo), v);
    }
    mbar_wait(bar_win, 0);
    const uint4 win = lds128(sb + OFF_WR + 336);
    if (win.x != slot && lane < 10) stg128(ob2 + crow * 2560 + lane * 16 + (lane < 8 ? 0 : remo), held);
    if (!ffn1) {
      TS(10);
      uint4 w2[6];
      const uint32_t a2 = sb + OFF_W2 + (warp * 192 + 8 * (((lane >> 3) & 1) * 4 + ((lane & 7) >> 1)) + 2 * (lane >> 4) + (lane & 1)) * 16;
#pragma unroll
      for (int s = 0; s < 6; s++) w2[s] = ldsm4t(a2 + (s >> 1) * 1024 + (s & 1) * 64);
      const uint4* p = (const uint4*)(g_x.act + warp * 96) + (r & 1) * 4 + c;
      const uint32_t* pb = (const uint32_t*)&g_x.cand[win.x][fj < 64 ? fj >> 3 : (fj - 64) >> 1][fj < 64 ? 12 + (fj & 7) : 20 + (fj & 1)] + c;
      uint32_t* const op = pin((uint32_t*)(out + win.y * 640 + fj * 8) + c);
      uint4 c0, c1, c2; uint32_t bw;
      if (ACT_NS) __nanosleep(ACT_NS);
      do {
        c0 = ldg_pkt(p); c1 = ldg_pkt(p + 8); c2 = ldg_pkt(p + 16); bw = ldg_rlx32(pb);
      } while (anyw(max(max(max(max(c0.x, c0.y), max(c0.z, c0.w)), max(max(c1.x, c1.y), max(c1.z, c1.w))), max(max(max(c2.x, c2.y), max(c2.z, c2.w)), bw)) == SENT) && --guard > 0);
      TS(11);
      float a[4] = {0.f, 0.f, 0.f, 0.f}, b[4] = {0.f, 0.f, 0.f, 0.f}, d[4] = {0.f, 0.f, 0.f, 0.f};
      mma_acc(a, w2[0], c0.x, c0.y); mma_acc(b, w2[2], c1.x, c1.y); mma_acc(d, w2[4], c2.x, c2.y);
      mma_acc(a, w2[1], c0.z, c0.w); mma_acc(b, w2[3], c1.z, c1.w); mma_acc(d, w2[5], c2.z, c2.w);
      if (c == 0) sts32f(red + (warp * 8 + r) * 4, ((a[0] + a[3]) + (b[0] + b[3])) + (d[0] + d[3]));
      bar_sync(1, 256);
      if (tid < 4) {
        float2 t[8];
#pragma unroll
        for (int i = 0; i < 8; i++) t[i] = lds64f(red + (i * 4 + tid) * 8);
        const float y0 = ((t[0].x + t[1].x) + (t[2].x + t[3].x)) + ((t[4].x + t[5].x) + (t[6].x + t[7].x));
        const float y1 = ((t[0].y + t[1].y) + (t[2].y + t[3].y)) + ((t[4].y + t[5].y) + (t[6].y + t[7].y));
        const float sg = __uint_as_float(win.z);
        *op = pack_bf16(fmaf(y0, sg, bf_lo(bw)), fmaf(y1, sg, bf_hi(bw)));
      }
    }
    TS(12);
#undef TS_T
  }
}

typedef CUresult (*EncodeFn)(CUtensorMap*, CUtensorMapDataType, cuuint32_t, void*, const cuuint64_t*, const cuuint64_t*, const cuuint32_t*,
                             const cuuint32_t*, CUtensorMapInterleave, CUtensorMapSwizzle, CUtensorMapL2promotion, CUtensorMapFloatOOBfill);

void make_map(EncodeFn enc, CUtensorMap* m, const void* base, const cuuint64_t* dims, const cuuint64_t* strides, const cuuint32_t* box,
              CUtensorMapSwizzle swz) {
  const cuuint32_t es[3] = {1, 1, 1};
  enc(m, CU_TENSOR_MAP_DATA_TYPE_BFLOAT16, 3, (void*)base, dims, strides, box, es, CU_TENSOR_MAP_INTERLEAVE_NONE, swz,
      CU_TENSOR_MAP_L2_PROMOTION_L2_128B, CU_TENSOR_MAP_FLOAT_OOB_FILL_NONE);
}

}

extern "C" void kernel_launch(void* const* d_in, const int* in_sizes, int n_in, void* d_out, int out_size) {
  const __nv_bfloat16* x = (const __nv_bfloat16*)d_in[0];
  const __nv_bfloat16* wqkv = (const __nv_bfloat16*)d_in[1];
  const __nv_bfloat16* wo = (const __nv_bfloat16*)d_in[2];
  void* fn = nullptr;
  cudaDriverEntryPointQueryResult st;
  cudaGetDriverEntryPoint("cuTensorMapEncodeTiled", &fn, cudaEnableDefault, &st);
  EncodeFn enc = (EncodeFn)fn;
  void* scp = nullptr;
  cudaGetSymbolAddress(&scp, g_scratch);
  Maps tm;
  { const cuuint64_t d[3] = {640, 1024, 2}, s[2] = {2560, 1280}; const cuuint32_t b[3] = {64, 64, 2}; make_map(enc, &tm.x, x, d, s, b, CU_TENSOR_MAP_SWIZZLE_128B); }
  { const cuuint64_t d[3] = {640, 640, 3}, s[2] = {3840, 1280}; const cuuint32_t b[3] = {64, 64, 1}; make_map(enc, &tm.w, wqkv, d, s, b, CU_TENSOR_MAP_SWIZZLE_128B); }
  { const cuuint64_t d[3] = {640, 640, 3}, s[2] = {3840, 1280}; const cuuint32_t b[3] = {16, 64, 3}; make_map(enc, &tm.wr, wqkv, d, s, b, CU_TENSOR_MAP_SWIZZLE_32B); }
  { const cuuint64_t d[3] = {32, 640, 20}, s[2] = {1280, 64}; const cuuint32_t b[3] = {32, 80, 2}; make_map(enc, &tm.wo, wo, d, s, b, CU_TENSOR_MAP_SWIZZLE_64B); }
  { const cuuint64_t d[3] = {640, 640, 1}, s[2] = {1280, 819200}; const cuuint32_t b[3] = {16, 80, 1}; make_map(enc, &tm.wor, wo, d, s, b, CU_TENSOR_MAP_SWIZZLE_64B); }
  { const cuuint64_t d[3] = {1536, 640, 1}, s[2] = {3072, 1966080}; const cuuint32_t b[3] = {32, 128, 1};
    make_map(enc, &tm.gate, d_in[5], d, s, b, CU_TENSOR_MAP_SWIZZLE_64B); make_map(enc, &tm.up, d_in[6], d, s, b, CU_TENSOR_MAP_SWIZZLE_64B); }
  { const cuuint64_t d[3] = {640, 1536, 1}, s[2] = {1280, 1966080}; const cuuint32_t b[3] = {8, 128, 1}; make_map(enc, &tm.down, d_in[7], d, s, b, CU_TENSOR_MAP_SWIZZLE_NONE); }
  cudaFuncSetAttribute(fused_kernel, cudaFuncAttributeMaxDynamicSharedMemorySize, SMEM_BYTES);
  fused_kernel<<<128, 512, SMEM_BYTES, cudaStreamPerThread>>>(x, wqkv, wo, (const __nv_bfloat16*)d_in[4], (const __nv_bfloat16*)d_in[5],
                                                              (const __nv_bfloat16*)d_in[6], (const __nv_bfloat16*)d_in[7], (__nv_bfloat16*)d_out, (Scratch*)scp, tm);
}
```

```cpp
#include <cuda_runtime.h>
#include <cuda_bf16.h>
#include <cuda.h>
#include <stdint.h>

#define PF0 1
#define PF_NS 100
#define PFX_IT 0
#define PFW_NS 100
#define ACT_NS 0
#define F_IT 6
#define F_MAX 12
#define F_PER 2
#define OUT_LATE 1
#define REG_P 72
#define REG_C 184
#define AUX_NS 50
#define LEAD 1
#define RST_IT 0
#define ORDX 1

namespace {

constexpr int SLOT    = 47104;
constexpr int OFF_O   = 122880;
constexpr int OFF_W2  = 4 * SLOT;
constexpr int OFF_CS  = OFF_W2 + 32768;
constexpr int OFF_RS  = OFF_CS + 3840;
constexpr int OFF_MN  = OFF_RS + 576;
constexpr int OFF_WR  = OFF_MN + 1024;
constexpr int OFF_RED = OFF_CS;
constexpr int OFF_HN  = OFF_CS + 2048;
constexpr int OFF_PT  = OFF_WR + 352;
constexpr int OFF_BAR = OFF_PT + 768;
constexpr int SMEM_BYTES = OFF_BAR + 240 + 384;
constexpr uint32_t SENT = 0xFFFFFFFFu;
constexpr int SPIN_MAX = 1 << 20;

struct Glob {
  uint4 cand[128][8][24];
  uint32_t act[768];
  uint32_t pad[256];
};
constexpr int GLOB_PER_CTA = sizeof(Glob) / 16 / 128;
static_assert(GLOB_PER_CTA * 128 * 16 == sizeof(Glob), "glob size");
struct Own {
  uint4 halo[2][5][32];
  uint4 st1[32];
  uint2 cs[32];
  uint4 st2[16];
  uint4 cnt[8];
};
struct Scratch {
  Glob x;
  Own own[128];
  uint4 o[32][8][640];
  uint32_t epoch[128];
};
__device__ __align__(128) Scratch g_scratch;
#define g_x (sc->x)
#define g_own (sc->own)
#define g_o (sc->o)
#define g_epoch (sc->epoch)
#define TS(i)

__device__ __forceinline__ void mbar_init(uint32_t bar, uint32_t cnt) { asm volatile("mbarrier.init.shared::cta.b64 [%0], %1;" :: "r"(bar), "r"(cnt) : "memory"); }
__device__ __forceinline__ void mbar_expect_tx(uint32_t bar, uint32_t bytes) { asm volatile("mbarrier.arrive.expect_tx.shared::cta.b64 _, [%0], %1;" :: "r"(bar), "r"(bytes) : "memory"); }
__device__ __forceinline__ void mbar_arrive(uint32_t bar) { asm volatile("mbarrier.arrive.shared::cta.b64 _, [%0];" :: "r"(bar) : "memory"); }
__device__ __forceinline__ void mbar_arrive_cta(uint32_t bar, uint32_t cta) {
  asm volatile("{\n.reg .b32 ra;\nmapa.shared::cluster.u32 ra, %0, %1;\nmbarrier.arrive.shared::cluster.b64 _, [ra];\n}\n" :: "r"(bar), "r"(cta) : "memory");
}
__device__ __forceinline__ void mbar_wait(uint32_t bar, uint32_t parity) {
  asm volatile("{\n.reg .pred p;\n.reg .u32 n;\nmov.u32 n, 0;\nW:\nmbarrier.try_wait.parity.shared::cta.b64 p, [%0], %1;\n@p bra.uni D;\n"
               "add.u32 n, n, 1;\nsetp.lt.u32 p, n, %2;\n@p bra.uni W;\nD:\n}\n" :: "r"(bar), "r"(parity), "n"(SPIN_MAX) : "memory");
}
__device__ __forceinline__ void tma_3d(uint32_t dst, const void* tm, uint32_t bar, int c0, int c1, int c2) {
  asm volatile("cp.async.bulk.tensor.3d.shared::cluster.global.mbarrier::complete_tx::bytes [%0], [%1, {%3, %4, %5}], [%2];" :: "r"(dst), "l"(tm), "r"(bar), "r"(c0), "r"(c1), "r"(c2) : "memory");
}
__device__ __forceinline__ void tma_3d_mc(uint32_t dst, const void* tm, uint32_t bar, int c0, int c1, int c2) {
  asm volatile("cp.async.bulk.tensor.3d.shared::cluster.global.mbarrier::complete_tx::bytes.multicast::cluster [%0], [%1, {%3, %4, %5}], [%2], %6;" :: "r"(dst), "l"(tm), "r"(bar), "r"(c0), "r"(c1), "r"(c2), "h"((uint16_t)3) : "memory");
}
__device__ __forceinline__ void wgmma_fence() { asm volatile("wgmma.fence.sync.aligned;" ::: "memory"); }
__device__ __forceinline__ void wgmma_commit() { asm volatile("wgmma.commit_group.sync.aligned;" ::: "memory"); }
template <int N> __device__ __forceinline__ void wgmma_wait() { asm volatile("wgmma.wait_group.sync.aligned %0;" :: "n"(N) : "memory"); }
__device__ __forceinline__ uint64_t make_desc(uint32_t addr, uint32_t lbo, uint32_t sbo, uint32_t swz) {
  return (uint64_t)(((addr & 0x3FFFF) >> 4) | ((lbo >> 4) << 16)) | ((uint64_t)((sbo >> 4) | (swz << 30)) << 32);
}
__device__ __forceinline__ void bar_sync(int id, int n) { asm volatile("bar.sync %0, %1;" :: "r"(id), "r"(n) : "memory"); }
__device__ __forceinline__ uint4 ld_pkt(const void* p) {
  uint4 v;
  asm volatile("{\n.reg .b128 t;\n.reg .b64 lo, hi;\nld.relaxed.gpu.b128 t, [%4];\nmov.b128 {lo, hi}, t;\nmov.b64 {%0, %1}, lo;\nmov.b64 {%2, %3}, hi;\n}\n"
               : "=r"(v.x), "=r"(v.y), "=r"(v.z), "=r"(v.w) : "l"(p) : "memory");
  return v;
}
__device__ __forceinline__ void st_pkt(void* p, uint32_t a, uint32_t b, uint32_t c, uint32_t d) {
  asm volatile("{\n.reg .b128 t;\n.reg .b64 lo, hi;\nmov.b64 lo, {%1, %2};\nmov.b64 hi, {%3, %4};\nmov.b128 t, {lo, hi};\nst.relaxed.gpu.b128 [%0], t;\n}\n"
               :: "l"(p), "r"(a), "r"(b), "r"(c), "r"(d) : "memory");
}
__device__ __forceinline__ uint4 ldg_pkt(const void* p) {
  uint4 v;
  asm volatile("{\n.reg .b128 t;\n.reg .b64 lo, hi;\nld.relaxed.gpu.global.b128 t, [%4];\nmov.b128 {lo, hi}, t;\nmov.b64 {%0, %1}, lo;\nmov.b64 {%2, %3}, hi;\n}\n"
               : "=r"(v.x), "=r"(v.y), "=r"(v.z), "=r"(v.w) : "l"(p) : "memory");
  return v;
}
__device__ __forceinline__ void stg_pkt(void* p, uint32_t a, uint32_t b, uint32_t c, uint32_t d) {
  asm volatile("{\n.reg .b128 t;\n.reg .b64 lo, hi;\nmov.b64 lo, {%1, %2};\nmov.b64 hi, {%3, %4};\nmov.b128 t, {lo, hi};\nst.relaxed.gpu.global.b128 [%0], t;\n}\n"
               :: "l"(p), "r"(a), "r"(b), "r"(c), "r"(d) : "memory");
}
__device__ __forceinline__ uint32_t ldg_rlx32(const void* p) { uint32_t v; asm volatile("ld.relaxed.gpu.global.u32 %0, [%1];" : "=r"(v) : "l"(p) : "memory"); return v; }
__device__ __forceinline__ uint2 ldg_rlx64(const void* p) { uint2 v; asm volatile("ld.relaxed.gpu.global.v2.u32 {%0, %1}, [%2];" : "=r"(v.x), "=r"(v.y) : "l"(p) : "memory"); return v; }
__device__ __forceinline__ void stg128(void* p, const uint4& v) { asm volatile("st.global.v4.u32 [%0], {%1, %2, %3, %4};" :: "l"(p), "r"(v.x), "r"(v.y), "r"(v.z), "r"(v.w) : "memory"); }
__device__ __forceinline__ uint32_t pin(uint32_t v) { asm volatile("" : "+r"(v)); return v; }
__device__ __forceinline__ uint64_t mk64(uint32_t lo, uint32_t hi) { return ((uint64_t)hi << 32) | lo; }
template <class T> __device__ __forceinline__ T* pin(T* p) { asm volatile("" : "+l"(p)); return p; }
__device__ __forceinline__ void stg_rlx32(void* p, uint32_t v) { asm volatile("st.relaxed.gpu.global.u32 [%0], %1;" :: "l"(p), "r"(v) : "memory"); }
__device__ __forceinline__ void stg_rlx64(void* p, uint32_t a, uint32_t b) { asm volatile("st.relaxed.gpu.global.v2.u32 [%0], {%1, %2};" :: "l"(p), "r"(a), "r"(b) : "memory"); }
__device__ __forceinline__ uint4 ldsm4(uint32_t a) { uint4 v; asm volatile("ldmatrix.sync.aligned.m8n8.x4.shared.b16 {%0, %1, %2, %3}, [%4];" : "=r"(v.x), "=r"(v.y), "=r"(v.z), "=r"(v.w) : "r"(a) : "memory"); return v; }
__device__ __forceinline__ uint4 ldsm4t(uint32_t a) { uint4 v; asm volatile("ldmatrix.sync.aligned.m8n8.x4.trans.shared.b16 {%0, %1, %2, %3}, [%4];" : "=r"(v.x), "=r"(v.y), "=r"(v.z), "=r"(v.w) : "r"(a) : "memory"); return v; }
__device__ __forceinline__ void stsm4(uint32_t a, uint32_t x, uint32_t y, uint32_t z, uint32_t w) { asm volatile("stmatrix.sync.aligned.m8n8.x4.shared.b16 [%0], {%1, %2, %3, %4};" :: "r"(a), "r"(x), "r"(y), "r"(z), "r"(w) : "memory"); }
__device__ __forceinline__ void mma_acc(float (&c)[4], const uint4& a, uint32_t b0, uint32_t b1) {
  asm("mma.sync.aligned.m16n8k16.row.col.f32.bf16.bf16.f32 {%0,%1,%2,%3}, {%4,%5,%6,%7}, {%8,%9}, {%0,%1,%2,%3};"
      : "+f"(c[0]), "+f"(c[1]), "+f"(c[2]), "+f"(c[3]) : "r"(a.x), "r"(a.y), "r"(a.z), "r"(a.w), "r"(b0), "r"(b1));
}
__device__ __forceinline__ uint4 lds128(uint32_t a) { uint4 v; asm volatile("ld.shared.v4.u32 {%0, %1, %2, %3}, [%4];" : "=r"(v.x), "=r"(v.y), "=r"(v.z), "=r"(v.w) : "r"(a) : "memory"); return v; }
__device__ __forceinline__ float2 lds64f(uint32_t a) { float2 v; asm volatile("ld.shared.v2.f32 {%0, %1}, [%2];" : "=f"(v.x), "=f"(v.y) : "r"(a)); return v; }
__device__ __forceinline__ float lds32f(uint32_t a) { float v; asm volatile("ld.shared.f32 %0, [%1];" : "=f"(v) : "r"(a)); return v; }
__device__ __forceinline__ void sts32f(uint32_t a, float v) { asm volatile("st.shared.f32 [%0], %1;" :: "r"(a), "f"(v) : "memory"); }
__device__ __forceinline__ uint32_t pack_bf16(float lo, float hi) { uint32_t r; asm("cvt.rn.bf16x2.f32 %0, %1, %2;" : "=r"(r) : "f"(hi), "f"(lo)); return r; }
__device__ __forceinline__ float bf_lo(uint32_t v) { return __uint_as_float(v << 16); }
__device__ __forceinline__ float bf_hi(uint32_t v) { return __uint_as_float(v & 0xffff0000u); }
__device__ __forceinline__ uint32_t movm(uint32_t a) { uint32_t d; asm("movmatrix.sync.aligned.m8n8.trans.b16 %0, %1;" : "=r"(d) : "r"(a)); return d; }
__device__ __forceinline__ float ex2(float x) { float y; asm("ex2.approx.ftz.f32 %0, %1;" : "=f"(y) : "f"(x)); return y; }
__device__ __forceinline__ float rsq(float x) { float y; asm("rsqrt.approx.ftz.f32 %0, %1;" : "=f"(y) : "f"(x)); return y; }
__device__ __forceinline__ float rcp(float x) { float y; asm("rcp.approx.ftz.f32 %0, %1;" : "=f"(y) : "f"(x)); return y; }
__device__ __forceinline__ bool elect() { uint32_t p; asm volatile("{\n.reg .pred q;\nelect.sync _|q, 0xffffffff;\nselp.u32 %0, 1, 0, q;\n}\n" : "=r"(p)); return p; }
__device__ __forceinline__ void pf_l2(const void* p) { asm volatile("prefetch.global.L2 [%0];" :: "l"(p)); }
__device__ __forceinline__ bool anyw(bool p) { return __any_sync(0xffffffffu, p); }
__device__ __forceinline__ float shx(float v, int m) { return __shfl_xor_sync(0xffffffffu, v, m); }
__device__ __forceinline__ void mma_k24(float (&c)[4], uint32_t a0, uint32_t a1, uint32_t a2, uint32_t a3, uint32_t b0, uint32_t b1,
                                        uint32_t e0, uint32_t e1, uint32_t f0) {
  asm("mma.sync.aligned.m16n8k16.row.col.f32.bf16.bf16.f32 {%0,%1,%2,%3}, {%4,%5,%6,%7}, {%8,%9}, {%10,%10,%10,%10};"
      : "=f"(c[0]), "=f"(c[1]), "=f"(c[2]), "=f"(c[3]) : "r"(a0), "r"(a1), "r"(a2), "r"(a3), "r"(b0), "r"(b1), "f"(0.f));
  asm("mma.sync.aligned.m16n8k8.row.col.f32.bf16.bf16.f32 {%0,%1,%2,%3}, {%4,%5}, {%6}, {%0,%1,%2,%3};"
      : "+f"(c[0]), "+f"(c[1]), "+f"(c[2]), "+f"(c[3]) : "r"(e0), "r"(e1), "r"(f0));
}
__device__ __forceinline__ uint32_t ord_key(float r) { uint32_t u = __float_as_uint(r); return u ^ ((uint32_t)((int32_t)u >> 31) | 0x80000000u); }

__device__ __forceinline__ void wgmma_n48hi_ss(float (&d)[120], uint64_t da, uint64_t db, int scale_d) {
  asm volatile("{\n.reg .pred p;\nsetp.ne.b32 p, %26, 0;\n"
    "wgmma.mma_async.sync.aligned.m64n48k16.f32.bf16.bf16 "
    "{%0, %1, %2, %3, %4, %5, %6, %7, %8, %9, %10, %11, %12, %13, %14, %15, "
    "%16, %17, %18, %19, %20, %21, %22, %23}, "
    "%24, %25, p, 1, 1, 0, 1;\n}\n"
    : "+f"(d[96]), "+f"(d[97]), "+f"(d[98]), "+f"(d[99]), "+f"(d[100]), "+f"(d[101]), "+f"(d[102]), "+f"(d[103]),
      "+f"(d[104]), "+f"(d[105]), "+f"(d[106]), "+f"(d[107]), "+f"(d[108]), "+f"(d[109]), "+f"(d[110]), "+f"(d[111]),
      "+f"(d[112]), "+f"(d[113]), "+f"(d[114]), "+f"(d[115]), "+f"(d[116]), "+f"(d[117]), "+f"(d[118]), "+f"(d[119])
    : "l"(da), "l"(db), "r"(scale_d));
}
__device__ __forceinline__ void wgmma_n192lo_ss(float (&d)[120], uint64_t da, uint64_t db, int scale_d) {
  asm volatile("{\n.reg .pred p;\nsetp.ne.b32 p, %98, 0;\n"
    "wgmma.mma_async.sync.aligned.m64n192k16.f32.bf16.bf16 "
    "{%0, %1, %2, %3, %4, %5, %6, %7, %8, %9, %10, %11, %12, %13, %14, %15, "
    "%16, %17, %18, %19, %20, %21, %22, %23, %24, %25, %26, %27, %28, %29, %30, %31, "
    "%32, %33, %34, %35, %36, %37, %38, %39, %40, %41, %42, %43, %44, %45, %46, %47, "
    "%48, %49, %50, %51, %52, %53, %54, %55, %56, %57, %58, %59, %60, %61, %62, %63, "
    "%64, %65, %66, %67, %68, %69, %70, %71, %72, %73, %74, %75, %76, %77, %78, %79, "
    "%80, %81, %82, %83, %84, %85, %86, %87, %88, %89, %90, %91, %92, %93, %94, %95}, "
    "%96, %97, p, 1, 1, 0, 1;\n}\n"
    : "+f"(d[0]), "+f"(d[1]), "+f"(d[2]), "+f"(d[3]), "+f"(d[4]), "+f"(d[5]), "+f"(d[6]), "+f"(d[7]),
      "+f"(d[8]), "+f"(d[9]), "+f"(d[10]), "+f"(d[11]), "+f"(d[12]), "+f"(d[13]), "+f"(d[14]), "+f"(d[15]),
      "+f"(d[16]), "+f"(d[17]), "+f"(d[18]), "+f"(d[19]), "+f"(d[20]), "+f"(d[21]), "+f"(d[22]), "+f"(d[23]),
      "+f"(d[24]), "+f"(d[25]), "+f"(d[26]), "+f"(d[27]), "+f"(d[28]), "+f"(d[29]), "+f"(d[30]), "+f"(d[31]),
      "+f"(d[32]), "+f"(d[33]), "+f"(d[34]), "+f"(d[35]), "+f"(d[36]), "+f"(d[37]), "+f"(d[38]), "+f"(d[39]),
      "+f"(d[40]), "+f"(d[41]), "+f"(d[42]), "+f"(d[43]), "+f"(d[44]), "+f"(d[45]), "+f"(d[46]), "+f"(d[47]),
      "+f"(d[48]), "+f"(d[49]), "+f"(d[50]), "+f"(d[51]), "+f"(d[52]), "+f"(d[53]), "+f"(d[54]), "+f"(d[55]),
      "+f"(d[56]), "+f"(d[57]), "+f"(d[58]), "+f"(d[59]), "+f"(d[60]), "+f"(d[61]), "+f"(d[62]), "+f"(d[63]),
      "+f"(d[64]), "+f"(d[65]), "+f"(d[66]), "+f"(d[67]), "+f"(d[68]), "+f"(d[69]), "+f"(d[70]), "+f"(d[71]),
      "+f"(d[72]), "+f"(d[73]), "+f"(d[74]), "+f"(d[75]), "+f"(d[76]), "+f"(d[77]), "+f"(d[78]), "+f"(d[79]),
      "+f"(d[80]), "+f"(d[81]), "+f"(d[82]), "+f"(d[83]), "+f"(d[84]), "+f"(d[85]), "+f"(d[86]), "+f"(d[87]),
      "+f"(d[88]), "+f"(d[89]), "+f"(d[90]), "+f"(d[91]), "+f"(d[92]), "+f"(d[93]), "+f"(d[94]), "+f"(d[95])
    : "l"(da), "l"(db), "r"(scale_d));
}
__device__ __forceinline__ void wgmma_n48hi_rk(float (&d)[120], uint32_t a0, uint32_t a1, uint32_t a2, uint32_t a3, uint64_t db, int scale_d) {
  asm volatile("{\n.reg .pred p;\nsetp.ne.b32 p, %29, 0;\n"
    "wgmma.mma_async.sync.aligned.m64n48k16.f32.bf16.bf16 "
    "{%0, %1, %2, %3, %4, %5, %6, %7, %8, %9, %10, %11, %12, %13, %14, %15, "
    "%16, %17, %18, %19, %20, %21, %22, %23}, "
    "{%24, %25, %26, %27}, %28, p, 1, 1, 0;\n}\n"
    : "+f"(d[96]), "+f"(d[97]), "+f"(d[98]), "+f"(d[99]), "+f"(d[100]), "+f"(d[101]), "+f"(d[102]), "+f"(d[103]),
      "+f"(d[104]), "+f"(d[105]), "+f"(d[106]), "+f"(d[107]), "+f"(d[108]), "+f"(d[109]), "+f"(d[110]), "+f"(d[111]),
      "+f"(d[112]), "+f"(d[113]), "+f"(d[114]), "+f"(d[115]), "+f"(d[116]), "+f"(d[117]), "+f"(d[118]), "+f"(d[119])
    : "r"(a0), "r"(a1), "r"(a2), "r"(a3), "l"(db), "r"(scale_d));
}
__device__ __forceinline__ void wgmma_n192lo_rk(float (&d)[120], uint32_t a0, uint32_t a1, uint32_t a2, uint32_t a3, uint64_t db, int scale_d) {
  asm volatile("{\n.reg .pred p;\nsetp.ne.b32 p, %101, 0;\n"
    "wgmma.mma_async.sync.aligned.m64n192k16.f32.bf16.bf16 "
    "{%0, %1, %2, %3, %4, %5, %6, %7, %8, %9, %10, %11, %12, %13, %14, %15, "
    "%16, %17, %18, %19, %20, %21, %22, %23, %24, %25, %26, %27, %28, %29, %30, %31, "
    "%32, %33, %34, %35, %36, %37, %38, %39, %40, %41, %42, %43, %44, %45, %46, %47, "
    "%48, %49, %50, %51, %52, %53, %54, %55, %56, %57, %58, %59, %60, %61, %62, %63, "
    "%64, %65, %66, %67, %68, %69, %70, %71, %72, %73, %74, %75, %76, %77, %78, %79, "
    "%80, %81, %82, %83, %84, %85, %86, %87, %88, %89, %90, %91, %92, %93, %94, %95}, "
    "{%96, %97, %98, %99}, %100, p, 1, 1, 0;\n}\n"
    : "+f"(d[0]), "+f"(d[1]), "+f"(d[2]), "+f"(d[3]), "+f"(d[4]), "+f"(d[5]), "+f"(d[6]), "+f"(d[7]),
      "+f"(d[8]), "+f"(d[9]), "+f"(d[10]), "+f"(d[11]), "+f"(d[12]), "+f"(d[13]), "+f"(d[14]), "+f"(d[15]),
      "+f"(d[16]), "+f"(d[17]), "+f"(d[18]), "+f"(d[19]), "+f"(d[20]), "+f"(d[21]), "+f"(d[22]), "+f"(d[23]),
      "+f"(d[24]), "+f"(d[25]), "+f"(d[26]), "+f"(d[27]), "+f"(d[28]), "+f"(d[29]), "+f"(d[30]), "+f"(d[31]),
      "+f"(d[32]), "+f"(d[33]), "+f"(d[34]), "+f"(d[35]), "+f"(d[36]), "+f"(d[37]), "+f"(d[38]), "+f"(d[39]),
      "+f"(d[40]), "+f"(d[41]), "+f"(d[42]), "+f"(d[43]), "+f"(d[44]), "+f"(d[45]), "+f"(d[46]), "+f"(d[47]),
      "+f"(d[48]), "+f"(d[49]), "+f"(d[50]), "+f"(d[51]), "+f"(d[52]), "+f"(d[53]), "+f"(d[54]), "+f"(d[55]),
      "+f"(d[56]), "+f"(d[57]), "+f"(d[58]), "+f"(d[59]), "+f"(d[60]), "+f"(d[61]), "+f"(d[62]), "+f"(d[63]),
      "+f"(d[64]), "+f"(d[65]), "+f"(d[66]), "+f"(d[67]), "+f"(d[68]), "+f"(d[69]), "+f"(d[70]), "+f"(d[71]),
      "+f"(d[72]), "+f"(d[73]), "+f"(d[74]), "+f"(d[75]), "+f"(d[76]), "+f"(d[77]), "+f"(d[78]), "+f"(d[79]),
      "+f"(d[80]), "+f"(d[81]), "+f"(d[82]), "+f"(d[83]), "+f"(d[84]), "+f"(d[85]), "+f"(d[86]), "+f"(d[87]),
      "+f"(d[88]), "+f"(d[89]), "+f"(d[90]), "+f"(d[91]), "+f"(d[92]), "+f"(d[93]), "+f"(d[94]), "+f"(d[95])
    : "r"(a0), "r"(a1), "r"(a2), "r"(a3), "l"(db), "r"(scale_d));
}
__device__ __forceinline__ void wgmma_n80_rs(float (&d)[40], uint32_t a0, uint32_t a1, uint32_t a2, uint32_t a3, uint64_t db, int scale_d) {
  asm volatile("{\n.reg .pred p;\nsetp.ne.b32 p, %45, 0;\n"
    "wgmma.mma_async.sync.aligned.m64n80k16.f32.bf16.bf16 "
    "{%0, %1, %2, %3, %4, %5, %6, %7, %8, %9, %10, %11, %12, %13, %14, %15, "
    "%16, %17, %18, %19, %20, %21, %22, %23, %24, %25, %26, %27, %28, %29, %30, %31, "
    "%32, %33, %34, %35, %36, %37, %38, %39}, "
    "{%40, %41, %42, %43}, %44, p, 1, 1, 1;\n}\n"
    : "+f"(d[0]), "+f"(d[1]), "+f"(d[2]), "+f"(d[3]), "+f"(d[4]), "+f"(d[5]), "+f"(d[6]), "+f"(d[7]),
      "+f"(d[8]), "+f"(d[9]), "+f"(d[10]), "+f"(d[11]), "+f"(d[12]), "+f"(d[13]), "+f"(d[14]), "+f"(d[15]),
      "+f"(d[16]), "+f"(d[17]), "+f"(d[18]), "+f"(d[19]), "+f"(d[20]), "+f"(d[21]), "+f"(d[22]), "+f"(d[23]),
      "+f"(d[24]), "+f"(d[25]), "+f"(d[26]), "+f"(d[27]), "+f"(d[28]), "+f"(d[29]), "+f"(d[30]), "+f"(d[31]),
      "+f"(d[32]), "+f"(d[33]), "+f"(d[34]), "+f"(d[35]), "+f"(d[36]), "+f"(d[37]), "+f"(d[38]), "+f"(d[39])
    : "r"(a0), "r"(a1), "r"(a2), "r"(a3), "l"(db), "r"(scale_d));
}
__device__ __forceinline__ void wgmma_n80_ss(float (&d)[40], uint64_t da, uint64_t db, int scale_d) {
  asm volatile("{\n.reg .pred p;\nsetp.ne.b32 p, %42, 0;\n"
    "wgmma.mma_async.sync.aligned.m64n80k16.f32.bf16.bf16 "
    "{%0, %1, %2, %3, %4, %5, %6, %7, %8, %9, %10, %11, %12, %13, %14, %15, "
    "%16, %17, %18, %19, %20, %21, %22, %23, %24, %25, %26, %27, %28, %29, %30, %31, "
    "%32, %33, %34, %35, %36, %37, %38, %39}, "
    "%40, %41, p, 1, 1, 0, 1;\n}\n"
    : "+f"(d[0]), "+f"(d[1]), "+f"(d[2]), "+f"(d[3]), "+f"(d[4]), "+f"(d[5]), "+f"(d[6]), "+f"(d[7]),
      "+f"(d[8]), "+f"(d[9]), "+f"(d[10]), "+f"(d[11]), "+f"(d[12]), "+f"(d[13]), "+f"(d[14]), "+f"(d[15]),
      "+f"(d[16]), "+f"(d[17]), "+f"(d[18]), "+f"(d[19]), "+f"(d[20]), "+f"(d[21]), "+f"(d[22]), "+f"(d[23]),
      "+f"(d[24]), "+f"(d[25]), "+f"(d[26]), "+f"(d[27]), "+f"(d[28]), "+f"(d[29]), "+f"(d[30]), "+f"(d[31]),
      "+f"(d[32]), "+f"(d[33]), "+f"(d[34]), "+f"(d[35]), "+f"(d[36]), "+f"(d[37]), "+f"(d[38]), "+f"(d[39])
    : "l"(da), "l"(db), "r"(scale_d));
}

__device__ __forceinline__ constexpr int QT(int t) { return t < 8 ? t : 16 + t; }
__device__ __forceinline__ constexpr int KT(int t) { return t < 8 ? 8 + t : 18 + t; }
__device__ __forceinline__ constexpr int VT(int t) { return t < 8 ? 16 + t : 20 + t; }

struct Maps { CUtensorMap x, w, wr, wo, wor, gate, up, down; };

__global__ void __cluster_dims__(2, 1, 1) __launch_bounds__(512, 1)
fused_kernel(const __nv_bfloat16* __restrict__ x, const __nv_bfloat16* __restrict__ wqkv,
             const __nv_bfloat16* __restrict__ wo, const __nv_bfloat16* __restrict__ w_r, const __nv_bfloat16* __restrict__ w_gate,
             const __nv_bfloat16* __restrict__ w_up, const __nv_bfloat16* __restrict__ w_down, __nv_bfloat16* __restrict__ out,
             Scratch* __restrict__ sc, const __grid_constant__ Maps tm) {
  extern __shared__ __align__(1024) uint8_t smem[];
  const int tid = threadIdx.x, warp = __shfl_sync(0xffffffffu, tid >> 5, 0), lane = tid & 31, bid = blockIdx.x;
  const uint32_t sb = (uint32_t)__cvta_generic_to_shared(smem);
  const uint32_t bar_full = sb + OFF_BAR, bar_empty = bar_full + 32, bar_aux = bar_full + 64, bar_ffn = bar_full + 72, bar_win = bar_full + 80,
                 bar_o = bar_full + 96;
  if (warp < 4 && elect()) {
    mbar_init(bar_full + 8 * (warp ^ 2), 1);
    mbar_init(bar_empty + 8 * warp, 12);
    mbar_init(bar_aux + 8 * warp, warp == 0 ? 64 : warp == 2 ? 32 : 1);
    asm volatile("fence.mbarrier_init.release.cluster;" ::: "memory");
  }
  if (warp >= 4 && warp < 12 && elect()) { mbar_init(bar_o + 16 * (warp - 4), 1); mbar_init(bar_o + 16 * (warp - 4) + 8, (warp & 3) == 1 ? 128 : 1); }
  asm volatile("barrier.cluster.arrive.relaxed.aligned;" ::: "memory");
  if (warp >= 8 && warp < 11 && elect()) asm volatile("prefetch.tensormap [%0];" :: "l"(&tm.x + (warp - 8)) : "memory");
  auto pf_slice = [&](int ks) {
    pf_l2(lane < 16 ? (const char*)x + ((bid * 16 + lane) * 1280 + ks * 128) : (const char*)wqkv + ((bid * 15 + min(lane, 30) - 16) * 128 + ks * 245760));
  };
  if (warp >= 4 && warp < 4 + PF0) {
    if (warp > 4) __nanosleep(300 + (warp - 4) * PF_NS);
    pf_slice(warp == 6 ? 5 : warp - 4);
  }
  const int rank = bid & 1, cl = bid >> 1;
  const int q7 = ((cl - 36) * 37) >> 8;
  const int P = cl < 4 ? 0 : cl < 36 ? (cl - 4) & 7 : cl - 35 - 7 * q7;
  const int g = cl < 4 ? 4 + cl : cl < 36 ? (cl - 4) >> 3 : 4 + q7;
  const int mt = 2 * P + rank, cid = mt * 8 + g;
  const bool ffn1 = g < 3;
  const int fj = ffn1 ? mt * 3 + g : (P * 5 + g - 3) * 2 + rank;
  const int ord = ((g >> 2) ^ P) & 1;
  auto ks_of = [&](int it) { return !ORDX || ord == 0 || it == 0 ? it : it <= 5 ? it + 4 : it - 5; };
  auto load_w = [&](int it, uint32_t a, uint32_t full) {
    tma_3d_mc(a + 16384 + rank * 16384, &tm.w, full, g * 80, it * 64, rank * 2);
    tma_3d_mc(a + (rank ? 40960 : 24576), rank ? &tm.wr : &tm.w, full, g * 80 + rank * 64, it * 64, 1 - rank);
  };
  if (warp == 0 && elect()) {
    mbar_expect_tx(bar_full + 16, SLOT);
    tma_3d(sb + 2 * SLOT, &tm.x, bar_full + 16, 0, mt * 64, 0);
  }
  asm volatile("barrier.cluster.wait.aligned;" ::: "memory");
  if (warp == 0) {
    if (elect()) load_w(0, sb + 2 * SLOT, bar_full + 16);
    asm volatile("bar.arrive 4, 64;" ::: "memory");
  }

  if (warp >= 8) {
    asm volatile("setmaxnreg.dec.sync.aligned.u32 %0;" :: "n"(REG_P));
#define TS_T 0
    if (warp == 8) {
      TS(8);
      bar_sync(4, 64);
      if (elect()) {
        TS(10);
        int fjn = 0;
#pragma unroll 1
        for (int it = 1; it < 17; it++) {
          const int s = (it + 2) & 3;
          const uint32_t full = bar_full + 8 * s, a = sb + s * SLOT;
          if (it >= 13) { mbar_wait(bar_o + 32 + 8 * (it - 13), 0); mbar_wait(bar_o + 96 + 8 * (it - 13), 0); }
          else if (it >= 4) mbar_wait(bar_empty + 8 * s, ((it >> 2) - 1) & 1);
          if (it < 10) {
            const int ks = ks_of(it);
            mbar_expect_tx(full, SLOT);
            tma_3d(a, &tm.x, full, ks * 64, mt * 64, 0);
            load_w(ks, a, full);
            TS(12 + it);
          } else if (it < 13) {
            const int g0 = 3 * (it - 10), g1 = min(g0 + 3, 8);
            mbar_expect_tx(full, (g1 - g0) * 12800);
#pragma unroll 1
            for (int gp = g0 + ((g0 ^ rank) & 1); gp < g1; gp += 2) {
              tma_3d_mc(sb + gp * 15360, &tm.wo, full, 0, gp * 80, g * 2);
              tma_3d_mc(sb + gp * 15360 + 10240, &tm.wor, full, 512 + g * 16, gp * 80, 0);
            }
          }
          if (it == 4) mbar_expect_tx(bar_ffn, ffn1 ? 81920 : 24576);
          const int j1 = ffn1 ? (it >= 13 ? min(2 * it - 21, 10) : min(max(it - F_IT + 1, 0), 4)) : (it >= 13 ? 12 : min(max((it - F_IT + 1) * F_PER, 0), F_MAX));
#pragma unroll 1
          for (; fjn < j1; fjn++) {
            const int j = fjn < 4 ? fjn + 6 : fjn - 4;
            if (ffn1) tma_3d(sb + (j < 6 ? 0 : OFF_W2 - 49152) + j * 8192, j < 5 ? &tm.gate : &tm.up, bar_ffn, fj * 32, (j < 5 ? j : j - 5) * 128, 0);
            else tma_3d(sb + OFF_W2 + fjn * 2048, &tm.down, bar_ffn, fj * 8, fjn * 128, 0);
          }
        }
        TS(11);
      }
#undef TS_T
#define TS_T 0
    } else if (warp >= 12) {
      const int l7 = lane & 7, j = warp - 12, ch = min((P >> 1) * 4 + rank * 2 + (j >> 1), 14);
      const uint32_t sxo = ((g & 3) * 32 + j * 8 + l7) * 128 + (((lane >> 3) ^ l7) * 16);
      const uint32_t swo = ch < 12 ? 16384 + (ch >> 2) * 8192 + lane * 128 + ((((ch & 3) * 2 + (j & 1)) ^ l7) * 16)
                                   : 40960 + (ch - 12) * 2048 + lane * 32 + (((j & 1) ^ (l7 >> 2)) * 16);
      float ps = 0.f, pq = 0.f, pq1 = 0.f, pc = 0.f;
#pragma unroll 1
      for (int it = ord; it < ord + 5; it++) {
        const int sl = (it + 2) & 3;
        mbar_wait(bar_full + 8 * sl, (it >> 2) & 1);
        TS(it);
        const uint32_t a = sb + sl * SLOT;
        const uint4 v0 = ldsm4(a + sxo), v1 = ldsm4((a + sxo) ^ 64), w0 = ldsm4t(a + swo), w1 = ldsm4t(a + swo + (ch < 12 ? 4096 : 1024));
        if (lane + (int)((v0.x & v1.x & w0.x & w1.x) == 0x7fc17fc1u && (v0.x | v1.x) == 0u) < 2) mbar_arrive_cta(bar_empty + 8 * sl, lane);
        const uint32_t vv[8] = {v0.x, v0.y, v0.z, v0.w, v1.x, v1.y, v1.z, v1.w}, ww[8] = {w0.x, w0.y, w0.z, w0.w, w1.x, w1.y, w1.z, w1.w};
#pragma unroll
        for (int i = 0; i < 8; i++) {
          const float d = bf_lo(vv[i]), e = bf_hi(vv[i]);
          ps += d + e; pq = fmaf(d, d, pq); pq1 = fmaf(e, e, pq1); pc += bf_lo(ww[i]) + bf_hi(ww[i]);
        }
      }
      pq += pq1;
      ps += shx(ps, 1); pq += shx(pq, 1); pc += shx(pc, 1);
      ps += shx(ps, 2); pq += shx(pq, 2); pc += shx(pc, 2);
      const int c = lane & 3;
      if (c < 3) sts32f(sb + OFF_PT + (c * 32 + j * 8 + (lane >> 2)) * 4, c == 0 ? ps : c == 1 ? pq : pc);
      asm volatile("bar.arrive 2, 224;" ::: "memory");
#undef TS_T
#define TS_T 32
    } else if (warp < 11) {
      Own* const own = g_own + cid;
      const int l7 = lane & 7, hk = lane >> 4, idx = lane;
      mbar_wait(bar_full + 8 * ((PFX_IT + 2) & 3), 0);
      pf_slice(warp == 9 ? 4 : 8);
      if (warp == 9) pf_slice(9);
      bar_sync(2, 224);
      TS(0);
      const uint32_t tag = __float_as_uint(lds32f(sb + OFF_WR + 324));
      const float s0 = lds32f(sb + OFF_PT + lane * 4 + (warp - 9) * 256), q0 = lds32f(sb + OFF_PT + 128 + lane * 4);
      int guard = SPIN_MAX;
      if (warp == 9) {
        stg_pkt(&own->st1[idx], __float_as_uint(s0), __float_as_uint(q0), tag, 0u);
        TS(1);
        const uint4* sp = &g_own[mt * 8].st1[lane];
        const uint4* hp = &g_own[max(mt - 1, 0) * 8 + hk * 2 + 1].st1[24 + l7];
        uint4 a[5], b[5];
        bool bad;
        do {
          __nanosleep(AUX_NS);
          bad = false;
#pragma unroll
          for (int i = 0; i < 5; i++) {
            const uint4* q = i < 4 ? sp + i * (sizeof(Own) / 16) : hp;
            a[i] = ldg_pkt(q); b[i] = ldg_pkt(q + 4 * sizeof(Own) / 16);
          }
#pragma unroll
          for (int i = 0; i < 5; i++) bad |= a[i].z != tag || b[i].z != tag;
        } while (anyw(bad) && --guard);
#pragma unroll
        for (int i = 0; i < 5; i++) {
          const float m = (__uint_as_float(a[i].x) + __uint_as_float(b[i].x)) * (1.f / 640.f);
          const float rs = rsq(fmaxf(fmaf(-m, m, (__uint_as_float(a[i].y) + __uint_as_float(b[i].y)) * (1.f / 640.f)), 0.f) + 1e-5f);
          ((float*)(smem + OFF_RS))[i < 4 ? 8 + lane + 32 * i + 8 * (i >> 1) : hk * 72 + l7] = rs;
          const uint32_t mh = pack_bf16(-m, -m);
          const float ml = -m - bf_lo(mh);
          if (i < 4) ((uint2*)(smem + OFF_MN))[lane + 32 * i] = make_uint2(mh, pack_bf16(ml, ml));
        }
      } else {
        stg_rlx64(&own->cs[idx], __float_as_uint(s0), tag);
        const uint4* cp = (const uint4*)g_own[hk * 8 + g].cs + (lane & 15);
        uint4 a[4], b[4];
        bool bad;
        do {
          __nanosleep(AUX_NS);
          bad = false;
#pragma unroll
          for (int i = 0; i < 4; i++) { a[i] = ldg_pkt(cp + i * 32 * sizeof(Own) / 16); b[i] = ldg_pkt(cp + (i * 32 + 16) * sizeof(Own) / 16); }
#pragma unroll
          for (int i = 0; i < 4; i++) bad |= a[i].y != tag || a[i].w != tag || b[i].y != tag || b[i].w != tag;
        } while (anyw(bad) && --guard);
#pragma unroll
        for (int i = 0; i < 4; i++)
          if (i < 3 || lane < 24) {
            const float c0 = __uint_as_float(a[i].x) + __uint_as_float(b[i].x), c1 = __uint_as_float(a[i].z) + __uint_as_float(b[i].z);
            const uint32_t hi = pack_bf16(c0, c1), w0 = pack_bf16(c0, c0 - bf_lo(hi)), w1 = pack_bf16(c1, c1 - bf_hi(hi));
            uint4* const d = (uint4*)(smem + OFF_CS) + 2 * (lane + 32 * i);
            d[0] = make_uint4(w0, w0, 0, 0); d[1] = make_uint4(w1, w1, 0, 0);
          }
        asm volatile("fence.proxy.async.shared::cta;" ::: "memory");
      }
      mbar_arrive(bar_aux);
      TS(2);
      const int wq = warp - 9;
      const uint4* const fp = pin(g_own[mt * 8 + wq * 4].cnt);
      const char* const src = (const char*)g_o[mt * 2 + wq];
      bar_sync(5 + wq, 160);
      if (elect()) {
        while (ldg_rlx32(fp) != 32u && --guard > 0) {}
        asm volatile("fence.proxy.async.global;" ::: "memory");
        TS(6);
#pragma unroll 1
        for (int i = 0, sl = 0; i < 7; i++) {
          const uint32_t full = bar_o + wq * 64 + 8 * sl;
          if (i >= 3) mbar_wait(bar_o + wq * 64 + 8 + 8 * i, 0);
          mbar_expect_tx(full, 10240);
          asm volatile("cp.async.bulk.shared::cluster.global.mbarrier::complete_tx::bytes [%0], [%1], 10240, [%2];"
                       :: "r"(sb + OFF_O + sl * 20480 + wq * 10240), "l"(src + (i + (i >= g)) * 10240), "r"(full) : "memory");
          sl = sl == 2 ? 0 : sl + 1;
        }
      }
#undef TS_T
#define TS_T 96
    } else {
#pragma unroll 1
      for (int i = lane; i < 224; i += 32) { const uint32_t f = i < 200 ? SENT : 0u; ((uint4*)(smem + OFF_CS))[i] = make_uint4(f, f, f, f); }
      asm volatile("fence.proxy.async.shared::cta;" ::: "memory");
      mbar_wait(bar_full + 8 * ((RST_IT + 2) & 3), 0);
      TS(4);
      if (elect()) {
        asm volatile("cp.async.bulk.global.shared::cta.bulk_group [%0], [%1], 2688;" :: "l"(g_own + cid), "r"(sb + OFF_CS) : "memory");
        asm volatile("cp.async.bulk.global.shared::cta.bulk_group [%0], [%1], 3584;" :: "l"((char*)(g_own + cid) + 2688), "r"(sb + OFF_CS) : "memory");
        asm volatile("cp.async.bulk.global.shared::cta.bulk_group [%0], [%1], %2;\ncp.async.bulk.commit_group;" :: "l"((uint4*)&g_x + cid * GLOB_PER_CTA), "r"(sb + OFF_CS), "n"(GLOB_PER_CTA * 16) : "memory");
      }
      const uint32_t epoch = ldg_rlx32(g_epoch + cid) + 1;
      uint32_t wv[10];
#pragma unroll
      for (int i = 0; i < 10; i++) wv[i] = __ldg((const uint32_t*)w_r + lane + 32 * i);
      float s = 0.f;
#pragma unroll
      for (int i = 0; i < 10; i++) {
        s += bf_lo(wv[i]) + bf_hi(wv[i]);
        const unsigned u = i < 8 ? lane + 32 * (i - g) : lane + 32 * (i - 7) - g * 8;
        if (i < 8 ? u < 32u : u - 32u < 8u) *(float2*)(smem + OFF_WR + ((u & 3) * 10 + (u >> 2)) * 8) = make_float2(bf_lo(wv[i]), bf_hi(wv[i]));
      }
#pragma unroll
      for (int m = 1; m < 32; m <<= 1) s += shx(s, m);
      *(float2*)(smem + OFF_WR + 320) = make_float2(s, __uint_as_float(epoch * 0x9E3779B8u));
      g_epoch[cid] = epoch;
      TS(3);
      asm volatile("cp.async.bulk.wait_group 0;" ::: "memory");
      TS(5);
      asm volatile("bar.arrive 2, 224;" ::: "memory");
#pragma unroll 1
      for (int i = 0; i < 14; i++) {
        const int m = (i + 2) >> 2, n = m == 0 ? 50 : 120, t = (m == 0 ? i : (i + 2) & 3) * 32 + lane;
        const char* b = (const char*)(m == 0 ? wo : m == 1 ? w_up : m == 2 ? w_down : w_gate);
        if (t < n) pf_l2(b + (bid * n + t) * 128);
        __nanosleep(PFW_NS);
      }
      bar_sync(3, 64);
      const uint4* const kp = g_own[1].cnt;
      const uint4* const cb = &g_x.cand[0][lane >> 2][lane & 3];
      uint4 k = ldg_pkt(kp), c0 = make_uint4(0, 0, 0, 0), c1 = c0; uint2 c2 = make_uint2(0, 0);
      int guard = SPIN_MAX, ws;
      while (true) {
        const uint32_t tk = 2047u - (k.x & 2047u);
        ws = (tk >> 7) * 8 + (tk & 1) * 4 + ((tk >> 5) & 3);
        const uint32_t prev = k.x;
        if (ffn1) { const uint4* q = cb + ws * 192; c0 = ldg_pkt(q); c1 = ldg_pkt(q + 4); c2 = ldg_rlx64(q + 8); }
        if (k.z != 128u) k = ldg_pkt(kp);
        if ((k.z == 128u && k.x == prev && !anyw(c0.x == SENT || c1.x == SENT || c2.x == SENT)) || --guard <= 0) break;
      }
      *(uint4*)(smem + OFF_HN + lane * 16) = c0; *(uint4*)(smem + OFF_HN + 512 + lane * 16) = c1; *(uint2*)(smem + OFF_HN + 1024 + lane * 16) = c2;
      const float rw = __uint_as_float(k.y ^ ((uint32_t)((int32_t)~k.y >> 31) | 0x80000000u));
      *(uint4*)(smem + OFF_WR + 336) = make_uint4(ws, 2047u - (k.x & 2047u), __float_as_uint(rcp(1.f + ex2(-1.4426950408889634f * rw))), 0);
      mbar_arrive(bar_win);
      TS(7);
    }
#undef TS_T
  } else {
#define TS_T 0
    TS(23);
    asm volatile("setmaxnreg.inc.sync.aligned.u32 %0;" :: "n"(REG_C));
    const int wg = warp >> 2, w4 = warp & 3, r = lane >> 2, c = lane & 3;
    float acc[120];
    uint4 xr[5];
    const uint32_t xa = pin(sb + (warp * 16 + (lane & 15)) * 128 + ((lane >> 4) ^ (lane & 7)) * 16);
    const bool first = (mt == 0) && (w4 == 0);
    uint4* const kvd = pin(w4 < 3 ? (uint4*)(smem + OFF_O + warp * 2560) + lane : &g_own[cid].halo[wg][0][lane]);
    const uint4* const kvs = pin(first ? kvd : w4 > 0 ? (const uint4*)(smem + OFF_O + (warp - 1) * 2560) + lane : &g_own[cid - 8].halo[wg][0][lane]);
    uint32_t m0 = 0, m1 = 0;
    const uint32_t d0 = (sb & 0x3FFFF) >> 4;
    const int itx = ord == 0 || g == 0 ? g : g < 5 ? g + 5 : g - 4, ity = (ord ? 4 : 8) + (g >> 2);
    uint32_t rel;
    asm volatile("mapa.shared::cluster.u32 %0, %1, %2;" : "=r"(rel) : "r"(bar_empty), "r"(tid & 1));
    TS(0);
#pragma unroll 1
    for (int it = 0; it < 10; it++) {
      const int s = (it + 2) & 3;
      const uint32_t dl = d0 + s * (SLOT >> 4);
      const uint64_t da = mk64(dl + wg * 512 + (1u << 16), 0x40000040u), db = mk64(dl + 1024 + (512u << 16), 0x40000040u), dr = mk64(dl + 2560 + (128u << 16), 0xC0000010u);
      if (it == 9) {
        mbar_wait(bar_aux, 0);
        TS(3);
        if (c < 2) { m0 = __float_as_uint(lds32f(sb + OFF_MN + (warp * 16 + r) * 8 + c * 4)); m1 = __float_as_uint(lds32f(sb + OFF_MN + (warp * 16 + r) * 8 + c * 4 + 64)); }
        bar_sync(7 + wg, 256);
      }
      mbar_wait(bar_full + 8 * s, (it >> 2) & 1);
      TS(13 + it);
      wgmma_fence();
      wgmma_n48hi_ss(acc, da, dr, it != 0);
      wgmma_n192lo_ss(acc, da, db, it != 0);
      wgmma_commit();
      wgmma_wait<1>();
      if ((tid & 127) < (it == 0 ? 0 : (unsigned)(it - 1 - ord) < 5u ? 2 : 6))
        asm volatile("mbarrier.arrive.shared::cluster.b64 _, [%0];" :: "r"(rel + 8 * ((it + 1) & 3)) : "memory");
#pragma unroll
      for (int kk = 1; kk < 4; kk++) {
        wgmma_n48hi_ss(acc, da + kk * 2, dr + kk * 32, 1);
        wgmma_n192lo_ss(acc, da + kk * 2, db + kk * 128, 1);
      }
      wgmma_commit();
      if (it == 8 && wg != LEAD) asm volatile("bar.arrive %0, 256;" :: "r"(7 + LEAD) : "memory");
      if (it == itx) {
#pragma unroll
        for (int j = 0; j < 4; j++) xr[j] = ldsm4((xa + s * SLOT) ^ (j * 32));
      }
      if (it == ity) xr[4] = ldsm4((xa + s * SLOT) ^ ((g & 3) * 32));
    }
    {
      if (wg == LEAD) asm volatile("bar.arrive %0, 256;" :: "r"(8 - LEAD) : "memory");
      const uint64_t dc = make_desc(sb + OFF_CS, 0, 128, 0);
      wgmma_fence();
      wgmma_n48hi_rk(acc, m0, m1, 0u, 0u, dc + 192, 1);
      wgmma_n192lo_rk(acc, m0, m1, 0u, 0u, dc, 1);
      wgmma_commit();
    }
    const uint32_t stb = sb + OFF_RS + (wg * 72 + 16 * w4) * 4;
    const float rlo = lds32f(stb + (8 + r) * 4), rhi = lds32f(stb + (16 + r) * 4);
    wgmma_wait<0>();
#pragma unroll
    for (int i = 0; i < 120; i++) asm volatile("" : "+f"(acc[i]) :: "memory");
    if (wg != LEAD) asm volatile("bar.arrive 9, 256;" ::: "memory");
    TS(2);
    uint32_t Qlo[10], Qhi[10], Klo[10], Khi[10], Vlo[10], Vhi[10];
#pragma unroll
    for (int t = 0; t < 10; t++) {
      const int k = KT(t), v = VT(t);
      Khi[t] = pack_bf16(acc[4 * k + 2], acc[4 * k + 3]);
      Vhi[t] = pack_bf16(acc[4 * v + 2] * rhi, acc[4 * v + 3] * rhi);
    }
    st_pkt(kvd, Khi[0], Khi[1], Khi[3], Khi[4]);
    st_pkt(kvd + 32, Khi[5], Khi[6], Khi[8], Khi[9]);
    st_pkt(kvd + 64, Khi[2], Khi[7], Vhi[0], Vhi[1]);
    st_pkt(kvd + 96, Vhi[2], Vhi[3], Vhi[4], Vhi[5]);
    st_pkt(kvd + 128, Vhi[6], Vhi[7], Vhi[8], Vhi[9]);
    mbar_arrive(bar_o + wg * 64 + 24);
#pragma unroll
    for (int t = 0; t < 10; t++) {
      const int q = QT(t), k = KT(t), v = VT(t);
      Vhi[t] = movm(Vhi[t]);
      Klo[t] = pack_bf16(acc[4 * k], acc[4 * k + 1]);
      Vlo[t] = movm(pack_bf16(acc[4 * v] * rlo, acc[4 * v + 1] * rlo));
      Qlo[t] = pack_bf16(acc[4 * q], acc[4 * q + 1]);
      Qhi[t] = pack_bf16(acc[4 * q + 2], acc[4 * q + 3]);
    }
    const bool in0 = 2 * c <= r, in1 = 2 * c + 1 <= r;
    const uint32_t mL = (in0 ? 0xffffu : 0u) | (in1 ? 0xffff0000u : 0u);
    const float qs = 0.22360679774997896f * 1.4426950408889634f;
    const uint32_t kb0 = stb + (2 * c + (in0 ? 8 : 0)) * 4, kb1 = stb + (2 * c + 1 + (in1 ? 8 : 0)) * 4;
    const float scl0 = lds32f(kb0) * rlo * qs, scl1 = lds32f(kb1) * rlo * qs;
    const float sch0 = lds32f(kb0 + 32) * rhi * qs, sch1 = lds32f(kb1 + 32) * rhi * qs;
    const float bias0 = (first && !in0) ? -INFINITY : 0.f, bias1 = (first && !in1) ? -INFINITY : 0.f;
    const int slot = mt * 8 + warp;
    int guard = SPIN_MAX;
    uint4 pv[5];
    mbar_wait(bar_o + wg * 64 + 24, 0);
    do {
#pragma unroll
      for (int j = 0; j < 5; j++) pv[j] = ld_pkt(kvs + 32 * j);
    } while (anyw(pv[0].x == SENT || pv[1].x == SENT || pv[2].x == SENT || pv[3].x == SENT || pv[4].x == SENT) && --guard);
    if (wg == LEAD) bar_sync(9, 256);
    TS(4);
    const uint32_t Kp[10] = {pv[0].x, pv[0].y, pv[2].x, pv[0].z, pv[0].w, pv[1].x, pv[1].y, pv[2].y, pv[1].z, pv[1].w};
    const uint32_t Vp[10] = {movm(pv[2].z), movm(pv[2].w), movm(pv[3].x), movm(pv[3].y), movm(pv[3].z), movm(pv[3].w), movm(pv[4].x), movm(pv[4].y), movm(pv[4].z), movm(pv[4].w)};
    const bool cA = c < 2, nA = r < 4;
    const uint32_t ONES = 0x3f803f80u;
    uint32_t of[20];
#pragma unroll
    for (int hp = 0; hp < 2; hp++) {
      float o[6][4];
#pragma unroll
      for (int hh = 0; hh < 2; hh++) {
        const int ta = 5 * hp + 3 * hh, ts = 5 * hp + 2;
        const bool mine = hh == 0 ? cA : !cA;
        const uint32_t e0 = mine ? Qlo[ts] : 0u, e1 = mine ? Qhi[ts] : 0u;
        float sp[4], sl[4], sh[4];
        mma_k24(sp, Qlo[ta], Qhi[ta], Qlo[ta + 1], Qhi[ta + 1], Kp[ta], Kp[ta + 1], e0, e1, Kp[ts]);
        mma_k24(sl, Qlo[ta], Qhi[ta], Qlo[ta + 1], Qhi[ta + 1], Klo[ta], Klo[ta + 1], e0, e1, Klo[ts]);
        mma_k24(sh, Qlo[ta], Qhi[ta], Qlo[ta + 1], Qhi[ta + 1], Khi[ta], Khi[ta + 1], e0, e1, Khi[ts]);
        const float tl0 = fmaf(in0 ? sl[0] : sp[0], scl0, bias0), tl1 = fmaf(in1 ? sl[1] : sp[1], scl1, bias1);
        const float th0 = (in0 ? sh[2] : sl[2]) * sch0, th1 = (in1 ? sh[3] : sl[3]) * sch1;
        float ml = fmaxf(tl0, tl1), mh = fmaxf(th0, th1);
        ml = fmaxf(ml, shx(ml, 1)); mh = fmaxf(mh, shx(mh, 1));
        ml = fmaxf(ml, shx(ml, 2)); mh = fmaxf(mh, shx(mh, 2));
        const uint32_t Pl = pack_bf16(ex2(tl0 - ml), ex2(tl1 - ml)), Ph = pack_bf16(ex2(th0 - mh), ex2(th1 - mh));
        const uint32_t a0 = Pl & mL, a1 = Ph & ~mL, a3 = Ph & mL, ap = Pl & ~mL;
        const bool vm = hh == 0 ? nA : !nA;
        mma_k24(o[3 * hh], a0, a1, 0u, a3, Vlo[ta], Vhi[ta], ap, 0u, Vp[ta]);
        mma_k24(o[3 * hh + 1], a0, a1, 0u, a3, Vlo[ta + 1], Vhi[ta + 1], ap, 0u, Vp[ta + 1]);
        mma_k24(o[3 * hh + 2], a0, a1, 0u, a3, vm ? Vlo[ts] : ONES, vm ? Vhi[ts] : ONES, ap, 0u, vm ? Vp[ts] : ONES);
      }
      const float il = rcp(cA ? o[5][0] : o[2][0]), ih = rcp(cA ? o[5][2] : o[2][2]);
      const float jl = shx(il, 2), jh = shx(ih, 2);
      const float al = cA ? jl : il, ah = cA ? jh : ih, bl = cA ? il : jl, bh = cA ? ih : jh;
      const int t0 = 5 * hp;
      of[2 * t0]     = pack_bf16(o[0][0] * al, o[0][1] * al); of[2 * t0 + 1] = pack_bf16(o[0][2] * ah, o[0][3] * ah);
      of[2 * t0 + 2] = pack_bf16(o[1][0] * al, o[1][1] * al); of[2 * t0 + 3] = pack_bf16(o[1][2] * ah, o[1][3] * ah);
      of[2 * t0 + 4] = pack_bf16((cA ? o[2][0] : o[5][0]) * jl, (cA ? o[2][1] : o[5][1]) * jl);
      of[2 * t0 + 5] = pack_bf16((cA ? o[2][2] : o[5][2]) * jh, (cA ? o[2][3] : o[5][3]) * jh);
      of[2 * t0 + 6] = pack_bf16(o[3][0] * bl, o[3][1] * bl); of[2 * t0 + 7] = pack_bf16(o[3][2] * bh, o[3][3] * bh);
      of[2 * t0 + 8] = pack_bf16(o[4][0] * bl, o[4][1] * bl); of[2 * t0 + 9] = pack_bf16(o[4][2] * bh, o[4][3] * bh);
    }
    {
      const uint32_t os = sb + OFF_O + 20480 + warp * 2560, oa = os + ((lane >> 3) & 1) * 1280 + (lane >> 4) * 128 + (lane & 7) * 16;
#pragma unroll
      for (int s = 0; s < 5; s++) stsm4(oa + s * 256, of[4 * s], of[4 * s + 1], of[4 * s + 2], of[4 * s + 3]);
      asm volatile("fence.proxy.async.shared::cta;" ::: "memory");
      __syncwarp();
      if (elect()) {
        asm volatile("cp.async.bulk.global.shared::cta.bulk_group [%0], [%1], 2560;\ncp.async.bulk.commit_group;" :: "l"(&g_o[mt * 2 + wg][g][w4 * 160]), "r"(os) : "memory");
      }
    }
    TS(5);
    float h[40];
#pragma unroll
    for (int s = 0; s < 5; s++) {
      const uint4 v = xr[s];
      h[8 * s] = bf_lo(v.x); h[8 * s + 1] = bf_hi(v.x); h[8 * s + 2] = bf_lo(v.y); h[8 * s + 3] = bf_hi(v.y);
      h[8 * s + 4] = bf_lo(v.z); h[8 * s + 5] = bf_hi(v.z); h[8 * s + 6] = bf_lo(v.w); h[8 * s + 7] = bf_hi(v.w);
    }
    mbar_wait(bar_full, 0); mbar_wait(bar_full + 8, 0); mbar_wait(bar_full + 16, 1);
    if (elect()) {
      asm volatile("cp.async.bulk.wait_group 0;" ::: "memory");
      asm volatile("red.relaxed.gpu.global.add.u32 [%0], 1;" :: "l"(g_own[mt * 8 + wg * 4].cnt) : "memory");
    }
    asm volatile("bar.arrive %0, 160;" :: "r"(5 + wg) : "memory");
    bar_sync(1, 256);
    const uint64_t dwo = make_desc(sb, 5120, 512, 2);
    wgmma_fence();
#pragma unroll
    for (int s = 0; s < 5; s++) wgmma_n80_rs(h, of[4 * s], of[4 * s + 1], of[4 * s + 2], of[4 * s + 3], dwo + g * 960 + s * 64, 1);
    wgmma_commit();
    TS(6);
#pragma unroll 1
    for (int i = 0, sl = 0; i < 7; i++) {
      mbar_wait(bar_o + wg * 64 + 8 * sl, i >= 3 && i < 6);
      if (i == 0) TS(1);
      const uint64_t da = make_desc(sb + OFF_O + sl * 20480 + wg * 10240, 128, 1280, 0), db = dwo + (i + (i >= g)) * 960;
      wgmma_fence();
#pragma unroll
      for (int s = 0; s < 5; s++) wgmma_n80_ss(h, da + s * 16, db + s * 64, 1);
      wgmma_commit();
      wgmma_wait<1>();
      if ((tid & 127) == 0 && i > 0 && i < 5) mbar_arrive(bar_o + wg * 64 + 24 + 8 * i);
      sl = sl == 2 ? 0 : sl + 1;
    }
    const bool odd = c & 1;
    float wr[20];
#pragma unroll
    for (int j = 0; j < 5; j++) {
      const uint4 v = lds128(sb + OFF_WR + c * 80 + j * 16);
      wr[4 * j] = __uint_as_float(v.x); wr[4 * j + 1] = __uint_as_float(v.y); wr[4 * j + 2] = __uint_as_float(v.z); wr[4 * j + 3] = __uint_as_float(v.w);
    }
    const float wsum = lds32f(sb + OFF_WR + 320);
    uint4* const sp = pin(&g_own[slot].st2[r + (odd ? 8 : 0)]);
    uint4* const cdp = pin(&g_x.cand[slot][g][0]);
    const int tok0 = mt * 128 + 32 * w4 + wg;
    wgmma_wait<0>();
#pragma unroll
    for (int i = 0; i < 40; i++) asm volatile("" : "+f"(h[i]) :: "memory");
    TS(7);
    float mean, rstd, rr;
    {
      float l1 = 0.f, l2 = 0.f, l3 = 0.f, h1 = 0.f, h2 = 0.f, h3 = 0.f;
#pragma unroll
      for (int j = 0; j < 10; j++) {
        l1 += h[4 * j] + h[4 * j + 1]; h1 += h[4 * j + 2] + h[4 * j + 3];
        l2 = fmaf(h[4 * j], h[4 * j], l2); l2 = fmaf(h[4 * j + 1], h[4 * j + 1], l2);
        h2 = fmaf(h[4 * j + 2], h[4 * j + 2], h2); h2 = fmaf(h[4 * j + 3], h[4 * j + 3], h2);
        l3 = fmaf(h[4 * j], wr[2 * j], l3); l3 = fmaf(h[4 * j + 1], wr[2 * j + 1], l3);
        h3 = fmaf(h[4 * j + 2], wr[2 * j], h3); h3 = fmaf(h[4 * j + 3], wr[2 * j + 1], h3);
      }
      float s1 = (odd ? h1 : l1) + shx(odd ? l1 : h1, 1), s2 = (odd ? h2 : l2) + shx(odd ? l2 : h2, 1), s3 = (odd ? h3 : l3) + shx(odd ? l3 : h3, 1);
      s1 += shx(s1, 2); s2 += shx(s2, 2); s3 += shx(s3, 2);
      if (cA) asm volatile("red.relaxed.gpu.global.add.v4.f32 [%0], {%1, %2, %3, %4};" :: "l"(sp), "f"(s1), "f"(s2), "f"(s3), "f"(1.f) : "memory");
      uint4 p0;
      do { p0 = ldg_pkt(sp); } while (anyw(p0.w != 0x41000000u) && --guard > 0);
      mean = __uint_as_float(p0.x) * (1.f / 640.f);
      rstd = rsq(fmaxf(fmaf(-mean, mean, __uint_as_float(p0.y) * (1.f / 640.f)), 0.f) + 1e-5f);
      rr = fmaf(-mean, wsum, __uint_as_float(p0.z)) * rstd;
    }
    TS(8);
    const uint32_t kk = ord_key(rr), kmax = __reduce_max_sync(0xffffffffu, kk);
    const int L = __ffs(__ballot_sync(0xffffffffu, kk == kmax)) - 1;
    const int crow = (L >> 2) + 8 * (L & 1);
    if (warp == g) {
      if (elect()) {
        asm volatile("red.relaxed.gpu.global.max.u64 [%0], %1;" :: "l"(g_own[1].cnt), "l"(((uint64_t)kmax << 32) | (uint32_t)(2047 - tok0 - 2 * crow)) : "memory");
        asm volatile("red.relaxed.gpu.global.add.u32 [%0], 1;" :: "l"(&g_own[1].cnt[0].z) : "memory");
      }
      asm volatile("bar.arrive 3, 64;" ::: "memory");
    }
    const uint32_t stg = sb + OFF_O + warp * 2560;
    uint4 held;
    {
      const float om = shx(mean, 1), os = shx(rstd, 1);
      const float rl = odd ? os : rstd, rh = odd ? rstd : os;
      const float bl = -(odd ? om : mean) * rl, bh = -(odd ? mean : om) * rh, al = 1.f + rl, ah = 1.f + rh;
      if ((L >> 2) == r) {
        const bool chi = L & 1;
        const float rc = chi ? rh : rl, bc = chi ? bh : bl;
        uint32_t n[10];
#pragma unroll
        for (int j = 0; j < 10; j++) n[j] = pack_bf16(fmaf(chi ? h[4 * j + 2] : h[4 * j], rc, bc), fmaf(chi ? h[4 * j + 3] : h[4 * j + 1], rc, bc));
        uint4* d = cdp + c;
        stg_pkt(d, n[0], n[1], n[2], n[3]); stg_pkt(d + 4, n[4], n[5], n[6], n[7]); stg_rlx64(d + 8, n[8], n[9]);
      }
      __syncwarp();
      const uint32_t fa = stg + (lane & 15) * 160 + (lane >> 4) * 16;
#pragma unroll
      for (int s = 0; s < 5; s++)
        stsm4(fa + s * 32, pack_bf16(fmaf(h[8 * s], al, bl), fmaf(h[8 * s + 1], al, bl)), pack_bf16(fmaf(h[8 * s + 2], ah, bh), fmaf(h[8 * s + 3], ah, bh)),
              pack_bf16(fmaf(h[8 * s + 4], al, bl), fmaf(h[8 * s + 5], al, bl)), pack_bf16(fmaf(h[8 * s + 6], ah, bh), fmaf(h[8 * s + 7], ah, bh)));
      __syncwarp();
      held = lds128(stg + crow * 160 + min(lane, 9) * 16);
      if (lane < 10) stg_pkt(cdp + 12 + lane, held.x, held.y, held.z, held.w);
    }
    TS(9);
    mbar_wait(bar_ffn, 0);
    const uint32_t red = sb + OFF_RED;
    if (ffn1) {
      uint4 w1[4][5];
      {
        const int k = (lane & 7) + (lane >> 4) * 8;
        const uint32_t a1 = sb + k * 64, sw = ((lane >> 3) & 1) ^ ((lane >> 1) & 3);
#pragma unroll
        for (int s = 0; s < 5; s++)
#pragma unroll
          for (int u = 0; u < 4; u++)
            w1[u][s] = ldsm4t(a1 + (s < 4 ? warp * 4096 + s * 1024 : 32768 + warp * 1024) + (u >> 1) * (40960 + (s == 4 || warp >= 2 ? OFF_W2 - 49152 : 0)) + ((sw ^ (2 * (u & 1))) * 16));
      }
      uint32_t* const ap = pin(g_x.act + fj * 16 + (lane >> 1));
      mbar_wait(bar_win, 0);
      const uint32_t hp = sb + OFF_HN + (warp * 4 + c) * 16;
      const uint4 c0 = lds128(hp), c1 = lds128(hp + 512), c2 = lds128(hp + 1024);
      TS(10);
      float a[4][4];
#pragma unroll
      for (int u = 0; u < 4; u++) {
        a[u][0] = a[u][1] = a[u][2] = a[u][3] = 0.f;
        mma_acc(a[u], w1[u][0], c0.x, c0.y); mma_acc(a[u], w1[u][1], c0.z, c0.w); mma_acc(a[u], w1[u][2], c1.x, c1.y);
        mma_acc(a[u], w1[u][3], c1.z, c1.w); mma_acc(a[u], w1[u][4], c2.x, c2.y);
      }
      asm volatile("st.shared.v2.f32 [%0], {%1, %2};" :: "r"(red + (warp * 32 + c * 8 + r) * 8),
                   "f"(cA ? (odd ? a[0][2] : a[0][0]) : (odd ? a[1][2] : a[1][0])), "f"(cA ? (odd ? a[2][2] : a[2][0]) : (odd ? a[3][2] : a[3][0])) : "memory");
      bar_sync(1, 256);
      if (warp == 0) {
        float2 t[8];
#pragma unroll
        for (int i = 0; i < 8; i++) t[i] = lds64f(red + (i * 32 + lane) * 8);
        const float s = ((t[0].x + t[1].x) + (t[2].x + t[3].x)) + ((t[4].x + t[5].x) + (t[6].x + t[7].x));
        const float u = ((t[0].y + t[1].y) + (t[2].y + t[3].y)) + ((t[4].y + t[5].y) + (t[6].y + t[7].y));
        const float av = s * u * rcp(1.f + ex2(-1.4426950408889634f * s));
        const float an = shx(av, 1);
        if (!odd) stg_rlx32(ap, pack_bf16(av, an));
      }
      bar_sync(1, 256);
      TS(11);
    }
    if (OUT_LATE) mbar_wait(bar_win, 0);
    char* const ob2 = (char*)(out + tok0 * 640 + g * 64);
    const int remo = 896 - 96 * g;
#pragma unroll
    for (int s = 0; s < 5; s++) {
      const int row = s < 4 ? 4 * s + (lane >> 3) : lane >> 1, pc = s < 4 ? lane & 7 : 8 + (lane & 1);
      const uint4 v = lds128(stg + row * 160 + pc * 16);
      if (row != crow) stg128(ob2 + row * 2560 + pc * 16 + (s < 4 ? 0 : remo), v);
    }
    mbar_wait(bar_win, 0);
    const uint4 win = lds128(sb + OFF_WR + 336);
    if (win.x != slot && lane < 10) stg128(ob2 + crow * 2560 + lane * 16 + (lane < 8 ? 0 : remo), held);
    if (!ffn1) {
      TS(10);
      uint4 w2[6];
      const uint32_t a2 = sb + OFF_W2 + (warp * 192 + 8 * (((lane >> 3) & 1) * 4 + ((lane & 7) >> 1)) + 2 * (lane >> 4) + (lane & 1)) * 16;
#pragma unroll
      for (int s = 0; s < 6; s++) w2[s] = ldsm4t(a2 + (s >> 1) * 1024 + (s & 1) * 64);
      const uint4* p = (const uint4*)(g_x.act + warp * 96) + (r & 1) * 4 + c;
      const uint32_t* pb = (const uint32_t*)&g_x.cand[win.x][fj < 64 ? fj >> 3 : (fj - 64) >> 1][fj < 64 ? 12 + (fj & 7) : 20 + (fj & 1)] + c;
      uint32_t* const op = pin((uint32_t*)(out + win.y * 640 + fj * 8) + c);
      uint4 c0, c1, c2; uint32_t bw;
      if (ACT_NS) __nanosleep(ACT_NS);
      do {
        c0 = ldg_pkt(p); c1 = ldg_pkt(p + 8); c2 = ldg_pkt(p + 16); bw = ldg_rlx32(pb);
      } while (anyw(max(max(max(max(c0.x, c0.y), max(c0.z, c0.w)), max(max(c1.x, c1.y), max(c1.z, c1.w))), max(max(max(c2.x, c2.y), max(c2.z, c2.w)), bw)) == SENT) && --guard > 0);
      TS(11);
      float a[4] = {0.f, 0.f, 0.f, 0.f}, b[4] = {0.f, 0.f, 0.f, 0.f}, d[4] = {0.f, 0.f, 0.f, 0.f};
      mma_acc(a, w2[0], c0.x, c0.y); mma_acc(b, w2[2], c1.x, c1.y); mma_acc(d, w2[4], c2.x, c2.y);
      mma_acc(a, w2[1], c0.z, c0.w); mma_acc(b, w2[3], c1.z, c1.w); mma_acc(d, w2[5], c2.z, c2.w);
      if (c == 0) sts32f(red + (warp * 8 + r) * 4, ((a[0] + a[3]) + (b[0] + b[3])) + (d[0] + d[3]));
      bar_sync(1, 256);
      if (tid < 4) {
        float2 t[8];
#pragma unroll
        for (int i = 0; i < 8; i++) t[i] = lds64f(red + (i * 4 + tid) * 8);
        const float y0 = ((t[0].x + t[1].x) + (t[2].x + t[3].x)) + ((t[4].x + t[5].x) + (t[6].x + t[7].x));
        const float y1 = ((t[0].y + t[1].y) + (t[2].y + t[3].y)) + ((t[4].y + t[5].y) + (t[6].y + t[7].y));
        const float sg = __uint_as_float(win.z);
        *op = pack_bf16(fmaf(y0, sg, bf_lo(bw)), fmaf(y1, sg, bf_hi(bw)));
      }
    }
    TS(12);
#undef TS_T
  }
}

typedef CUresult (*EncodeFn)(CUtensorMap*, CUtensorMapDataType, cuuint32_t, void*, const cuuint64_t*, const cuuint64_t*, const cuuint32_t*,
                             const cuuint32_t*, CUtensorMapInterleave, CUtensorMapSwizzle, CUtensorMapL2promotion, CUtensorMapFloatOOBfill);

void make_map(EncodeFn enc, CUtensorMap* m, const void* base, const cuuint64_t* dims, const cuuint64_t* strides, const cuuint32_t* box,
              CUtensorMapSwizzle swz) {
  const cuuint32_t es[3] = {1, 1, 1};
  enc(m, CU_TENSOR_MAP_DATA_TYPE_BFLOAT16, 3, (void*)base, dims, strides, box, es, CU_TENSOR_MAP_INTERLEAVE_NONE, swz,
      CU_TENSOR_MAP_L2_PROMOTION_L2_128B, CU_TENSOR_MAP_FLOAT_OOB_FILL_NONE);
}

}

extern "C" void kernel_launch(void* const* d_in, const int* in_sizes, int n_in, void* d_out, int out_size) {
  const __nv_bfloat16* x = (const __nv_bfloat16*)d_in[0];
  const __nv_bfloat16* wqkv = (const __nv_bfloat16*)d_in[1];
  const __nv_bfloat16* wo = (const __nv_bfloat16*)d_in[2];
  void* fn = nullptr;
  cudaDriverEntryPointQueryResult st;
  cudaGetDriverEntryPoint("cuTensorMapEncodeTiled", &fn, cudaEnableDefault, &st);
  EncodeFn enc = (EncodeFn)fn;
  void* scp = nullptr;
  cudaGetSymbolAddress(&scp, g_scratch);
  Maps tm;
  { const cuuint64_t d[3] = {640, 1024, 2}, s[2] = {2560, 1280}; const cuuint32_t b[3] = {64, 64, 2}; make_map(enc, &tm.x, x, d, s, b, CU_TENSOR_MAP_SWIZZLE_128B); }
  { const cuuint64_t d[3] = {640, 640, 3}, s[2] = {3840, 1280}; const cuuint32_t b[3] = {64, 64, 1}; make_map(enc, &tm.w, wqkv, d, s, b, CU_TENSOR_MAP_SWIZZLE_128B); }
  { const cuuint64_t d[3] = {640, 640, 3}, s[2] = {3840, 1280}; const cuuint32_t b[3] = {16, 64, 3}; make_map(enc, &tm.wr, wqkv, d, s, b, CU_TENSOR_MAP_SWIZZLE_32B); }
  { const cuuint64_t d[3] = {32, 640, 20}, s[2] = {1280, 64}; const cuuint32_t b[3] = {32, 80, 2}; make_map(enc, &tm.wo, wo, d, s, b, CU_TENSOR_MAP_SWIZZLE_64B); }
  { const cuuint64_t d[3] = {640, 640, 1}, s[2] = {1280, 819200}; const cuuint32_t b[3] = {16, 80, 1}; make_map(enc, &tm.wor, wo, d, s, b, CU_TENSOR_MAP_SWIZZLE_64B); }
  { const cuuint64_t d[3] = {1536, 640, 1}, s[2] = {3072, 1966080}; const cuuint32_t b[3] = {32, 128, 1};
    make_map(enc, &tm.gate, d_in[5], d, s, b, CU_TENSOR_MAP_SWIZZLE_64B); make_map(enc, &tm.up, d_in[6], d, s, b, CU_TENSOR_MAP_SWIZZLE_64B); }
  { const cuuint64_t d[3] = {640, 1536, 1}, s[2] = {1280, 1966080}; const cuuint32_t b[3] = {8, 128, 1}; make_map(enc, &tm.down, d_in[7], d, s, b, CU_TENSOR_MAP_SWIZZLE_NONE); }
  cudaFuncSetAttribute(fused_kernel, cudaFuncAttributeMaxDynamicSharedMemorySize, SMEM_BYTES);
  fused_kernel<<<128, 512, SMEM_BYTES, cudaStreamPerThread>>>(x, wqkv, wo, (const __nv_bfloat16*)d_in[4], (const __nv_bfloat16*)d_in[5],
                                                              (const __nv_bfloat16*)d_in[6], (const __nv_bfloat16*)d_in[7], (__nv_bfloat16*)d_out, (Scratch*)scp, tm);
}
```

```cpp
#include <cuda_runtime.h>
#include <cuda_bf16.h>
#include <cuda.h>
#include <stdint.h>

#define PF0 1
#define PF_CLK 300
#define SKEW_IT 20
#define PFX_IT 0
#define PFW_NS 100
#define ACT_NS 0
#define F_IT 6
#define F_MAX 12
#define F_PER 2
#define OUT_LATE 1
#define REG_P 72
#define REG_C 184
#define AUX_NS 50
#define LEAD 1
#define RST_IT 0
#define ORDX 1

namespace {

constexpr int SLOT    = 47104;
constexpr int OFF_O   = 122880;
constexpr int OFF_W2  = 4 * SLOT;
constexpr int OFF_CS  = OFF_W2 + 32768;
constexpr int OFF_RS  = OFF_CS + 3840;
constexpr int OFF_MN  = OFF_RS + 576;
constexpr int OFF_WR  = OFF_MN + 1024;
constexpr int OFF_RED = OFF_CS;
constexpr int OFF_HN  = OFF_CS + 2048;
constexpr int OFF_PT  = OFF_WR + 352;
constexpr int OFF_BAR = OFF_PT + 768;
constexpr int SMEM_BYTES = OFF_BAR + 240 + 384;
constexpr uint32_t SENT = 0xFFFFFFFFu;
constexpr int SPIN_MAX = 1 << 20;

struct Glob {
  uint4 cand[128][8][24];
  uint32_t act[768];
  uint32_t pad[256];
};
constexpr int GLOB_PER_CTA = sizeof(Glob) / 16 / 128;
static_assert(GLOB_PER_CTA * 128 * 16 == sizeof(Glob), "glob size");
struct Own {
  uint4 halo[2][5][32];
  uint4 st1[32];
  uint2 cs[32];
  uint4 st2[16];
  uint4 cnt[8];
};
struct Scratch {
  Glob x;
  Own own[128];
  uint4 o[32][8][640];
  uint32_t epoch[128];
};
__device__ __align__(128) Scratch g_scratch;
#define g_x (sc->x)
#define g_own (sc->own)
#define g_o (sc->o)
#define g_epoch (sc->epoch)
#define TS(i)

__device__ __forceinline__ void mbar_init(uint32_t bar, uint32_t cnt) { asm volatile("mbarrier.init.shared::cta.b64 [%0], %1;" :: "r"(bar), "r"(cnt) : "memory"); }
__device__ __forceinline__ void mbar_expect_tx(uint32_t bar, uint32_t bytes) { asm volatile("mbarrier.arrive.expect_tx.shared::cta.b64 _, [%0], %1;" :: "r"(bar), "r"(bytes) : "memory"); }
__device__ __forceinline__ void mbar_arrive(uint32_t bar) { asm volatile("mbarrier.arrive.shared::cta.b64 _, [%0];" :: "r"(bar) : "memory"); }
__device__ __forceinline__ void mbar_arrive_cta(uint32_t bar, uint32_t cta) {
  asm volatile("{\n.reg .b32 ra;\nmapa.shared::cluster.u32 ra, %0, %1;\nmbarrier.arrive.shared::cluster.b64 _, [ra];\n}\n" :: "r"(bar), "r"(cta) : "memory");
}
__device__ __forceinline__ void mbar_wait(uint32_t bar, uint32_t parity) {
  asm volatile("{\n.reg .pred p;\n.reg .u32 n;\nmov.u32 n, 0;\nW:\nmbarrier.try_wait.parity.shared::cta.b64 p, [%0], %1;\n@p bra.uni D;\n"
               "add.u32 n, n, 1;\nsetp.lt.u32 p, n, %2;\n@p bra.uni W;\nD:\n}\n" :: "r"(bar), "r"(parity), "n"(SPIN_MAX) : "memory");
}
__device__ __forceinline__ void tma_3d(uint32_t dst, const void* tm, uint32_t bar, int c0, int c1, int c2) {
  asm volatile("cp.async.bulk.tensor.3d.shared::cluster.global.mbarrier::complete_tx::bytes [%0], [%1, {%3, %4, %5}], [%2];" :: "r"(dst), "l"(tm), "r"(bar), "r"(c0), "r"(c1), "r"(c2) : "memory");
}
__device__ __forceinline__ void tma_3d_mc(uint32_t dst, const void* tm, uint32_t bar, int c0, int c1, int c2) {
  asm volatile("cp.async.bulk.tensor.3d.shared::cluster.global.mbarrier::complete_tx::bytes.multicast::cluster [%0], [%1, {%3, %4, %5}], [%2], %6;" :: "r"(dst), "l"(tm), "r"(bar), "r"(c0), "r"(c1), "r"(c2), "h"((uint16_t)3) : "memory");
}
__device__ __forceinline__ void wgmma_fence() { asm volatile("wgmma.fence.sync.aligned;" ::: "memory"); }
__device__ __forceinline__ void wgmma_commit() { asm volatile("wgmma.commit_group.sync.aligned;" ::: "memory"); }
template <int N> __device__ __forceinline__ void wgmma_wait() { asm volatile("wgmma.wait_group.sync.aligned %0;" :: "n"(N) : "memory"); }
__device__ __forceinline__ uint64_t make_desc(uint32_t addr, uint32_t lbo, uint32_t sbo, uint32_t swz) {
  return (uint64_t)(((addr & 0x3FFFF) >> 4) | ((lbo >> 4) << 16)) | ((uint64_t)((sbo >> 4) | (swz << 30)) << 32);
}
__device__ __forceinline__ void bar_sync(int id, int n) { asm volatile("bar.sync %0, %1;" :: "r"(id), "r"(n) : "memory"); }
__device__ __forceinline__ uint4 ld_pkt(const void* p) {
  uint4 v;
  asm volatile("{\n.reg .b128 t;\n.reg .b64 lo, hi;\nld.relaxed.gpu.b128 t, [%4];\nmov.b128 {lo, hi}, t;\nmov.b64 {%0, %1}, lo;\nmov.b64 {%2, %3}, hi;\n}\n"
               : "=r"(v.x), "=r"(v.y), "=r"(v.z), "=r"(v.w) : "l"(p) : "memory");
  return v;
}
__device__ __forceinline__ void st_pkt(void* p, uint32_t a, uint32_t b, uint32_t c, uint32_t d) {
  asm volatile("{\n.reg .b128 t;\n.reg .b64 lo, hi;\nmov.b64 lo, {%1, %2};\nmov.b64 hi, {%3, %4};\nmov.b128 t, {lo, hi};\nst.relaxed.gpu.b128 [%0], t;\n}\n"
               :: "l"(p), "r"(a), "r"(b), "r"(c), "r"(d) : "memory");
}
__device__ __forceinline__ uint4 ldg_pkt(const void* p) {
  uint4 v;
  asm volatile("{\n.reg .b128 t;\n.reg .b64 lo, hi;\nld.relaxed.gpu.global.b128 t, [%4];\nmov.b128 {lo, hi}, t;\nmov.b64 {%0, %1}, lo;\nmov.b64 {%2, %3}, hi;\n}\n"
               : "=r"(v.x), "=r"(v.y), "=r"(v.z), "=r"(v.w) : "l"(p) : "memory");
  return v;
}
__device__ __forceinline__ void stg_pkt(void* p, uint32_t a, uint32_t b, uint32_t c, uint32_t d) {
  asm volatile("{\n.reg .b128 t;\n.reg .b64 lo, hi;\nmov.b64 lo, {%1, %2};\nmov.b64 hi, {%3, %4};\nmov.b128 t, {lo, hi};\nst.relaxed.gpu.global.b128 [%0], t;\n}\n"
               :: "l"(p), "r"(a), "r"(b), "r"(c), "r"(d) : "memory");
}
__device__ __forceinline__ uint32_t ldg_rlx32(const void* p) { uint32_t v; asm volatile("ld.relaxed.gpu.global.u32 %0, [%1];" : "=r"(v) : "l"(p) : "memory"); return v; }
__device__ __forceinline__ uint2 ldg_rlx64(const void* p) { uint2 v; asm volatile("ld.relaxed.gpu.global.v2.u32 {%0, %1}, [%2];" : "=r"(v.x), "=r"(v.y) : "l"(p) : "memory"); return v; }
__device__ __forceinline__ void stg128(void* p, const uint4& v) { asm volatile("st.global.v4.u32 [%0], {%1, %2, %3, %4};" :: "l"(p), "r"(v.x), "r"(v.y), "r"(v.z), "r"(v.w) : "memory"); }
__device__ __forceinline__ uint32_t pin(uint32_t v) { asm volatile("" : "+r"(v)); return v; }
__device__ __forceinline__ uint64_t mk64(uint32_t lo, uint32_t hi) { return ((uint64_t)hi << 32) | lo; }
template <class T> __device__ __forceinline__ T* pin(T* p) { asm volatile("" : "+l"(p)); return p; }
__device__ __forceinline__ void stg_rlx32(void* p, uint32_t v) { asm volatile("st.relaxed.gpu.global.u32 [%0], %1;" :: "l"(p), "r"(v) : "memory"); }
__device__ __forceinline__ void stg_rlx64(void* p, uint32_t a, uint32_t b) { asm volatile("st.relaxed.gpu.global.v2.u32 [%0], {%1, %2};" :: "l"(p), "r"(a), "r"(b) : "memory"); }
__device__ __forceinline__ uint4 ldsm4(uint32_t a) { uint4 v; asm volatile("ldmatrix.sync.aligned.m8n8.x4.shared.b16 {%0, %1, %2, %3}, [%4];" : "=r"(v.x), "=r"(v.y), "=r"(v.z), "=r"(v.w) : "r"(a) : "memory"); return v; }
__device__ __forceinline__ uint4 ldsm4t(uint32_t a) { uint4 v; asm volatile("ldmatrix.sync.aligned.m8n8.x4.trans.shared.b16 {%0, %1, %2, %3}, [%4];" : "=r"(v.x), "=r"(v.y), "=r"(v.z), "=r"(v.w) : "r"(a) : "memory"); return v; }
__device__ __forceinline__ void stsm4(uint32_t a, uint32_t x, uint32_t y, uint32_t z, uint32_t w) { asm volatile("stmatrix.sync.aligned.m8n8.x4.shared.b16 [%0], {%1, %2, %3, %4};" :: "r"(a), "r"(x), "r"(y), "r"(z), "r"(w) : "memory"); }
__device__ __forceinline__ void mma_acc(float (&c)[4], const uint4& a, uint32_t b0, uint32_t b1) {
  asm("mma.sync.aligned.m16n8k16.row.col.f32.bf16.bf16.f32 {%0,%1,%2,%3}, {%4,%5,%6,%7}, {%8,%9}, {%0,%1,%2,%3};"
      : "+f"(c[0]), "+f"(c[1]), "+f"(c[2]), "+f"(c[3]) : "r"(a.x), "r"(a.y), "r"(a.z), "r"(a.w), "r"(b0), "r"(b1));
}
__device__ __forceinline__ uint4 lds128(uint32_t a) { uint4 v; asm volatile("ld.shared.v4.u32 {%0, %1, %2, %3}, [%4];" : "=r"(v.x), "=r"(v.y), "=r"(v.z), "=r"(v.w) : "r"(a) : "memory"); return v; }
__device__ __forceinline__ float2 lds64f(uint32_t a) { float2 v; asm volatile("ld.shared.v2.f32 {%0, %1}, [%2];" : "=f"(v.x), "=f"(v.y) : "r"(a)); return v; }
__device__ __forceinline__ float lds32f(uint32_t a) { float v; asm volatile("ld.shared.f32 %0, [%1];" : "=f"(v) : "r"(a)); return v; }
__device__ __forceinline__ void sts32f(uint32_t a, float v) { asm volatile("st.shared.f32 [%0], %1;" :: "r"(a), "f"(v) : "memory"); }
__device__ __forceinline__ uint32_t pack_bf16(float lo, float hi) { uint32_t r; asm("cvt.rn.bf16x2.f32 %0, %1, %2;" : "=r"(r) : "f"(hi), "f"(lo)); return r; }
__device__ __forceinline__ float bf_lo(uint32_t v) { return __uint_as_float(v << 16); }
__device__ __forceinline__ float bf_hi(uint32_t v) { return __uint_as_float(v & 0xffff0000u); }
__device__ __forceinline__ uint32_t movm(uint32_t a) { uint32_t d; asm("movmatrix.sync.aligned.m8n8.trans.b16 %0, %1;" : "=r"(d) : "r"(a)); return d; }
__device__ __forceinline__ float ex2(float x) { float y; asm("ex2.approx.ftz.f32 %0, %1;" : "=f"(y) : "f"(x)); return y; }
__device__ __forceinline__ float rsq(float x) { float y; asm("rsqrt.approx.ftz.f32 %0, %1;" : "=f"(y) : "f"(x)); return y; }
__device__ __forceinline__ float rcp(float x) { float y; asm("rcp.approx.ftz.f32 %0, %1;" : "=f"(y) : "f"(x)); return y; }
__device__ __forceinline__ bool elect() { uint32_t p; asm volatile("{\n.reg .pred q;\nelect.sync _|q, 0xffffffff;\nselp.u32 %0, 1, 0, q;\n}\n" : "=r"(p)); return p; }
__device__ __forceinline__ void pf_l2(const void* p) { asm volatile("prefetch.global.L2 [%0];" :: "l"(p)); }
__device__ __forceinline__ bool anyw(bool p) { return __any_sync(0xffffffffu, p); }
__device__ __forceinline__ float shx(float v, int m) { return __shfl_xor_sync(0xffffffffu, v, m); }
__device__ __forceinline__ void mma_k24(float (&c)[4], uint32_t a0, uint32_t a1, uint32_t a2, uint32_t a3, uint32_t b0, uint32_t b1,
                                        uint32_t e0, uint32_t e1, uint32_t f0) {
  asm("mma.sync.aligned.m16n8k16.row.col.f32.bf16.bf16.f32 {%0,%1,%2,%3}, {%4,%5,%6,%7}, {%8,%9}, {%10,%10,%10,%10};"
      : "=f"(c[0]), "=f"(c[1]), "=f"(c[2]), "=f"(c[3]) : "r"(a0), "r"(a1), "r"(a2), "r"(a3), "r"(b0), "r"(b1), "f"(0.f));
  asm("mma.sync.aligned.m16n8k8.row.col.f32.bf16.bf16.f32 {%0,%1,%2,%3}, {%4,%5}, {%6}, {%0,%1,%2,%3};"
      : "+f"(c[0]), "+f"(c[1]), "+f"(c[2]), "+f"(c[3]) : "r"(e0), "r"(e1), "r"(f0));
}
__device__ __forceinline__ uint32_t ord_key(float r) { uint32_t u = __float_as_uint(r); return u ^ ((uint32_t)((int32_t)u >> 31) | 0x80000000u); }

__device__ __forceinline__ void wgmma_n48hi_ss(float (&d)[120], uint64_t da, uint64_t db, int scale_d) {
  asm volatile("{\n.reg .pred p;\nsetp.ne.b32 p, %26, 0;\n"
    "wgmma.mma_async.sync.aligned.m64n48k16.f32.bf16.bf16 "
    "{%0, %1, %2, %3, %4, %5, %6, %7, %8, %9, %10, %11, %12, %13, %14, %15, "
    "%16, %17, %18, %19, %20, %21, %22, %23}, "
    "%24, %25, p, 1, 1, 0, 1;\n}\n"
    : "+f"(d[96]), "+f"(d[97]), "+f"(d[98]), "+f"(d[99]), "+f"(d[100]), "+f"(d[101]), "+f"(d[102]), "+f"(d[103]),
      "+f"(d[104]), "+f"(d[105]), "+f"(d[106]), "+f"(d[107]), "+f"(d[108]), "+f"(d[109]), "+f"(d[110]), "+f"(d[111]),
      "+f"(d[112]), "+f"(d[113]), "+f"(d[114]), "+f"(d[115]), "+f"(d[116]), "+f"(d[117]), "+f"(d[118]), "+f"(d[119])
    : "l"(da), "l"(db), "r"(scale_d));
}
__device__ __forceinline__ void wgmma_n192lo_ss(float (&d)[120], uint64_t da, uint64_t db, int scale_d) {
  asm volatile("{\n.reg .pred p;\nsetp.ne.b32 p, %98, 0;\n"
    "wgmma.mma_async.sync.aligned.m64n192k16.f32.bf16.bf16 "
    "{%0, %1, %2, %3, %4, %5, %6, %7, %8, %9, %10, %11, %12, %13, %14, %15, "
    "%16, %17, %18, %19, %20, %21, %22, %23, %24, %25, %26, %27, %28, %29, %30, %31, "
    "%32, %33, %34, %35, %36, %37, %38, %39, %40, %41, %42, %43, %44, %45, %46, %47, "
    "%48, %49, %50, %51, %52, %53, %54, %55, %56, %57, %58, %59, %60, %61, %62, %63, "
    "%64, %65, %66, %67, %68, %69, %70, %71, %72, %73, %74, %75, %76, %77, %78, %79, "
    "%80, %81, %82, %83, %84, %85, %86, %87, %88, %89, %90, %91, %92, %93, %94, %95}, "
    "%96, %97, p, 1, 1, 0, 1;\n}\n"
    : "+f"(d[0]), "+f"(d[1]), "+f"(d[2]), "+f"(d[3]), "+f"(d[4]), "+f"(d[5]), "+f"(d[6]), "+f"(d[7]),
      "+f"(d[8]), "+f"(d[9]), "+f"(d[10]), "+f"(d[11]), "+f"(d[12]), "+f"(d[13]), "+f"(d[14]), "+f"(d[15]),
      "+f"(d[16]), "+f"(d[17]), "+f"(d[18]), "+f"(d[19]), "+f"(d[20]), "+f"(d[21]), "+f"(d[22]), "+f"(d[23]),
      "+f"(d[24]), "+f"(d[25]), "+f"(d[26]), "+f"(d[27]), "+f"(d[28]), "+f"(d[29]), "+f"(d[30]), "+f"(d[31]),
      "+f"(d[32]), "+f"(d[33]), "+f"(d[34]), "+f"(d[35]), "+f"(d[36]), "+f"(d[37]), "+f"(d[38]), "+f"(d[39]),
      "+f"(d[40]), "+f"(d[41]), "+f"(d[42]), "+f"(d[43]), "+f"(d[44]), "+f"(d[45]), "+f"(d[46]), "+f"(d[47]),
      "+f"(d[48]), "+f"(d[49]), "+f"(d[50]), "+f"(d[51]), "+f"(d[52]), "+f"(d[53]), "+f"(d[54]), "+f"(d[55]),
      "+f"(d[56]), "+f"(d[57]), "+f"(d[58]), "+f"(d[59]), "+f"(d[60]), "+f"(d[61]), "+f"(d[62]), "+f"(d[63]),
      "+f"(d[64]), "+f"(d[65]), "+f"(d[66]), "+f"(d[67]), "+f"(d[68]), "+f"(d[69]), "+f"(d[70]), "+f"(d[71]),
      "+f"(d[72]), "+f"(d[73]), "+f"(d[74]), "+f"(d[75]), "+f"(d[76]), "+f"(d[77]), "+f"(d[78]), "+f"(d[79]),
      "+f"(d[80]), "+f"(d[81]), "+f"(d[82]), "+f"(d[83]), "+f"(d[84]), "+f"(d[85]), "+f"(d[86]), "+f"(d[87]),
      "+f"(d[88]), "+f"(d[89]), "+f"(d[90]), "+f"(d[91]), "+f"(d[92]), "+f"(d[93]), "+f"(d[94]), "+f"(d[95])
    : "l"(da), "l"(db), "r"(scale_d));
}
__device__ __forceinline__ void wgmma_n48hi_rk(float (&d)[120], uint32_t a0, uint32_t a1, uint32_t a2, uint32_t a3, uint64_t db, int scale_d) {
  asm volatile("{\n.reg .pred p;\nsetp.ne.b32 p, %29, 0;\n"
    "wgmma.mma_async.sync.aligned.m64n48k16.f32.bf16.bf16 "
    "{%0, %1, %2, %3, %4, %5, %6, %7, %8, %9, %10, %11, %12, %13, %14, %15, "
    "%16, %17, %18, %19, %20, %21, %22, %23}, "
    "{%24, %25, %26, %27}, %28, p, 1, 1, 0;\n}\n"
    : "+f"(d[96]), "+f"(d[97]), "+f"(d[98]), "+f"(d[99]), "+f"(d[100]), "+f"(d[101]), "+f"(d[102]), "+f"(d[103]),
      "+f"(d[104]), "+f"(d[105]), "+f"(d[106]), "+f"(d[107]), "+f"(d[108]), "+f"(d[109]), "+f"(d[110]), "+f"(d[111]),
      "+f"(d[112]), "+f"(d[113]), "+f"(d[114]), "+f"(d[115]), "+f"(d[116]), "+f"(d[117]), "+f"(d[118]), "+f"(d[119])
    : "r"(a0), "r"(a1), "r"(a2), "r"(a3), "l"(db), "r"(scale_d));
}
__device__ __forceinline__ void wgmma_n192lo_rk(float (&d)[120], uint32_t a0, uint32_t a1, uint32_t a2, uint32_t a3, uint64_t db, int scale_d) {
  asm volatile("{\n.reg .pred p;\nsetp.ne.b32 p, %101, 0;\n"
    "wgmma.mma_async.sync.aligned.m64n192k16.f32.bf16.bf16 "
    "{%0, %1, %2, %3, %4, %5, %6, %7, %8, %9, %10, %11, %12, %13, %14, %15, "
    "%16, %17, %18, %19, %20, %21, %22, %23, %24, %25, %26, %27, %28, %29, %30, %31, "
    "%32, %33, %34, %35, %36, %37, %38, %39, %40, %41, %42, %43, %44, %45, %46, %47, "
    "%48, %49, %50, %51, %52, %53, %54, %55, %56, %57, %58, %59, %60, %61, %62, %63, "
    "%64, %65, %66, %67, %68, %69, %70, %71, %72, %73, %74, %75, %76, %77, %78, %79, "
    "%80, %81, %82, %83, %84, %85, %86, %87, %88, %89, %90, %91, %92, %93, %94, %95}, "
    "{%96, %97, %98, %99}, %100, p, 1, 1, 0;\n}\n"
    : "+f"(d[0]), "+f"(d[1]), "+f"(d[2]), "+f"(d[3]), "+f"(d[4]), "+f"(d[5]), "+f"(d[6]), "+f"(d[7]),
      "+f"(d[8]), "+f"(d[9]), "+f"(d[10]), "+f"(d[11]), "+f"(d[12]), "+f"(d[13]), "+f"(d[14]), "+f"(d[15]),
      "+f"(d[16]), "+f"(d[17]), "+f"(d[18]), "+f"(d[19]), "+f"(d[20]), "+f"(d[21]), "+f"(d[22]), "+f"(d[23]),
      "+f"(d[24]), "+f"(d[25]), "+f"(d[26]), "+f"(d[27]), "+f"(d[28]), "+f"(d[29]), "+f"(d[30]), "+f"(d[31]),
      "+f"(d[32]), "+f"(d[33]), "+f"(d[34]), "+f"(d[35]), "+f"(d[36]), "+f"(d[37]), "+f"(d[38]), "+f"(d[39]),
      "+f"(d[40]), "+f"(d[41]), "+f"(d[42]), "+f"(d[43]), "+f"(d[44]), "+f"(d[45]), "+f"(d[46]), "+f"(d[47]),
      "+f"(d[48]), "+f"(d[49]), "+f"(d[50]), "+f"(d[51]), "+f"(d[52]), "+f"(d[53]), "+f"(d[54]), "+f"(d[55]),
      "+f"(d[56]), "+f"(d[57]), "+f"(d[58]), "+f"(d[59]), "+f"(d[60]), "+f"(d[61]), "+f"(d[62]), "+f"(d[63]),
      "+f"(d[64]), "+f"(d[65]), "+f"(d[66]), "+f"(d[67]), "+f"(d[68]), "+f"(d[69]), "+f"(d[70]), "+f"(d[71]),
      "+f"(d[72]), "+f"(d[73]), "+f"(d[74]), "+f"(d[75]), "+f"(d[76]), "+f"(d[77]), "+f"(d[78]), "+f"(d[79]),
      "+f"(d[80]), "+f"(d[81]), "+f"(d[82]), "+f"(d[83]), "+f"(d[84]), "+f"(d[85]), "+f"(d[86]), "+f"(d[87]),
      "+f"(d[88]), "+f"(d[89]), "+f"(d[90]), "+f"(d[91]), "+f"(d[92]), "+f"(d[93]), "+f"(d[94]), "+f"(d[95])
    : "r"(a0), "r"(a1), "r"(a2), "r"(a3), "l"(db), "r"(scale_d));
}
__device__ __forceinline__ void wgmma_n80_rs(float (&d)[40], uint32_t a0, uint32_t a1, uint32_t a2, uint32_t a3, uint64_t db, int scale_d) {
  asm volatile("{\n.reg .pred p;\nsetp.ne.b32 p, %45, 0;\n"
    "wgmma.mma_async.sync.aligned.m64n80k16.f32.bf16.bf16 "
    "{%0, %1, %2, %3, %4, %5, %6, %7, %8, %9, %10, %11, %12, %13, %14, %15, "
    "%16, %17, %18, %19, %20, %21, %22, %23, %24, %25, %26, %27, %28, %29, %30, %31, "
    "%32, %33, %34, %35, %36, %37, %38, %39}, "
    "{%40, %41, %42, %43}, %44, p, 1, 1, 1;\n}\n"
    : "+f"(d[0]), "+f"(d[1]), "+f"(d[2]), "+f"(d[3]), "+f"(d[4]), "+f"(d[5]), "+f"(d[6]), "+f"(d[7]),
      "+f"(d[8]), "+f"(d[9]), "+f"(d[10]), "+f"(d[11]), "+f"(d[12]), "+f"(d[13]), "+f"(d[14]), "+f"(d[15]),
      "+f"(d[16]), "+f"(d[17]), "+f"(d[18]), "+f"(d[19]), "+f"(d[20]), "+f"(d[21]), "+f"(d[22]), "+f"(d[23]),
      "+f"(d[24]), "+f"(d[25]), "+f"(d[26]), "+f"(d[27]), "+f"(d[28]), "+f"(d[29]), "+f"(d[30]), "+f"(d[31]),
      "+f"(d[32]), "+f"(d[33]), "+f"(d[34]), "+f"(d[35]), "+f"(d[36]), "+f"(d[37]), "+f"(d[38]), "+f"(d[39])
    : "r"(a0), "r"(a1), "r"(a2), "r"(a3), "l"(db), "r"(scale_d));
}
__device__ __forceinline__ void wgmma_n80_ss(float (&d)[40], uint64_t da, uint64_t db, int scale_d) {
  asm volatile("{\n.reg .pred p;\nsetp.ne.b32 p, %42, 0;\n"
    "wgmma.mma_async.sync.aligned.m64n80k16.f32.bf16.bf16 "
    "{%0, %1, %2, %3, %4, %5, %6, %7, %8, %9, %10, %11, %12, %13, %14, %15, "
    "%16, %17, %18, %19, %20, %21, %22, %23, %24, %25, %26, %27, %28, %29, %30, %31, "
    "%32, %33, %34, %35, %36, %37, %38, %39}, "
    "%40, %41, p, 1, 1, 0, 1;\n}\n"
    : "+f"(d[0]), "+f"(d[1]), "+f"(d[2]), "+f"(d[3]), "+f"(d[4]), "+f"(d[5]), "+f"(d[6]), "+f"(d[7]),
      "+f"(d[8]), "+f"(d[9]), "+f"(d[10]), "+f"(d[11]), "+f"(d[12]), "+f"(d[13]), "+f"(d[14]), "+f"(d[15]),
      "+f"(d[16]), "+f"(d[17]), "+f"(d[18]), "+f"(d[19]), "+f"(d[20]), "+f"(d[21]), "+f"(d[22]), "+f"(d[23]),
      "+f"(d[24]), "+f"(d[25]), "+f"(d[26]), "+f"(d[27]), "+f"(d[28]), "+f"(d[29]), "+f"(d[30]), "+f"(d[31]),
      "+f"(d[32]), "+f"(d[33]), "+f"(d[34]), "+f"(d[35]), "+f"(d[36]), "+f"(d[37]), "+f"(d[38]), "+f"(d[39])
    : "l"(da), "l"(db), "r"(scale_d));
}

__device__ __forceinline__ constexpr int QT(int t) { return t < 8 ? t : 16 + t; }
__device__ __forceinline__ constexpr int KT(int t) { return t < 8 ? 8 + t : 18 + t; }
__device__ __forceinline__ constexpr int VT(int t) { return t < 8 ? 16 + t : 20 + t; }

struct Maps { CUtensorMap x, w, wr, wo, wor, gate, up, down; };

__global__ void __cluster_dims__(2, 1, 1) __launch_bounds__(512, 1)
fused_kernel(const __nv_bfloat16* __restrict__ x, const __nv_bfloat16* __restrict__ wqkv,
             const __nv_bfloat16* __restrict__ wo, const __nv_bfloat16* __restrict__ w_r, const __nv_bfloat16* __restrict__ w_gate,
             const __nv_bfloat16* __restrict__ w_up, const __nv_bfloat16* __restrict__ w_down, __nv_bfloat16* __restrict__ out,
             Scratch* __restrict__ sc, const __grid_constant__ Maps tm) {
  extern __shared__ __align__(1024) uint8_t smem[];
  const int tid = threadIdx.x, warp = __shfl_sync(0xffffffffu, tid >> 5, 0), lane = tid & 31, bid = blockIdx.x;
  const uint32_t sb = (uint32_t)__cvta_generic_to_shared(smem);
  const uint32_t bar_full = sb + OFF_BAR, bar_empty = bar_full + 32, bar_aux = bar_full + 64, bar_ffn = bar_full + 72, bar_win = bar_full + 80,
                 bar_o = bar_full + 96;
  if (warp < 4 && elect()) {
    mbar_init(bar_full + 8 * (warp ^ 2), 1);
    mbar_init(bar_empty + 8 * warp, 12);
    mbar_init(bar_aux + 8 * warp, warp == 0 ? 64 : warp == 2 ? 32 : 1);
    asm volatile("fence.mbarrier_init.release.cluster;" ::: "memory");
  }
  if (warp >= 4 && warp < 12 && elect()) { mbar_init(bar_o + 16 * (warp - 4), 1); mbar_init(bar_o + 16 * (warp - 4) + 8, (warp & 3) == 1 ? 128 : 1); }
  asm volatile("barrier.cluster.arrive.relaxed.aligned;" ::: "memory");
  if (warp >= 8 && warp < 11 && elect()) asm volatile("prefetch.tensormap [%0];" :: "l"(&tm.x + (warp - 8)) : "memory");
  auto pf_slice = [&](int ks) {
    pf_l2(lane < 16 ? (const char*)x + ((bid * 16 + lane) * 1280 + ks * 128) : (const char*)wqkv + ((bid * 15 + min(lane, 30) - 16) * 128 + ks * 245760));
  };
  if (warp >= 12 && warp < 8 + PF0) {
    const int t0 = clock(); while (clock() - t0 < ((warp - 7) >> 1) * PF_CLK) {}
    pf_slice(((warp - 7) >> 1) + ((warp & 1) ? 0 : 4));
  }
  if (warp >= 4 && warp < 4 + (PF0 < 4 ? PF0 : 4)) {
    if (warp > 4) { const int t0 = clock(); while (clock() - t0 < ((warp - 3) >> 1) * PF_CLK) {} }
    pf_slice(((warp - 3) >> 1) + ((warp & 1) || warp == 4 ? 0 : 4));
  }
  const int rank = bid & 1, cl = bid >> 1;
  const int q7 = ((cl - 36) * 37) >> 8;
  const int P = cl < 4 ? 0 : cl < 36 ? (cl - 4) & 7 : cl - 35 - 7 * q7;
  const int g = cl < 4 ? 4 + cl : cl < 36 ? (cl - 4) >> 3 : 4 + q7;
  const int mt = 2 * P + rank, cid = mt * 8 + g;
  const bool ffn1 = g < 3;
  const int fj = ffn1 ? mt * 3 + g : (P * 5 + g - 3) * 2 + rank;
  const int ord = ((g >> 2) ^ P) & 1;
  auto ks_of = [&](int it) { return !ORDX || ord == 0 || it == 0 ? it : it <= 5 ? it + 4 : it - 5; };
  auto load_w = [&](int it, uint32_t a, uint32_t full) {
    tma_3d_mc(a + 16384 + rank * 16384, &tm.w, full, g * 80, it * 64, rank * 2);
    tma_3d_mc(a + (rank ? 40960 : 24576), rank ? &tm.wr : &tm.w, full, g * 80 + rank * 64, it * 64, 1 - rank);
  };
  if (warp == 0 && elect()) {
    mbar_expect_tx(bar_full + 16, SLOT);
    tma_3d(sb + 2 * SLOT, &tm.x, bar_full + 16, 0, mt * 64, 0);
  }
  asm volatile("barrier.cluster.wait.aligned;" ::: "memory");
  if (warp == 0) {
    if (elect()) load_w(0, sb + 2 * SLOT, bar_full + 16);
    asm volatile("bar.arrive 4, 64;" ::: "memory");
  }

  if (warp >= 8) {
    asm volatile("setmaxnreg.dec.sync.aligned.u32 %0;" :: "n"(REG_P));
#define TS_T 0
    if (warp == 8) {
      TS(8);
      bar_sync(4, 64);
      if (elect()) {
        TS(10);
        int fjn = 0;
#pragma unroll 1
        for (int it = 1; it < 17; it++) {
          const int s = (it + 2) & 3;
          const uint32_t full = bar_full + 8 * s, a = sb + s * SLOT;
          if (it >= 13) { mbar_wait(bar_o + 32 + 8 * (it - 13), 0); mbar_wait(bar_o + 96 + 8 * (it - 13), 0); }
          else if (it >= 4) mbar_wait(bar_empty + 8 * s, ((it >> 2) - 1) & 1);
          if (it < 10) {
            const int ks = ks_of(it);
            mbar_expect_tx(full, SLOT);
            tma_3d(a, &tm.x, full, ks * 64, mt * 64, 0);
            load_w(ks, a, full);
            TS(12 + it);
          } else if (it < 13) {
            const int g0 = 3 * (it - 10), g1 = min(g0 + 3, 8);
            mbar_expect_tx(full, (g1 - g0) * 12800);
#pragma unroll 1
            for (int gp = g0 + ((g0 ^ rank) & 1); gp < g1; gp += 2) {
              tma_3d_mc(sb + gp * 15360, &tm.wo, full, 0, gp * 80, g * 2);
              tma_3d_mc(sb + gp * 15360 + 10240, &tm.wor, full, 512 + g * 16, gp * 80, 0);
            }
          }
          if (it == 4) mbar_expect_tx(bar_ffn, ffn1 ? 81920 : 24576);
          const int j1 = ffn1 ? (it >= 13 ? min(2 * it - 21, 10) : min(max(it - F_IT + 1, 0), 4)) : (it >= 13 ? 12 : min(max((it - F_IT + 1) * F_PER, 0), F_MAX));
#pragma unroll 1
          for (; fjn < j1; fjn++) {
            const int j = fjn < 4 ? fjn + 6 : fjn - 4;
            if (ffn1) tma_3d(sb + (j < 6 ? 0 : OFF_W2 - 49152) + j * 8192, j < 5 ? &tm.gate : &tm.up, bar_ffn, fj * 32, (j < 5 ? j : j - 5) * 128, 0);
            else tma_3d(sb + OFF_W2 + fjn * 2048, &tm.down, bar_ffn, fj * 8, fjn * 128, 0);
          }
        }
        TS(11);
      }
#undef TS_T
#define TS_T 0
    } else if (warp >= 12) {
      const int l7 = lane & 7, j = warp - 12, ch = min((P >> 1) * 4 + rank * 2 + (j >> 1), 14);
      const uint32_t sxo = ((g & 3) * 32 + j * 8 + l7) * 128 + (((lane >> 3) ^ l7) * 16);
      const uint32_t swo = ch < 12 ? 16384 + (ch >> 2) * 8192 + lane * 128 + ((((ch & 3) * 2 + (j & 1)) ^ l7) * 16)
                                   : 40960 + (ch - 12) * 2048 + lane * 32 + (((j & 1) ^ (l7 >> 2)) * 16);
      float ps = 0.f, pq = 0.f, pq1 = 0.f, pc = 0.f;
#pragma unroll 1
      for (int it = ord; it < ord + 5; it++) {
        const int sl = (it + 2) & 3;
        mbar_wait(bar_full + 8 * sl, (it >> 2) & 1);
        TS(it);
        const uint32_t a = sb + sl * SLOT;
        const uint4 v0 = ldsm4(a + sxo), v1 = ldsm4((a + sxo) ^ 64), w0 = ldsm4t(a + swo), w1 = ldsm4t(a + swo + (ch < 12 ? 4096 : 1024));
        if (lane + (int)((v0.x & v1.x & w0.x & w1.x) == 0x7fc17fc1u && (v0.x | v1.x) == 0u) < 2) mbar_arrive_cta(bar_empty + 8 * sl, lane);
        const uint32_t vv[8] = {v0.x, v0.y, v0.z, v0.w, v1.x, v1.y, v1.z, v1.w}, ww[8] = {w0.x, w0.y, w0.z, w0.w, w1.x, w1.y, w1.z, w1.w};
#pragma unroll
        for (int i = 0; i < 8; i++) {
          const float d = bf_lo(vv[i]), e = bf_hi(vv[i]);
          ps += d + e; pq = fmaf(d, d, pq); pq1 = fmaf(e, e, pq1); pc += bf_lo(ww[i]) + bf_hi(ww[i]);
        }
      }
      pq += pq1;
      ps += shx(ps, 1); pq += shx(pq, 1); pc += shx(pc, 1);
      ps += shx(ps, 2); pq += shx(pq, 2); pc += shx(pc, 2);
      const int c = lane & 3;
      if (c < 3) sts32f(sb + OFF_PT + (c * 32 + j * 8 + (lane >> 2)) * 4, c == 0 ? ps : c == 1 ? pq : pc);
      asm volatile("bar.arrive 2, 224;" ::: "memory");
#undef TS_T
#define TS_T 32
    } else if (warp < 11) {
      Own* const own = g_own + cid;
      const int l7 = lane & 7, hk = lane >> 4, idx = lane;
      mbar_wait(bar_full + 8 * ((PFX_IT + 2) & 3), 0);
      pf_slice(warp == 9 ? 4 : 8);
      if (warp == 9) pf_slice(9);
      bar_sync(2, 224);
      TS(0);
      const uint32_t tag = __float_as_uint(lds32f(sb + OFF_WR + 324));
      const float s0 = lds32f(sb + OFF_PT + lane * 4 + (warp - 9) * 256), q0 = lds32f(sb + OFF_PT + 128 + lane * 4);
      int guard = SPIN_MAX;
      if (warp == 9) {
        stg_pkt(&own->st1[idx], __float_as_uint(s0), __float_as_uint(q0), tag, 0u);
        TS(1);
        const uint4* sp = &g_own[mt * 8].st1[lane];
        const uint4* hp = &g_own[max(mt - 1, 0) * 8 + hk * 2 + 1].st1[24 + l7];
        uint4 a[5], b[5];
        bool bad;
        do {
          __nanosleep(AUX_NS);
          bad = false;
#pragma unroll
          for (int i = 0; i < 5; i++) {
            const uint4* q = i < 4 ? sp + i * (sizeof(Own) / 16) : hp;
            a[i] = ldg_pkt(q); b[i] = ldg_pkt(q + 4 * sizeof(Own) / 16);
          }
#pragma unroll
          for (int i = 0; i < 5; i++) bad |= a[i].z != tag || b[i].z != tag;
        } while (anyw(bad) && --guard);
#pragma unroll
        for (int i = 0; i < 5; i++) {
          const float m = (__uint_as_float(a[i].x) + __uint_as_float(b[i].x)) * (1.f / 640.f);
          const float rs = rsq(fmaxf(fmaf(-m, m, (__uint_as_float(a[i].y) + __uint_as_float(b[i].y)) * (1.f / 640.f)), 0.f) + 1e-5f);
          ((float*)(smem + OFF_RS))[i < 4 ? 8 + lane + 32 * i + 8 * (i >> 1) : hk * 72 + l7] = rs;
          const uint32_t mh = pack_bf16(-m, -m);
          const float ml = -m - bf_lo(mh);
          if (i < 4) ((uint2*)(smem + OFF_MN))[lane + 32 * i] = make_uint2(mh, pack_bf16(ml, ml));
        }
      } else {
        stg_rlx64(&own->cs[idx], __float_as_uint(s0), tag);
        const uint4* cp = (const uint4*)g_own[hk * 8 + g].cs + (lane & 15);
        uint4 a[4], b[4];
        bool bad;
        do {
          __nanosleep(AUX_NS);
          bad = false;
#pragma unroll
          for (int i = 0; i < 4; i++) { a[i] = ldg_pkt(cp + i * 32 * sizeof(Own) / 16); b[i] = ldg_pkt(cp + (i * 32 + 16) * sizeof(Own) / 16); }
#pragma unroll
          for (int i = 0; i < 4; i++) bad |= a[i].y != tag || a[i].w != tag || b[i].y != tag || b[i].w != tag;
        } while (anyw(bad) && --guard);
#pragma unroll
        for (int i = 0; i < 4; i++)
          if (i < 3 || lane < 24) {
            const float c0 = __uint_as_float(a[i].x) + __uint_as_float(b[i].x), c1 = __uint_as_float(a[i].z) + __uint_as_float(b[i].z);
            const uint32_t hi = pack_bf16(c0, c1), w0 = pack_bf16(c0, c0 - bf_lo(hi)), w1 = pack_bf16(c1, c1 - bf_hi(hi));
            uint4* const d = (uint4*)(smem + OFF_CS) + 2 * (lane + 32 * i);
            d[0] = make_uint4(w0, w0, 0, 0); d[1] = make_uint4(w1, w1, 0, 0);
          }
        asm volatile("fence.proxy.async.shared::cta;" ::: "memory");
      }
      mbar_arrive(bar_aux);
      TS(2);
      const int wq = warp - 9;
      const uint4* const fp = pin(g_own[mt * 8 + wq * 4].cnt);
      const char* const src = (const char*)g_o[mt * 2 + wq];
      bar_sync(5 + wq, 160);
      if (elect()) {
        while (ldg_rlx32(fp) != 32u && --guard > 0) {}
        asm volatile("fence.proxy.async.global;" ::: "memory");
        TS(6);
#pragma unroll 1
        for (int i = 0, sl = 0; i < 7; i++) {
          const uint32_t full = bar_o + wq * 64 + 8 * sl;
          if (i >= 3) mbar_wait(bar_o + wq * 64 + 8 + 8 * i, 0);
          mbar_expect_tx(full, 10240);
          asm volatile("cp.async.bulk.shared::cluster.global.mbarrier::complete_tx::bytes [%0], [%1], 10240, [%2];"
                       :: "r"(sb + OFF_O + sl * 20480 + wq * 10240), "l"(src + (i + (i >= g)) * 10240), "r"(full) : "memory");
          sl = sl == 2 ? 0 : sl + 1;
        }
      }
#undef TS_T
#define TS_T 96
    } else {
#pragma unroll 1
      for (int i = lane; i < 224; i += 32) { const uint32_t f = i < 200 ? SENT : 0u; ((uint4*)(smem + OFF_CS))[i] = make_uint4(f, f, f, f); }
      asm volatile("fence.proxy.async.shared::cta;" ::: "memory");
      mbar_wait(bar_full + 8 * ((RST_IT + 2) & 3), 0);
      TS(4);
      if (elect()) {
        asm volatile("cp.async.bulk.global.shared::cta.bulk_group [%0], [%1], 2688;" :: "l"(g_own + cid), "r"(sb + OFF_CS) : "memory");
        asm volatile("cp.async.bulk.global.shared::cta.bulk_group [%0], [%1], 3584;" :: "l"((char*)(g_own + cid) + 2688), "r"(sb + OFF_CS) : "memory");
        asm volatile("cp.async.bulk.global.shared::cta.bulk_group [%0], [%1], %2;\ncp.async.bulk.commit_group;" :: "l"((uint4*)&g_x + cid * GLOB_PER_CTA), "r"(sb + OFF_CS), "n"(GLOB_PER_CTA * 16) : "memory");
      }
      const uint32_t epoch = ldg_rlx32(g_epoch + cid) + 1;
      uint32_t wv[10];
#pragma unroll
      for (int i = 0; i < 10; i++) wv[i] = __ldg((const uint32_t*)w_r + lane + 32 * i);
      float s = 0.f;
#pragma unroll
      for (int i = 0; i < 10; i++) {
        s += bf_lo(wv[i]) + bf_hi(wv[i]);
        const unsigned u = i < 8 ? lane + 32 * (i - g) : lane + 32 * (i - 7) - g * 8;
        if (i < 8 ? u < 32u : u - 32u < 8u) *(float2*)(smem + OFF_WR + ((u & 3) * 10 + (u >> 2)) * 8) = make_float2(bf_lo(wv[i]), bf_hi(wv[i]));
      }
#pragma unroll
      for (int m = 1; m < 32; m <<= 1) s += shx(s, m);
      *(float2*)(smem + OFF_WR + 320) = make_float2(s, __uint_as_float(epoch * 0x9E3779B8u));
      g_epoch[cid] = epoch;
      TS(3);
      asm volatile("cp.async.bulk.wait_group 0;" ::: "memory");
      TS(5);
      asm volatile("bar.arrive 2, 224;" ::: "memory");
#pragma unroll 1
      for (int i = 0; i < 14; i++) {
        const int m = (i + 2) >> 2, n = m == 0 ? 50 : 120, t = (m == 0 ? i : (i + 2) & 3) * 32 + lane;
        const char* b = (const char*)(m == 0 ? wo : m == 1 ? w_up : m == 2 ? w_down : w_gate);
        if (t < n) pf_l2(b + (bid * n + t) * 128);
        __nanosleep(PFW_NS);
      }
      bar_sync(3, 64);
      const uint4* const kp = g_own[1].cnt;
      const uint4* const cb = &g_x.cand[0][lane >> 2][lane & 3];
      uint4 k = ldg_pkt(kp), c0 = make_uint4(0, 0, 0, 0), c1 = c0; uint2 c2 = make_uint2(0, 0);
      int guard = SPIN_MAX, ws;
      while (true) {
        const uint32_t tk = 2047u - (k.x & 2047u);
        ws = (tk >> 7) * 8 + (tk & 1) * 4 + ((tk >> 5) & 3);
        const uint32_t prev = k.x;
        if (ffn1) { const uint4* q = cb + ws * 192; c0 = ldg_pkt(q); c1 = ldg_pkt(q + 4); c2 = ldg_rlx64(q + 8); }
        if (k.z != 128u) k = ldg_pkt(kp);
        if ((k.z == 128u && k.x == prev && !anyw(c0.x == SENT || c1.x == SENT || c2.x == SENT)) || --guard <= 0) break;
      }
      *(uint4*)(smem + OFF_HN + lane * 16) = c0; *(uint4*)(smem + OFF_HN + 512 + lane * 16) = c1; *(uint2*)(smem + OFF_HN + 1024 + lane * 16) = c2;
      const float rw = __uint_as_float(k.y ^ ((uint32_t)((int32_t)~k.y >> 31) | 0x80000000u));
      *(uint4*)(smem + OFF_WR + 336) = make_uint4(ws, 2047u - (k.x & 2047u), __float_as_uint(rcp(1.f + ex2(-1.4426950408889634f * rw))), 0);
      mbar_arrive(bar_win);
      TS(7);
    }
#undef TS_T
  } else {
#define TS_T 0
    TS(23);
    asm volatile("setmaxnreg.inc.sync.aligned.u32 %0;" :: "n"(REG_C));
    const int wg = warp >> 2, w4 = warp & 3, r = lane >> 2, c = lane & 3;
    float acc[120];
    uint4 xr[5];
    const uint32_t xa = pin(sb + (warp * 16 + (lane & 15)) * 128 + ((lane >> 4) ^ (lane & 7)) * 16);
    const bool first = (mt == 0) && (w4 == 0);
    uint4* const kvd = pin(w4 < 3 ? (uint4*)(smem + OFF_O + warp * 2560) + lane : &g_own[cid].halo[wg][0][lane]);
    const uint4* const kvs = pin(first ? kvd : w4 > 0 ? (const uint4*)(smem + OFF_O + (warp - 1) * 2560) + lane : &g_own[cid - 8].halo[wg][0][lane]);
    uint32_t m0 = 0, m1 = 0;
    const uint32_t d0 = (sb & 0x3FFFF) >> 4;
    const int itx = ord == 0 || g == 0 ? g : g < 5 ? g + 5 : g - 4, ity = (ord ? 4 : 8) + (g >> 2);
    uint32_t rel;
    asm volatile("mapa.shared::cluster.u32 %0, %1, %2;" : "=r"(rel) : "r"(bar_empty), "r"(tid & 1));
    TS(0);
#pragma unroll 1
    for (int it = 0; it < 10; it++) {
      const int s = (it + 2) & 3;
      const uint32_t dl = d0 + s * (SLOT >> 4);
      const uint64_t da = mk64(dl + wg * 512 + (1u << 16), 0x40000040u), db = mk64(dl + 1024 + (512u << 16), 0x40000040u), dr = mk64(dl + 2560 + (128u << 16), 0xC0000010u);
      if (it == 9) {
        mbar_wait(bar_aux, 0);
        TS(3);
        if (c < 2) { m0 = __float_as_uint(lds32f(sb + OFF_MN + (warp * 16 + r) * 8 + c * 4)); m1 = __float_as_uint(lds32f(sb + OFF_MN + (warp * 16 + r) * 8 + c * 4 + 64)); }
        bar_sync(10 + wg, 256);
      }
      if (it == SKEW_IT && wg != LEAD) bar_sync(7, 256);
      mbar_wait(bar_full + 8 * s, (it >> 2) & 1);
      TS(13 + it);
      wgmma_fence();
      wgmma_n48hi_ss(acc, da, dr, it != 0);
      wgmma_n192lo_ss(acc, da, db, it != 0);
      wgmma_commit();
      wgmma_wait<1>();
      if ((tid & 127) < (it == 0 ? 0 : (unsigned)(it - 1 - ord) < 5u ? 2 : 6))
        asm volatile("mbarrier.arrive.shared::cluster.b64 _, [%0];" :: "r"(rel + 8 * ((it + 1) & 3)) : "memory");
#pragma unroll
      for (int kk = 1; kk < 4; kk++) {
        wgmma_n48hi_ss(acc, da + kk * 2, dr + kk * 32, 1);
        wgmma_n192lo_ss(acc, da + kk * 2, db + kk * 128, 1);
      }
      wgmma_commit();
      if (it == SKEW_IT && wg == LEAD) asm volatile("bar.arrive 7, 256;" ::: "memory");
      if (it == (wg == LEAD ? 9 : 8)) asm volatile("bar.arrive %0, 256;" :: "r"(11 - wg) : "memory");
      if (it == itx) {
#pragma unroll
        for (int j = 0; j < 4; j++) xr[j] = ldsm4((xa + s * SLOT) ^ (j * 32));
      }
      if (it == ity) xr[4] = ldsm4((xa + s * SLOT) ^ ((g & 3) * 32));
    }
    {
      const uint64_t dc = make_desc(sb + OFF_CS, 0, 128, 0);
      wgmma_fence();
      wgmma_n48hi_rk(acc, m0, m1, 0u, 0u, dc + 192, 1);
      wgmma_n192lo_rk(acc, m0, m1, 0u, 0u, dc, 1);
      wgmma_commit();
    }
    const uint32_t stb = sb + OFF_RS + (wg * 72 + 16 * w4) * 4;
    const float rlo = lds32f(stb + (8 + r) * 4), rhi = lds32f(stb + (16 + r) * 4);
    wgmma_wait<0>();
#pragma unroll
    for (int i = 0; i < 120; i++) asm volatile("" : "+f"(acc[i]) :: "memory");
    if (wg != LEAD) asm volatile("bar.arrive 9, 256;" ::: "memory");
    TS(2);
    uint32_t Qlo[10], Qhi[10], Klo[10], Khi[10], Vlo[10], Vhi[10];
#pragma unroll
    for (int t = 0; t < 10; t++) {
      const int k = KT(t), v = VT(t);
      Khi[t] = pack_bf16(acc[4 * k + 2], acc[4 * k + 3]);
      Vhi[t] = pack_bf16(acc[4 * v + 2] * rhi, acc[4 * v + 3] * rhi);
    }
    st_pkt(kvd, Khi[0], Khi[1], Khi[3], Khi[4]);
    st_pkt(kvd + 32, Khi[5], Khi[6], Khi[8], Khi[9]);
    st_pkt(kvd + 64, Khi[2], Khi[7], Vhi[0], Vhi[1]);
    st_pkt(kvd + 96, Vhi[2], Vhi[3], Vhi[4], Vhi[5]);
    st_pkt(kvd + 128, Vhi[6], Vhi[7], Vhi[8], Vhi[9]);
    mbar_arrive(bar_o + wg * 64 + 24);
#pragma unroll
    for (int t = 0; t < 10; t++) {
      const int q = QT(t), k = KT(t), v = VT(t);
      Vhi[t] = movm(Vhi[t]);
      Klo[t] = pack_bf16(acc[4 * k], acc[4 * k + 1]);
      Vlo[t] = movm(pack_bf16(acc[4 * v] * rlo, acc[4 * v + 1] * rlo));
      Qlo[t] = pack_bf16(acc[4 * q], acc[4 * q + 1]);
      Qhi[t] = pack_bf16(acc[4 * q + 2], acc[4 * q + 3]);
    }
    const bool in0 = 2 * c <= r, in1 = 2 * c + 1 <= r;
    const uint32_t mL = (in0 ? 0xffffu : 0u) | (in1 ? 0xffff0000u : 0u);
    const float qs = 0.22360679774997896f * 1.4426950408889634f;
    const uint32_t kb0 = stb + (2 * c + (in0 ? 8 : 0)) * 4, kb1 = stb + (2 * c + 1 + (in1 ? 8 : 0)) * 4;
    const float scl0 = lds32f(kb0) * rlo * qs, scl1 = lds32f(kb1) * rlo * qs;
    const float sch0 = lds32f(kb0 + 32) * rhi * qs, sch1 = lds32f(kb1 + 32) * rhi * qs;
    const float bias0 = (first && !in0) ? -INFINITY : 0.f, bias1 = (first && !in1) ? -INFINITY : 0.f;
    const int slot = mt * 8 + warp;
    int guard = SPIN_MAX;
    uint4 pv[5];
    mbar_wait(bar_o + wg * 64 + 24, 0);
    do {
#pragma unroll
      for (int j = 0; j < 5; j++) pv[j] = ld_pkt(kvs + 32 * j);
    } while (anyw(pv[0].x == SENT || pv[1].x == SENT || pv[2].x == SENT || pv[3].x == SENT || pv[4].x == SENT) && --guard);
    if (wg == LEAD) bar_sync(9, 256);
    TS(4);
    const uint32_t Kp[10] = {pv[0].x, pv[0].y, pv[2].x, pv[0].z, pv[0].w, pv[1].x, pv[1].y, pv[2].y, pv[1].z, pv[1].w};
    const uint32_t Vp[10] = {movm(pv[2].z), movm(pv[2].w), movm(pv[3].x), movm(pv[3].y), movm(pv[3].z), movm(pv[3].w), movm(pv[4].x), movm(pv[4].y), movm(pv[4].z), movm(pv[4].w)};
    const bool cA = c < 2, nA = r < 4;
    const uint32_t ONES = 0x3f803f80u;
    uint32_t of[20];
#pragma unroll
    for (int hp = 0; hp < 2; hp++) {
      float o[6][4];
#pragma unroll
      for (int hh = 0; hh < 2; hh++) {
        const int ta = 5 * hp + 3 * hh, ts = 5 * hp + 2;
        const bool mine = hh == 0 ? cA : !cA;
        const uint32_t e0 = mine ? Qlo[ts] : 0u, e1 = mine ? Qhi[ts] : 0u;
        float sp[4], sl[4], sh[4];
        mma_k24(sp, Qlo[ta], Qhi[ta], Qlo[ta + 1], Qhi[ta + 1], Kp[ta], Kp[ta + 1], e0, e1, Kp[ts]);
        mma_k24(sl, Qlo[ta], Qhi[ta], Qlo[ta + 1], Qhi[ta + 1], Klo[ta], Klo[ta + 1], e0, e1, Klo[ts]);
        mma_k24(sh, Qlo[ta], Qhi[ta], Qlo[ta + 1], Qhi[ta + 1], Khi[ta], Khi[ta + 1], e0, e1, Khi[ts]);
        const float tl0 = fmaf(in0 ? sl[0] : sp[0], scl0, bias0), tl1 = fmaf(in1 ? sl[1] : sp[1], scl1, bias1);
        const float th0 = (in0 ? sh[2] : sl[2]) * sch0, th1 = (in1 ? sh[3] : sl[3]) * sch1;
        float ml = fmaxf(tl0, tl1), mh = fmaxf(th0, th1);
        ml = fmaxf(ml, shx(ml, 1)); mh = fmaxf(mh, shx(mh, 1));
        ml = fmaxf(ml, shx(ml, 2)); mh = fmaxf(mh, shx(mh, 2));
        const uint32_t Pl = pack_bf16(ex2(tl0 - ml), ex2(tl1 - ml)), Ph = pack_bf16(ex2(th0 - mh), ex2(th1 - mh));
        const uint32_t a0 = Pl & mL, a1 = Ph & ~mL, a3 = Ph & mL, ap = Pl & ~mL;
        const bool vm = hh == 0 ? nA : !nA;
        mma_k24(o[3 * hh], a0, a1, 0u, a3, Vlo[ta], Vhi[ta], ap, 0u, Vp[ta]);
        mma_k24(o[3 * hh + 1], a0, a1, 0u, a3, Vlo[ta + 1], Vhi[ta + 1], ap, 0u, Vp[ta + 1]);
        mma_k24(o[3 * hh + 2], a0, a1, 0u, a3, vm ? Vlo[ts] : ONES, vm ? Vhi[ts] : ONES, ap, 0u, vm ? Vp[ts] : ONES);
      }
      const float il = rcp(cA ? o[5][0] : o[2][0]), ih = rcp(cA ? o[5][2] : o[2][2]);
      const float jl = shx(il, 2), jh = shx(ih, 2);
      const float al = cA ? jl : il, ah = cA ? jh : ih, bl = cA ? il : jl, bh = cA ? ih : jh;
      const int t0 = 5 * hp;
      of[2 * t0]     = pack_bf16(o[0][0] * al, o[0][1] * al); of[2 * t0 + 1] = pack_bf16(o[0][2] * ah, o[0][3] * ah);
      of[2 * t0 + 2] = pack_bf16(o[1][0] * al, o[1][1] * al); of[2 * t0 + 3] = pack_bf16(o[1][2] * ah, o[1][3] * ah);
      of[2 * t0 + 4] = pack_bf16((cA ? o[2][0] : o[5][0]) * jl, (cA ? o[2][1] : o[5][1]) * jl);
      of[2 * t0 + 5] = pack_bf16((cA ? o[2][2] : o[5][2]) * jh, (cA ? o[2][3] : o[5][3]) * jh);
      of[2 * t0 + 6] = pack_bf16(o[3][0] * bl, o[3][1] * bl); of[2 * t0 + 7] = pack_bf16(o[3][2] * bh, o[3][3] * bh);
      of[2 * t0 + 8] = pack_bf16(o[4][0] * bl, o[4][1] * bl); of[2 * t0 + 9] = pack_bf16(o[4][2] * bh, o[4][3] * bh);
    }
    {
      const uint32_t os = sb + OFF_O + 20480 + warp * 2560, oa = os + ((lane >> 3) & 1) * 1280 + (lane >> 4) * 128 + (lane & 7) * 16;
#pragma unroll
      for (int s = 0; s < 5; s++) stsm4(oa + s * 256, of[4 * s], of[4 * s + 1], of[4 * s + 2], of[4 * s + 3]);
      asm volatile("fence.proxy.async.shared::cta;" ::: "memory");
      __syncwarp();
      if (elect()) {
        asm volatile("cp.async.bulk.global.shared::cta.bulk_group [%0], [%1], 2560;\ncp.async.bulk.commit_group;" :: "l"(&g_o[mt * 2 + wg][g][w4 * 160]), "r"(os) : "memory");
      }
    }
    TS(5);
    float h[40];
#pragma unroll
    for (int s = 0; s < 5; s++) {
      const uint4 v = xr[s];
      h[8 * s] = bf_lo(v.x); h[8 * s + 1] = bf_hi(v.x); h[8 * s + 2] = bf_lo(v.y); h[8 * s + 3] = bf_hi(v.y);
      h[8 * s + 4] = bf_lo(v.z); h[8 * s + 5] = bf_hi(v.z); h[8 * s + 6] = bf_lo(v.w); h[8 * s + 7] = bf_hi(v.w);
    }
    mbar_wait(bar_full, 0); mbar_wait(bar_full + 8, 0); mbar_wait(bar_full + 16, 1);
    if (elect()) {
      asm volatile("cp.async.bulk.wait_group 0;" ::: "memory");
      asm volatile("red.relaxed.gpu.global.add.u32 [%0], 1;" :: "l"(g_own[mt * 8 + wg * 4].cnt) : "memory");
    }
    asm volatile("bar.arrive %0, 160;" :: "r"(5 + wg) : "memory");
    bar_sync(1, 256);
    const uint64_t dwo = make_desc(sb, 5120, 512, 2);
    wgmma_fence();
#pragma unroll
    for (int s = 0; s < 5; s++) wgmma_n80_rs(h, of[4 * s], of[4 * s + 1], of[4 * s + 2], of[4 * s + 3], dwo + g * 960 + s * 64, 1);
    wgmma_commit();
    TS(6);
#pragma unroll 1
    for (int i = 0, sl = 0; i < 7; i++) {
      mbar_wait(bar_o + wg * 64 + 8 * sl, i >= 3 && i < 6);
      if (i == 0) TS(1);
      const uint64_t da = make_desc(sb + OFF_O + sl * 20480 + wg * 10240, 128, 1280, 0), db = dwo + (i + (i >= g)) * 960;
      wgmma_fence();
#pragma unroll
      for (int s = 0; s < 5; s++) wgmma_n80_ss(h, da + s * 16, db + s * 64, 1);
      wgmma_commit();
      wgmma_wait<1>();
      if ((tid & 127) == 0 && i > 0 && i < 5) mbar_arrive(bar_o + wg * 64 + 24 + 8 * i);
      sl = sl == 2 ? 0 : sl + 1;
    }
    const bool odd = c & 1;
    float wr[20];
#pragma unroll
    for (int j = 0; j < 5; j++) {
      const uint4 v = lds128(sb + OFF_WR + c * 80 + j * 16);
      wr[4 * j] = __uint_as_float(v.x); wr[4 * j + 1] = __uint_as_float(v.y); wr[4 * j + 2] = __uint_as_float(v.z); wr[4 * j + 3] = __uint_as_float(v.w);
    }
    const float wsum = lds32f(sb + OFF_WR + 320);
    uint4* const sp = pin(&g_own[slot].st2[r + (odd ? 8 : 0)]);
    uint4* const cdp = pin(&g_x.cand[slot][g][0]);
    const int tok0 = mt * 128 + 32 * w4 + wg;
    wgmma_wait<0>();
#pragma unroll
    for (int i = 0; i < 40; i++) asm volatile("" : "+f"(h[i]) :: "memory");
    TS(7);
    float mean, rstd, rr;
    {
      float l1 = 0.f, l2 = 0.f, l3 = 0.f, h1 = 0.f, h2 = 0.f, h3 = 0.f;
#pragma unroll
      for (int j = 0; j < 10; j++) {
        l1 += h[4 * j] + h[4 * j + 1]; h1 += h[4 * j + 2] + h[4 * j + 3];
        l2 = fmaf(h[4 * j], h[4 * j], l2); l2 = fmaf(h[4 * j + 1], h[4 * j + 1], l2);
        h2 = fmaf(h[4 * j + 2], h[4 * j + 2], h2); h2 = fmaf(h[4 * j + 3], h[4 * j + 3], h2);
        l3 = fmaf(h[4 * j], wr[2 * j], l3); l3 = fmaf(h[4 * j + 1], wr[2 * j + 1], l3);
        h3 = fmaf(h[4 * j + 2], wr[2 * j], h3); h3 = fmaf(h[4 * j + 3], wr[2 * j + 1], h3);
      }
      float s1 = (odd ? h1 : l1) + shx(odd ? l1 : h1, 1), s2 = (odd ? h2 : l2) + shx(odd ? l2 : h2, 1), s3 = (odd ? h3 : l3) + shx(odd ? l3 : h3, 1);
      s1 += shx(s1, 2); s2 += shx(s2, 2); s3 += shx(s3, 2);
      if (cA) asm volatile("red.relaxed.gpu.global.add.v4.f32 [%0], {%1, %2, %3, %4};" :: "l"(sp), "f"(s1), "f"(s2), "f"(s3), "f"(1.f) : "memory");
      uint4 p0;
      do { p0 = ldg_pkt(sp); } while (anyw(p0.w != 0x41000000u) && --guard > 0);
      mean = __uint_as_float(p0.x) * (1.f / 640.f);
      rstd = rsq(fmaxf(fmaf(-mean, mean, __uint_as_float(p0.y) * (1.f / 640.f)), 0.f) + 1e-5f);
      rr = fmaf(-mean, wsum, __uint_as_float(p0.z)) * rstd;
    }
    TS(8);
    const uint32_t kk = ord_key(rr), kmax = __reduce_max_sync(0xffffffffu, kk);
    const int L = __ffs(__ballot_sync(0xffffffffu, kk == kmax)) - 1;
    const int crow = (L >> 2) + 8 * (L & 1);
    if (warp == g) {
      if (elect()) {
        asm volatile("red.relaxed.gpu.global.max.u64 [%0], %1;" :: "l"(g_own[1].cnt), "l"(((uint64_t)kmax << 32) | (uint32_t)(2047 - tok0 - 2 * crow)) : "memory");
        asm volatile("red.relaxed.gpu.global.add.u32 [%0], 1;" :: "l"(&g_own[1].cnt[0].z) : "memory");
      }
      asm volatile("bar.arrive 3, 64;" ::: "memory");
    }
    const uint32_t stg = sb + OFF_O + warp * 2560;
    uint4 held;
    {
      const float om = shx(mean, 1), os = shx(rstd, 1);
      const float rl = odd ? os : rstd, rh = odd ? rstd : os;
      const float bl = -(odd ? om : mean) * rl, bh = -(odd ? mean : om) * rh, al = 1.f + rl, ah = 1.f + rh;
      if ((L >> 2) == r) {
        const bool chi = L & 1;
        const float rc = chi ? rh : rl, bc = chi ? bh : bl;
        uint32_t n[10];
#pragma unroll
        for (int j = 0; j < 10; j++) n[j] = pack_bf16(fmaf(chi ? h[4 * j + 2] : h[4 * j], rc, bc), fmaf(chi ? h[4 * j + 3] : h[4 * j + 1], rc, bc));
        uint4* d = cdp + c;
        stg_pkt(d, n[0], n[1], n[2], n[3]); stg_pkt(d + 4, n[4], n[5], n[6], n[7]); stg_rlx64(d + 8, n[8], n[9]);
      }
      __syncwarp();
      const uint32_t fa = stg + (lane & 15) * 160 + (lane >> 4) * 16;
#pragma unroll
      for (int s = 0; s < 5; s++)
        stsm4(fa + s * 32, pack_bf16(fmaf(h[8 * s], al, bl), fmaf(h[8 * s + 1], al, bl)), pack_bf16(fmaf(h[8 * s + 2], ah, bh), fmaf(h[8 * s + 3], ah, bh)),
              pack_bf16(fmaf(h[8 * s + 4], al, bl), fmaf(h[8 * s + 5], al, bl)), pack_bf16(fmaf(h[8 * s + 6], ah, bh), fmaf(h[8 * s + 7], ah, bh)));
      __syncwarp();
      held = lds128(stg + crow * 160 + min(lane, 9) * 16);
      if (lane < 10) stg_pkt(cdp + 12 + lane, held.x, held.y, held.z, held.w);
    }
    TS(9);
    mbar_wait(bar_ffn, 0);
    const uint32_t red = sb + OFF_RED;
    if (ffn1) {
      uint4 w1[4][5];
      {
        const int k = (lane & 7) + (lane >> 4) * 8;
        const uint32_t a1 = sb + k * 64, sw = ((lane >> 3) & 1) ^ ((lane >> 1) & 3);
#pragma unroll
        for (int s = 0; s < 5; s++)
#pragma unroll
          for (int u = 0; u < 4; u++)
            w1[u][s] = ldsm4t(a1 + (s < 4 ? warp * 4096 + s * 1024 : 32768 + warp * 1024) + (u >> 1) * (40960 + (s == 4 || warp >= 2 ? OFF_W2 - 49152 : 0)) + ((sw ^ (2 * (u & 1))) * 16));
      }
      uint32_t* const ap = pin(g_x.act + fj * 16 + (lane >> 1));
      mbar_wait(bar_win, 0);
      const uint32_t hp = sb + OFF_HN + (warp * 4 + c) * 16;
      const uint4 c0 = lds128(hp), c1 = lds128(hp + 512), c2 = lds128(hp + 1024);
      TS(10);
      float a[4][4];
#pragma unroll
      for (int u = 0; u < 4; u++) {
        a[u][0] = a[u][1] = a[u][2] = a[u][3] = 0.f;
        mma_acc(a[u], w1[u][0], c0.x, c0.y); mma_acc(a[u], w1[u][1], c0.z, c0.w); mma_acc(a[u], w1[u][2], c1.x, c1.y);
        mma_acc(a[u], w1[u][3], c1.z, c1.w); mma_acc(a[u], w1[u][4], c2.x, c2.y);
      }
      asm volatile("st.shared.v2.f32 [%0], {%1, %2};" :: "r"(red + (warp * 32 + c * 8 + r) * 8),
                   "f"(cA ? (odd ? a[0][2] : a[0][0]) : (odd ? a[1][2] : a[1][0])), "f"(cA ? (odd ? a[2][2] : a[2][0]) : (odd ? a[3][2] : a[3][0])) : "memory");
      bar_sync(1, 256);
      if (warp == 0) {
        float2 t[8];
#pragma unroll
        for (int i = 0; i < 8; i++) t[i] = lds64f(red + (i * 32 + lane) * 8);
        const float s = ((t[0].x + t[1].x) + (t[2].x + t[3].x)) + ((t[4].x + t[5].x) + (t[6].x + t[7].x));
        const float u = ((t[0].y + t[1].y) + (t[2].y + t[3].y)) + ((t[4].y + t[5].y) + (t[6].y + t[7].y));
        const float av = s * u * rcp(1.f + ex2(-1.4426950408889634f * s));
        const float an = shx(av, 1);
        if (!odd) stg_rlx32(ap, pack_bf16(av, an));
      }
      bar_sync(1, 256);
      TS(11);
    }
    if (OUT_LATE) mbar_wait(bar_win, 0);
    char* const ob2 = (char*)(out + tok0 * 640 + g * 64);
    const int remo = 896 - 96 * g;
#pragma unroll
    for (int s = 0; s < 5; s++) {
      const int row = s < 4 ? 4 * s + (lane >> 3) : lane >> 1, pc = s < 4 ? lane & 7 : 8 + (lane & 1);
      const uint4 v = lds128(stg + row * 160 + pc * 16);
      if (row != crow) stg128(ob2 + row * 2560 + pc * 16 + (s < 4 ? 0 : remo), v);
    }
    mbar_wait(bar_win, 0);
    const uint4 win = lds128(sb + OFF_WR + 336);
    if (win.x != slot && lane < 10) stg128(ob2 + crow * 2560 + lane * 16 + (lane < 8 ? 0 : remo), held);
    if (!ffn1) {
      TS(10);
      uint4 w2[6];
      const uint32_t a2 = sb + OFF_W2 + (warp * 192 + 8 * (((lane >> 3) & 1) * 4 + ((lane & 7) >> 1)) + 2 * (lane >> 4) + (lane & 1)) * 16;
#pragma unroll
      for (int s = 0; s < 6; s++) w2[s] = ldsm4t(a2 + (s >> 1) * 1024 + (s & 1) * 64);
      const uint4* p = (const uint4*)(g_x.act + warp * 96) + (r & 1) * 4 + c;
      const uint32_t* pb = (const uint32_t*)&g_x.cand[win.x][fj < 64 ? fj >> 3 : (fj - 64) >> 1][fj < 64 ? 12 + (fj & 7) : 20 + (fj & 1)] + c;
      uint32_t* const op = pin((uint32_t*)(out + win.y * 640 + fj * 8) + c);
      uint4 c0, c1, c2; uint32_t bw;
      if (ACT_NS) __nanosleep(ACT_NS);
      do {
        c0 = ldg_pkt(p); c1 = ldg_pkt(p + 8); c2 = ldg_pkt(p + 16); bw = ldg_rlx32(pb);
      } while (anyw(max(max(max(max(c0.x, c0.y), max(c0.z, c0.w)), max(max(c1.x, c1.y), max(c1.z, c1.w))), max(max(max(c2.x, c2.y), max(c2.z, c2.w)), bw)) == SENT) && --guard > 0);
      TS(11);
      float a[4] = {0.f, 0.f, 0.f, 0.f}, b[4] = {0.f, 0.f, 0.f, 0.f}, d[4] = {0.f, 0.f, 0.f, 0.f};
      mma_acc(a, w2[0], c0.x, c0.y); mma_acc(b, w2[2], c1.x, c1.y); mma_acc(d, w2[4], c2.x, c2.y);
      mma_acc(a, w2[1], c0.z, c0.w); mma_acc(b, w2[3], c1.z, c1.w); mma_acc(d, w2[5], c2.z, c2.w);
      if (c == 0) sts32f(red + (warp * 8 + r) * 4, ((a[0] + a[3]) + (b[0] + b[3])) + (d[0] + d[3]));
      bar_sync(1, 256);
      if (tid < 4) {
        float2 t[8];
#pragma unroll
        for (int i = 0; i < 8; i++) t[i] = lds64f(red + (i * 4 + tid) * 8);
        const float y0 = ((t[0].x + t[1].x) + (t[2].x + t[3].x)) + ((t[4].x + t[5].x) + (t[6].x + t[7].x));
        const float y1 = ((t[0].y + t[1].y) + (t[2].y + t[3].y)) + ((t[4].y + t[5].y) + (t[6].y + t[7].y));
        const float sg = __uint_as_float(win.z);
        *op = pack_bf16(fmaf(y0, sg, bf_lo(bw)), fmaf(y1, sg, bf_hi(bw)));
      }
    }
    TS(12);
#undef TS_T
  }
}

typedef CUresult (*EncodeFn)(CUtensorMap*, CUtensorMapDataType, cuuint32_t, void*, const cuuint64_t*, const cuuint64_t*, const cuuint32_t*,
                             const cuuint32_t*, CUtensorMapInterleave, CUtensorMapSwizzle, CUtensorMapL2promotion, CUtensorMapFloatOOBfill);

void make_map(EncodeFn enc, CUtensorMap* m, const void* base, const cuuint64_t* dims, const cuuint64_t* strides, const cuuint32_t* box,
              CUtensorMapSwizzle swz) {
  const cuuint32_t es[3] = {1, 1, 1};
  enc(m, CU_TENSOR_MAP_DATA_TYPE_BFLOAT16, 3, (void*)base, dims, strides, box, es, CU_TENSOR_MAP_INTERLEAVE_NONE, swz,
      CU_TENSOR_MAP_L2_PROMOTION_L2_128B, CU_TENSOR_MAP_FLOAT_OOB_FILL_NONE);
}

}

extern "C" void kernel_launch(void* const* d_in, const int* in_sizes, int n_in, void* d_out, int out_size) {
  const __nv_bfloat16* x = (const __nv_bfloat16*)d_in[0];
  const __nv_bfloat16* wqkv = (const __nv_bfloat16*)d_in[1];
  const __nv_bfloat16* wo = (const __nv_bfloat16*)d_in[2];
  void* fn = nullptr;
  cudaDriverEntryPointQueryResult st;
  cudaGetDriverEntryPoint("cuTensorMapEncodeTiled", &fn, cudaEnableDefault, &st);
  EncodeFn enc = (EncodeFn)fn;
  void* scp = nullptr;
  cudaGetSymbolAddress(&scp, g_scratch);
  Maps tm;
  { const cuuint64_t d[3] = {640, 1024, 2}, s[2] = {2560, 1280}; const cuuint32_t b[3] = {64, 64, 2}; make_map(enc, &tm.x, x, d, s, b, CU_TENSOR_MAP_SWIZZLE_128B); }
  { const cuuint64_t d[3] = {640, 640, 3}, s[2] = {3840, 1280}; const cuuint32_t b[3] = {64, 64, 1}; make_map(enc, &tm.w, wqkv, d, s, b, CU_TENSOR_MAP_SWIZZLE_128B); }
  { const cuuint64_t d[3] = {640, 640, 3}, s[2] = {3840, 1280}; const cuuint32_t b[3] = {16, 64, 3}; make_map(enc, &tm.wr, wqkv, d, s, b, CU_TENSOR_MAP_SWIZZLE_32B); }
  { const cuuint64_t d[3] = {32, 640, 20}, s[2] = {1280, 64}; const cuuint32_t b[3] = {32, 80, 2}; make_map(enc, &tm.wo, wo, d, s, b, CU_TENSOR_MAP_SWIZZLE_64B); }
  { const cuuint64_t d[3] = {640, 640, 1}, s[2] = {1280, 819200}; const cuuint32_t b[3] = {16, 80, 1}; make_map(enc, &tm.wor, wo, d, s, b, CU_TENSOR_MAP_SWIZZLE_64B); }
  { const cuuint64_t d[3] = {1536, 640, 1}, s[2] = {3072, 1966080}; const cuuint32_t b[3] = {32, 128, 1};
    make_map(enc, &tm.gate, d_in[5], d, s, b, CU_TENSOR_MAP_SWIZZLE_64B); make_map(enc, &tm.up, d_in[6], d, s, b, CU_TENSOR_MAP_SWIZZLE_64B); }
  { const cuuint64_t d[3] = {640, 1536, 1}, s[2] = {1280, 1966080}; const cuuint32_t b[3] = {8, 128, 1}; make_map(enc, &tm.down, d_in[7], d, s, b, CU_TENSOR_MAP_SWIZZLE_NONE); }
  cudaFuncSetAttribute(fused_kernel, cudaFuncAttributeMaxDynamicSharedMemorySize, SMEM_BYTES);
  fused_kernel<<<128, 512, SMEM_BYTES, cudaStreamPerThread>>>(x, wqkv, wo, (const __nv_bfloat16*)d_in[4], (const __nv_bfloat16*)d_in[5],
                                                              (const __nv_bfloat16*)d_in[6], (const __nv_bfloat16*)d_in[7], (__nv_bfloat16*)d_out, (Scratch*)scp, tm);
}
```

```cpp
#include <cuda_runtime.h>
#include <cuda_bf16.h>
#include <cuda.h>
#include <stdint.h>

#define PFW_NS 100
#define ACT_NS 0
#define OUT_LATE 0
#define REG_P 72
#define REG_C 184
#define AUX_NS 50
#define LEAD 1
#define RST_IT 3
#define ORDX 1
#define THR 2
#define PF_FIRST 3
#define PF_T0 1700
#define PF_CLK 500
#define HK_IT 1
#define F_IT 7
#define F_PER 2
#define F_MAX 12
#define LK 4

namespace {

constexpr int SLOT    = 47104;
constexpr int OFF_O   = 122880;
constexpr int OFF_W2  = 4 * SLOT;
constexpr int OFF_CS  = OFF_W2 + 32768;
constexpr int OFF_RS  = OFF_CS + 3840;
constexpr int OFF_MN  = OFF_RS + 576;
constexpr int OFF_WR  = OFF_MN + 1024;
constexpr int OFF_RED = OFF_CS;
constexpr int OFF_HN  = OFF_CS + 2048;
constexpr int OFF_PT  = OFF_WR + 352;
constexpr int OFF_BAR = OFF_PT + 768;
constexpr int SMEM_BYTES = OFF_BAR + 240 + 384;
constexpr uint32_t D0 = 1024 >> 4;
constexpr uint32_t SENT = 0xFFFFFFFFu;
constexpr int SPIN_MAX = 1 << 20;

struct Glob {
  uint4 cand[128][8][24];
  uint32_t act[768];
  uint32_t pad[256];
};
constexpr int GLOB_PER_CTA = sizeof(Glob) / 16 / 128;
static_assert(GLOB_PER_CTA * 128 * 16 == sizeof(Glob), "glob size");
struct Own {
  uint4 halo[2][5][32];
  uint4 st1[32];
  uint2 cs[32];
  uint4 st2[16];
  uint4 cnt[8];
};
struct Scratch {
  Glob x;
  Own own[128];
  uint4 o[32][8][640];
  uint32_t epoch[128];
};
__device__ __align__(128) Scratch g_scratch;
#define g_x (sc->x)
#define g_own (sc->own)
#define g_o (sc->o)
#define g_epoch (sc->epoch)
#define TS(i)

__device__ __forceinline__ void mbar_init(uint32_t bar, uint32_t cnt) { asm volatile("mbarrier.init.shared::cta.b64 [%0], %1;" :: "r"(bar), "r"(cnt) : "memory"); }
__device__ __forceinline__ void mbar_expect_tx(uint32_t bar, uint32_t bytes) { asm volatile("mbarrier.arrive.expect_tx.shared::cta.b64 _, [%0], %1;" :: "r"(bar), "r"(bytes) : "memory"); }
__device__ __forceinline__ void mbar_arrive(uint32_t bar) { asm volatile("mbarrier.arrive.shared::cta.b64 _, [%0];" :: "r"(bar) : "memory"); }
__device__ __forceinline__ void mbar_arrive_cta(uint32_t bar, uint32_t cta) {
  asm volatile("{\n.reg .b32 ra;\nmapa.shared::cluster.u32 ra, %0, %1;\nmbarrier.arrive.shared::cluster.b64 _, [ra];\n}\n" :: "r"(bar), "r"(cta) : "memory");
}
__device__ __forceinline__ void mbar_wait(uint32_t bar, uint32_t parity) {
  asm volatile("{\n.reg .pred p;\n.reg .u32 n;\nmov.u32 n, 0;\nW:\nmbarrier.try_wait.parity.shared::cta.b64 p, [%0], %1;\n@p bra.uni D;\n"
               "add.u32 n, n, 1;\nsetp.lt.u32 p, n, %2;\n@p bra.uni W;\nD:\n}\n" :: "r"(bar), "r"(parity), "n"(SPIN_MAX) : "memory");
}
__device__ __forceinline__ void tma_3d(uint32_t dst, const void* tm, uint32_t bar, int c0, int c1, int c2) {
  asm volatile("cp.async.bulk.tensor.3d.shared::cluster.global.mbarrier::complete_tx::bytes [%0], [%1, {%3, %4, %5}], [%2];" :: "r"(dst), "l"(tm), "r"(bar), "r"(c0), "r"(c1), "r"(c2) : "memory");
}
__device__ __forceinline__ void tma_3d_mc(uint32_t dst, const void* tm, uint32_t bar, int c0, int c1, int c2) {
  asm volatile("cp.async.bulk.tensor.3d.shared::cluster.global.mbarrier::complete_tx::bytes.multicast::cluster [%0], [%1, {%3, %4, %5}], [%2], %6;" :: "r"(dst), "l"(tm), "r"(bar), "r"(c0), "r"(c1), "r"(c2), "h"((uint16_t)3) : "memory");
}
__device__ __forceinline__ void wgmma_fence() { asm volatile("wgmma.fence.sync.aligned;" ::: "memory"); }
__device__ __forceinline__ void wgmma_commit() { asm volatile("wgmma.commit_group.sync.aligned;" ::: "memory"); }
template <int N> __device__ __forceinline__ void wgmma_wait() { asm volatile("wgmma.wait_group.sync.aligned %0;" :: "n"(N) : "memory"); }
__device__ __forceinline__ uint64_t make_desc(uint32_t addr, uint32_t lbo, uint32_t sbo, uint32_t swz) {
  return (uint64_t)(((addr & 0x3FFFF) >> 4) | ((lbo >> 4) << 16)) | ((uint64_t)((sbo >> 4) | (swz << 30)) << 32);
}
__device__ __forceinline__ void bar_sync(int id, int n) { asm volatile("bar.sync %0, %1;" :: "r"(id), "r"(n) : "memory"); }
__device__ __forceinline__ uint4 ld_pkt(const void* p) {
  uint4 v;
  asm volatile("{\n.reg .b128 t;\n.reg .b64 lo, hi;\nld.relaxed.gpu.b128 t, [%4];\nmov.b128 {lo, hi}, t;\nmov.b64 {%0, %1}, lo;\nmov.b64 {%2, %3}, hi;\n}\n"
               : "=r"(v.x), "=r"(v.y), "=r"(v.z), "=r"(v.w) : "l"(p) : "memory");
  return v;
}
__device__ __forceinline__ void st_pkt(void* p, uint32_t a, uint32_t b, uint32_t c, uint32_t d) {
  asm volatile("{\n.reg .b128 t;\n.reg .b64 lo, hi;\nmov.b64 lo, {%1, %2};\nmov.b64 hi, {%3, %4};\nmov.b128 t, {lo, hi};\nst.relaxed.gpu.b128 [%0], t;\n}\n"
               :: "l"(p), "r"(a), "r"(b), "r"(c), "r"(d) : "memory");
}
__device__ __forceinline__ uint4 ldg_pkt(const void* p) {
  uint4 v;
  asm volatile("{\n.reg .b128 t;\n.reg .b64 lo, hi;\nld.relaxed.gpu.global.b128 t, [%4];\nmov.b128 {lo, hi}, t;\nmov.b64 {%0, %1}, lo;\nmov.b64 {%2, %3}, hi;\n}\n"
               : "=r"(v.x), "=r"(v.y), "=r"(v.z), "=r"(v.w) : "l"(p) : "memory");
  return v;
}
__device__ __forceinline__ void stg_pkt(void* p, uint32_t a, uint32_t b, uint32_t c, uint32_t d) {
  asm volatile("{\n.reg .b128 t;\n.reg .b64 lo, hi;\nmov.b64 lo, {%1, %2};\nmov.b64 hi, {%3, %4};\nmov.b128 t, {lo, hi};\nst.relaxed.gpu.global.b128 [%0], t;\n}\n"
               :: "l"(p), "r"(a), "r"(b), "r"(c), "r"(d) : "memory");
}
__device__ __forceinline__ uint32_t ldg_rlx32(const void* p) { uint32_t v; asm volatile("ld.relaxed.gpu.global.u32 %0, [%1];" : "=r"(v) : "l"(p) : "memory"); return v; }
__device__ __forceinline__ uint2 ldg_rlx64(const void* p) { uint2 v; asm volatile("ld.relaxed.gpu.global.v2.u32 {%0, %1}, [%2];" : "=r"(v.x), "=r"(v.y) : "l"(p) : "memory"); return v; }
__device__ __forceinline__ void stg128(void* p, const uint4& v) { asm volatile("st.global.v4.u32 [%0], {%1, %2, %3, %4};" :: "l"(p), "r"(v.x), "r"(v.y), "r"(v.z), "r"(v.w) : "memory"); }
__device__ __forceinline__ uint32_t pin(uint32_t v) { asm volatile("" : "+r"(v)); return v; }
__device__ __forceinline__ uint64_t mk64(uint32_t lo, uint32_t hi) { return ((uint64_t)hi << 32) | lo; }
template <class T> __device__ __forceinline__ T* pin(T* p) { asm volatile("" : "+l"(p)); return p; }
__device__ __forceinline__ void stg_rlx32(void* p, uint32_t v) { asm volatile("st.relaxed.gpu.global.u32 [%0], %1;" :: "l"(p), "r"(v) : "memory"); }
__device__ __forceinline__ void stg_rlx64(void* p, uint32_t a, uint32_t b) { asm volatile("st.relaxed.gpu.global.v2.u32 [%0], {%1, %2};" :: "l"(p), "r"(a), "r"(b) : "memory"); }
__device__ __forceinline__ uint4 ldsm4(uint32_t a) { uint4 v; asm volatile("ldmatrix.sync.aligned.m8n8.x4.shared.b16 {%0, %1, %2, %3}, [%4];" : "=r"(v.x), "=r"(v.y), "=r"(v.z), "=r"(v.w) : "r"(a) : "memory"); return v; }
__device__ __forceinline__ void ldsm4_if(uint4& v, uint32_t a, int off, bool p) {
  asm volatile("{\n.reg .pred q;\nsetp.ne.u32 q, %5, 0;\n@q ldmatrix.sync.aligned.m8n8.x4.shared.b16 {%0, %1, %2, %3}, [%4];\n}\n"
               : "+r"(v.x), "+r"(v.y), "+r"(v.z), "+r"(v.w) : "r"(a + off), "r"((int)p) : "memory");
}
__device__ __forceinline__ uint4 ldsm4t(uint32_t a) { uint4 v; asm volatile("ldmatrix.sync.aligned.m8n8.x4.trans.shared.b16 {%0, %1, %2, %3}, [%4];" : "=r"(v.x), "=r"(v.y), "=r"(v.z), "=r"(v.w) : "r"(a) : "memory"); return v; }
__device__ __forceinline__ void stsm4(uint32_t a, uint32_t x, uint32_t y, uint32_t z, uint32_t w) { asm volatile("stmatrix.sync.aligned.m8n8.x4.shared.b16 [%0], {%1, %2, %3, %4};" :: "r"(a), "r"(x), "r"(y), "r"(z), "r"(w) : "memory"); }
__device__ __forceinline__ void mma_acc(float (&c)[4], const uint4& a, uint32_t b0, uint32_t b1) {
  asm("mma.sync.aligned.m16n8k16.row.col.f32.bf16.bf16.f32 {%0,%1,%2,%3}, {%4,%5,%6,%7}, {%8,%9}, {%0,%1,%2,%3};"
      : "+f"(c[0]), "+f"(c[1]), "+f"(c[2]), "+f"(c[3]) : "r"(a.x), "r"(a.y), "r"(a.z), "r"(a.w), "r"(b0), "r"(b1));
}
__device__ __forceinline__ uint4 lds128(uint32_t a) { uint4 v; asm volatile("ld.shared.v4.u32 {%0, %1, %2, %3}, [%4];" : "=r"(v.x), "=r"(v.y), "=r"(v.z), "=r"(v.w) : "r"(a) : "memory"); return v; }
__device__ __forceinline__ float2 lds64f(uint32_t a) { float2 v; asm volatile("ld.shared.v2.f32 {%0, %1}, [%2];" : "=f"(v.x), "=f"(v.y) : "r"(a)); return v; }
__device__ __forceinline__ float lds32f(uint32_t a) { float v; asm volatile("ld.shared.f32 %0, [%1];" : "=f"(v) : "r"(a)); return v; }
__device__ __forceinline__ void sts32f(uint32_t a, float v) { asm volatile("st.shared.f32 [%0], %1;" :: "r"(a), "f"(v) : "memory"); }
__device__ __forceinline__ uint32_t pack_bf16(float lo, float hi) { uint32_t r; asm("cvt.rn.bf16x2.f32 %0, %1, %2;" : "=r"(r) : "f"(hi), "f"(lo)); return r; }
__device__ __forceinline__ float bf_lo(uint32_t v) { return __uint_as_float(v << 16); }
__device__ __forceinline__ float bf_hi(uint32_t v) { return __uint_as_float(v & 0xffff0000u); }
__device__ __forceinline__ uint32_t movm(uint32_t a) { uint32_t d; asm("movmatrix.sync.aligned.m8n8.trans.b16 %0, %1;" : "=r"(d) : "r"(a)); return d; }
__device__ __forceinline__ float ex2(float x) { float y; asm("ex2.approx.ftz.f32 %0, %1;" : "=f"(y) : "f"(x)); return y; }
__device__ __forceinline__ float rsq(float x) { float y; asm("rsqrt.approx.ftz.f32 %0, %1;" : "=f"(y) : "f"(x)); return y; }
__device__ __forceinline__ float rcp(float x) { float y; asm("rcp.approx.ftz.f32 %0, %1;" : "=f"(y) : "f"(x)); return y; }
__device__ __forceinline__ bool elect() { uint32_t p; asm volatile("{\n.reg .pred q;\nelect.sync _|q, 0xffffffff;\nselp.u32 %0, 1, 0, q;\n}\n" : "=r"(p)); return p; }
__device__ __forceinline__ int clk() { int c; asm volatile("mov.u32 %0, %%clock;" : "=r"(c) :: "memory"); return c; }
__device__ __forceinline__ void pf_l2(const void* p) { asm volatile("prefetch.global.L2 [%0];" :: "l"(p)); }
__device__ __forceinline__ bool anyw(bool p) { return __any_sync(0xffffffffu, p); }
__device__ __forceinline__ float shx(float v, int m) { return __shfl_xor_sync(0xffffffffu, v, m); }
__device__ __forceinline__ void mma_k24(float (&c)[4], uint32_t a0, uint32_t a1, uint32_t a2, uint32_t a3, uint32_t b0, uint32_t b1,
                                        uint32_t e0, uint32_t e1, uint32_t f0) {
  asm("mma.sync.aligned.m16n8k16.row.col.f32.bf16.bf16.f32 {%0,%1,%2,%3}, {%4,%5,%6,%7}, {%8,%9}, {%10,%10,%10,%10};"
      : "=f"(c[0]), "=f"(c[1]), "=f"(c[2]), "=f"(c[3]) : "r"(a0), "r"(a1), "r"(a2), "r"(a3), "r"(b0), "r"(b1), "f"(0.f));
  asm("mma.sync.aligned.m16n8k8.row.col.f32.bf16.bf16.f32 {%0,%1,%2,%3}, {%4,%5}, {%6}, {%0,%1,%2,%3};"
      : "+f"(c[0]), "+f"(c[1]), "+f"(c[2]), "+f"(c[3]) : "r"(e0), "r"(e1), "r"(f0));
}
__device__ __forceinline__ uint32_t ord_key(float r) { uint32_t u = __float_as_uint(r); return u ^ ((uint32_t)((int32_t)u >> 31) | 0x80000000u); }

__device__ __forceinline__ void wgmma_n48hi_ss(float (&d)[120], uint64_t da, uint64_t db, int scale_d) {
  asm volatile("{\n.reg .pred p;\nsetp.ne.b32 p, %26, 0;\n"
    "wgmma.mma_async.sync.aligned.m64n48k16.f32.bf16.bf16 "
    "{%0, %1, %2, %3, %4, %5, %6, %7, %8, %9, %10, %11, %12, %13, %14, %15, "
    "%16, %17, %18, %19, %20, %21, %22, %23}, "
    "%24, %25, p, 1, 1, 0, 1;\n}\n"
    : "+f"(d[96]), "+f"(d[97]), "+f"(d[98]), "+f"(d[99]), "+f"(d[100]), "+f"(d[101]), "+f"(d[102]), "+f"(d[103]),
      "+f"(d[104]), "+f"(d[105]), "+f"(d[106]), "+f"(d[107]), "+f"(d[108]), "+f"(d[109]), "+f"(d[110]), "+f"(d[111]),
      "+f"(d[112]), "+f"(d[113]), "+f"(d[114]), "+f"(d[115]), "+f"(d[116]), "+f"(d[117]), "+f"(d[118]), "+f"(d[119])
    : "l"(da), "l"(db), "r"(scale_d));
}
__device__ __forceinline__ void wgmma_n192lo_ss(float (&d)[120], uint64_t da, uint64_t db, int scale_d) {
  asm volatile("{\n.reg .pred p;\nsetp.ne.b32 p, %98, 0;\n"
    "wgmma.mma_async.sync.aligned.m64n192k16.f32.bf16.bf16 "
    "{%0, %1, %2, %3, %4, %5, %6, %7, %8, %9, %10, %11, %12, %13, %14, %15, "
    "%16, %17, %18, %19, %20, %21, %22, %23, %24, %25, %26, %27, %28, %29, %30, %31, "
    "%32, %33, %34, %35, %36, %37, %38, %39, %40, %41, %42, %43, %44, %45, %46, %47, "
    "%48, %49, %50, %51, %52, %53, %54, %55, %56, %57, %58, %59, %60, %61, %62, %63, "
    "%64, %65, %66, %67, %68, %69, %70, %71, %72, %73, %74, %75, %76, %77, %78, %79, "
    "%80, %81, %82, %83, %84, %85, %86, %87, %88, %89, %90, %91, %92, %93, %94, %95}, "
    "%96, %97, p, 1, 1, 0, 1;\n}\n"
    : "+f"(d[0]), "+f"(d[1]), "+f"(d[2]), "+f"(d[3]), "+f"(d[4]), "+f"(d[5]), "+f"(d[6]), "+f"(d[7]),
      "+f"(d[8]), "+f"(d[9]), "+f"(d[10]), "+f"(d[11]), "+f"(d[12]), "+f"(d[13]), "+f"(d[14]), "+f"(d[15]),
      "+f"(d[16]), "+f"(d[17]), "+f"(d[18]), "+f"(d[19]), "+f"(d[20]), "+f"(d[21]), "+f"(d[22]), "+f"(d[23]),
      "+f"(d[24]), "+f"(d[25]), "+f"(d[26]), "+f"(d[27]), "+f"(d[28]), "+f"(d[29]), "+f"(d[30]), "+f"(d[31]),
      "+f"(d[32]), "+f"(d[33]), "+f"(d[34]), "+f"(d[35]), "+f"(d[36]), "+f"(d[37]), "+f"(d[38]), "+f"(d[39]),
      "+f"(d[40]), "+f"(d[41]), "+f"(d[42]), "+f"(d[43]), "+f"(d[44]), "+f"(d[45]), "+f"(d[46]), "+f"(d[47]),
      "+f"(d[48]), "+f"(d[49]), "+f"(d[50]), "+f"(d[51]), "+f"(d[52]), "+f"(d[53]), "+f"(d[54]), "+f"(d[55]),
      "+f"(d[56]), "+f"(d[57]), "+f"(d[58]), "+f"(d[59]), "+f"(d[60]), "+f"(d[61]), "+f"(d[62]), "+f"(d[63]),
      "+f"(d[64]), "+f"(d[65]), "+f"(d[66]), "+f"(d[67]), "+f"(d[68]), "+f"(d[69]), "+f"(d[70]), "+f"(d[71]),
      "+f"(d[72]), "+f"(d[73]), "+f"(d[74]), "+f"(d[75]), "+f"(d[76]), "+f"(d[77]), "+f"(d[78]), "+f"(d[79]),
      "+f"(d[80]), "+f"(d[81]), "+f"(d[82]), "+f"(d[83]), "+f"(d[84]), "+f"(d[85]), "+f"(d[86]), "+f"(d[87]),
      "+f"(d[88]), "+f"(d[89]), "+f"(d[90]), "+f"(d[91]), "+f"(d[92]), "+f"(d[93]), "+f"(d[94]), "+f"(d[95])
    : "l"(da), "l"(db), "r"(scale_d));
}
__device__ __forceinline__ void wgmma_n48hi_rk(float (&d)[120], uint32_t a0, uint32_t a1, uint32_t a2, uint32_t a3, uint64_t db, int scale_d) {
  asm volatile("{\n.reg .pred p;\nsetp.ne.b32 p, %29, 0;\n"
    "wgmma.mma_async.sync.aligned.m64n48k16.f32.bf16.bf16 "
    "{%0, %1, %2, %3, %4, %5, %6, %7, %8, %9, %10, %11, %12, %13, %14, %15, "
    "%16, %17, %18, %19, %20, %21, %22, %23}, "
    "{%24, %25, %26, %27}, %28, p, 1, 1, 0;\n}\n"
    : "+f"(d[96]), "+f"(d[97]), "+f"(d[98]), "+f"(d[99]), "+f"(d[100]), "+f"(d[101]), "+f"(d[102]), "+f"(d[103]),
      "+f"(d[104]), "+f"(d[105]), "+f"(d[106]), "+f"(d[107]), "+f"(d[108]), "+f"(d[109]), "+f"(d[110]), "+f"(d[111]),
      "+f"(d[112]), "+f"(d[113]), "+f"(d[114]), "+f"(d[115]), "+f"(d[116]), "+f"(d[117]), "+f"(d[118]), "+f"(d[119])
    : "r"(a0), "r"(a1), "r"(a2), "r"(a3), "l"(db), "r"(scale_d));
}
__device__ __forceinline__ void wgmma_n192lo_rk(float (&d)[120], uint32_t a0, uint32_t a1, uint32_t a2, uint32_t a3, uint64_t db, int scale_d) {
  asm volatile("{\n.reg .pred p;\nsetp.ne.b32 p, %101, 0;\n"
    "wgmma.mma_async.sync.aligned.m64n192k16.f32.bf16.bf16 "
    "{%0, %1, %2, %3, %4, %5, %6, %7, %8, %9, %10, %11, %12, %13, %14, %15, "
    "%16, %17, %18, %19, %20, %21, %22, %23, %24, %25, %26, %27, %28, %29, %30, %31, "
    "%32, %33, %34, %35, %36, %37, %38, %39, %40, %41, %42, %43, %44, %45, %46, %47, "
    "%48, %49, %50, %51, %52, %53, %54, %55, %56, %57, %58, %59, %60, %61, %62, %63, "
    "%64, %65, %66, %67, %68, %69, %70, %71, %72, %73, %74, %75, %76, %77, %78, %79, "
    "%80, %81, %82, %83, %84, %85, %86, %87, %88, %89, %90, %91, %92, %93, %94, %95}, "
    "{%96, %97, %98, %99}, %100, p, 1, 1, 0;\n}\n"
    : "+f"(d[0]), "+f"(d[1]), "+f"(d[2]), "+f"(d[3]), "+f"(d[4]), "+f"(d[5]), "+f"(d[6]), "+f"(d[7]),
      "+f"(d[8]), "+f"(d[9]), "+f"(d[10]), "+f"(d[11]), "+f"(d[12]), "+f"(d[13]), "+f"(d[14]), "+f"(d[15]),
      "+f"(d[16]), "+f"(d[17]), "+f"(d[18]), "+f"(d[19]), "+f"(d[20]), "+f"(d[21]), "+f"(d[22]), "+f"(d[23]),
      "+f"(d[24]), "+f"(d[25]), "+f"(d[26]), "+f"(d[27]), "+f"(d[28]), "+f"(d[29]), "+f"(d[30]), "+f"(d[31]),
      "+f"(d[32]), "+f"(d[33]), "+f"(d[34]), "+f"(d[35]), "+f"(d[36]), "+f"(d[37]), "+f"(d[38]), "+f"(d[39]),
      "+f"(d[40]), "+f"(d[41]), "+f"(d[42]), "+f"(d[43]), "+f"(d[44]), "+f"(d[45]), "+f"(d[46]), "+f"(d[47]),
      "+f"(d[48]), "+f"(d[49]), "+f"(d[50]), "+f"(d[51]), "+f"(d[52]), "+f"(d[53]), "+f"(d[54]), "+f"(d[55]),
      "+f"(d[56]), "+f"(d[57]), "+f"(d[58]), "+f"(d[59]), "+f"(d[60]), "+f"(d[61]), "+f"(d[62]), "+f"(d[63]),
      "+f"(d[64]), "+f"(d[65]), "+f"(d[66]), "+f"(d[67]), "+f"(d[68]), "+f"(d[69]), "+f"(d[70]), "+f"(d[71]),
      "+f"(d[72]), "+f"(d[73]), "+f"(d[74]), "+f"(d[75]), "+f"(d[76]), "+f"(d[77]), "+f"(d[78]), "+f"(d[79]),
      "+f"(d[80]), "+f"(d[81]), "+f"(d[82]), "+f"(d[83]), "+f"(d[84]), "+f"(d[85]), "+f"(d[86]), "+f"(d[87]),
      "+f"(d[88]), "+f"(d[89]), "+f"(d[90]), "+f"(d[91]), "+f"(d[92]), "+f"(d[93]), "+f"(d[94]), "+f"(d[95])
    : "r"(a0), "r"(a1), "r"(a2), "r"(a3), "l"(db), "r"(scale_d));
}
__device__ __forceinline__ void wgmma_n80_rs(float (&d)[40], uint32_t a0, uint32_t a1, uint32_t a2, uint32_t a3, uint64_t db, int scale_d) {
  asm volatile("{\n.reg .pred p;\nsetp.ne.b32 p, %45, 0;\n"
    "wgmma.mma_async.sync.aligned.m64n80k16.f32.bf16.bf16 "
    "{%0, %1, %2, %3, %4, %5, %6, %7, %8, %9, %10, %11, %12, %13, %14, %15, "
    "%16, %17, %18, %19, %20, %21, %22, %23, %24, %25, %26, %27, %28, %29, %30, %31, "
    "%32, %33, %34, %35, %36, %37, %38, %39}, "
    "{%40, %41, %42, %43}, %44, p, 1, 1, 1;\n}\n"
    : "+f"(d[0]), "+f"(d[1]), "+f"(d[2]), "+f"(d[3]), "+f"(d[4]), "+f"(d[5]), "+f"(d[6]), "+f"(d[7]),
      "+f"(d[8]), "+f"(d[9]), "+f"(d[10]), "+f"(d[11]), "+f"(d[12]), "+f"(d[13]), "+f"(d[14]), "+f"(d[15]),
      "+f"(d[16]), "+f"(d[17]), "+f"(d[18]), "+f"(d[19]), "+f"(d[20]), "+f"(d[21]), "+f"(d[22]), "+f"(d[23]),
      "+f"(d[24]), "+f"(d[25]), "+f"(d[26]), "+f"(d[27]), "+f"(d[28]), "+f"(d[29]), "+f"(d[30]), "+f"(d[31]),
      "+f"(d[32]), "+f"(d[33]), "+f"(d[34]), "+f"(d[35]), "+f"(d[36]), "+f"(d[37]), "+f"(d[38]), "+f"(d[39])
    : "r"(a0), "r"(a1), "r"(a2), "r"(a3), "l"(db), "r"(scale_d));
}
__device__ __forceinline__ void wgmma_n80_ss(float (&d)[40], uint64_t da, uint64_t db, int scale_d) {
  asm volatile("{\n.reg .pred p;\nsetp.ne.b32 p, %42, 0;\n"
    "wgmma.mma_async.sync.aligned.m64n80k16.f32.bf16.bf16 "
    "{%0, %1, %2, %3, %4, %5, %6, %7, %8, %9, %10, %11, %12, %13, %14, %15, "
    "%16, %17, %18, %19, %20, %21, %22, %23, %24, %25, %26, %27, %28, %29, %30, %31, "
    "%32, %33, %34, %35, %36, %37, %38, %39}, "
    "%40, %41, p, 1, 1, 0, 1;\n}\n"
    : "+f"(d[0]), "+f"(d[1]), "+f"(d[2]), "+f"(d[3]), "+f"(d[4]), "+f"(d[5]), "+f"(d[6]), "+f"(d[7]),
      "+f"(d[8]), "+f"(d[9]), "+f"(d[10]), "+f"(d[11]), "+f"(d[12]), "+f"(d[13]), "+f"(d[14]), "+f"(d[15]),
      "+f"(d[16]), "+f"(d[17]), "+f"(d[18]), "+f"(d[19]), "+f"(d[20]), "+f"(d[21]), "+f"(d[22]), "+f"(d[23]),
      "+f"(d[24]), "+f"(d[25]), "+f"(d[26]), "+f"(d[27]), "+f"(d[28]), "+f"(d[29]), "+f"(d[30]), "+f"(d[31]),
      "+f"(d[32]), "+f"(d[33]), "+f"(d[34]), "+f"(d[35]), "+f"(d[36]), "+f"(d[37]), "+f"(d[38]), "+f"(d[39])
    : "l"(da), "l"(db), "r"(scale_d));
}

__device__ __forceinline__ constexpr int QT(int t) { return t < 8 ? t : 16 + t; }
__device__ __forceinline__ constexpr int KT(int t) { return t < 8 ? 8 + t : 18 + t; }
__device__ __forceinline__ constexpr int VT(int t) { return t < 8 ? 16 + t : 20 + t; }

struct Maps { CUtensorMap x, w, wr, wo, wor, gate, up, down; };

__global__ void __cluster_dims__(2, 1, 1) __launch_bounds__(512, 1)
fused_kernel(const __nv_bfloat16* __restrict__ x, const __nv_bfloat16* __restrict__ wqkv,
             const __nv_bfloat16* __restrict__ wo, const __nv_bfloat16* __restrict__ w_r, const __nv_bfloat16* __restrict__ w_gate,
             const __nv_bfloat16* __restrict__ w_up, const __nv_bfloat16* __restrict__ w_down, __nv_bfloat16* __restrict__ out,
             Scratch* __restrict__ sc, const __grid_constant__ Maps tm) {
  extern __shared__ __align__(1024) uint8_t smem[];
  const int tid = threadIdx.x, warp = __shfl_sync(0xffffffffu, tid >> 5, 0), lane = tid & 31, bid = blockIdx.x;
  const uint32_t sb = (uint32_t)__cvta_generic_to_shared(smem);
  const uint32_t bar_full = sb + OFF_BAR, bar_empty = bar_full + 32, bar_aux = bar_full + 64, bar_ffn = bar_full + 72, bar_win = bar_full + 80, bar_rst = bar_full + 88,
                 bar_o = bar_full + 96;
  if (warp < 4 && elect()) {
    mbar_init(bar_full + 8 * (warp ^ 2), 1);
    mbar_init(bar_empty + 8 * warp, 24);
    mbar_init(bar_aux + 8 * warp, warp == 0 ? 64 : warp == 2 ? 32 : 1);
    asm volatile("fence.mbarrier_init.release.cluster;" ::: "memory");
  }
  if (warp >= 4 && warp < 12 && elect()) { mbar_init(bar_o + 16 * (warp - 4), (warp & 2) ? 4 : 1); mbar_init(bar_o + 16 * (warp - 4) + 8, (warp & 2) ? 4 : (warp & 1) ? 128 : 1); }
  asm volatile("barrier.cluster.arrive.relaxed.aligned;" ::: "memory");
  if (warp >= 8 && warp < 11 && elect()) asm volatile("prefetch.tensormap [%0];" :: "l"(&tm.x + (warp - 8)) : "memory");
  auto pf_slice = [&](int ks) {
    pf_l2(lane < 16 ? (const char*)x + ((bid * 16 + lane) * 1280 + ks * 128) : (const char*)wqkv + ((bid * 15 + min(lane, 30) - 16) * 128 + ks * 245760));
  };
  if (warp == 4) pf_slice(0);
  const int rank = bid & 1, cl = bid >> 1;
  const int q7 = ((cl - 36) * 37) >> 8;
  const int P = cl < 4 ? 0 : cl < 36 ? (cl - 4) & 7 : cl - 35 - 7 * q7;
  const int g = cl < 4 ? 4 + cl : cl < 36 ? (cl - 4) >> 3 : 4 + q7;
  const int mt = 2 * P + rank, cid = mt * 8 + g;
  const bool ffn1 = g < 3;
  const int fj = ffn1 ? mt * 3 + g : (P * 5 + g - 3) * 2 + rank;
  const int ord = ((g >> 2) ^ P) & 1;
  auto ks_of = [&](int it) { return !ORDX || ord == 0 || it == 0 ? it : it <= 5 ? it + 4 : it - 5; };
  auto load_w = [&](int it, uint32_t a, uint32_t full) {
    tma_3d_mc(a + 16384 + rank * 16384, &tm.w, full, g * 80, it * 64, rank * 2);
    tma_3d_mc(a + (rank ? 40960 : 24576), rank ? &tm.wr : &tm.w, full, g * 80 + rank * 64, it * 64, 1 - rank);
  };
  if (warp == 0 && elect()) {
    mbar_expect_tx(bar_full + 16, SLOT);
    tma_3d(sb + 2 * SLOT, &tm.x, bar_full + 16, 0, mt * 64, 0);
  }
  asm volatile("barrier.cluster.wait.aligned;" ::: "memory");
  if (warp == 0) {
    if (elect()) load_w(0, sb + 2 * SLOT, bar_full + 16);
    asm volatile("bar.arrive 4, 64;" ::: "memory");
  }

  if (warp >= 8) {
    asm volatile("setmaxnreg.dec.sync.aligned.u32 %0;" :: "n"(REG_P));
#define TS_T 0
    if (warp == 8) {
      TS(8);
      bar_sync(4, 64);
      if (elect()) {
        TS(10);
        int fjn = 0;
#pragma unroll 1
        for (int it = 1; it < 17; it++) {
          const int s = (it + 2) & 3;
          const uint32_t full = bar_full + 8 * s, a = sb + s * SLOT;
          if (it >= 13) { mbar_wait(bar_o + 32 + 8 * (it - 13), 0); mbar_wait(bar_o + 96 + 8 * (it - 13), 0); }
          else if (it >= 4) mbar_wait(bar_empty + 8 * s, ((it >> 2) - 1) & 1);
          else if (it >= THR) mbar_wait(bar_full + 8 * ((it - THR + 2) & 3), 0);
          if (it < 10) {
            const int ks = ks_of(it);
            mbar_expect_tx(full, SLOT);
            tma_3d(a, &tm.x, full, ks * 64, mt * 64, 0);
            load_w(ks, a, full);
            TS(12 + it);
            if ((unsigned)(it - RST_IT) < 3u) {
              mbar_wait(bar_rst, 0);
              char* const d = it == RST_IT ? (char*)(g_own + cid) : it == RST_IT + 1 ? (char*)(g_own + cid) + 2688 : (char*)((uint4*)&g_x + cid * GLOB_PER_CTA);
              asm volatile("cp.async.bulk.global.shared::cta.bulk_group [%0], [%1], %2;\ncp.async.bulk.commit_group;"
                           :: "l"(d), "r"(sb + OFF_CS), "r"(it == RST_IT ? 2688 : it == RST_IT + 1 ? 3584 : GLOB_PER_CTA * 16) : "memory");
            }
            if (it == RST_IT + 3) { asm volatile("cp.async.bulk.wait_group 0;" ::: "memory"); mbar_arrive(bar_rst); }
          } else if (it < 13) {
            const int g0 = 3 * (it - 10), g1 = min(g0 + 3, 8);
            mbar_expect_tx(full, (g1 - g0) * 12800);
#pragma unroll 1
            for (int gp = g0 + ((g0 ^ rank) & 1); gp < g1; gp += 2) {
              tma_3d_mc(sb + gp * 15360, &tm.wo, full, 0, gp * 80, g * 2);
              tma_3d_mc(sb + gp * 15360 + 10240, &tm.wor, full, 512 + g * 16, gp * 80, 0);
            }
          }
          if (it == 4) mbar_expect_tx(bar_ffn, ffn1 ? 81920 : 24576);
          const int j1 = ffn1 ? (it >= 13 ? min(2 * it - 21, 10) : min(max(it - F_IT + 1, 0), 4)) : (it >= 13 ? 12 : min(max((it - F_IT + 1) * F_PER, 0), F_MAX));
#pragma unroll 1
          for (; fjn < j1; fjn++) {
            const int j = fjn < 4 ? fjn + 6 : fjn - 4;
            if (ffn1) tma_3d(sb + (j < 6 ? 0 : OFF_W2 - 49152) + j * 8192, j < 5 ? &tm.gate : &tm.up, bar_ffn, fj * 32, (j < 5 ? j : j - 5) * 128, 0);
            else tma_3d(sb + OFF_W2 + fjn * 2048, &tm.down, bar_ffn, fj * 8, fjn * 128, 0);
          }
        }
        TS(11);
      }
#undef TS_T
#define TS_T 0
    } else if (warp >= 12) {
      const int l7 = lane & 7, j = warp - 12, ch = min((P >> 1) * 4 + rank * 2 + (j >> 1), 14);
      const uint32_t sxo = ((g & 3) * 32 + j * 8 + l7) * 128 + (((lane >> 3) ^ l7) * 16);
      const uint32_t swo = ch < 12 ? 16384 + (ch >> 2) * 8192 + lane * 128 + ((((ch & 3) * 2 + (j & 1)) ^ l7) * 16)
                                   : 40960 + (ch - 12) * 2048 + lane * 32 + (((j & 1) ^ (l7 >> 2)) * 16);
      float ps = 0.f, pq = 0.f, pq1 = 0.f, pc = 0.f;
#pragma unroll 1
      for (int it = ord; it < ord + 5; it++) {
        const int sl = (it + 2) & 3;
        mbar_wait(bar_full + 8 * sl, (it >> 2) & 1);
        TS(it);
        const uint32_t a = sb + sl * SLOT;
        const uint4 v0 = ldsm4(a + sxo), v1 = ldsm4((a + sxo) ^ 64), w0 = ldsm4t(a + swo), w1 = ldsm4t(a + swo + (ch < 12 ? 4096 : 1024));
        if (lane + (int)((v0.x & v1.x & w0.x & w1.x) == 0x7fc17fc1u && (v0.x | v1.x) == 0u) < 2) mbar_arrive_cta(bar_empty + 8 * sl, lane);
        const uint32_t vv[8] = {v0.x, v0.y, v0.z, v0.w, v1.x, v1.y, v1.z, v1.w}, ww[8] = {w0.x, w0.y, w0.z, w0.w, w1.x, w1.y, w1.z, w1.w};
#pragma unroll
        for (int i = 0; i < 8; i++) {
          const float d = bf_lo(vv[i]), e = bf_hi(vv[i]);
          ps += d + e; pq = fmaf(d, d, pq); pq1 = fmaf(e, e, pq1); pc += bf_lo(ww[i]) + bf_hi(ww[i]);
        }
      }
      pq += pq1;
      ps += shx(ps, 1); pq += shx(pq, 1); pc += shx(pc, 1);
      ps += shx(ps, 2); pq += shx(pq, 2); pc += shx(pc, 2);
      const int c = lane & 3;
      if (c < 3) sts32f(sb + OFF_PT + (c * 32 + j * 8 + (lane >> 2)) * 4, c == 0 ? ps : c == 1 ? pq : pc);
      asm volatile("bar.arrive 2, 224;" ::: "memory");
#undef TS_T
#define TS_T 32
    } else if (warp < 11) {
      Own* const own = g_own + cid;
      const int l7 = lane & 7, hk = lane >> 4, idx = lane;
      {
        const int t0 = clk();
#pragma unroll 1
        for (int i = PF_FIRST; i < 6; i++) {
          while (clk() - t0 < PF_T0 + (i - PF_FIRST) * PF_CLK) __nanosleep(20);
          pf_slice(warp == 9 ? min(i, 4) : i + 4);
        }
      }
      bar_sync(2, 224);
      mbar_wait(bar_rst, 1);
      TS(0);
      const uint32_t tag = __float_as_uint(lds32f(sb + OFF_WR + 324));
      const float s0 = lds32f(sb + OFF_PT + lane * 4 + (warp - 9) * 256), q0 = lds32f(sb + OFF_PT + 128 + lane * 4);
      int guard = SPIN_MAX;
      if (warp == 9) {
        stg_pkt(&own->st1[idx], __float_as_uint(s0), __float_as_uint(q0), tag, 0u);
        TS(1);
        const uint4* sp = &g_own[mt * 8].st1[lane];
        const uint4* hp = &g_own[max(mt - 1, 0) * 8 + hk * 2 + 1].st1[24 + l7];
        uint4 a[5], b[5];
        bool bad;
        do {
          __nanosleep(AUX_NS);
          bad = false;
#pragma unroll
          for (int i = 0; i < 5; i++) {
            const uint4* q = i < 4 ? sp + i * (sizeof(Own) / 16) : hp;
            a[i] = ldg_pkt(q); b[i] = ldg_pkt(q + 4 * sizeof(Own) / 16);
          }
#pragma unroll
          for (int i = 0; i < 5; i++) bad |= a[i].z != tag || b[i].z != tag;
        } while (anyw(bad) && --guard);
#pragma unroll
        for (int i = 0; i < 5; i++) {
          const float m = (__uint_as_float(a[i].x) + __uint_as_float(b[i].x)) * (1.f / 640.f);
          const float rs = rsq(fmaxf(fmaf(-m, m, (__uint_as_float(a[i].y) + __uint_as_float(b[i].y)) * (1.f / 640.f)), 0.f) + 1e-5f);
          ((float*)(smem + OFF_RS))[i < 4 ? 8 + lane + 32 * i + 8 * (i >> 1) : hk * 72 + l7] = rs;
          const uint32_t mh = pack_bf16(-m, -m);
          const float ml = -m - bf_lo(mh);
          if (i < 4) ((uint2*)(smem + OFF_MN))[lane + 32 * i] = make_uint2(mh, pack_bf16(ml, ml));
        }
      } else {
        stg_rlx64(&own->cs[idx], __float_as_uint(s0), tag);
        const uint4* cp = (const uint4*)g_own[hk * 8 + g].cs + (lane & 15);
        uint4 a[4], b[4];
        bool bad;
        do {
          __nanosleep(AUX_NS);
          bad = false;
#pragma unroll
          for (int i = 0; i < 4; i++) { a[i] = ldg_pkt(cp + i * 32 * sizeof(Own) / 16); b[i] = ldg_pkt(cp + (i * 32 + 16) * sizeof(Own) / 16); }
#pragma unroll
          for (int i = 0; i < 4; i++) bad |= a[i].y != tag || a[i].w != tag || b[i].y != tag || b[i].w != tag;
        } while (anyw(bad) && --guard);
#pragma unroll
        for (int i = 0; i < 4; i++)
          if (i < 3 || lane < 24) {
            const float c0 = __uint_as_float(a[i].x) + __uint_as_float(b[i].x), c1 = __uint_as_float(a[i].z) + __uint_as_float(b[i].z);
            const uint32_t hi = pack_bf16(c0, c1), w0 = pack_bf16(c0, c0 - bf_lo(hi)), w1 = pack_bf16(c1, c1 - bf_hi(hi));
            uint4* const d = (uint4*)(smem + OFF_CS) + 2 * (lane + 32 * i);
            d[0] = make_uint4(w0, w0, 0, 0); d[1] = make_uint4(w1, w1, 0, 0);
          }
        asm volatile("fence.proxy.async.shared::cta;" ::: "memory");
      }
      mbar_arrive(bar_aux);
      TS(2);
      const int wq = warp - 9;
      const uint4* const fp = pin(g_own[mt * 8 + wq * 4].cnt);
      const char* const src = (const char*)g_o[mt * 2 + wq];
      bar_sync(5 + wq, 160);
      if (elect()) {
        while (ldg_rlx32(fp) != 32u && --guard > 0) {}
        asm volatile("fence.proxy.async.global;" ::: "memory");
        TS(6);
#pragma unroll 1
        for (int i = 0, sl = 0; i < 7; i++) {
          const uint32_t full = bar_o + wq * 64 + 8 * sl;
          if (i >= 3) mbar_wait(bar_o + wq * 64 + 8 + 8 * i, 0);
          mbar_expect_tx(full, 10240);
          asm volatile("cp.async.bulk.shared::cluster.global.mbarrier::complete_tx::bytes [%0], [%1], 10240, [%2];"
                       :: "r"(sb + OFF_O + sl * 20480 + wq * 10240), "l"(src + (i + (i >= g)) * 10240), "r"(full) : "memory");
          sl = sl == 2 ? 0 : sl + 1;
        }
      }
#undef TS_T
#define TS_T 96
    } else {
      if ((sb & 0x3FFFF) != D0 * 16) __trap();
#pragma unroll 1
      for (int i = lane; i < 224; i += 32) { const uint32_t f = i < 200 ? SENT : 0u; ((uint4*)(smem + OFF_CS))[i] = make_uint4(f, f, f, f); }
      asm volatile("fence.proxy.async.shared::cta;" ::: "memory");
      if (elect()) mbar_arrive(bar_rst);
      mbar_wait(bar_full + 8 * ((HK_IT + 2) & 3), 0);
      TS(4);
      const uint32_t epoch = ldg_rlx32(g_epoch + cid) + 1;
      uint32_t wv[10];
#pragma unroll
      for (int i = 0; i < 10; i++) wv[i] = __ldg((const uint32_t*)w_r + lane + 32 * i);
      float s = 0.f;
#pragma unroll
      for (int i = 0; i < 10; i++) {
        s += bf_lo(wv[i]) + bf_hi(wv[i]);
        const unsigned u = i < 8 ? lane + 32 * (i - g) : lane + 32 * (i - 7) - g * 8;
        if (i < 8 ? u < 32u : u - 32u < 8u) *(float2*)(smem + OFF_WR + ((u & 3) * 10 + (u >> 2)) * 8) = make_float2(bf_lo(wv[i]), bf_hi(wv[i]));
      }
#pragma unroll
      for (int m = 1; m < 32; m <<= 1) s += shx(s, m);
      *(float2*)(smem + OFF_WR + 320) = make_float2(s, __uint_as_float(epoch * 0x9E3779B8u));
      g_epoch[cid] = epoch;
      TS(3);
      TS(5);
      asm volatile("bar.arrive 2, 224;" ::: "memory");
#pragma unroll 1
      for (int i = 0; i < 14; i++) {
        const int m = (i + 2) >> 2, n = m == 0 ? 50 : 120, t = (m == 0 ? i : (i + 2) & 3) * 32 + lane;
        const char* b = (const char*)(m == 0 ? wo : m == 1 ? w_up : m == 2 ? w_down : w_gate);
        if (t < n) pf_l2(b + (bid * n + t) * 128);
        __nanosleep(PFW_NS);
      }
      bar_sync(3, 64);
      const uint4* const kp = g_own[1].cnt;
      const uint4* const cb = &g_x.cand[0][lane >> 2][lane & 3];
      uint4 k = ldg_pkt(kp), c0 = make_uint4(0, 0, 0, 0), c1 = c0; uint2 c2 = make_uint2(0, 0);
      int guard = SPIN_MAX, ws;
      while (true) {
        const uint32_t tk = 2047u - (k.x & 2047u);
        ws = (tk >> 7) * 8 + (tk & 1) * 4 + ((tk >> 5) & 3);
        const uint32_t prev = k.x;
        if (ffn1) { const uint4* q = cb + ws * 192; c0 = ldg_pkt(q); c1 = ldg_pkt(q + 4); c2 = ldg_rlx64(q + 8); }
        if (k.z != 128u) k = ldg_pkt(kp);
        if ((k.z == 128u && k.x == prev && !anyw(c0.x == SENT || c1.x == SENT || c2.x == SENT)) || --guard <= 0) break;
      }
      *(uint4*)(smem + OFF_HN + lane * 16) = c0; *(uint4*)(smem + OFF_HN + 512 + lane * 16) = c1; *(uint2*)(smem + OFF_HN + 1024 + lane * 16) = c2;
      const float rw = __uint_as_float(k.y ^ ((uint32_t)((int32_t)~k.y >> 31) | 0x80000000u));
      *(uint4*)(smem + OFF_WR + 336) = make_uint4(ws, 2047u - (k.x & 2047u), __float_as_uint(rcp(1.f + ex2(-1.4426950408889634f * rw))), 0);
      mbar_arrive(bar_win);
      TS(7);
    }
#undef TS_T
  } else {
#define TS_T 0
    TS(23);
    asm volatile("setmaxnreg.inc.sync.aligned.u32 %0;" :: "n"(REG_C));
    const int wg = warp >> 2, w4 = warp & 3, r = lane >> 2, c = lane & 3;
    float acc[120];
    uint4 xr[5] = {};
    const uint32_t xa = pin(sb + (warp * 16 + (lane & 15)) * 128 + ((lane >> 4) ^ (lane & 7)) * 16);
    const bool first = (mt == 0) && (w4 == 0);
    uint4* const kvd = pin(w4 < 3 ? (uint4*)(smem + OFF_O + warp * 2560) + lane : &g_own[cid].halo[wg][0][lane]);
    const uint4* const kvs = pin(first ? kvd : w4 > 0 ? (const uint4*)(smem + OFF_O + (warp - 1) * 2560) + lane : &g_own[cid - 8].halo[wg][0][lane]);
    uint32_t m0 = 0, m1 = 0;
    const uint32_t mna = pin(sb + OFF_MN + (warp * 16 + r) * 8 + c * 4);
    const int itx = ord == 0 || g == 0 ? g : g < 5 ? g + 5 : g - 4, ity = (ord ? 4 : 8) + (g >> 2);
    uint32_t rel;
    asm volatile("mapa.shared::cluster.u32 %0, %1, %2;" : "=r"(rel) : "r"(bar_empty), "r"(tid & 1));
    const uint32_t xa1 = pin(xa ^ 32), xa2 = pin(xa ^ 64), xa3 = pin(xa ^ 96), xb = pin(xa ^ ((g & 3) * 32));
    const uint32_t da0 = wg * 512;
    const bool rel2 = lane < 2, rel6 = lane < 2 + 2 * (warp & 1);
    const uint32_t zero = (uint32_t)(uintptr_t)x & 8u;
    TS(0);
    mbar_wait(bar_full + 16, 0);
    TS(13);
    wgmma_fence();
#pragma unroll
    for (int it = 0; it < 10; it++) {
      const int s = (it + 2) & 3;
      if (it == 9) bar_sync(10 + wg, 256);
#pragma unroll
      for (int kk = 0; kk < 4; kk++) {
        if (kk == 2 && it > 0) {
          wgmma_commit();
          wgmma_wait<1>();
          const uint32_t ra = ((xr[0].x ^ xr[1].x ^ xr[2].x ^ xr[3].x ^ xr[4].x) & zero) | rel;
          if (it == 1 ? (ord ? rel6 : rel2) : it == 6 ? (ord ? rel2 : rel6) : it < 6 ? rel2 : rel6)
            asm volatile("mbarrier.arrive.shared::cluster.b64 _, [%0];" :: "r"(ra + 8 * ((it + 1) & 3)) : "memory");
        }
        if (kk == 2) {
          ldsm4_if(xr[0], xa, s * SLOT, it == itx); ldsm4_if(xr[1], xa1, s * SLOT, it == itx);
          ldsm4_if(xr[2], xa2, s * SLOT, it == itx); ldsm4_if(xr[3], xa3, s * SLOT, it == itx);
          if ((it & 6) == 4 || it >= 8) ldsm4_if(xr[4], xb, s * SLOT, it == ity);
        }
        if (kk == 3 && it < 9) {
          mbar_wait(bar_full + 8 * ((it + 3) & 3), ((it + 1) >> 2) & 1);
          TS(14 + it);
        }
        if (kk == LK && it >= 8 && it == (wg == LEAD ? 9 : 8)) asm volatile("bar.arrive %0, 256;" :: "r"(11 - wg) : "memory");
        const uint64_t da = mk64(da0 + (D0 + s * (SLOT >> 4) + kk * 2 + (1 << 16)), 0x40000040u);
        wgmma_n48hi_ss(acc, da, mk64(D0 + s * (SLOT >> 4) + 2560 + kk * 32 + (128 << 16), 0xC0000010u), (it | kk) != 0);
        wgmma_n192lo_ss(acc, da, mk64(D0 + s * (SLOT >> 4) + 1024 + kk * 128 + (512 << 16), 0x40000040u), (it | kk) != 0);
      }
      wgmma_commit();
      if (LK == 4 && it >= 8 && it == (wg == LEAD ? 9 : 8)) asm volatile("bar.arrive %0, 256;" :: "r"(11 - wg) : "memory");
      if (it == 8) {
        mbar_wait(bar_aux, 0);
        TS(3);
        if (c < 2) { m0 = __float_as_uint(lds32f(mna)); m1 = __float_as_uint(lds32f(mna + 64)); }
      }
    }
    {
      const uint64_t dc = make_desc(D0 * 16 + OFF_CS, 0, 128, 0);
      wgmma_fence();
      wgmma_n48hi_rk(acc, m0, m1, 0u, 0u, dc + 192, 1);
      wgmma_n192lo_rk(acc, m0, m1, 0u, 0u, dc, 1);
      wgmma_commit();
    }
    const uint32_t stb = sb + OFF_RS + (wg * 72 + 16 * w4) * 4;
    const float rlo = lds32f(stb + (8 + r) * 4), rhi = lds32f(stb + (16 + r) * 4);
    wgmma_wait<0>();
#pragma unroll
    for (int i = 0; i < 120; i++) asm volatile("" : "+f"(acc[i]) :: "memory");
    if (wg != LEAD) asm volatile("bar.arrive 9, 256;" ::: "memory");
    TS(2);
    uint32_t Qlo[10], Qhi[10], Klo[10], Khi[10], Vlo[10], Vhi[10];
#pragma unroll
    for (int t = 0; t < 10; t++) {
      const int k = KT(t), v = VT(t);
      Khi[t] = pack_bf16(acc[4 * k + 2], acc[4 * k + 3]);
      Vhi[t] = pack_bf16(acc[4 * v + 2] * rhi, acc[4 * v + 3] * rhi);
    }
    st_pkt(kvd, Khi[0], Khi[1], Khi[3], Khi[4]);
    st_pkt(kvd + 32, Khi[5], Khi[6], Khi[8], Khi[9]);
    st_pkt(kvd + 64, Khi[2], Khi[7], Vhi[0], Vhi[1]);
    st_pkt(kvd + 96, Vhi[2], Vhi[3], Vhi[4], Vhi[5]);
    st_pkt(kvd + 128, Vhi[6], Vhi[7], Vhi[8], Vhi[9]);
    mbar_arrive(bar_o + wg * 64 + 24);
#pragma unroll
    for (int t = 0; t < 10; t++) {
      const int q = QT(t), k = KT(t), v = VT(t);
      Vhi[t] = movm(Vhi[t]);
      Klo[t] = pack_bf16(acc[4 * k], acc[4 * k + 1]);
      Vlo[t] = movm(pack_bf16(acc[4 * v] * rlo, acc[4 * v + 1] * rlo));
      Qlo[t] = pack_bf16(acc[4 * q], acc[4 * q + 1]);
      Qhi[t] = pack_bf16(acc[4 * q + 2], acc[4 * q + 3]);
    }
    const bool in0 = 2 * c <= r, in1 = 2 * c + 1 <= r;
    const uint32_t mL = (in0 ? 0xffffu : 0u) | (in1 ? 0xffff0000u : 0u);
    const float qs = 0.22360679774997896f * 1.4426950408889634f;
    const uint32_t kb0 = stb + (2 * c + (in0 ? 8 : 0)) * 4, kb1 = stb + (2 * c + 1 + (in1 ? 8 : 0)) * 4;
    const float scl0 = lds32f(kb0) * rlo * qs, scl1 = lds32f(kb1) * rlo * qs;
    const float sch0 = lds32f(kb0 + 32) * rhi * qs, sch1 = lds32f(kb1 + 32) * rhi * qs;
    const float bias0 = (first && !in0) ? -INFINITY : 0.f, bias1 = (first && !in1) ? -INFINITY : 0.f;
    const int slot = mt * 8 + warp;
    int guard = SPIN_MAX;
    uint4 pv[5];
    mbar_wait(bar_o + wg * 64 + 24, 0);
    do {
#pragma unroll
      for (int j = 0; j < 5; j++) pv[j] = ld_pkt(kvs + 32 * j);
    } while (anyw(pv[0].x == SENT || pv[1].x == SENT || pv[2].x == SENT || pv[3].x == SENT || pv[4].x == SENT) && --guard);
    if (wg == LEAD) bar_sync(9, 256);
    TS(4);
    const uint32_t Kp[10] = {pv[0].x, pv[0].y, pv[2].x, pv[0].z, pv[0].w, pv[1].x, pv[1].y, pv[2].y, pv[1].z, pv[1].w};
    const uint32_t Vp[10] = {movm(pv[2].z), movm(pv[2].w), movm(pv[3].x), movm(pv[3].y), movm(pv[3].z), movm(pv[3].w), movm(pv[4].x), movm(pv[4].y), movm(pv[4].z), movm(pv[4].w)};
    const bool cA = c < 2, nA = r < 4;
    const uint32_t ONES = 0x3f803f80u;
    uint32_t of[20];
#pragma unroll
    for (int hp = 0; hp < 2; hp++) {
      float o[6][4];
#pragma unroll
      for (int hh = 0; hh < 2; hh++) {
        const int ta = 5 * hp + 3 * hh, ts = 5 * hp + 2;
        const bool mine = hh == 0 ? cA : !cA;
        const uint32_t e0 = mine ? Qlo[ts] : 0u, e1 = mine ? Qhi[ts] : 0u;
        float sp[4], sl[4], sh[4];
        mma_k24(sp, Qlo[ta], Qhi[ta], Qlo[ta + 1], Qhi[ta + 1], Kp[ta], Kp[ta + 1], e0, e1, Kp[ts]);
        mma_k24(sl, Qlo[ta], Qhi[ta], Qlo[ta + 1], Qhi[ta + 1], Klo[ta], Klo[ta + 1], e0, e1, Klo[ts]);
        mma_k24(sh, Qlo[ta], Qhi[ta], Qlo[ta + 1], Qhi[ta + 1], Khi[ta], Khi[ta + 1], e0, e1, Khi[ts]);
        const float tl0 = fmaf(in0 ? sl[0] : sp[0], scl0, bias0), tl1 = fmaf(in1 ? sl[1] : sp[1], scl1, bias1);
        const float th0 = (in0 ? sh[2] : sl[2]) * sch0, th1 = (in1 ? sh[3] : sl[3]) * sch1;
        float ml = fmaxf(tl0, tl1), mh = fmaxf(th0, th1);
        ml = fmaxf(ml, shx(ml, 1)); mh = fmaxf(mh, shx(mh, 1));
        ml = fmaxf(ml, shx(ml, 2)); mh = fmaxf(mh, shx(mh, 2));
        const uint32_t Pl = pack_bf16(ex2(tl0 - ml), ex2(tl1 - ml)), Ph = pack_bf16(ex2(th0 - mh), ex2(th1 - mh));
        const uint32_t a0 = Pl & mL, a1 = Ph & ~mL, a3 = Ph & mL, ap = Pl & ~mL;
        const bool vm = hh == 0 ? nA : !nA;
        mma_k24(o[3 * hh], a0, a1, 0u, a3, Vlo[ta], Vhi[ta], ap, 0u, Vp[ta]);
        mma_k24(o[3 * hh + 1], a0, a1, 0u, a3, Vlo[ta + 1], Vhi[ta + 1], ap, 0u, Vp[ta + 1]);
        mma_k24(o[3 * hh + 2], a0, a1, 0u, a3, vm ? Vlo[ts] : ONES, vm ? Vhi[ts] : ONES, ap, 0u, vm ? Vp[ts] : ONES);
      }
      const float il = rcp(cA ? o[5][0] : o[2][0]), ih = rcp(cA ? o[5][2] : o[2][2]);
      const float jl = shx(il, 2), jh = shx(ih, 2);
      const float al = cA ? jl : il, ah = cA ? jh : ih, bl = cA ? il : jl, bh = cA ? ih : jh;
      const int t0 = 5 * hp;
      of[2 * t0]     = pack_bf16(o[0][0] * al, o[0][1] * al); of[2 * t0 + 1] = pack_bf16(o[0][2] * ah, o[0][3] * ah);
      of[2 * t0 + 2] = pack_bf16(o[1][0] * al, o[1][1] * al); of[2 * t0 + 3] = pack_bf16(o[1][2] * ah, o[1][3] * ah);
      of[2 * t0 + 4] = pack_bf16((cA ? o[2][0] : o[5][0]) * jl, (cA ? o[2][1] : o[5][1]) * jl);
      of[2 * t0 + 5] = pack_bf16((cA ? o[2][2] : o[5][2]) * jh, (cA ? o[2][3] : o[5][3]) * jh);
      of[2 * t0 + 6] = pack_bf16(o[3][0] * bl, o[3][1] * bl); of[2 * t0 + 7] = pack_bf16(o[3][2] * bh, o[3][3] * bh);
      of[2 * t0 + 8] = pack_bf16(o[4][0] * bl, o[4][1] * bl); of[2 * t0 + 9] = pack_bf16(o[4][2] * bh, o[4][3] * bh);
    }
    {
      const uint32_t os = sb + OFF_O + 20480 + warp * 2560, oa = os + ((lane >> 3) & 1) * 1280 + (lane >> 4) * 128 + (lane & 7) * 16;
#pragma unroll
      for (int s = 0; s < 5; s++) stsm4(oa + s * 256, of[4 * s], of[4 * s + 1], of[4 * s + 2], of[4 * s + 3]);
      asm volatile("fence.proxy.async.shared::cta;" ::: "memory");
      __syncwarp();
      if (elect()) {
        asm volatile("cp.async.bulk.global.shared::cta.bulk_group [%0], [%1], 2560;\ncp.async.bulk.commit_group;" :: "l"(&g_o[mt * 2 + wg][g][w4 * 160]), "r"(os) : "memory");
      }
    }
    TS(5);
    float h[40];
#pragma unroll
    for (int s = 0; s < 5; s++) {
      const uint4 v = xr[s];
      h[8 * s] = bf_lo(v.x); h[8 * s + 1] = bf_hi(v.x); h[8 * s + 2] = bf_lo(v.y); h[8 * s + 3] = bf_hi(v.y);
      h[8 * s + 4] = bf_lo(v.z); h[8 * s + 5] = bf_hi(v.z); h[8 * s + 6] = bf_lo(v.w); h[8 * s + 7] = bf_hi(v.w);
    }
    mbar_wait(bar_full, 0); mbar_wait(bar_full + 8, 0); mbar_wait(bar_full + 16, 1);
    if (elect()) {
      asm volatile("cp.async.bulk.wait_group 0;" ::: "memory");
      asm volatile("red.relaxed.gpu.global.add.u32 [%0], 1;" :: "l"(g_own[mt * 8 + wg * 4].cnt) : "memory");
    }
    asm volatile("bar.arrive %0, 160;" :: "r"(5 + wg) : "memory");
    bar_sync(1, 256);
    const uint64_t dwo = make_desc(D0 * 16, 5120, 512, 2);
    wgmma_fence();
#pragma unroll
    for (int s = 0; s < 5; s++) wgmma_n80_rs(h, of[4 * s], of[4 * s + 1], of[4 * s + 2], of[4 * s + 3], dwo + g * 960 + s * 64, 1);
    wgmma_commit();
    TS(6);
#pragma unroll 1
    for (int i = 0, sl = 0; i < 7; i++) {
      mbar_wait(bar_o + wg * 64 + 8 * sl, i >= 3 && i < 6);
      if (i == 0) TS(1);
      const uint64_t da = make_desc(D0 * 16 + OFF_O + sl * 20480 + wg * 10240, 128, 1280, 0), db = dwo + (i + (i >= g)) * 960;
      wgmma_fence();
#pragma unroll
      for (int s = 0; s < 5; s++) wgmma_n80_ss(h, da + s * 16, db + s * 64, 1);
      wgmma_commit();
      wgmma_wait<1>();
      if (lane == 0 && i > 0 && i < 5) mbar_arrive(bar_o + wg * 64 + 24 + 8 * i);
      sl = sl == 2 ? 0 : sl + 1;
    }
    const bool odd = c & 1;
    float wr[20];
#pragma unroll
    for (int j = 0; j < 5; j++) {
      const uint4 v = lds128(sb + OFF_WR + c * 80 + j * 16);
      wr[4 * j] = __uint_as_float(v.x); wr[4 * j + 1] = __uint_as_float(v.y); wr[4 * j + 2] = __uint_as_float(v.z); wr[4 * j + 3] = __uint_as_float(v.w);
    }
    const float wsum = lds32f(sb + OFF_WR + 320);
    uint4* const sp = pin(&g_own[slot].st2[r + (odd ? 8 : 0)]);
    uint4* const cdp = pin(&g_x.cand[slot][g][0]);
    const int tok0 = mt * 128 + 32 * w4 + wg;
    wgmma_wait<0>();
#pragma unroll
    for (int i = 0; i < 40; i++) asm volatile("" : "+f"(h[i]) :: "memory");
    TS(7);
    float mean, rstd, rr;
    {
      float l1 = 0.f, l2 = 0.f, l3 = 0.f, h1 = 0.f, h2 = 0.f, h3 = 0.f;
#pragma unroll
      for (int j = 0; j < 10; j++) {
        l1 += h[4 * j] + h[4 * j + 1]; h1 += h[4 * j + 2] + h[4 * j + 3];
        l2 = fmaf(h[4 * j], h[4 * j], l2); l2 = fmaf(h[4 * j + 1], h[4 * j + 1], l2);
        h2 = fmaf(h[4 * j + 2], h[4 * j + 2], h2); h2 = fmaf(h[4 * j + 3], h[4 * j + 3], h2);
        l3 = fmaf(h[4 * j], wr[2 * j], l3); l3 = fmaf(h[4 * j + 1], wr[2 * j + 1], l3);
        h3 = fmaf(h[4 * j + 2], wr[2 * j], h3); h3 = fmaf(h[4 * j + 3], wr[2 * j + 1], h3);
      }
      float s1 = (odd ? h1 : l1) + shx(odd ? l1 : h1, 1), s2 = (odd ? h2 : l2) + shx(odd ? l2 : h2, 1), s3 = (odd ? h3 : l3) + shx(odd ? l3 : h3, 1);
      s1 += shx(s1, 2); s2 += shx(s2, 2); s3 += shx(s3, 2);
      if (cA) asm volatile("red.relaxed.gpu.global.add.v4.f32 [%0], {%1, %2, %3, %4};" :: "l"(sp), "f"(s1), "f"(s2), "f"(s3), "f"(1.f) : "memory");
      uint4 p0;
      do { p0 = ldg_pkt(sp); } while (anyw(p0.w != 0x41000000u) && --guard > 0);
      mean = __uint_as_float(p0.x) * (1.f / 640.f);
      rstd = rsq(fmaxf(fmaf(-mean, mean, __uint_as_float(p0.y) * (1.f / 640.f)), 0.f) + 1e-5f);
      rr = fmaf(-mean, wsum, __uint_as_float(p0.z)) * rstd;
    }
    TS(8);
    const uint32_t kk = ord_key(rr), kmax = __reduce_max_sync(0xffffffffu, kk);
    const int L = __ffs(__ballot_sync(0xffffffffu, kk == kmax)) - 1;
    const int crow = (L >> 2) + 8 * (L & 1);
    if (warp == g) {
      if (elect()) {
        asm volatile("red.relaxed.gpu.global.max.u64 [%0], %1;" :: "l"(g_own[1].cnt), "l"(((uint64_t)kmax << 32) | (uint32_t)(2047 - tok0 - 2 * crow)) : "memory");
        asm volatile("red.relaxed.gpu.global.add.u32 [%0], 1;" :: "l"(&g_own[1].cnt[0].z) : "memory");
      }
      asm volatile("bar.arrive 3, 64;" ::: "memory");
    }
    const uint32_t stg = sb + OFF_O + warp * 2560;
    uint4 held;
    {
      const float om = shx(mean, 1), os = shx(rstd, 1);
      const float rl = odd ? os : rstd, rh = odd ? rstd : os;
      const float bl = -(odd ? om : mean) * rl, bh = -(odd ? mean : om) * rh, al = 1.f + rl, ah = 1.f + rh;
      if ((L >> 2) == r) {
        const bool chi = L & 1;
        const float rc = chi ? rh : rl, bc = chi ? bh : bl;
        uint32_t n[10];
#pragma unroll
        for (int j = 0; j < 10; j++) n[j] = pack_bf16(fmaf(chi ? h[4 * j + 2] : h[4 * j], rc, bc), fmaf(chi ? h[4 * j + 3] : h[4 * j + 1], rc, bc));
        uint4* d = cdp + c;
        stg_pkt(d, n[0], n[1], n[2], n[3]); stg_pkt(d + 4, n[4], n[5], n[6], n[7]); stg_rlx64(d + 8, n[8], n[9]);
      }
      __syncwarp();
      const uint32_t fa = stg + (lane & 15) * 160 + (lane >> 4) * 16;
#pragma unroll
      for (int s = 0; s < 5; s++)
        stsm4(fa + s * 32, pack_bf16(fmaf(h[8 * s], al, bl), fmaf(h[8 * s + 1], al, bl)), pack_bf16(fmaf(h[8 * s + 2], ah, bh), fmaf(h[8 * s + 3], ah, bh)),
              pack_bf16(fmaf(h[8 * s + 4], al, bl), fmaf(h[8 * s + 5], al, bl)), pack_bf16(fmaf(h[8 * s + 6], ah, bh), fmaf(h[8 * s + 7], ah, bh)));
      __syncwarp();
      held = lds128(stg + crow * 160 + min(lane, 9) * 16);
      if (lane < 10) stg_pkt(cdp + 12 + lane, held.x, held.y, held.z, held.w);
    }
    TS(9);
    mbar_wait(bar_ffn, 0);
    const uint32_t red = sb + OFF_RED;
    if (ffn1) {
      uint4 w1[4][5];
      {
        const int k = (lane & 7) + (lane >> 4) * 8;
        const uint32_t a1 = sb + k * 64, sw = ((lane >> 3) & 1) ^ ((lane >> 1) & 3);
#pragma unroll
        for (int s = 0; s < 5; s++)
#pragma unroll
          for (int u = 0; u < 4; u++)
            w1[u][s] = ldsm4t(a1 + (s < 4 ? warp * 4096 + s * 1024 : 32768 + warp * 1024) + (u >> 1) * (40960 + (s == 4 || warp >= 2 ? OFF_W2 - 49152 : 0)) + ((sw ^ (2 * (u & 1))) * 16));
      }
      uint32_t* const ap = pin(g_x.act + fj * 16 + (lane >> 1));
      mbar_wait(bar_win, 0);
      const uint32_t hp = sb + OFF_HN + (warp * 4 + c) * 16;
      const uint4 c0 = lds128(hp), c1 = lds128(hp + 512), c2 = lds128(hp + 1024);
      TS(10);
      float a[4][4];
#pragma unroll
      for (int u = 0; u < 4; u++) {
        a[u][0] = a[u][1] = a[u][2] = a[u][3] = 0.f;
        mma_acc(a[u], w1[u][0], c0.x, c0.y); mma_acc(a[u], w1[u][1], c0.z, c0.w); mma_acc(a[u], w1[u][2], c1.x, c1.y);
        mma_acc(a[u], w1[u][3], c1.z, c1.w); mma_acc(a[u], w1[u][4], c2.x, c2.y);
      }
      asm volatile("st.shared.v2.f32 [%0], {%1, %2};" :: "r"(red + (warp * 32 + c * 8 + r) * 8),
                   "f"(cA ? (odd ? a[0][2] : a[0][0]) : (odd ? a[1][2] : a[1][0])), "f"(cA ? (odd ? a[2][2] : a[2][0]) : (odd ? a[3][2] : a[3][0])) : "memory");
      bar_sync(1, 256);
      if (warp == 0) {
        float2 t[8];
#pragma unroll
        for (int i = 0; i < 8; i++) t[i] = lds64f(red + (i * 32 + lane) * 8);
        const float s = ((t[0].x + t[1].x) + (t[2].x + t[3].x)) + ((t[4].x + t[5].x) + (t[6].x + t[7].x));
        const float u = ((t[0].y + t[1].y) + (t[2].y + t[3].y)) + ((t[4].y + t[5].y) + (t[6].y + t[7].y));
        const float av = s * u * rcp(1.f + ex2(-1.4426950408889634f * s));
        const float an = shx(av, 1);
        if (!odd) stg_rlx32(ap, pack_bf16(av, an));
      }
      bar_sync(1, 256);
      TS(11);
    }
    if (OUT_LATE) mbar_wait(bar_win, 0);
    char* const ob2 = (char*)(out + tok0 * 640 + g * 64);
    const int remo = 896 - 96 * g;
#pragma unroll
    for (int s = 0; s < 5; s++) {
      const int row = s < 4 ? 4 * s + (lane >> 3) : lane >> 1, pc = s < 4 ? lane & 7 : 8 + (lane & 1);
      const uint4 v = lds128(stg + row * 160 + pc * 16);
      if (row != crow) stg128(ob2 + row * 2560 + pc * 16 + (s < 4 ? 0 : remo), v);
    }
    mbar_wait(bar_win, 0);
    const uint4 win = lds128(sb + OFF_WR + 336);
    if (win.x != slot && lane < 10) stg128(ob2 + crow * 2560 + lane * 16 + (lane < 8 ? 0 : remo), held);
    if (!ffn1) {
      TS(10);
      uint4 w2[6];
      const uint32_t a2 = sb + OFF_W2 + (warp * 192 + 8 * (((lane >> 3) & 1) * 4 + ((lane & 7) >> 1)) + 2 * (lane >> 4) + (lane & 1)) * 16;
#pragma unroll
      for (int s = 0; s < 6; s++) w2[s] = ldsm4t(a2 + (s >> 1) * 1024 + (s & 1) * 64);
      const uint4* p = (const uint4*)(g_x.act + warp * 96) + (r & 1) * 4 + c;
      const uint32_t* pb = (const uint32_t*)&g_x.cand[win.x][fj < 64 ? fj >> 3 : (fj - 64) >> 1][fj < 64 ? 12 + (fj & 7) : 20 + (fj & 1)] + c;
      uint32_t* const op = pin((uint32_t*)(out + win.y * 640 + fj * 8) + c);
      uint4 c0, c1, c2; uint32_t bw;
      if (ACT_NS) __nanosleep(ACT_NS);
      do {
        c0 = ldg_pkt(p); c1 = ldg_pkt(p + 8); c2 = ldg_pkt(p + 16); bw = ldg_rlx32(pb);
      } while (anyw(max(max(max(max(c0.x, c0.y), max(c0.z, c0.w)), max(max(c1.x, c1.y), max(c1.z, c1.w))), max(max(max(c2.x, c2.y), max(c2.z, c2.w)), bw)) == SENT) && --guard > 0);
      TS(11);
      float a[4] = {0.f, 0.f, 0.f, 0.f}, b[4] = {0.f, 0.f, 0.f, 0.f}, d[4] = {0.f, 0.f, 0.f, 0.f};
      mma_acc(a, w2[0], c0.x, c0.y); mma_acc(b, w2[2], c1.x, c1.y); mma_acc(d, w2[4], c2.x, c2.y);
      mma_acc(a, w2[1], c0.z, c0.w); mma_acc(b, w2[3], c1.z, c1.w); mma_acc(d, w2[5], c2.z, c2.w);
      if (c == 0) sts32f(red + (warp * 8 + r) * 4, ((a[0] + a[3]) + (b[0] + b[3])) + (d[0] + d[3]));
      bar_sync(1, 256);
      if (tid < 4) {
        float2 t[8];
#pragma unroll
        for (int i = 0; i < 8; i++) t[i] = lds64f(red + (i * 4 + tid) * 8);
        const float y0 = ((t[0].x + t[1].x) + (t[2].x + t[3].x)) + ((t[4].x + t[5].x) + (t[6].x + t[7].x));
        const float y1 = ((t[0].y + t[1].y) + (t[2].y + t[3].y)) + ((t[4].y + t[5].y) + (t[6].y + t[7].y));
        const float sg = __uint_as_float(win.z);
        *op = pack_bf16(fmaf(y0, sg, bf_lo(bw)), fmaf(y1, sg, bf_hi(bw)));
      }
    }
    TS(12);
#undef TS_T
  }
}

typedef CUresult (*EncodeFn)(CUtensorMap*, CUtensorMapDataType, cuuint32_t, void*, const cuuint64_t*, const cuuint64_t*, const cuuint32_t*,
                             const cuuint32_t*, CUtensorMapInterleave, CUtensorMapSwizzle, CUtensorMapL2promotion, CUtensorMapFloatOOBfill);

void make_map(EncodeFn enc, CUtensorMap* m, const void* base, const cuuint64_t* dims, const cuuint64_t* strides, const cuuint32_t* box,
              CUtensorMapSwizzle swz) {
  const cuuint32_t es[3] = {1, 1, 1};
  enc(m, CU_TENSOR_MAP_DATA_TYPE_BFLOAT16, 3, (void*)base, dims, strides, box, es, CU_TENSOR_MAP_INTERLEAVE_NONE, swz,
      CU_TENSOR_MAP_L2_PROMOTION_L2_128B, CU_TENSOR_MAP_FLOAT_OOB_FILL_NONE);
}

}

extern "C" void kernel_launch(void* const* d_in, const int* in_sizes, int n_in, void* d_out, int out_size) {
  const __nv_bfloat16* x = (const __nv_bfloat16*)d_in[0];
  const __nv_bfloat16* wqkv = (const __nv_bfloat16*)d_in[1];
  const __nv_bfloat16* wo = (const __nv_bfloat16*)d_in[2];
  void* fn = nullptr;
  cudaDriverEntryPointQueryResult st;
  cudaGetDriverEntryPoint("cuTensorMapEncodeTiled", &fn, cudaEnableDefault, &st);
  EncodeFn enc = (EncodeFn)fn;
  void* scp = nullptr;
  cudaGetSymbolAddress(&scp, g_scratch);
  Maps tm;
  { const cuuint64_t d[3] = {640, 1024, 2}, s[2] = {2560, 1280}; const cuuint32_t b[3] = {64, 64, 2}; make_map(enc, &tm.x, x, d, s, b, CU_TENSOR_MAP_SWIZZLE_128B); }
  { const cuuint64_t d[3] = {640, 640, 3}, s[2] = {3840, 1280}; const cuuint32_t b[3] = {64, 64, 1}; make_map(enc, &tm.w, wqkv, d, s, b, CU_TENSOR_MAP_SWIZZLE_128B); }
  { const cuuint64_t d[3] = {640, 640, 3}, s[2] = {3840, 1280}; const cuuint32_t b[3] = {16, 64, 3}; make_map(enc, &tm.wr, wqkv, d, s, b, CU_TENSOR_MAP_SWIZZLE_32B); }
  { const cuuint64_t d[3] = {32, 640, 20}, s[2] = {1280, 64}; const cuuint32_t b[3] = {32, 80, 2}; make_map(enc, &tm.wo, wo, d, s, b, CU_TENSOR_MAP_SWIZZLE_64B); }
  { const cuuint64_t d[3] = {640, 640, 1}, s[2] = {1280, 819200}; const cuuint32_t b[3] = {16, 80, 1}; make_map(enc, &tm.wor, wo, d, s, b, CU_TENSOR_MAP_SWIZZLE_64B); }
  { const cuuint64_t d[3] = {1536, 640, 1}, s[2] = {3072, 1966080}; const cuuint32_t b[3] = {32, 128, 1};
    make_map(enc, &tm.gate, d_in[5], d, s, b, CU_TENSOR_MAP_SWIZZLE_64B); make_map(enc, &tm.up, d_in[6], d, s, b, CU_TENSOR_MAP_SWIZZLE_64B); }
  { const cuuint64_t d[3] = {640, 1536, 1}, s[2] = {1280, 1966080}; const cuuint32_t b[3] = {8, 128, 1}; make_map(enc, &tm.down, d_in[7], d, s, b, CU_TENSOR_MAP_SWIZZLE_NONE); }
  cudaFuncSetAttribute(fused_kernel, cudaFuncAttributeMaxDynamicSharedMemorySize, SMEM_BYTES);
  fused_kernel<<<128, 512, SMEM_BYTES, cudaStreamPerThread>>>(x, wqkv, wo, (const __nv_bfloat16*)d_in[4], (const __nv_bfloat16*)d_in[5],
                                                              (const __nv_bfloat16*)d_in[6], (const __nv_bfloat16*)d_in[7], (__nv_bfloat16*)d_out, (Scratch*)scp, tm);
}
```

```cpp
#include <cuda_runtime.h>
#include <cuda_bf16.h>
#include <cuda.h>
#include <stdint.h>

#define PFW_NS 100
#define ACT_NS 0
#define OUT_LATE 0
#define REG_P 72
#define REG_C 184
#define AUX_NS 50
#define LEAD 1
#define RST_IT 3
#define ORDX 1
#define THR 3
#define PF_FIRST 4
#define PF_T0 2500
#define PF_CLK 500
#define HK_IT 1
#define F_IT 7
#define F_PER 2
#define F_MAX 12
#define LK 5

namespace {

constexpr int SLOT    = 47104;
constexpr int OFF_O   = 122880;
constexpr int OFF_W2  = 4 * SLOT;
constexpr int OFF_CS  = OFF_W2 + 32768;
constexpr int OFF_RS  = OFF_CS + 3840;
constexpr int OFF_MN  = OFF_RS + 576;
constexpr int OFF_WR  = OFF_MN + 1024;
constexpr int OFF_RED = OFF_CS;
constexpr int OFF_HN  = OFF_CS + 2048;
constexpr int OFF_PT  = OFF_WR + 352;
constexpr int OFF_BAR = OFF_PT + 768;
constexpr int SMEM_BYTES = OFF_BAR + 240 + 384;
constexpr uint32_t D0 = 1024 >> 4;
constexpr uint32_t SENT = 0xFFFFFFFFu;
constexpr int SPIN_MAX = 1 << 20;

struct Glob {
  uint4 cand[128][8][24];
  uint32_t act[768];
  uint32_t pad[256];
};
constexpr int GLOB_PER_CTA = sizeof(Glob) / 16 / 128;
static_assert(GLOB_PER_CTA * 128 * 16 == sizeof(Glob), "glob size");
struct Own {
  uint4 halo[2][5][32];
  uint4 st1[32];
  uint2 cs[32];
  uint4 st2[16];
  uint4 cnt[8];
};
struct Scratch {
  Glob x;
  Own own[128];
  uint4 o[32][8][640];
  uint32_t epoch[128];
};
__device__ __align__(128) Scratch g_scratch;
#define g_x (sc->x)
#define g_own (sc->own)
#define g_o (sc->o)
#define g_epoch (sc->epoch)
#define TS(i)

__device__ __forceinline__ void mbar_init(uint32_t bar, uint32_t cnt) { asm volatile("mbarrier.init.shared::cta.b64 [%0], %1;" :: "r"(bar), "r"(cnt) : "memory"); }
__device__ __forceinline__ void mbar_expect_tx(uint32_t bar, uint32_t bytes) { asm volatile("mbarrier.arrive.expect_tx.shared::cta.b64 _, [%0], %1;" :: "r"(bar), "r"(bytes) : "memory"); }
__device__ __forceinline__ void mbar_arrive(uint32_t bar) { asm volatile("mbarrier.arrive.shared::cta.b64 _, [%0];" :: "r"(bar) : "memory"); }
__device__ __forceinline__ void mbar_arrive_cta(uint32_t bar, uint32_t cta) {
  asm volatile("{\n.reg .b32 ra;\nmapa.shared::cluster.u32 ra, %0, %1;\nmbarrier.arrive.shared::cluster.b64 _, [ra];\n}\n" :: "r"(bar), "r"(cta) : "memory");
}
__device__ __forceinline__ void mbar_wait(uint32_t bar, uint32_t parity) {
  asm volatile("{\n.reg .pred p;\n.reg .u32 n;\nmov.u32 n, 0;\nW:\nmbarrier.try_wait.parity.shared::cta.b64 p, [%0], %1;\n@p bra.uni D;\n"
               "add.u32 n, n, 1;\nsetp.lt.u32 p, n, %2;\n@p bra.uni W;\nD:\n}\n" :: "r"(bar), "r"(parity), "n"(SPIN_MAX) : "memory");
}
__device__ __forceinline__ void tma_3d(uint32_t dst, const void* tm, uint32_t bar, int c0, int c1, int c2) {
  asm volatile("cp.async.bulk.tensor.3d.shared::cluster.global.mbarrier::complete_tx::bytes [%0], [%1, {%3, %4, %5}], [%2];" :: "r"(dst), "l"(tm), "r"(bar), "r"(c0), "r"(c1), "r"(c2) : "memory");
}
__device__ __forceinline__ void tma_3d_mc(uint32_t dst, const void* tm, uint32_t bar, int c0, int c1, int c2) {
  asm volatile("cp.async.bulk.tensor.3d.shared::cluster.global.mbarrier::complete_tx::bytes.multicast::cluster [%0], [%1, {%3, %4, %5}], [%2], %6;" :: "r"(dst), "l"(tm), "r"(bar), "r"(c0), "r"(c1), "r"(c2), "h"((uint16_t)3) : "memory");
}
__device__ __forceinline__ void wgmma_fence() { asm volatile("wgmma.fence.sync.aligned;" ::: "memory"); }
__device__ __forceinline__ void wgmma_commit() { asm volatile("wgmma.commit_group.sync.aligned;" ::: "memory"); }
template <int N> __device__ __forceinline__ void wgmma_wait() { asm volatile("wgmma.wait_group.sync.aligned %0;" :: "n"(N) : "memory"); }
__device__ __forceinline__ uint64_t make_desc(uint32_t addr, uint32_t lbo, uint32_t sbo, uint32_t swz) {
  return (uint64_t)(((addr & 0x3FFFF) >> 4) | ((lbo >> 4) << 16)) | ((uint64_t)((sbo >> 4) | (swz << 30)) << 32);
}
__device__ __forceinline__ void bar_sync(int id, int n) { asm volatile("bar.sync %0, %1;" :: "r"(id), "r"(n) : "memory"); }
__device__ __forceinline__ uint4 ld_pkt(const void* p) {
  uint4 v; asm volatile("ld.relaxed.gpu.v4.u32 {%0, %1, %2, %3}, [%4];" : "=r"(v.x), "=r"(v.y), "=r"(v.z), "=r"(v.w) : "l"(p) : "memory"); return v;
}
__device__ __forceinline__ void st_pkt(void* p, uint32_t a, uint32_t b, uint32_t c, uint32_t d) {
  asm volatile("st.relaxed.gpu.v4.u32 [%0], {%1, %2, %3, %4};" :: "l"(p), "r"(a), "r"(b), "r"(c), "r"(d) : "memory");
}
__device__ __forceinline__ uint4 ldg_pkt(const void* p) {
  uint4 v; asm volatile("ld.relaxed.gpu.global.v4.u32 {%0, %1, %2, %3}, [%4];" : "=r"(v.x), "=r"(v.y), "=r"(v.z), "=r"(v.w) : "l"(p) : "memory"); return v;
}
__device__ __forceinline__ void stg_pkt(void* p, uint32_t a, uint32_t b, uint32_t c, uint32_t d) {
  asm volatile("st.relaxed.gpu.global.v4.u32 [%0], {%1, %2, %3, %4};" :: "l"(p), "r"(a), "r"(b), "r"(c), "r"(d) : "memory");
}
__device__ __forceinline__ uint32_t ldg_rlx32(const void* p) { uint32_t v; asm volatile("ld.relaxed.gpu.global.u32 %0, [%1];" : "=r"(v) : "l"(p) : "memory"); return v; }
__device__ __forceinline__ uint2 ldg_rlx64(const void* p) { uint2 v; asm volatile("ld.relaxed.gpu.global.v2.u32 {%0, %1}, [%2];" : "=r"(v.x), "=r"(v.y) : "l"(p) : "memory"); return v; }
__device__ __forceinline__ void stg128(void* p, const uint4& v) { asm volatile("st.global.v4.u32 [%0], {%1, %2, %3, %4};" :: "l"(p), "r"(v.x), "r"(v.y), "r"(v.z), "r"(v.w) : "memory"); }
__device__ __forceinline__ uint32_t pin(uint32_t v) { asm volatile("" : "+r"(v)); return v; }
__device__ __forceinline__ uint64_t mk64(uint32_t lo, uint32_t hi) { return ((uint64_t)hi << 32) | lo; }
template <class T> __device__ __forceinline__ T* hold(T* p) { return (T*)__shfl_sync(0xffffffffu, (unsigned long long)p, threadIdx.x & 31); }
template <class T> __device__ __forceinline__ T* pin(T* p) { asm volatile("" : "+l"(p)); return p; }
__device__ __forceinline__ void stg_rlx32(void* p, uint32_t v) { asm volatile("st.relaxed.gpu.global.u32 [%0], %1;" :: "l"(p), "r"(v) : "memory"); }
__device__ __forceinline__ void stg_rlx64(void* p, uint32_t a, uint32_t b) { asm volatile("st.relaxed.gpu.global.v2.u32 [%0], {%1, %2};" :: "l"(p), "r"(a), "r"(b) : "memory"); }
__device__ __forceinline__ uint4 ldsm4(uint32_t a) { uint4 v; asm volatile("ldmatrix.sync.aligned.m8n8.x4.shared.b16 {%0, %1, %2, %3}, [%4];" : "=r"(v.x), "=r"(v.y), "=r"(v.z), "=r"(v.w) : "r"(a) : "memory"); return v; }
__device__ __forceinline__ void ldsm4_if(uint4& v, uint32_t a, int off, bool p) {
  asm volatile("{\n.reg .pred q;\nsetp.ne.u32 q, %5, 0;\n@q ldmatrix.sync.aligned.m8n8.x4.shared.b16 {%0, %1, %2, %3}, [%4];\n}\n"
               : "+r"(v.x), "+r"(v.y), "+r"(v.z), "+r"(v.w) : "r"(a + off), "r"((int)p) : "memory");
}
__device__ __forceinline__ uint4 ldsm4t(uint32_t a) { uint4 v; asm volatile("ldmatrix.sync.aligned.m8n8.x4.trans.shared.b16 {%0, %1, %2, %3}, [%4];" : "=r"(v.x), "=r"(v.y), "=r"(v.z), "=r"(v.w) : "r"(a) : "memory"); return v; }
__device__ __forceinline__ void stsm4(uint32_t a, uint32_t x, uint32_t y, uint32_t z, uint32_t w) { asm volatile("stmatrix.sync.aligned.m8n8.x4.shared.b16 [%0], {%1, %2, %3, %4};" :: "r"(a), "r"(x), "r"(y), "r"(z), "r"(w) : "memory"); }
__device__ __forceinline__ void mma_acc(float (&c)[4], const uint4& a, uint32_t b0, uint32_t b1) {
  asm("mma.sync.aligned.m16n8k16.row.col.f32.bf16.bf16.f32 {%0,%1,%2,%3}, {%4,%5,%6,%7}, {%8,%9}, {%0,%1,%2,%3};"
      : "+f"(c[0]), "+f"(c[1]), "+f"(c[2]), "+f"(c[3]) : "r"(a.x), "r"(a.y), "r"(a.z), "r"(a.w), "r"(b0), "r"(b1));
}
__device__ __forceinline__ uint4 lds128(uint32_t a) { uint4 v; asm volatile("ld.shared.v4.u32 {%0, %1, %2, %3}, [%4];" : "=r"(v.x), "=r"(v.y), "=r"(v.z), "=r"(v.w) : "r"(a) : "memory"); return v; }
__device__ __forceinline__ float2 lds64f(uint32_t a) { float2 v; asm volatile("ld.shared.v2.f32 {%0, %1}, [%2];" : "=f"(v.x), "=f"(v.y) : "r"(a)); return v; }
__device__ __forceinline__ float lds32f(uint32_t a) { float v; asm volatile("ld.shared.f32 %0, [%1];" : "=f"(v) : "r"(a)); return v; }
__device__ __forceinline__ void sts32f(uint32_t a, float v) { asm volatile("st.shared.f32 [%0], %1;" :: "r"(a), "f"(v) : "memory"); }
__device__ __forceinline__ uint32_t pack_bf16(float lo, float hi) { uint32_t r; asm("cvt.rn.bf16x2.f32 %0, %1, %2;" : "=r"(r) : "f"(hi), "f"(lo)); return r; }
__device__ __forceinline__ float bf_lo(uint32_t v) { return __uint_as_float(v << 16); }
__device__ __forceinline__ float bf_hi(uint32_t v) { return __uint_as_float(v & 0xffff0000u); }
__device__ __forceinline__ uint32_t movm(uint32_t a) { uint32_t d; asm("movmatrix.sync.aligned.m8n8.trans.b16 %0, %1;" : "=r"(d) : "r"(a)); return d; }
__device__ __forceinline__ float ex2(float x) { float y; asm("ex2.approx.ftz.f32 %0, %1;" : "=f"(y) : "f"(x)); return y; }
__device__ __forceinline__ float rsq(float x) { float y; asm("rsqrt.approx.ftz.f32 %0, %1;" : "=f"(y) : "f"(x)); return y; }
__device__ __forceinline__ float rcp(float x) { float y; asm("rcp.approx.ftz.f32 %0, %1;" : "=f"(y) : "f"(x)); return y; }
__device__ __forceinline__ bool elect() { uint32_t p; asm volatile("{\n.reg .pred q;\nelect.sync _|q, 0xffffffff;\nselp.u32 %0, 1, 0, q;\n}\n" : "=r"(p)); return p; }
__device__ __forceinline__ int clk() { int c; asm volatile("mov.u32 %0, %%clock;" : "=r"(c) :: "memory"); return c; }
__device__ __forceinline__ void pf_l2(const void* p) { asm volatile("prefetch.global.L2 [%0];" :: "l"(p)); }
__device__ __forceinline__ bool anyw(bool p) { return __any_sync(0xffffffffu, p); }
__device__ __forceinline__ float shx(float v, int m) { return __shfl_xor_sync(0xffffffffu, v, m); }
__device__ __forceinline__ void mma_k24(float (&c)[4], uint32_t a0, uint32_t a1, uint32_t a2, uint32_t a3, uint32_t b0, uint32_t b1,
                                        uint32_t e0, uint32_t e1, uint32_t f0) {
  asm("mma.sync.aligned.m16n8k16.row.col.f32.bf16.bf16.f32 {%0,%1,%2,%3}, {%4,%5,%6,%7}, {%8,%9}, {%10,%10,%10,%10};"
      : "=f"(c[0]), "=f"(c[1]), "=f"(c[2]), "=f"(c[3]) : "r"(a0), "r"(a1), "r"(a2), "r"(a3), "r"(b0), "r"(b1), "f"(0.f));
  asm("mma.sync.aligned.m16n8k8.row.col.f32.bf16.bf16.f32 {%0,%1,%2,%3}, {%4,%5}, {%6}, {%0,%1,%2,%3};"
      : "+f"(c[0]), "+f"(c[1]), "+f"(c[2]), "+f"(c[3]) : "r"(e0), "r"(e1), "r"(f0));
}
__device__ __forceinline__ uint32_t ord_key(float r) { uint32_t u = __float_as_uint(r); return u ^ ((uint32_t)((int32_t)u >> 31) | 0x80000000u); }

__device__ __forceinline__ void wgmma_n48hi_ss(float (&d)[120], uint64_t da, uint64_t db, int scale_d) {
  asm volatile("{\n.reg .pred p;\nsetp.ne.b32 p, %26, 0;\n"
    "wgmma.mma_async.sync.aligned.m64n48k16.f32.bf16.bf16 "
    "{%0, %1, %2, %3, %4, %5, %6, %7, %8, %9, %10, %11, %12, %13, %14, %15, "
    "%16, %17, %18, %19, %20, %21, %22, %23}, "
    "%24, %25, p, 1, 1, 0, 1;\n}\n"
    : "+f"(d[96]), "+f"(d[97]), "+f"(d[98]), "+f"(d[99]), "+f"(d[100]), "+f"(d[101]), "+f"(d[102]), "+f"(d[103]),
      "+f"(d[104]), "+f"(d[105]), "+f"(d[106]), "+f"(d[107]), "+f"(d[108]), "+f"(d[109]), "+f"(d[110]), "+f"(d[111]),
      "+f"(d[112]), "+f"(d[113]), "+f"(d[114]), "+f"(d[115]), "+f"(d[116]), "+f"(d[117]), "+f"(d[118]), "+f"(d[119])
    : "l"(da), "l"(db), "r"(scale_d));
}
__device__ __forceinline__ void wgmma_n192lo_ss(float (&d)[120], uint64_t da, uint64_t db, int scale_d) {
  asm volatile("{\n.reg .pred p;\nsetp.ne.b32 p, %98, 0;\n"
    "wgmma.mma_async.sync.aligned.m64n192k16.f32.bf16.bf16 "
    "{%0, %1, %2, %3, %4, %5, %6, %7, %8, %9, %10, %11, %12, %13, %14, %15, "
    "%16, %17, %18, %19, %20, %21, %22, %23, %24, %25, %26, %27, %28, %29, %30, %31, "
    "%32, %33, %34, %35, %36, %37, %38, %39, %40, %41, %42, %43, %44, %45, %46, %47, "
    "%48, %49, %50, %51, %52, %53, %54, %55, %56, %57, %58, %59, %60, %61, %62, %63, "
    "%64, %65, %66, %67, %68, %69, %70, %71, %72, %73, %74, %75, %76, %77, %78, %79, "
    "%80, %81, %82, %83, %84, %85, %86, %87, %88, %89, %90, %91, %92, %93, %94, %95}, "
    "%96, %97, p, 1, 1, 0, 1;\n}\n"
    : "+f"(d[0]), "+f"(d[1]), "+f"(d[2]), "+f"(d[3]), "+f"(d[4]), "+f"(d[5]), "+f"(d[6]), "+f"(d[7]),
      "+f"(d[8]), "+f"(d[9]), "+f"(d[10]), "+f"(d[11]), "+f"(d[12]), "+f"(d[13]), "+f"(d[14]), "+f"(d[15]),
      "+f"(d[16]), "+f"(d[17]), "+f"(d[18]), "+f"(d[19]), "+f"(d[20]), "+f"(d[21]), "+f"(d[22]), "+f"(d[23]),
      "+f"(d[24]), "+f"(d[25]), "+f"(d[26]), "+f"(d[27]), "+f"(d[28]), "+f"(d[29]), "+f"(d[30]), "+f"(d[31]),
      "+f"(d[32]), "+f"(d[33]), "+f"(d[34]), "+f"(d[35]), "+f"(d[36]), "+f"(d[37]), "+f"(d[38]), "+f"(d[39]),
      "+f"(d[40]), "+f"(d[41]), "+f"(d[42]), "+f"(d[43]), "+f"(d[44]), "+f"(d[45]), "+f"(d[46]), "+f"(d[47]),
      "+f"(d[48]), "+f"(d[49]), "+f"(d[50]), "+f"(d[51]), "+f"(d[52]), "+f"(d[53]), "+f"(d[54]), "+f"(d[55]),
      "+f"(d[56]), "+f"(d[57]), "+f"(d[58]), "+f"(d[59]), "+f"(d[60]), "+f"(d[61]), "+f"(d[62]), "+f"(d[63]),
      "+f"(d[64]), "+f"(d[65]), "+f"(d[66]), "+f"(d[67]), "+f"(d[68]), "+f"(d[69]), "+f"(d[70]), "+f"(d[71]),
      "+f"(d[72]), "+f"(d[73]), "+f"(d[74]), "+f"(d[75]), "+f"(d[76]), "+f"(d[77]), "+f"(d[78]), "+f"(d[79]),
      "+f"(d[80]), "+f"(d[81]), "+f"(d[82]), "+f"(d[83]), "+f"(d[84]), "+f"(d[85]), "+f"(d[86]), "+f"(d[87]),
      "+f"(d[88]), "+f"(d[89]), "+f"(d[90]), "+f"(d[91]), "+f"(d[92]), "+f"(d[93]), "+f"(d[94]), "+f"(d[95])
    : "l"(da), "l"(db), "r"(scale_d));
}
__device__ __forceinline__ void wgmma_n48hi_rk(float (&d)[120], uint32_t a0, uint32_t a1, uint32_t a2, uint32_t a3, uint64_t db, int scale_d) {
  asm volatile("{\n.reg .pred p;\nsetp.ne.b32 p, %29, 0;\n"
    "wgmma.mma_async.sync.aligned.m64n48k16.f32.bf16.bf16 "
    "{%0, %1, %2, %3, %4, %5, %6, %7, %8, %9, %10, %11, %12, %13, %14, %15, "
    "%16, %17, %18, %19, %20, %21, %22, %23}, "
    "{%24, %25, %26, %27}, %28, p, 1, 1, 0;\n}\n"
    : "+f"(d[96]), "+f"(d[97]), "+f"(d[98]), "+f"(d[99]), "+f"(d[100]), "+f"(d[101]), "+f"(d[102]), "+f"(d[103]),
      "+f"(d[104]), "+f"(d[105]), "+f"(d[106]), "+f"(d[107]), "+f"(d[108]), "+f"(d[109]), "+f"(d[110]), "+f"(d[111]),
      "+f"(d[112]), "+f"(d[113]), "+f"(d[114]), "+f"(d[115]), "+f"(d[116]), "+f"(d[117]), "+f"(d[118]), "+f"(d[119])
    : "r"(a0), "r"(a1), "r"(a2), "r"(a3), "l"(db), "r"(scale_d));
}
__device__ __forceinline__ void wgmma_n192lo_rk(float (&d)[120], uint32_t a0, uint32_t a1, uint32_t a2, uint32_t a3, uint64_t db, int scale_d) {
  asm volatile("{\n.reg .pred p;\nsetp.ne.b32 p, %101, 0;\n"
    "wgmma.mma_async.sync.aligned.m64n192k16.f32.bf16.bf16 "
    "{%0, %1, %2, %3, %4, %5, %6, %7, %8, %9, %10, %11, %12, %13, %14, %15, "
    "%16, %17, %18, %19, %20, %21, %22, %23, %24, %25, %26, %27, %28, %29, %30, %31, "
    "%32, %33, %34, %35, %36, %37, %38, %39, %40, %41, %42, %43, %44, %45, %46, %47, "
    "%48, %49, %50, %51, %52, %53, %54, %55, %56, %57, %58, %59, %60, %61, %62, %63, "
    "%64, %65, %66, %67, %68, %69, %70, %71, %72, %73, %74, %75, %76, %77, %78, %79, "
    "%80, %81, %82, %83, %84, %85, %86, %87, %88, %89, %90, %91, %92, %93, %94, %95}, "
    "{%96, %97, %98, %99}, %100, p, 1, 1, 0;\n}\n"
    : "+f"(d[0]), "+f"(d[1]), "+f"(d[2]), "+f"(d[3]), "+f"(d[4]), "+f"(d[5]), "+f"(d[6]), "+f"(d[7]),
      "+f"(d[8]), "+f"(d[9]), "+f"(d[10]), "+f"(d[11]), "+f"(d[12]), "+f"(d[13]), "+f"(d[14]), "+f"(d[15]),
      "+f"(d[16]), "+f"(d[17]), "+f"(d[18]), "+f"(d[19]), "+f"(d[20]), "+f"(d[21]), "+f"(d[22]), "+f"(d[23]),
      "+f"(d[24]), "+f"(d[25]), "+f"(d[26]), "+f"(d[27]), "+f"(d[28]), "+f"(d[29]), "+f"(d[30]), "+f"(d[31]),
      "+f"(d[32]), "+f"(d[33]), "+f"(d[34]), "+f"(d[35]), "+f"(d[36]), "+f"(d[37]), "+f"(d[38]), "+f"(d[39]),
      "+f"(d[40]), "+f"(d[41]), "+f"(d[42]), "+f"(d[43]), "+f"(d[44]), "+f"(d[45]), "+f"(d[46]), "+f"(d[47]),
      "+f"(d[48]), "+f"(d[49]), "+f"(d[50]), "+f"(d[51]), "+f"(d[52]), "+f"(d[53]), "+f"(d[54]), "+f"(d[55]),
      "+f"(d[56]), "+f"(d[57]), "+f"(d[58]), "+f"(d[59]), "+f"(d[60]), "+f"(d[61]), "+f"(d[62]), "+f"(d[63]),
      "+f"(d[64]), "+f"(d[65]), "+f"(d[66]), "+f"(d[67]), "+f"(d[68]), "+f"(d[69]), "+f"(d[70]), "+f"(d[71]),
      "+f"(d[72]), "+f"(d[73]), "+f"(d[74]), "+f"(d[75]), "+f"(d[76]), "+f"(d[77]), "+f"(d[78]), "+f"(d[79]),
      "+f"(d[80]), "+f"(d[81]), "+f"(d[82]), "+f"(d[83]), "+f"(d[84]), "+f"(d[85]), "+f"(d[86]), "+f"(d[87]),
      "+f"(d[88]), "+f"(d[89]), "+f"(d[90]), "+f"(d[91]), "+f"(d[92]), "+f"(d[93]), "+f"(d[94]), "+f"(d[95])
    : "r"(a0), "r"(a1), "r"(a2), "r"(a3), "l"(db), "r"(scale_d));
}
__device__ __forceinline__ void wgmma_n80_rs(float (&d)[40], uint32_t a0, uint32_t a1, uint32_t a2, uint32_t a3, uint64_t db, int scale_d) {
  asm volatile("{\n.reg .pred p;\nsetp.ne.b32 p, %45, 0;\n"
    "wgmma.mma_async.sync.aligned.m64n80k16.f32.bf16.bf16 "
    "{%0, %1, %2, %3, %4, %5, %6, %7, %8, %9, %10, %11, %12, %13, %14, %15, "
    "%16, %17, %18, %19, %20, %21, %22, %23, %24, %25, %26, %27, %28, %29, %30, %31, "
    "%32, %33, %34, %35, %36, %37, %38, %39}, "
    "{%40, %41, %42, %43}, %44, p, 1, 1, 1;\n}\n"
    : "+f"(d[0]), "+f"(d[1]), "+f"(d[2]), "+f"(d[3]), "+f"(d[4]), "+f"(d[5]), "+f"(d[6]), "+f"(d[7]),
      "+f"(d[8]), "+f"(d[9]), "+f"(d[10]), "+f"(d[11]), "+f"(d[12]), "+f"(d[13]), "+f"(d[14]), "+f"(d[15]),
      "+f"(d[16]), "+f"(d[17]), "+f"(d[18]), "+f"(d[19]), "+f"(d[20]), "+f"(d[21]), "+f"(d[22]), "+f"(d[23]),
      "+f"(d[24]), "+f"(d[25]), "+f"(d[26]), "+f"(d[27]), "+f"(d[28]), "+f"(d[29]), "+f"(d[30]), "+f"(d[31]),
      "+f"(d[32]), "+f"(d[33]), "+f"(d[34]), "+f"(d[35]), "+f"(d[36]), "+f"(d[37]), "+f"(d[38]), "+f"(d[39])
    : "r"(a0), "r"(a1), "r"(a2), "r"(a3), "l"(db), "r"(scale_d));
}
__device__ __forceinline__ void wgmma_n80_ss(float (&d)[40], uint64_t da, uint64_t db, int scale_d) {
  asm volatile("{\n.reg .pred p;\nsetp.ne.b32 p, %42, 0;\n"
    "wgmma.mma_async.sync.aligned.m64n80k16.f32.bf16.bf16 "
    "{%0, %1, %2, %3, %4, %5, %6, %7, %8, %9, %10, %11, %12, %13, %14, %15, "
    "%16, %17, %18, %19, %20, %21, %22, %23, %24, %25, %26, %27, %28, %29, %30, %31, "
    "%32, %33, %34, %35, %36, %37, %38, %39}, "
    "%40, %41, p, 1, 1, 0, 1;\n}\n"
    : "+f"(d[0]), "+f"(d[1]), "+f"(d[2]), "+f"(d[3]), "+f"(d[4]), "+f"(d[5]), "+f"(d[6]), "+f"(d[7]),
      "+f"(d[8]), "+f"(d[9]), "+f"(d[10]), "+f"(d[11]), "+f"(d[12]), "+f"(d[13]), "+f"(d[14]), "+f"(d[15]),
      "+f"(d[16]), "+f"(d[17]), "+f"(d[18]), "+f"(d[19]), "+f"(d[20]), "+f"(d[21]), "+f"(d[22]), "+f"(d[23]),
      "+f"(d[24]), "+f"(d[25]), "+f"(d[26]), "+f"(d[27]), "+f"(d[28]), "+f"(d[29]), "+f"(d[30]), "+f"(d[31]),
      "+f"(d[32]), "+f"(d[33]), "+f"(d[34]), "+f"(d[35]), "+f"(d[36]), "+f"(d[37]), "+f"(d[38]), "+f"(d[39])
    : "l"(da), "l"(db), "r"(scale_d));
}

__device__ __forceinline__ constexpr int QT(int t) { return t < 8 ? t : 16 + t; }
__device__ __forceinline__ constexpr int KT(int t) { return t < 8 ? 8 + t : 18 + t; }
__device__ __forceinline__ constexpr int VT(int t) { return t < 8 ? 16 + t : 20 + t; }

struct Maps { CUtensorMap x, w, wr, wo, wor, gate, up, down; };

__global__ void __cluster_dims__(2, 1, 1) __launch_bounds__(512, 1)
fused_kernel(const __nv_bfloat16* __restrict__ x, const __nv_bfloat16* __restrict__ wqkv,
             const __nv_bfloat16* __restrict__ wo, const __nv_bfloat16* __restrict__ w_r, const __nv_bfloat16* __restrict__ w_gate,
             const __nv_bfloat16* __restrict__ w_up, const __nv_bfloat16* __restrict__ w_down, __nv_bfloat16* __restrict__ out,
             Scratch* __restrict__ sc, const __grid_constant__ Maps tm) {
  extern __shared__ __align__(1024) uint8_t smem[];
  const int tid = threadIdx.x, warp = __shfl_sync(0xffffffffu, tid >> 5, 0), lane = tid & 31, bid = blockIdx.x;
  const uint32_t sb = (uint32_t)__cvta_generic_to_shared(smem);
  const uint32_t bar_full = sb + OFF_BAR, bar_empty = bar_full + 32, bar_aux = bar_full + 64, bar_ffn = bar_full + 72, bar_win = bar_full + 80, bar_rst = bar_full + 88,
                 bar_o = bar_full + 96;
  if (warp < 4 && elect()) {
    mbar_init(bar_full + 8 * (warp ^ 2), 1);
    mbar_init(bar_empty + 8 * warp, 24);
    mbar_init(bar_aux + 8 * warp, warp == 0 ? 64 : warp == 2 ? 32 : 1);
    asm volatile("fence.mbarrier_init.release.cluster;" ::: "memory");
  }
  if (warp >= 4 && warp < 12 && elect()) { mbar_init(bar_o + 16 * (warp - 4), (warp & 2) ? 4 : 1); mbar_init(bar_o + 16 * (warp - 4) + 8, (warp & 2) ? 4 : (warp & 1) ? 128 : 1); }
  asm volatile("barrier.cluster.arrive.relaxed.aligned;" ::: "memory");
  if (warp >= 8 && warp < 11 && elect()) asm volatile("prefetch.tensormap [%0];" :: "l"(&tm.x + (warp - 8)) : "memory");
  auto pf_slice = [&](int ks) {
    pf_l2(lane < 16 ? (const char*)x + ((bid * 16 + lane) * 1280 + ks * 128) : (const char*)wqkv + ((bid * 15 + min(lane, 30) - 16) * 128 + ks * 245760));
  };
  if (warp == 4) pf_slice(0);
  const int rank = bid & 1, cl = bid >> 1;
  const int q7 = ((cl - 36) * 37) >> 8;
  const int P = cl < 4 ? 0 : cl < 36 ? (cl - 4) & 7 : cl - 35 - 7 * q7;
  const int g = cl < 4 ? 4 + cl : cl < 36 ? (cl - 4) >> 3 : 4 + q7;
  const int mt = 2 * P + rank, cid = mt * 8 + g;
  const bool ffn1 = g < 3;
  const int fj = ffn1 ? mt * 3 + g : (P * 5 + g - 3) * 2 + rank;
  const int ord = ((g >> 2) ^ P) & 1;
  auto ks_of = [&](int it) { return !ORDX || ord == 0 || it == 0 ? it : it <= 5 ? it + 4 : it - 5; };
  auto load_w = [&](int it, uint32_t a, uint32_t full) {
    tma_3d_mc(a + 16384 + rank * 16384, &tm.w, full, g * 80, it * 64, rank * 2);
    tma_3d_mc(a + (rank ? 40960 : 24576), rank ? &tm.wr : &tm.w, full, g * 80 + rank * 64, it * 64, 1 - rank);
  };
  if (warp == 0 && elect()) {
    mbar_expect_tx(bar_full + 16, SLOT);
    tma_3d(sb + 2 * SLOT, &tm.x, bar_full + 16, 0, mt * 64, 0);
  }
  asm volatile("barrier.cluster.wait.aligned;" ::: "memory");
  if (warp == 0) {
    if (elect()) load_w(0, sb + 2 * SLOT, bar_full + 16);
    asm volatile("bar.arrive 4, 64;" ::: "memory");
  }

  if (warp >= 8) {
    asm volatile("setmaxnreg.dec.sync.aligned.u32 %0;" :: "n"(REG_P));
#define TS_T 0
    if (warp == 8) {
      TS(8);
      bar_sync(4, 64);
      if (elect()) {
        TS(10);
        int fjn = 0;
#pragma unroll 1
        for (int it = 1; it < 17; it++) {
          const int s = (it + 2) & 3;
          const uint32_t full = bar_full + 8 * s, a = sb + s * SLOT;
          if (it >= 13) { mbar_wait(bar_o + 32 + 8 * (it - 13), 0); mbar_wait(bar_o + 96 + 8 * (it - 13), 0); }
          else if (it >= 4) mbar_wait(bar_empty + 8 * s, ((it >> 2) - 1) & 1);
          else if (it >= THR) mbar_wait(bar_full + 8 * ((it - THR + 2) & 3), 0);
          if (it < 10) {
            const int ks = ks_of(it);
            mbar_expect_tx(full, SLOT);
            tma_3d(a, &tm.x, full, ks * 64, mt * 64, 0);
            load_w(ks, a, full);
            TS(12 + it);
            if ((unsigned)(it - RST_IT) < 3u) {
              mbar_wait(bar_rst, 0);
              char* const d = it == RST_IT ? (char*)(g_own + cid) : it == RST_IT + 1 ? (char*)(g_own + cid) + 2688 : (char*)((uint4*)&g_x + cid * GLOB_PER_CTA);
              asm volatile("cp.async.bulk.global.shared::cta.bulk_group [%0], [%1], %2;\ncp.async.bulk.commit_group;"
                           :: "l"(d), "r"(sb + OFF_CS), "r"(it == RST_IT ? 2688 : it == RST_IT + 1 ? 3584 : GLOB_PER_CTA * 16) : "memory");
            }
            if (it == RST_IT + 3) { asm volatile("cp.async.bulk.wait_group 0;" ::: "memory"); mbar_arrive(bar_rst); }
          } else if (it < 13) {
            const int g0 = 3 * (it - 10), g1 = min(g0 + 3, 8);
            mbar_expect_tx(full, (g1 - g0) * 12800);
#pragma unroll 1
            for (int gp = g0 + ((g0 ^ rank) & 1); gp < g1; gp += 2) {
              tma_3d_mc(sb + gp * 15360, &tm.wo, full, 0, gp * 80, g * 2);
              tma_3d_mc(sb + gp * 15360 + 10240, &tm.wor, full, 512 + g * 16, gp * 80, 0);
            }
          }
          if (it == 4) mbar_expect_tx(bar_ffn, ffn1 ? 81920 : 24576);
          const int j1 = ffn1 ? (it >= 13 ? min(2 * it - 21, 10) : min(max(it - F_IT + 1, 0), 4)) : (it >= 13 ? 12 : min(max((it - F_IT + 1) * F_PER, 0), F_MAX));
#pragma unroll 1
          for (; fjn < j1; fjn++) {
            const int j = fjn < 4 ? fjn + 6 : fjn - 4;
            if (ffn1) tma_3d(sb + (j < 6 ? 0 : OFF_W2 - 49152) + j * 8192, j < 5 ? &tm.gate : &tm.up, bar_ffn, fj * 32, (j < 5 ? j : j - 5) * 128, 0);
            else tma_3d(sb + OFF_W2 + fjn * 2048, &tm.down, bar_ffn, fj * 8, fjn * 128, 0);
          }
        }
        TS(11);
      }
#undef TS_T
#define TS_T 0
    } else if (warp >= 12) {
      const int l7 = lane & 7, j = warp - 12, ch = min((P >> 1) * 4 + rank * 2 + (j >> 1), 14);
      const uint32_t sxo = ((g & 3) * 32 + j * 8 + l7) * 128 + (((lane >> 3) ^ l7) * 16);
      const uint32_t swo = ch < 12 ? 16384 + (ch >> 2) * 8192 + lane * 128 + ((((ch & 3) * 2 + (j & 1)) ^ l7) * 16)
                                   : 40960 + (ch - 12) * 2048 + lane * 32 + (((j & 1) ^ (l7 >> 2)) * 16);
      float ps = 0.f, pq = 0.f, pq1 = 0.f, pc = 0.f;
#pragma unroll 1
      for (int it = ord; it < ord + 5; it++) {
        const int sl = (it + 2) & 3;
        mbar_wait(bar_full + 8 * sl, (it >> 2) & 1);
        TS(it);
        const uint32_t a = sb + sl * SLOT;
        const uint4 v0 = ldsm4(a + sxo), v1 = ldsm4((a + sxo) ^ 64), w0 = ldsm4t(a + swo), w1 = ldsm4t(a + swo + (ch < 12 ? 4096 : 1024));
        if (lane + (int)((v0.x & v1.x & w0.x & w1.x) == 0x7fc17fc1u && (v0.x | v1.x) == 0u) < 2) mbar_arrive_cta(bar_empty + 8 * sl, lane);
        const uint32_t vv[8] = {v0.x, v0.y, v0.z, v0.w, v1.x, v1.y, v1.z, v1.w}, ww[8] = {w0.x, w0.y, w0.z, w0.w, w1.x, w1.y, w1.z, w1.w};
#pragma unroll
        for (int i = 0; i < 8; i++) {
          const float d = bf_lo(vv[i]), e = bf_hi(vv[i]);
          ps += d + e; pq = fmaf(d, d, pq); pq1 = fmaf(e, e, pq1); pc += bf_lo(ww[i]) + bf_hi(ww[i]);
        }
      }
      pq += pq1;
      ps += shx(ps, 1); pq += shx(pq, 1); pc += shx(pc, 1);
      ps += shx(ps, 2); pq += shx(pq, 2); pc += shx(pc, 2);
      const int c = lane & 3;
      if (c < 3) sts32f(sb + OFF_PT + (c * 32 + j * 8 + (lane >> 2)) * 4, c == 0 ? ps : c == 1 ? pq : pc);
      asm volatile("bar.arrive 2, 224;" ::: "memory");
#undef TS_T
#define TS_T 32
    } else if (warp < 11) {
      Own* const own = g_own + cid;
      const int l7 = lane & 7, hk = lane >> 4, idx = lane;
      {
        const int t0 = clk();
#pragma unroll 1
        for (int i = PF_FIRST; i < 6; i++) {
          while (clk() - t0 < PF_T0 + (i - PF_FIRST) * PF_CLK) __nanosleep(20);
          pf_slice(warp == 9 ? min(i, 4) : i + 4);
        }
      }
      bar_sync(2, 224);
      mbar_wait(bar_rst, 1);
      TS(0);
      const uint32_t tag = __float_as_uint(lds32f(sb + OFF_WR + 324));
      const float s0 = lds32f(sb + OFF_PT + lane * 4 + (warp - 9) * 256), q0 = lds32f(sb + OFF_PT + 128 + lane * 4);
      int guard = SPIN_MAX;
      if (warp == 9) {
        stg_pkt(&own->st1[idx], __float_as_uint(s0), __float_as_uint(q0), tag, 0u);
        TS(1);
        const uint4* sp = &g_own[mt * 8].st1[lane];
        const uint4* hp = &g_own[max(mt - 1, 0) * 8 + hk * 2 + 1].st1[24 + l7];
        uint4 a[5], b[5];
        bool bad;
        do {
          __nanosleep(AUX_NS);
          bad = false;
#pragma unroll
          for (int i = 0; i < 5; i++) {
            const uint4* q = i < 4 ? sp + i * (sizeof(Own) / 16) : hp;
            a[i] = ldg_pkt(q); b[i] = ldg_pkt(q + 4 * sizeof(Own) / 16);
          }
#pragma unroll
          for (int i = 0; i < 5; i++) bad |= a[i].z != tag || b[i].z != tag;
        } while (anyw(bad) && --guard);
#pragma unroll
        for (int i = 0; i < 5; i++) {
          const float m = (__uint_as_float(a[i].x) + __uint_as_float(b[i].x)) * (1.f / 640.f);
          const float rs = rsq(fmaxf(fmaf(-m, m, (__uint_as_float(a[i].y) + __uint_as_float(b[i].y)) * (1.f / 640.f)), 0.f) + 1e-5f);
          ((float*)(smem + OFF_RS))[i < 4 ? 8 + lane + 32 * i + 8 * (i >> 1) : hk * 72 + l7] = rs;
          const uint32_t mh = pack_bf16(-m, -m);
          const float ml = -m - bf_lo(mh);
          if (i < 4) ((uint2*)(smem + OFF_MN))[lane + 32 * i] = make_uint2(mh, pack_bf16(ml, ml));
        }
      } else {
        stg_rlx64(&own->cs[idx], __float_as_uint(s0), tag);
        const uint4* cp = (const uint4*)g_own[hk * 8 + g].cs + (lane & 15);
        uint4 a[4], b[4];
        bool bad;
        do {
          __nanosleep(AUX_NS);
          bad = false;
#pragma unroll
          for (int i = 0; i < 4; i++) { a[i] = ldg_pkt(cp + i * 32 * sizeof(Own) / 16); b[i] = ldg_pkt(cp + (i * 32 + 16) * sizeof(Own) / 16); }
#pragma unroll
          for (int i = 0; i < 4; i++) bad |= a[i].y != tag || a[i].w != tag || b[i].y != tag || b[i].w != tag;
        } while (anyw(bad) && --guard);
#pragma unroll
        for (int i = 0; i < 4; i++)
          if (i < 3 || lane < 24) {
            const float c0 = __uint_as_float(a[i].x) + __uint_as_float(b[i].x), c1 = __uint_as_float(a[i].z) + __uint_as_float(b[i].z);
            const uint32_t hi = pack_bf16(c0, c1), w0 = pack_bf16(c0, c0 - bf_lo(hi)), w1 = pack_bf16(c1, c1 - bf_hi(hi));
            uint4* const d = (uint4*)(smem + OFF_CS) + 2 * (lane + 32 * i);
            d[0] = make_uint4(w0, w0, 0, 0); d[1] = make_uint4(w1, w1, 0, 0);
          }
        asm volatile("fence.proxy.async.shared::cta;" ::: "memory");
      }
      mbar_arrive(bar_aux);
      TS(2);
      const int wq = warp - 9;
      const uint4* const fp = hold(g_own[mt * 8 + wq * 4].cnt);
      const char* const src = hold((const char*)g_o[mt * 2 + wq]);
      bar_sync(5 + wq, 160);
      if (elect()) {
        while (ldg_rlx32(fp) != 32u && --guard > 0) {}
        asm volatile("fence.proxy.async.global;" ::: "memory");
        TS(6);
#pragma unroll 1
        for (int i = 0, sl = 0; i < 7; i++) {
          const uint32_t full = bar_o + wq * 64 + 8 * sl;
          if (i >= 3) mbar_wait(bar_o + wq * 64 + 8 + 8 * i, 0);
          mbar_expect_tx(full, 10240);
          asm volatile("cp.async.bulk.shared::cluster.global.mbarrier::complete_tx::bytes [%0], [%1], 10240, [%2];"
                       :: "r"(sb + OFF_O + sl * 20480 + wq * 10240), "l"(src + (i + (i >= g)) * 10240), "r"(full) : "memory");
          sl = sl == 2 ? 0 : sl + 1;
        }
      }
#undef TS_T
#define TS_T 96
    } else {
      if ((sb & 0x3FFFF) != D0 * 16) __trap();
#pragma unroll 1
      for (int i = lane; i < 224; i += 32) { const uint32_t f = i < 200 ? SENT : 0u; ((uint4*)(smem + OFF_CS))[i] = make_uint4(f, f, f, f); }
      asm volatile("fence.proxy.async.shared::cta;" ::: "memory");
      if (elect()) mbar_arrive(bar_rst);
      mbar_wait(bar_full + 8 * ((HK_IT + 2) & 3), 0);
      TS(4);
      const uint32_t epoch = ldg_rlx32(g_epoch + cid) + 1;
      uint32_t wv[10];
#pragma unroll
      for (int i = 0; i < 10; i++) wv[i] = __ldg((const uint32_t*)w_r + lane + 32 * i);
      float s = 0.f;
#pragma unroll
      for (int i = 0; i < 10; i++) {
        s += bf_lo(wv[i]) + bf_hi(wv[i]);
        const unsigned u = i < 8 ? lane + 32 * (i - g) : lane + 32 * (i - 7) - g * 8;
        if (i < 8 ? u < 32u : u - 32u < 8u) *(float2*)(smem + OFF_WR + ((u & 3) * 10 + (u >> 2)) * 8) = make_float2(bf_lo(wv[i]), bf_hi(wv[i]));
      }
#pragma unroll
      for (int m = 1; m < 32; m <<= 1) s += shx(s, m);
      *(float2*)(smem + OFF_WR + 320) = make_float2(s, __uint_as_float(epoch * 0x9E3779B8u));
      g_epoch[cid] = epoch;
      TS(3);
      TS(5);
      asm volatile("bar.arrive 2, 224;" ::: "memory");
#pragma unroll 1
      for (int i = 0; i < 14; i++) {
        const int m = (i + 2) >> 2, n = m == 0 ? 50 : 120, t = (m == 0 ? i : (i + 2) & 3) * 32 + lane;
        const char* b = (const char*)(m == 0 ? wo : m == 1 ? w_up : m == 2 ? w_down : w_gate);
        if (t < n) pf_l2(b + (bid * n + t) * 128);
        __nanosleep(PFW_NS);
      }
      bar_sync(3, 64);
      const uint4* const kp = g_own[1].cnt;
      const uint4* const cb = &g_x.cand[0][lane >> 2][lane & 3];
      uint4 k = ldg_pkt(kp), c0 = make_uint4(0, 0, 0, 0), c1 = c0; uint2 c2 = make_uint2(0, 0);
      int guard = SPIN_MAX, ws;
      while (true) {
        const uint32_t tk = 2047u - (k.x & 2047u);
        ws = (tk >> 7) * 8 + (tk & 1) * 4 + ((tk >> 5) & 3);
        const uint32_t prev = k.x;
        if (ffn1) { const uint4* q = cb + ws * 192; c0 = ldg_pkt(q); c1 = ldg_pkt(q + 4); c2 = ldg_rlx64(q + 8); }
        if (k.z != 128u) k = ldg_pkt(kp);
        if ((k.z == 128u && k.x == prev && !anyw(c0.x == SENT || c1.x == SENT || c2.x == SENT)) || --guard <= 0) break;
      }
      *(uint4*)(smem + OFF_HN + lane * 16) = c0; *(uint4*)(smem + OFF_HN + 512 + lane * 16) = c1; *(uint2*)(smem + OFF_HN + 1024 + lane * 16) = c2;
      const float rw = __uint_as_float(k.y ^ ((uint32_t)((int32_t)~k.y >> 31) | 0x80000000u));
      *(uint4*)(smem + OFF_WR + 336) = make_uint4(ws, 2047u - (k.x & 2047u), __float_as_uint(rcp(1.f + ex2(-1.4426950408889634f * rw))), 0);
      mbar_arrive(bar_win);
      TS(7);
    }
#undef TS_T
  } else {
#define TS_T 0
    TS(23);
    asm volatile("setmaxnreg.inc.sync.aligned.u32 %0;" :: "n"(REG_C));
    const int wg = warp >> 2, w4 = warp & 3, r = lane >> 2, c = lane & 3;
    float acc[120];
    uint4 xr[5] = {};
    const uint32_t xa = pin(sb + (warp * 16 + (lane & 15)) * 128 + ((lane >> 4) ^ (lane & 7)) * 16);
    const bool first = (mt == 0) && (w4 == 0);
    uint4* const kvd = pin(w4 < 3 ? (uint4*)(smem + OFF_O + warp * 2560) + lane : &g_own[cid].halo[wg][0][lane]);
    const uint4* const kvs = pin(first ? kvd : w4 > 0 ? (const uint4*)(smem + OFF_O + (warp - 1) * 2560) + lane : &g_own[cid - 8].halo[wg][0][lane]);
    uint4* const odst = hold(&g_o[mt * 2 + wg][g][w4 * 160]);
    uint4* const ocnt = hold(g_own[mt * 8 + wg * 4].cnt);
    uint32_t m0 = 0, m1 = 0;
    const uint32_t mna = pin(sb + OFF_MN + (warp * 16 + r) * 8 + c * 4);
    const int itx = ord == 0 || g == 0 ? g : g < 5 ? g + 5 : g - 4, ity = (ord ? 4 : 8) + (g >> 2);
    uint32_t rel;
    asm volatile("mapa.shared::cluster.u32 %0, %1, %2;" : "=r"(rel) : "r"(bar_empty), "r"(tid & 1));
    const uint32_t xa1 = pin(xa ^ 32), xa2 = pin(xa ^ 64), xa3 = pin(xa ^ 96), xb = pin(xa ^ ((g & 3) * 32));
    const uint32_t da0 = wg * 512;
    const bool rel2 = lane < 2, rel6 = lane < 2 + 2 * (warp & 1);
    const uint32_t zero = (uint32_t)(uintptr_t)x & 8u;
    TS(0);
    mbar_wait(bar_full + 16, 0);
    TS(13);
    wgmma_fence();
#pragma unroll
    for (int it = 0; it < 10; it++) {
      const int s = (it + 2) & 3;
      if (it == 9) bar_sync(10 + wg, 256);
#pragma unroll
      for (int kk = 0; kk < 4; kk++) {
        if (kk == 2 && it > 0) {
          wgmma_commit();
          wgmma_wait<1>();
          const uint32_t ra = ((xr[0].x ^ xr[1].x ^ xr[2].x ^ xr[3].x ^ xr[4].x) & zero) | rel;
          if (it == 1 ? (ord ? rel6 : rel2) : it == 6 ? (ord ? rel2 : rel6) : it < 6 ? rel2 : rel6)
            asm volatile("mbarrier.arrive.shared::cluster.b64 _, [%0];" :: "r"(ra + 8 * ((it + 1) & 3)) : "memory");
        }
        if (kk == 2) {
          ldsm4_if(xr[0], xa, s * SLOT, it == itx); ldsm4_if(xr[1], xa1, s * SLOT, it == itx);
          ldsm4_if(xr[2], xa2, s * SLOT, it == itx); ldsm4_if(xr[3], xa3, s * SLOT, it == itx);
          if ((it & 6) == 4 || it >= 8) ldsm4_if(xr[4], xb, s * SLOT, it == ity);
        }
        if (kk == 3 && it < 9) {
          mbar_wait(bar_full + 8 * ((it + 3) & 3), ((it + 1) >> 2) & 1);
          TS(14 + it);
        }
        if (kk == LK && it >= 8 && it == (wg == LEAD ? 9 : 8)) asm volatile("bar.arrive %0, 256;" :: "r"(11 - wg) : "memory");
        const uint64_t da = mk64(da0 + (D0 + s * (SLOT >> 4) + kk * 2 + (1 << 16)), 0x40000040u);
        wgmma_n48hi_ss(acc, da, mk64(D0 + s * (SLOT >> 4) + 2560 + kk * 32 + (128 << 16), 0xC0000010u), (it | kk) != 0);
        wgmma_n192lo_ss(acc, da, mk64(D0 + s * (SLOT >> 4) + 1024 + kk * 128 + (512 << 16), 0x40000040u), (it | kk) != 0);
      }
      wgmma_commit();
      if (LK >= 4 && it >= 8 && it == (wg == LEAD ? (LK == 4 ? 9 : 10) : 8)) asm volatile("bar.arrive %0, 256;" :: "r"(11 - wg) : "memory");
      if (it == 8) {
        mbar_wait(bar_aux, 0);
        TS(3);
        if (c < 2) { m0 = __float_as_uint(lds32f(mna)); m1 = __float_as_uint(lds32f(mna + 64)); }
      }
    }
    {
      const uint64_t dc = make_desc(D0 * 16 + OFF_CS, 0, 128, 0);
      wgmma_fence();
      wgmma_n48hi_rk(acc, m0, m1, 0u, 0u, dc + 192, 1);
      wgmma_n192lo_rk(acc, m0, m1, 0u, 0u, dc, 1);
      wgmma_commit();
      if (LK == 5 && wg == LEAD) asm volatile("bar.arrive %0, 256;" :: "r"(11 - LEAD) : "memory");
    }
    const uint32_t stb = sb + OFF_RS + (wg * 72 + 16 * w4) * 4;
    const float rlo = lds32f(stb + (8 + r) * 4), rhi = lds32f(stb + (16 + r) * 4);
    wgmma_wait<0>();
#pragma unroll
    for (int i = 0; i < 120; i++) asm volatile("" : "+f"(acc[i]) :: "memory");
    if (wg != LEAD) asm volatile("bar.arrive 9, 256;" ::: "memory");
    TS(2);
    uint32_t Qlo[10], Qhi[10], Klo[10], Khi[10], Vlo[10], Vhi[10];
#pragma unroll
    for (int t = 0; t < 10; t++) {
      const int k = KT(t), v = VT(t);
      Khi[t] = pack_bf16(acc[4 * k + 2], acc[4 * k + 3]);
      Vhi[t] = pack_bf16(acc[4 * v + 2] * rhi, acc[4 * v + 3] * rhi);
    }
    st_pkt(kvd, Khi[0], Khi[1], Khi[3], Khi[4]);
    st_pkt(kvd + 32, Khi[5], Khi[6], Khi[8], Khi[9]);
    st_pkt(kvd + 64, Khi[2], Khi[7], Vhi[0], Vhi[1]);
    st_pkt(kvd + 96, Vhi[2], Vhi[3], Vhi[4], Vhi[5]);
    st_pkt(kvd + 128, Vhi[6], Vhi[7], Vhi[8], Vhi[9]);
    mbar_arrive(bar_o + wg * 64 + 24);
    mbar_wait(bar_full, 0);
#pragma unroll
    for (int t = 0; t < 10; t++) {
      const int q = QT(t), k = KT(t), v = VT(t);
      Vhi[t] = movm(Vhi[t]);
      Klo[t] = pack_bf16(acc[4 * k], acc[4 * k + 1]);
      Vlo[t] = movm(pack_bf16(acc[4 * v] * rlo, acc[4 * v + 1] * rlo));
      Qlo[t] = pack_bf16(acc[4 * q], acc[4 * q + 1]);
      Qhi[t] = pack_bf16(acc[4 * q + 2], acc[4 * q + 3]);
    }
    const bool in0 = 2 * c <= r, in1 = 2 * c + 1 <= r;
    const uint32_t mL = (in0 ? 0xffffu : 0u) | (in1 ? 0xffff0000u : 0u);
    const float qs = 0.22360679774997896f * 1.4426950408889634f;
    const uint32_t kb0 = stb + (2 * c + (in0 ? 8 : 0)) * 4, kb1 = stb + (2 * c + 1 + (in1 ? 8 : 0)) * 4;
    const float scl0 = lds32f(kb0) * rlo * qs, scl1 = lds32f(kb1) * rlo * qs;
    const float sch0 = lds32f(kb0 + 32) * rhi * qs, sch1 = lds32f(kb1 + 32) * rhi * qs;
    const float bias0 = (first && !in0) ? -INFINITY : 0.f, bias1 = (first && !in1) ? -INFINITY : 0.f;
    const int slot = mt * 8 + warp;
    int guard = SPIN_MAX;
    uint4 pv[5];
    const bool cA = c < 2, nA = r < 4;
    mbar_wait(bar_o + wg * 64 + 24, 0);
#pragma unroll
    for (int j = 0; j < 5; j++) pv[j] = ld_pkt(kvs + 32 * j);
    if (wg == LEAD) bar_sync(9, 256);
    uint32_t Ph[4], qe[4][2];
    float sl0[4], sl1[4];
#pragma unroll
    for (int hd = 0; hd < 4; hd++) {
      const int ta = 5 * (hd >> 1) + 3 * (hd & 1), ts = 5 * (hd >> 1) + 2;
      const bool mine = (hd & 1) ? !cA : cA;
      qe[hd][0] = mine ? Qlo[ts] : 0u; qe[hd][1] = mine ? Qhi[ts] : 0u;
      float sl[4], sh[4];
      mma_k24(sl, Qlo[ta], Qhi[ta], Qlo[ta + 1], Qhi[ta + 1], Klo[ta], Klo[ta + 1], qe[hd][0], qe[hd][1], Klo[ts]);
      mma_k24(sh, Qlo[ta], Qhi[ta], Qlo[ta + 1], Qhi[ta + 1], Khi[ta], Khi[ta + 1], qe[hd][0], qe[hd][1], Khi[ts]);
      const float th0 = (in0 ? sh[2] : sl[2]) * sch0, th1 = (in1 ? sh[3] : sl[3]) * sch1;
      float mh = fmaxf(th0, th1);
      mh = fmaxf(mh, shx(mh, 1)); mh = fmaxf(mh, shx(mh, 2));
      Ph[hd] = pin(pack_bf16(ex2(th0 - mh), ex2(th1 - mh)));
      sl0[hd] = sl[0]; sl1[hd] = sl[1];
    }
    while (anyw(pv[0].x == SENT || pv[1].x == SENT || pv[2].x == SENT || pv[3].x == SENT || pv[4].x == SENT) && --guard > 0) {
#pragma unroll
      for (int j = 0; j < 5; j++) pv[j] = ld_pkt(kvs + 32 * j);
    }
    TS(4);
    const uint32_t Kp[10] = {pv[0].x, pv[0].y, pv[2].x, pv[0].z, pv[0].w, pv[1].x, pv[1].y, pv[2].y, pv[1].z, pv[1].w};
    const uint32_t Vp[10] = {movm(pv[2].z), movm(pv[2].w), movm(pv[3].x), movm(pv[3].y), movm(pv[3].z), movm(pv[3].w), movm(pv[4].x), movm(pv[4].y), movm(pv[4].z), movm(pv[4].w)};
    const uint32_t ONES = 0x3f803f80u;
    uint32_t of[20];
#pragma unroll
    for (int hp = 0; hp < 2; hp++) {
      float o[6][4];
#pragma unroll
      for (int hh = 0; hh < 2; hh++) {
        const int hd = 2 * hp + hh, ta = 5 * hp + 3 * hh, ts = 5 * hp + 2;
        float sp[4];
        mma_k24(sp, Qlo[ta], Qhi[ta], Qlo[ta + 1], Qhi[ta + 1], Kp[ta], Kp[ta + 1], qe[hd][0], qe[hd][1], Kp[ts]);
        const float tl0 = fmaf(in0 ? sl0[hd] : sp[0], scl0, bias0), tl1 = fmaf(in1 ? sl1[hd] : sp[1], scl1, bias1);
        float ml = fmaxf(tl0, tl1);
        ml = fmaxf(ml, shx(ml, 1)); ml = fmaxf(ml, shx(ml, 2));
        const uint32_t Pl = pack_bf16(ex2(tl0 - ml), ex2(tl1 - ml));
        const uint32_t a0 = Pl & mL, a1 = Ph[hd] & ~mL, a3 = Ph[hd] & mL, ap = Pl & ~mL;
        const bool vm = hh == 0 ? nA : !nA;
        mma_k24(o[3 * hh], a0, a1, 0u, a3, Vlo[ta], Vhi[ta], ap, 0u, Vp[ta]);
        mma_k24(o[3 * hh + 1], a0, a1, 0u, a3, Vlo[ta + 1], Vhi[ta + 1], ap, 0u, Vp[ta + 1]);
        mma_k24(o[3 * hh + 2], a0, a1, 0u, a3, vm ? Vlo[ts] : ONES, vm ? Vhi[ts] : ONES, ap, 0u, vm ? Vp[ts] : ONES);
      }
      const float il = rcp(cA ? o[5][0] : o[2][0]), ih = rcp(cA ? o[5][2] : o[2][2]);
      const float jl = shx(il, 2), jh = shx(ih, 2);
      const float al = cA ? jl : il, ah = cA ? jh : ih, bl = cA ? il : jl, bh = cA ? ih : jh;
      const int t0 = 5 * hp;
      of[2 * t0]     = pack_bf16(o[0][0] * al, o[0][1] * al); of[2 * t0 + 1] = pack_bf16(o[0][2] * ah, o[0][3] * ah);
      of[2 * t0 + 2] = pack_bf16(o[1][0] * al, o[1][1] * al); of[2 * t0 + 3] = pack_bf16(o[1][2] * ah, o[1][3] * ah);
      of[2 * t0 + 4] = pack_bf16((cA ? o[2][0] : o[5][0]) * jl, (cA ? o[2][1] : o[5][1]) * jl);
      of[2 * t0 + 5] = pack_bf16((cA ? o[2][2] : o[5][2]) * jh, (cA ? o[2][3] : o[5][3]) * jh);
      of[2 * t0 + 6] = pack_bf16(o[3][0] * bl, o[3][1] * bl); of[2 * t0 + 7] = pack_bf16(o[3][2] * bh, o[3][3] * bh);
      of[2 * t0 + 8] = pack_bf16(o[4][0] * bl, o[4][1] * bl); of[2 * t0 + 9] = pack_bf16(o[4][2] * bh, o[4][3] * bh);
    }
    {
      const uint32_t os = sb + OFF_O + 20480 + warp * 2560, oa = os + ((lane >> 3) & 1) * 1280 + (lane >> 4) * 128 + (lane & 7) * 16;
#pragma unroll
      for (int s = 0; s < 5; s++) stsm4(oa + s * 256, of[4 * s], of[4 * s + 1], of[4 * s + 2], of[4 * s + 3]);
      asm volatile("fence.proxy.async.shared::cta;" ::: "memory");
      __syncwarp();
      if (elect()) {
        asm volatile("cp.async.bulk.global.shared::cta.bulk_group [%0], [%1], 2560;\ncp.async.bulk.commit_group;" :: "l"(odst), "r"(os) : "memory");
      }
    }
    TS(5);
    float h[40];
#pragma unroll
    for (int s = 0; s < 5; s++) {
      const uint4 v = xr[s];
      h[8 * s] = bf_lo(v.x); h[8 * s + 1] = bf_hi(v.x); h[8 * s + 2] = bf_lo(v.y); h[8 * s + 3] = bf_hi(v.y);
      h[8 * s + 4] = bf_lo(v.z); h[8 * s + 5] = bf_hi(v.z); h[8 * s + 6] = bf_lo(v.w); h[8 * s + 7] = bf_hi(v.w);
    }
    if (elect()) {
      asm volatile("cp.async.bulk.wait_group 0;" ::: "memory");
      asm volatile("red.relaxed.gpu.global.add.u32 [%0], 1;" :: "l"(ocnt) : "memory");
    }
    asm volatile("bar.arrive %0, 160;" :: "r"(5 + wg) : "memory");
    mbar_wait(bar_full + 8, 0); mbar_wait(bar_full + 16, 1);
    bar_sync(1, 256);
    const uint64_t dwo = make_desc(D0 * 16, 5120, 512, 2);
    wgmma_fence();
#pragma unroll
    for (int s = 0; s < 5; s++) wgmma_n80_rs(h, of[4 * s], of[4 * s + 1], of[4 * s + 2], of[4 * s + 3], dwo + g * 960 + s * 64, 1);
    wgmma_commit();
    TS(6);
#pragma unroll 1
    for (int i = 0, sl = 0; i < 7; i++) {
      mbar_wait(bar_o + wg * 64 + 8 * sl, i >= 3 && i < 6);
      if (i == 0) TS(1);
      const uint64_t da = make_desc(D0 * 16 + OFF_O + sl * 20480 + wg * 10240, 128, 1280, 0), db = dwo + (i + (i >= g)) * 960;
      wgmma_fence();
#pragma unroll
      for (int s = 0; s < 5; s++) wgmma_n80_ss(h, da + s * 16, db + s * 64, 1);
      wgmma_commit();
      wgmma_wait<1>();
      if (lane == 0 && i > 0 && i < 5) mbar_arrive(bar_o + wg * 64 + 24 + 8 * i);
      sl = sl == 2 ? 0 : sl + 1;
    }
    const bool odd = c & 1;
    float wr[20];
#pragma unroll
    for (int j = 0; j < 5; j++) {
      const uint4 v = lds128(sb + OFF_WR + c * 80 + j * 16);
      wr[4 * j] = __uint_as_float(v.x); wr[4 * j + 1] = __uint_as_float(v.y); wr[4 * j + 2] = __uint_as_float(v.z); wr[4 * j + 3] = __uint_as_float(v.w);
    }
    const float wsum = lds32f(sb + OFF_WR + 320);
    uint4* const sp = hold(&g_own[slot].st2[r + (odd ? 8 : 0)]);
    uint4* const cdp = hold(&g_x.cand[slot][g][0]);
    const int tok0 = mt * 128 + 32 * w4 + wg;
    wgmma_wait<0>();
#pragma unroll
    for (int i = 0; i < 40; i++) asm volatile("" : "+f"(h[i]) :: "memory");
    TS(7);
    float mean, rstd, rr;
    {
      float l1 = 0.f, l2 = 0.f, l3 = 0.f, h1 = 0.f, h2 = 0.f, h3 = 0.f;
#pragma unroll
      for (int j = 0; j < 10; j++) {
        l1 += h[4 * j] + h[4 * j + 1]; h1 += h[4 * j + 2] + h[4 * j + 3];
        l2 = fmaf(h[4 * j], h[4 * j], l2); l2 = fmaf(h[4 * j + 1], h[4 * j + 1], l2);
        h2 = fmaf(h[4 * j + 2], h[4 * j + 2], h2); h2 = fmaf(h[4 * j + 3], h[4 * j + 3], h2);
        l3 = fmaf(h[4 * j], wr[2 * j], l3); l3 = fmaf(h[4 * j + 1], wr[2 * j + 1], l3);
        h3 = fmaf(h[4 * j + 2], wr[2 * j], h3); h3 = fmaf(h[4 * j + 3], wr[2 * j + 1], h3);
      }
      float s1 = (odd ? h1 : l1) + shx(odd ? l1 : h1, 1), s2 = (odd ? h2 : l2) + shx(odd ? l2 : h2, 1), s3 = (odd ? h3 : l3) + shx(odd ? l3 : h3, 1);
      s1 += shx(s1, 2); s2 += shx(s2, 2); s3 += shx(s3, 2);
      if (cA) asm volatile("red.relaxed.gpu.global.add.v4.f32 [%0], {%1, %2, %3, %4};" :: "l"(sp), "f"(s1), "f"(s2), "f"(s3), "f"(1.f) : "memory");
      uint4 p0;
      do { p0 = ldg_pkt(sp); } while (anyw(p0.w != 0x41000000u) && --guard > 0);
      mean = __uint_as_float(p0.x) * (1.f / 640.f);
      rstd = rsq(fmaxf(fmaf(-mean, mean, __uint_as_float(p0.y) * (1.f / 640.f)), 0.f) + 1e-5f);
      rr = fmaf(-mean, wsum, __uint_as_float(p0.z)) * rstd;
    }
    TS(8);
    const uint32_t kk = ord_key(rr), kmax = __reduce_max_sync(0xffffffffu, kk);
    const int L = __ffs(__ballot_sync(0xffffffffu, kk == kmax)) - 1;
    const int crow = (L >> 2) + 8 * (L & 1);
    if (warp == g) {
      if (elect()) {
        asm volatile("red.relaxed.gpu.global.max.u64 [%0], %1;" :: "l"(g_own[1].cnt), "l"(((uint64_t)kmax << 32) | (uint32_t)(2047 - tok0 - 2 * crow)) : "memory");
        asm volatile("red.relaxed.gpu.global.add.u32 [%0], 1;" :: "l"(&g_own[1].cnt[0].z) : "memory");
      }
      asm volatile("bar.arrive 3, 64;" ::: "memory");
    }
    const uint32_t stg = sb + OFF_O + warp * 2560;
    uint4 held;
    {
      const float om = shx(mean, 1), os = shx(rstd, 1);
      const float rl = odd ? os : rstd, rh = odd ? rstd : os;
      const float bl = -(odd ? om : mean) * rl, bh = -(odd ? mean : om) * rh, al = 1.f + rl, ah = 1.f + rh;
      if ((L >> 2) == r) {
        const bool chi = L & 1;
        const float rc = chi ? rh : rl, bc = chi ? bh : bl;
        uint32_t n[10];
#pragma unroll
        for (int j = 0; j < 10; j++) n[j] = pack_bf16(fmaf(chi ? h[4 * j + 2] : h[4 * j], rc, bc), fmaf(chi ? h[4 * j + 3] : h[4 * j + 1], rc, bc));
        uint4* d = cdp + c;
        stg_pkt(d, n[0], n[1], n[2], n[3]); stg_pkt(d + 4, n[4], n[5], n[6], n[7]); stg_rlx64(d + 8, n[8], n[9]);
      }
      __syncwarp();
      const uint32_t fa = stg + (lane & 15) * 160 + (lane >> 4) * 16;
#pragma unroll
      for (int s = 0; s < 5; s++)
        stsm4(fa + s * 32, pack_bf16(fmaf(h[8 * s], al, bl), fmaf(h[8 * s + 1], al, bl)), pack_bf16(fmaf(h[8 * s + 2], ah, bh), fmaf(h[8 * s + 3], ah, bh)),
              pack_bf16(fmaf(h[8 * s + 4], al, bl), fmaf(h[8 * s + 5], al, bl)), pack_bf16(fmaf(h[8 * s + 6], ah, bh), fmaf(h[8 * s + 7], ah, bh)));
      __syncwarp();
      held = lds128(stg + crow * 160 + min(lane, 9) * 16);
      if (lane < 10) stg_pkt(cdp + 12 + lane, held.x, held.y, held.z, held.w);
    }
    TS(9);
    mbar_wait(bar_ffn, 0);
    const uint32_t red = sb + OFF_RED;
    if (ffn1) {
      uint4 w1[4][5];
      {
        const int k = (lane & 7) + (lane >> 4) * 8;
        const uint32_t a1 = sb + k * 64, sw = ((lane >> 3) & 1) ^ ((lane >> 1) & 3);
#pragma unroll
        for (int s = 0; s < 5; s++)
#pragma unroll
          for (int u = 0; u < 4; u++)
            w1[u][s] = ldsm4t(a1 + (s < 4 ? warp * 4096 + s * 1024 : 32768 + warp * 1024) + (u >> 1) * (40960 + (s == 4 || warp >= 2 ? OFF_W2 - 49152 : 0)) + ((sw ^ (2 * (u & 1))) * 16));
      }
      uint32_t* const ap = hold(g_x.act + fj * 16 + (lane >> 1));
      mbar_wait(bar_win, 0);
      const uint32_t hp = sb + OFF_HN + (warp * 4 + c) * 16;
      const uint4 c0 = lds128(hp), c1 = lds128(hp + 512), c2 = lds128(hp + 1024);
      TS(10);
      float a[4][4];
#pragma unroll
      for (int u = 0; u < 4; u++) {
        a[u][0] = a[u][1] = a[u][2] = a[u][3] = 0.f;
        mma_acc(a[u], w1[u][0], c0.x, c0.y); mma_acc(a[u], w1[u][1], c0.z, c0.w); mma_acc(a[u], w1[u][2], c1.x, c1.y);
        mma_acc(a[u], w1[u][3], c1.z, c1.w); mma_acc(a[u], w1[u][4], c2.x, c2.y);
      }
      asm volatile("st.shared.v2.f32 [%0], {%1, %2};" :: "r"(red + (warp * 32 + c * 8 + r) * 8),
                   "f"(cA ? (odd ? a[0][2] : a[0][0]) : (odd ? a[1][2] : a[1][0])), "f"(cA ? (odd ? a[2][2] : a[2][0]) : (odd ? a[3][2] : a[3][0])) : "memory");
      bar_sync(1, 256);
      if (warp == 0) {
        float2 t[8];
#pragma unroll
        for (int i = 0; i < 8; i++) t[i] = lds64f(red + (i * 32 + lane) * 8);
        const float s = ((t[0].x + t[1].x) + (t[2].x + t[3].x)) + ((t[4].x + t[5].x) + (t[6].x + t[7].x));
        const float u = ((t[0].y + t[1].y) + (t[2].y + t[3].y)) + ((t[4].y + t[5].y) + (t[6].y + t[7].y));
        const float av = s * u * rcp(1.f + ex2(-1.4426950408889634f * s));
        const float an = shx(av, 1);
        if (!odd) stg_rlx32(ap, pack_bf16(av, an));
      }
      bar_sync(1, 256);
      TS(11);
    }
    if (OUT_LATE) mbar_wait(bar_win, 0);
    char* const ob2 = (char*)(out + tok0 * 640 + g * 64);
    const int remo = 896 - 96 * g;
#pragma unroll
    for (int s = 0; s < 5; s++) {
      const int row = s < 4 ? 4 * s + (lane >> 3) : lane >> 1, pc = s < 4 ? lane & 7 : 8 + (lane & 1);
      const uint4 v = lds128(stg + row * 160 + pc * 16);
      if (row != crow) stg128(ob2 + row * 2560 + pc * 16 + (s < 4 ? 0 : remo), v);
    }
    mbar_wait(bar_win, 0);
    const uint4 win = lds128(sb + OFF_WR + 336);
    if (win.x != slot && lane < 10) stg128(ob2 + crow * 2560 + lane * 16 + (lane < 8 ? 0 : remo), held);
    if (!ffn1) {
      TS(10);
      uint4 w2[6];
      const uint32_t a2 = sb + OFF_W2 + (warp * 192 + 8 * (((lane >> 3) & 1) * 4 + ((lane & 7) >> 1)) + 2 * (lane >> 4) + (lane & 1)) * 16;
#pragma unroll
      for (int s = 0; s < 6; s++) w2[s] = ldsm4t(a2 + (s >> 1) * 1024 + (s & 1) * 64);
      const uint4* p = (const uint4*)(g_x.act + warp * 96) + (r & 1) * 4 + c;
      const uint32_t* pb = (const uint32_t*)&g_x.cand[win.x][fj < 64 ? fj >> 3 : (fj - 64) >> 1][fj < 64 ? 12 + (fj & 7) : 20 + (fj & 1)] + c;
      uint32_t* const op = hold((uint32_t*)(out + win.y * 640 + fj * 8) + c);
      uint4 c0, c1, c2; uint32_t bw;
      if (ACT_NS) __nanosleep(ACT_NS);
      do {
        c0 = ldg_pkt(p); c1 = ldg_pkt(p + 8); c2 = ldg_pkt(p + 16); bw = ldg_rlx32(pb);
      } while (anyw(max(max(max(max(c0.x, c0.y), max(c0.z, c0.w)), max(max(c1.x, c1.y), max(c1.z, c1.w))), max(max(max(c2.x, c2.y), max(c2.z, c2.w)), bw)) == SENT) && --guard > 0);
      TS(11);
      float a[4] = {0.f, 0.f, 0.f, 0.f}, b[4] = {0.f, 0.f, 0.f, 0.f}, d[4] = {0.f, 0.f, 0.f, 0.f};
      mma_acc(a, w2[0], c0.x, c0.y); mma_acc(b, w2[2], c1.x, c1.y); mma_acc(d, w2[4], c2.x, c2.y);
      mma_acc(a, w2[1], c0.z, c0.w); mma_acc(b, w2[3], c1.z, c1.w); mma_acc(d, w2[5], c2.z, c2.w);
      if (c == 0) sts32f(red + (warp * 8 + r) * 4, ((a[0] + a[3]) + (b[0] + b[3])) + (d[0] + d[3]));
      bar_sync(1, 256);
      if (tid < 4) {
        float2 t[8];
#pragma unroll
        for (int i = 0; i < 8; i++) t[i] = lds64f(red + (i * 4 + tid) * 8);
        const float y0 = ((t[0].x + t[1].x) + (t[2].x + t[3].x)) + ((t[4].x + t[5].x) + (t[6].x + t[7].x));
        const float y1 = ((t[0].y + t[1].y) + (t[2].y + t[3].y)) + ((t[4].y + t[5].y) + (t[6].y + t[7].y));
        const float sg = __uint_as_float(win.z);
        *op = pack_bf16(fmaf(y0, sg, bf_lo(bw)), fmaf(y1, sg, bf_hi(bw)));
      }
    }
    TS(12);
#undef TS_T
  }
}

typedef CUresult (*EncodeFn)(CUtensorMap*, CUtensorMapDataType, cuuint32_t, void*, const cuuint64_t*, const cuuint64_t*, const cuuint32_t*,
                             const cuuint32_t*, CUtensorMapInterleave, CUtensorMapSwizzle, CUtensorMapL2promotion, CUtensorMapFloatOOBfill);

void make_map(EncodeFn enc, CUtensorMap* m, const void* base, const cuuint64_t* dims, const cuuint64_t* strides, const cuuint32_t* box,
              CUtensorMapSwizzle swz) {
  const cuuint32_t es[3] = {1, 1, 1};
  enc(m, CU_TENSOR_MAP_DATA_TYPE_BFLOAT16, 3, (void*)base, dims, strides, box, es, CU_TENSOR_MAP_INTERLEAVE_NONE, swz,
      CU_TENSOR_MAP_L2_PROMOTION_L2_128B, CU_TENSOR_MAP_FLOAT_OOB_FILL_NONE);
}

}

extern "C" void kernel_launch(void* const* d_in, const int* in_sizes, int n_in, void* d_out, int out_size) {
  const __nv_bfloat16* x = (const __nv_bfloat16*)d_in[0];
  const __nv_bfloat16* wqkv = (const __nv_bfloat16*)d_in[1];
  const __nv_bfloat16* wo = (const __nv_bfloat16*)d_in[2];
  void* fn = nullptr;
  cudaDriverEntryPointQueryResult st;
  cudaGetDriverEntryPoint("cuTensorMapEncodeTiled", &fn, cudaEnableDefault, &st);
  EncodeFn enc = (EncodeFn)fn;
  void* scp = nullptr;
  cudaGetSymbolAddress(&scp, g_scratch);
  Maps tm;
  { const cuuint64_t d[3] = {640, 1024, 2}, s[2] = {2560, 1280}; const cuuint32_t b[3] = {64, 64, 2}; make_map(enc, &tm.x, x, d, s, b, CU_TENSOR_MAP_SWIZZLE_128B); }
  { const cuuint64_t d[3] = {640, 640, 3}, s[2] = {3840, 1280}; const cuuint32_t b[3] = {64, 64, 1}; make_map(enc, &tm.w, wqkv, d, s, b, CU_TENSOR_MAP_SWIZZLE_128B); }
  { const cuuint64_t d[3] = {640, 640, 3}, s[2] = {3840, 1280}; const cuuint32_t b[3] = {16, 64, 3}; make_map(enc, &tm.wr, wqkv, d, s, b, CU_TENSOR_MAP_SWIZZLE_32B); }
  { const cuuint64_t d[3] = {32, 640, 20}, s[2] = {1280, 64}; const cuuint32_t b[3] = {32, 80, 2}; make_map(enc, &tm.wo, wo, d, s, b, CU_TENSOR_MAP_SWIZZLE_64B); }
  { const cuuint64_t d[3] = {640, 640, 1}, s[2] = {1280, 819200}; const cuuint32_t b[3] = {16, 80, 1}; make_map(enc, &tm.wor, wo, d, s, b, CU_TENSOR_MAP_SWIZZLE_64B); }
  { const cuuint64_t d[3] = {1536, 640, 1}, s[2] = {3072, 1966080}; const cuuint32_t b[3] = {32, 128, 1};
    make_map(enc, &tm.gate, d_in[5], d, s, b, CU_TENSOR_MAP_SWIZZLE_64B); make_map(enc, &tm.up, d_in[6], d, s, b, CU_TENSOR_MAP_SWIZZLE_64B); }
  { const cuuint64_t d[3] = {640, 1536, 1}, s[2] = {1280, 1966080}; const cuuint32_t b[3] = {8, 128, 1}; make_map(enc, &tm.down, d_in[7], d, s, b, CU_TENSOR_MAP_SWIZZLE_NONE); }
  cudaFuncSetAttribute(fused_kernel, cudaFuncAttributeMaxDynamicSharedMemorySize, SMEM_BYTES);
  fused_kernel<<<128, 512, SMEM_BYTES, cudaStreamPerThread>>>(x, wqkv, wo, (const __nv_bfloat16*)d_in[4], (const __nv_bfloat16*)d_in[5],
                                                              (const __nv_bfloat16*)d_in[6], (const __nv_bfloat16*)d_in[7], (__nv_bfloat16*)d_out, (Scratch*)scp, tm);
}
```

```cpp
#include <cuda_runtime.h>
#include <cuda_bf16.h>
#include <cuda.h>
#include <stdint.h>

#define PFW_NS 100
#define ACT_NS 0
#define OUT_LATE 0
#define REG_P 72
#define REG_C 184
#define AUX_NS 50
#define LEAD 1
#define RST_IT 3
#define ORDX 1
#define THR 3
#define PF_FIRST 4
#define PF_T0 2500
#define PF_CLK 500
#define HK_IT 1
#define F_IT 7
#define F_PER 2
#define F_MAX 12
#define LK 5
#define HOLD 2
#define F_LATE 12

namespace {

constexpr int SLOT    = 47104;
constexpr int OFF_O   = 122880;
constexpr int OFF_W2  = 4 * SLOT;
constexpr int OFF_CS  = OFF_W2 + 32768;
constexpr int OFF_RS  = OFF_CS + 3840;
constexpr int OFF_MN  = OFF_RS + 576;
constexpr int OFF_WR  = OFF_MN + 1024;
constexpr int OFF_RED = OFF_CS;
constexpr int OFF_HN  = OFF_CS + 2048;
constexpr int OFF_PT  = OFF_WR + 352;
constexpr int OFF_BAR = OFF_PT + 768;
constexpr int SMEM_BYTES = OFF_BAR + 352 + 384;
constexpr uint32_t D0 = 1024 >> 4;
constexpr uint32_t SENT = 0xFFFFFFFFu;
constexpr int SPIN_MAX = 1 << 20;

struct Glob {
  uint4 cand[128][8][24];
  uint32_t act[768];
  uint32_t pad[256];
};
constexpr int GLOB_PER_CTA = sizeof(Glob) / 16 / 128;
static_assert(GLOB_PER_CTA * 128 * 16 == sizeof(Glob), "glob size");
struct Own {
  uint4 halo[2][5][32];
  uint4 st1[32];
  uint2 cs[32];
  uint4 st2[16];
  uint4 cnt[8];
};
struct Scratch {
  Glob x;
  Own own[128];
  uint4 o[32][8][640];
  uint32_t epoch[128];
};
__device__ __align__(128) Scratch g_scratch;
#define g_x (sc->x)
#define g_own (sc->own)
#define g_o (sc->o)
#define g_epoch (sc->epoch)
#define TS(i)

__device__ __forceinline__ void mbar_init(uint32_t bar, uint32_t cnt) { asm volatile("mbarrier.init.shared::cta.b64 [%0], %1;" :: "r"(bar), "r"(cnt) : "memory"); }
__device__ __forceinline__ void mbar_expect_tx(uint32_t bar, uint32_t bytes) { asm volatile("mbarrier.arrive.expect_tx.shared::cta.b64 _, [%0], %1;" :: "r"(bar), "r"(bytes) : "memory"); }
__device__ __forceinline__ void mbar_arrive(uint32_t bar) { asm volatile("mbarrier.arrive.shared::cta.b64 _, [%0];" :: "r"(bar) : "memory"); }
__device__ __forceinline__ void mbar_arrive_cta(uint32_t bar, uint32_t cta) {
  asm volatile("{\n.reg .b32 ra;\nmapa.shared::cluster.u32 ra, %0, %1;\nmbarrier.arrive.shared::cluster.b64 _, [ra];\n}\n" :: "r"(bar), "r"(cta) : "memory");
}
__device__ __forceinline__ void mbar_wait(uint32_t bar, uint32_t parity) {
  asm volatile("{\n.reg .pred p;\n.reg .u32 n;\nmov.u32 n, 0;\nW:\nmbarrier.try_wait.parity.shared::cta.b64 p, [%0], %1;\n@p bra.uni D;\n"
               "add.u32 n, n, 1;\nsetp.lt.u32 p, n, %2;\n@p bra.uni W;\nD:\n}\n" :: "r"(bar), "r"(parity), "n"(SPIN_MAX) : "memory");
}
__device__ __forceinline__ void tma_3d(uint32_t dst, const void* tm, uint32_t bar, int c0, int c1, int c2) {
  asm volatile("cp.async.bulk.tensor.3d.shared::cluster.global.mbarrier::complete_tx::bytes [%0], [%1, {%3, %4, %5}], [%2];" :: "r"(dst), "l"(tm), "r"(bar), "r"(c0), "r"(c1), "r"(c2) : "memory");
}
__device__ __forceinline__ void tma_3d_mc(uint32_t dst, const void* tm, uint32_t bar, int c0, int c1, int c2) {
  asm volatile("cp.async.bulk.tensor.3d.shared::cluster.global.mbarrier::complete_tx::bytes.multicast::cluster [%0], [%1, {%3, %4, %5}], [%2], %6;" :: "r"(dst), "l"(tm), "r"(bar), "r"(c0), "r"(c1), "r"(c2), "h"((uint16_t)3) : "memory");
}
__device__ __forceinline__ void wgmma_fence() { asm volatile("wgmma.fence.sync.aligned;" ::: "memory"); }
__device__ __forceinline__ void wgmma_commit() { asm volatile("wgmma.commit_group.sync.aligned;" ::: "memory"); }
template <int N> __device__ __forceinline__ void wgmma_wait() { asm volatile("wgmma.wait_group.sync.aligned %0;" :: "n"(N) : "memory"); }
__device__ __forceinline__ uint64_t make_desc(uint32_t addr, uint32_t lbo, uint32_t sbo, uint32_t swz) {
  return (uint64_t)(((addr & 0x3FFFF) >> 4) | ((lbo >> 4) << 16)) | ((uint64_t)((sbo >> 4) | (swz << 30)) << 32);
}
__device__ __forceinline__ void bar_sync(int id, int n) { asm volatile("bar.sync %0, %1;" :: "r"(id), "r"(n) : "memory"); }
__device__ __forceinline__ uint4 ld_pkt(const void* p) {
  uint4 v; asm volatile("ld.relaxed.gpu.v4.u32 {%0, %1, %2, %3}, [%4];" : "=r"(v.x), "=r"(v.y), "=r"(v.z), "=r"(v.w) : "l"(p) : "memory"); return v;
}
__device__ __forceinline__ void st_pkt(void* p, uint32_t a, uint32_t b, uint32_t c, uint32_t d) {
  asm volatile("st.relaxed.gpu.v4.u32 [%0], {%1, %2, %3, %4};" :: "l"(p), "r"(a), "r"(b), "r"(c), "r"(d) : "memory");
}
__device__ __forceinline__ uint4 ldg_pkt(const void* p) {
  uint4 v; asm volatile("ld.relaxed.gpu.global.v4.u32 {%0, %1, %2, %3}, [%4];" : "=r"(v.x), "=r"(v.y), "=r"(v.z), "=r"(v.w) : "l"(p) : "memory"); return v;
}
__device__ __forceinline__ void stg_pkt(void* p, uint32_t a, uint32_t b, uint32_t c, uint32_t d) {
  asm volatile("st.relaxed.gpu.global.v4.u32 [%0], {%1, %2, %3, %4};" :: "l"(p), "r"(a), "r"(b), "r"(c), "r"(d) : "memory");
}
__device__ __forceinline__ uint32_t ldg_rlx32(const void* p) { uint32_t v; asm volatile("ld.relaxed.gpu.global.u32 %0, [%1];" : "=r"(v) : "l"(p) : "memory"); return v; }
__device__ __forceinline__ uint2 ldg_rlx64(const void* p) { uint2 v; asm volatile("ld.relaxed.gpu.global.v2.u32 {%0, %1}, [%2];" : "=r"(v.x), "=r"(v.y) : "l"(p) : "memory"); return v; }
__device__ __forceinline__ void stg128(void* p, const uint4& v) { asm volatile("st.global.v4.u32 [%0], {%1, %2, %3, %4};" :: "l"(p), "r"(v.x), "r"(v.y), "r"(v.z), "r"(v.w) : "memory"); }
__device__ __forceinline__ uint32_t pin(uint32_t v) { asm volatile("" : "+r"(v)); return v; }
__device__ __forceinline__ uint64_t mk64(uint32_t lo, uint32_t hi) { return ((uint64_t)hi << 32) | lo; }
template <class T> __device__ __forceinline__ T* hold(T* p) { return (T*)__shfl_sync(0xffffffffu, (unsigned long long)p, threadIdx.x & 31); }
template <class T> __device__ __forceinline__ T* pin(T* p) { asm volatile("" : "+l"(p)); return p; }
__device__ __forceinline__ void stg_rlx32(void* p, uint32_t v) { asm volatile("st.relaxed.gpu.global.u32 [%0], %1;" :: "l"(p), "r"(v) : "memory"); }
__device__ __forceinline__ void stg_rlx64(void* p, uint32_t a, uint32_t b) { asm volatile("st.relaxed.gpu.global.v2.u32 [%0], {%1, %2};" :: "l"(p), "r"(a), "r"(b) : "memory"); }
__device__ __forceinline__ uint4 ldsm4(uint32_t a) { uint4 v; asm volatile("ldmatrix.sync.aligned.m8n8.x4.shared.b16 {%0, %1, %2, %3}, [%4];" : "=r"(v.x), "=r"(v.y), "=r"(v.z), "=r"(v.w) : "r"(a) : "memory"); return v; }
__device__ __forceinline__ void ldsm4_if(uint4& v, uint32_t a, int off, bool p) {
  asm volatile("{\n.reg .pred q;\nsetp.ne.u32 q, %5, 0;\n@q ldmatrix.sync.aligned.m8n8.x4.shared.b16 {%0, %1, %2, %3}, [%4];\n}\n"
               : "+r"(v.x), "+r"(v.y), "+r"(v.z), "+r"(v.w) : "r"(a + off), "r"((int)p) : "memory");
}
__device__ __forceinline__ uint4 ldsm4t(uint32_t a) { uint4 v; asm volatile("ldmatrix.sync.aligned.m8n8.x4.trans.shared.b16 {%0, %1, %2, %3}, [%4];" : "=r"(v.x), "=r"(v.y), "=r"(v.z), "=r"(v.w) : "r"(a) : "memory"); return v; }
__device__ __forceinline__ void stsm4(uint32_t a, uint32_t x, uint32_t y, uint32_t z, uint32_t w) { asm volatile("stmatrix.sync.aligned.m8n8.x4.shared.b16 [%0], {%1, %2, %3, %4};" :: "r"(a), "r"(x), "r"(y), "r"(z), "r"(w) : "memory"); }
__device__ __forceinline__ void mma_acc(float (&c)[4], const uint4& a, uint32_t b0, uint32_t b1) {
  asm("mma.sync.aligned.m16n8k16.row.col.f32.bf16.bf16.f32 {%0,%1,%2,%3}, {%4,%5,%6,%7}, {%8,%9}, {%0,%1,%2,%3};"
      : "+f"(c[0]), "+f"(c[1]), "+f"(c[2]), "+f"(c[3]) : "r"(a.x), "r"(a.y), "r"(a.z), "r"(a.w), "r"(b0), "r"(b1));
}
__device__ __forceinline__ uint4 lds128(uint32_t a) { uint4 v; asm volatile("ld.shared.v4.u32 {%0, %1, %2, %3}, [%4];" : "=r"(v.x), "=r"(v.y), "=r"(v.z), "=r"(v.w) : "r"(a) : "memory"); return v; }
__device__ __forceinline__ float2 lds64f(uint32_t a) { float2 v; asm volatile("ld.shared.v2.f32 {%0, %1}, [%2];" : "=f"(v.x), "=f"(v.y) : "r"(a)); return v; }
__device__ __forceinline__ float lds32f(uint32_t a) { float v; asm volatile("ld.shared.f32 %0, [%1];" : "=f"(v) : "r"(a)); return v; }
__device__ __forceinline__ void sts32f(uint32_t a, float v) { asm volatile("st.shared.f32 [%0], %1;" :: "r"(a), "f"(v) : "memory"); }
__device__ __forceinline__ uint32_t pack_bf16(float lo, float hi) { uint32_t r; asm("cvt.rn.bf16x2.f32 %0, %1, %2;" : "=r"(r) : "f"(hi), "f"(lo)); return r; }
__device__ __forceinline__ float bf_lo(uint32_t v) { return __uint_as_float(v << 16); }
__device__ __forceinline__ float bf_hi(uint32_t v) { return __uint_as_float(v & 0xffff0000u); }
__device__ __forceinline__ uint32_t movm(uint32_t a) { uint32_t d; asm("movmatrix.sync.aligned.m8n8.trans.b16 %0, %1;" : "=r"(d) : "r"(a)); return d; }
__device__ __forceinline__ float ex2(float x) { float y; asm("ex2.approx.ftz.f32 %0, %1;" : "=f"(y) : "f"(x)); return y; }
__device__ __forceinline__ float rsq(float x) { float y; asm("rsqrt.approx.ftz.f32 %0, %1;" : "=f"(y) : "f"(x)); return y; }
__device__ __forceinline__ float rcp(float x) { float y; asm("rcp.approx.ftz.f32 %0, %1;" : "=f"(y) : "f"(x)); return y; }
__device__ __forceinline__ bool elect() { uint32_t p; asm volatile("{\n.reg .pred q;\nelect.sync _|q, 0xffffffff;\nselp.u32 %0, 1, 0, q;\n}\n" : "=r"(p)); return p; }
__device__ __forceinline__ int clk() { int c; asm volatile("mov.u32 %0, %%clock;" : "=r"(c) :: "memory"); return c; }
__device__ __forceinline__ void pf_l2(const void* p) { asm volatile("prefetch.global.L2 [%0];" :: "l"(p)); }
__device__ __forceinline__ bool anyw(bool p) { return __any_sync(0xffffffffu, p); }
__device__ __forceinline__ float shx(float v, int m) { return __shfl_xor_sync(0xffffffffu, v, m); }
__device__ __forceinline__ void mma_k24(float (&c)[4], uint32_t a0, uint32_t a1, uint32_t a2, uint32_t a3, uint32_t b0, uint32_t b1,
                                        uint32_t e0, uint32_t e1, uint32_t f0) {
  asm("mma.sync.aligned.m16n8k16.row.col.f32.bf16.bf16.f32 {%0,%1,%2,%3}, {%4,%5,%6,%7}, {%8,%9}, {%10,%10,%10,%10};"
      : "=f"(c[0]), "=f"(c[1]), "=f"(c[2]), "=f"(c[3]) : "r"(a0), "r"(a1), "r"(a2), "r"(a3), "r"(b0), "r"(b1), "f"(0.f));
  asm("mma.sync.aligned.m16n8k8.row.col.f32.bf16.bf16.f32 {%0,%1,%2,%3}, {%4,%5}, {%6}, {%0,%1,%2,%3};"
      : "+f"(c[0]), "+f"(c[1]), "+f"(c[2]), "+f"(c[3]) : "r"(e0), "r"(e1), "r"(f0));
}
__device__ __forceinline__ uint32_t ord_key(float r) { uint32_t u = __float_as_uint(r); return u ^ ((uint32_t)((int32_t)u >> 31) | 0x80000000u); }

__device__ __forceinline__ void wgmma_n48hi_ss(float (&d)[120], uint64_t da, uint64_t db, int scale_d) {
  asm volatile("{\n.reg .pred p;\nsetp.ne.b32 p, %26, 0;\n"
    "wgmma.mma_async.sync.aligned.m64n48k16.f32.bf16.bf16 "
    "{%0, %1, %2, %3, %4, %5, %6, %7, %8, %9, %10, %11, %12, %13, %14, %15, "
    "%16, %17, %18, %19, %20, %21, %22, %23}, "
    "%24, %25, p, 1, 1, 0, 1;\n}\n"
    : "+f"(d[96]), "+f"(d[97]), "+f"(d[98]), "+f"(d[99]), "+f"(d[100]), "+f"(d[101]), "+f"(d[102]), "+f"(d[103]),
      "+f"(d[104]), "+f"(d[105]), "+f"(d[106]), "+f"(d[107]), "+f"(d[108]), "+f"(d[109]), "+f"(d[110]), "+f"(d[111]),
      "+f"(d[112]), "+f"(d[113]), "+f"(d[114]), "+f"(d[115]), "+f"(d[116]), "+f"(d[117]), "+f"(d[118]), "+f"(d[119])
    : "l"(da), "l"(db), "r"(scale_d));
}
__device__ __forceinline__ void wgmma_n192lo_ss(float (&d)[120], uint64_t da, uint64_t db, int scale_d) {
  asm volatile("{\n.reg .pred p;\nsetp.ne.b32 p, %98, 0;\n"
    "wgmma.mma_async.sync.aligned.m64n192k16.f32.bf16.bf16 "
    "{%0, %1, %2, %3, %4, %5, %6, %7, %8, %9, %10, %11, %12, %13, %14, %15, "
    "%16, %17, %18, %19, %20, %21, %22, %23, %24, %25, %26, %27, %28, %29, %30, %31, "
    "%32, %33, %34, %35, %36, %37, %38, %39, %40, %41, %42, %43, %44, %45, %46, %47, "
    "%48, %49, %50, %51, %52, %53, %54, %55, %56, %57, %58, %59, %60, %61, %62, %63, "
    "%64, %65, %66, %67, %68, %69, %70, %71, %72, %73, %74, %75, %76, %77, %78, %79, "
    "%80, %81, %82, %83, %84, %85, %86, %87, %88, %89, %90, %91, %92, %93, %94, %95}, "
    "%96, %97, p, 1, 1, 0, 1;\n}\n"
    : "+f"(d[0]), "+f"(d[1]), "+f"(d[2]), "+f"(d[3]), "+f"(d[4]), "+f"(d[5]), "+f"(d[6]), "+f"(d[7]),
      "+f"(d[8]), "+f"(d[9]), "+f"(d[10]), "+f"(d[11]), "+f"(d[12]), "+f"(d[13]), "+f"(d[14]), "+f"(d[15]),
      "+f"(d[16]), "+f"(d[17]), "+f"(d[18]), "+f"(d[19]), "+f"(d[20]), "+f"(d[21]), "+f"(d[22]), "+f"(d[23]),
      "+f"(d[24]), "+f"(d[25]), "+f"(d[26]), "+f"(d[27]), "+f"(d[28]), "+f"(d[29]), "+f"(d[30]), "+f"(d[31]),
      "+f"(d[32]), "+f"(d[33]), "+f"(d[34]), "+f"(d[35]), "+f"(d[36]), "+f"(d[37]), "+f"(d[38]), "+f"(d[39]),
      "+f"(d[40]), "+f"(d[41]), "+f"(d[42]), "+f"(d[43]), "+f"(d[44]), "+f"(d[45]), "+f"(d[46]), "+f"(d[47]),
      "+f"(d[48]), "+f"(d[49]), "+f"(d[50]), "+f"(d[51]), "+f"(d[52]), "+f"(d[53]), "+f"(d[54]), "+f"(d[55]),
      "+f"(d[56]), "+f"(d[57]), "+f"(d[58]), "+f"(d[59]), "+f"(d[60]), "+f"(d[61]), "+f"(d[62]), "+f"(d[63]),
      "+f"(d[64]), "+f"(d[65]), "+f"(d[66]), "+f"(d[67]), "+f"(d[68]), "+f"(d[69]), "+f"(d[70]), "+f"(d[71]),
      "+f"(d[72]), "+f"(d[73]), "+f"(d[74]), "+f"(d[75]), "+f"(d[76]), "+f"(d[77]), "+f"(d[78]), "+f"(d[79]),
      "+f"(d[80]), "+f"(d[81]), "+f"(d[82]), "+f"(d[83]), "+f"(d[84]), "+f"(d[85]), "+f"(d[86]), "+f"(d[87]),
      "+f"(d[88]), "+f"(d[89]), "+f"(d[90]), "+f"(d[91]), "+f"(d[92]), "+f"(d[93]), "+f"(d[94]), "+f"(d[95])
    : "l"(da), "l"(db), "r"(scale_d));
}
__device__ __forceinline__ void wgmma_n48hi_rk(float (&d)[120], uint32_t a0, uint32_t a1, uint32_t a2, uint32_t a3, uint64_t db, int scale_d) {
  asm volatile("{\n.reg .pred p;\nsetp.ne.b32 p, %29, 0;\n"
    "wgmma.mma_async.sync.aligned.m64n48k16.f32.bf16.bf16 "
    "{%0, %1, %2, %3, %4, %5, %6, %7, %8, %9, %10, %11, %12, %13, %14, %15, "
    "%16, %17, %18, %19, %20, %21, %22, %23}, "
    "{%24, %25, %26, %27}, %28, p, 1, 1, 0;\n}\n"
    : "+f"(d[96]), "+f"(d[97]), "+f"(d[98]), "+f"(d[99]), "+f"(d[100]), "+f"(d[101]), "+f"(d[102]), "+f"(d[103]),
      "+f"(d[104]), "+f"(d[105]), "+f"(d[106]), "+f"(d[107]), "+f"(d[108]), "+f"(d[109]), "+f"(d[110]), "+f"(d[111]),
      "+f"(d[112]), "+f"(d[113]), "+f"(d[114]), "+f"(d[115]), "+f"(d[116]), "+f"(d[117]), "+f"(d[118]), "+f"(d[119])
    : "r"(a0), "r"(a1), "r"(a2), "r"(a3), "l"(db), "r"(scale_d));
}
__device__ __forceinline__ void wgmma_n192lo_rk(float (&d)[120], uint32_t a0, uint32_t a1, uint32_t a2, uint32_t a3, uint64_t db, int scale_d) {
  asm volatile("{\n.reg .pred p;\nsetp.ne.b32 p, %101, 0;\n"
    "wgmma.mma_async.sync.aligned.m64n192k16.f32.bf16.bf16 "
    "{%0, %1, %2, %3, %4, %5, %6, %7, %8, %9, %10, %11, %12, %13, %14, %15, "
    "%16, %17, %18, %19, %20, %21, %22, %23, %24, %25, %26, %27, %28, %29, %30, %31, "
    "%32, %33, %34, %35, %36, %37, %38, %39, %40, %41, %42, %43, %44, %45, %46, %47, "
    "%48, %49, %50, %51, %52, %53, %54, %55, %56, %57, %58, %59, %60, %61, %62, %63, "
    "%64, %65, %66, %67, %68, %69, %70, %71, %72, %73, %74, %75, %76, %77, %78, %79, "
    "%80, %81, %82, %83, %84, %85, %86, %87, %88, %89, %90, %91, %92, %93, %94, %95}, "
    "{%96, %97, %98, %99}, %100, p, 1, 1, 0;\n}\n"
    : "+f"(d[0]), "+f"(d[1]), "+f"(d[2]), "+f"(d[3]), "+f"(d[4]), "+f"(d[5]), "+f"(d[6]), "+f"(d[7]),
      "+f"(d[8]), "+f"(d[9]), "+f"(d[10]), "+f"(d[11]), "+f"(d[12]), "+f"(d[13]), "+f"(d[14]), "+f"(d[15]),
      "+f"(d[16]), "+f"(d[17]), "+f"(d[18]), "+f"(d[19]), "+f"(d[20]), "+f"(d[21]), "+f"(d[22]), "+f"(d[23]),
      "+f"(d[24]), "+f"(d[25]), "+f"(d[26]), "+f"(d[27]), "+f"(d[28]), "+f"(d[29]), "+f"(d[30]), "+f"(d[31]),
      "+f"(d[32]), "+f"(d[33]), "+f"(d[34]), "+f"(d[35]), "+f"(d[36]), "+f"(d[37]), "+f"(d[38]), "+f"(d[39]),
      "+f"(d[40]), "+f"(d[41]), "+f"(d[42]), "+f"(d[43]), "+f"(d[44]), "+f"(d[45]), "+f"(d[46]), "+f"(d[47]),
      "+f"(d[48]), "+f"(d[49]), "+f"(d[50]), "+f"(d[51]), "+f"(d[52]), "+f"(d[53]), "+f"(d[54]), "+f"(d[55]),
      "+f"(d[56]), "+f"(d[57]), "+f"(d[58]), "+f"(d[59]), "+f"(d[60]), "+f"(d[61]), "+f"(d[62]), "+f"(d[63]),
      "+f"(d[64]), "+f"(d[65]), "+f"(d[66]), "+f"(d[67]), "+f"(d[68]), "+f"(d[69]), "+f"(d[70]), "+f"(d[71]),
      "+f"(d[72]), "+f"(d[73]), "+f"(d[74]), "+f"(d[75]), "+f"(d[76]), "+f"(d[77]), "+f"(d[78]), "+f"(d[79]),
      "+f"(d[80]), "+f"(d[81]), "+f"(d[82]), "+f"(d[83]), "+f"(d[84]), "+f"(d[85]), "+f"(d[86]), "+f"(d[87]),
      "+f"(d[88]), "+f"(d[89]), "+f"(d[90]), "+f"(d[91]), "+f"(d[92]), "+f"(d[93]), "+f"(d[94]), "+f"(d[95])
    : "r"(a0), "r"(a1), "r"(a2), "r"(a3), "l"(db), "r"(scale_d));
}
__device__ __forceinline__ void wgmma_n80_rs(float (&d)[40], uint32_t a0, uint32_t a1, uint32_t a2, uint32_t a3, uint64_t db, int scale_d) {
  asm volatile("{\n.reg .pred p;\nsetp.ne.b32 p, %45, 0;\n"
    "wgmma.mma_async.sync.aligned.m64n80k16.f32.bf16.bf16 "
    "{%0, %1, %2, %3, %4, %5, %6, %7, %8, %9, %10, %11, %12, %13, %14, %15, "
    "%16, %17, %18, %19, %20, %21, %22, %23, %24, %25, %26, %27, %28, %29, %30, %31, "
    "%32, %33, %34, %35, %36, %37, %38, %39}, "
    "{%40, %41, %42, %43}, %44, p, 1, 1, 1;\n}\n"
    : "+f"(d[0]), "+f"(d[1]), "+f"(d[2]), "+f"(d[3]), "+f"(d[4]), "+f"(d[5]), "+f"(d[6]), "+f"(d[7]),
      "+f"(d[8]), "+f"(d[9]), "+f"(d[10]), "+f"(d[11]), "+f"(d[12]), "+f"(d[13]), "+f"(d[14]), "+f"(d[15]),
      "+f"(d[16]), "+f"(d[17]), "+f"(d[18]), "+f"(d[19]), "+f"(d[20]), "+f"(d[21]), "+f"(d[22]), "+f"(d[23]),
      "+f"(d[24]), "+f"(d[25]), "+f"(d[26]), "+f"(d[27]), "+f"(d[28]), "+f"(d[29]), "+f"(d[30]), "+f"(d[31]),
      "+f"(d[32]), "+f"(d[33]), "+f"(d[34]), "+f"(d[35]), "+f"(d[36]), "+f"(d[37]), "+f"(d[38]), "+f"(d[39])
    : "r"(a0), "r"(a1), "r"(a2), "r"(a3), "l"(db), "r"(scale_d));
}
__device__ __forceinline__ void wgmma_n80_ss(float (&d)[40], uint64_t da, uint64_t db, int scale_d) {
  asm volatile("{\n.reg .pred p;\nsetp.ne.b32 p, %42, 0;\n"
    "wgmma.mma_async.sync.aligned.m64n80k16.f32.bf16.bf16 "
    "{%0, %1, %2, %3, %4, %5, %6, %7, %8, %9, %10, %11, %12, %13, %14, %15, "
    "%16, %17, %18, %19, %20, %21, %22, %23, %24, %25, %26, %27, %28, %29, %30, %31, "
    "%32, %33, %34, %35, %36, %37, %38, %39}, "
    "%40, %41, p, 1, 1, 0, 1;\n}\n"
    : "+f"(d[0]), "+f"(d[1]), "+f"(d[2]), "+f"(d[3]), "+f"(d[4]), "+f"(d[5]), "+f"(d[6]), "+f"(d[7]),
      "+f"(d[8]), "+f"(d[9]), "+f"(d[10]), "+f"(d[11]), "+f"(d[12]), "+f"(d[13]), "+f"(d[14]), "+f"(d[15]),
      "+f"(d[16]), "+f"(d[17]), "+f"(d[18]), "+f"(d[19]), "+f"(d[20]), "+f"(d[21]), "+f"(d[22]), "+f"(d[23]),
      "+f"(d[24]), "+f"(d[25]), "+f"(d[26]), "+f"(d[27]), "+f"(d[28]), "+f"(d[29]), "+f"(d[30]), "+f"(d[31]),
      "+f"(d[32]), "+f"(d[33]), "+f"(d[34]), "+f"(d[35]), "+f"(d[36]), "+f"(d[37]), "+f"(d[38]), "+f"(d[39])
    : "l"(da), "l"(db), "r"(scale_d));
}

__device__ __forceinline__ constexpr int QT(int t) { return t < 8 ? t : 16 + t; }
__device__ __forceinline__ constexpr int KT(int t) { return t < 8 ? 8 + t : 18 + t; }
__device__ __forceinline__ constexpr int VT(int t) { return t < 8 ? 16 + t : 20 + t; }

struct Maps { CUtensorMap x, w, wr, wo, wor, gate, up, down; };

__global__ void __cluster_dims__(2, 1, 1) __launch_bounds__(512, 1)
fused_kernel(const __nv_bfloat16* __restrict__ x, const __nv_bfloat16* __restrict__ wqkv,
             const __nv_bfloat16* __restrict__ wo, const __nv_bfloat16* __restrict__ w_r, const __nv_bfloat16* __restrict__ w_gate,
             const __nv_bfloat16* __restrict__ w_up, const __nv_bfloat16* __restrict__ w_down, __nv_bfloat16* __restrict__ out,
             Scratch* __restrict__ sc, const __grid_constant__ Maps tm) {
  extern __shared__ __align__(1024) uint8_t smem[];
  const int tid = threadIdx.x, warp = __shfl_sync(0xffffffffu, tid >> 5, 0), lane = tid & 31, bid = blockIdx.x;
  const uint32_t sb = (uint32_t)__cvta_generic_to_shared(smem);
  const uint32_t bar_full = sb + OFF_BAR, bar_empty = bar_full + 32, bar_aux = bar_full + 64, bar_ffn = bar_full + 72, bar_win = bar_full + 80, bar_rst = bar_full + 88,
                 bar_o = bar_full + 96, bar_oc = bar_o + 112, bar_st = bar_o + 224, bar_kv = bar_o + 240;
  if (warp < 4 && elect()) {
    mbar_init(bar_full + 8 * (warp ^ 2), 1);
    mbar_init(bar_empty + 8 * warp, 24);
    mbar_init(bar_aux + 8 * warp, warp == 0 ? 64 : warp == 2 ? 32 : 1);
    asm volatile("fence.mbarrier_init.release.cluster;" ::: "memory");
  }
  asm volatile("barrier.cluster.arrive.relaxed.aligned;" ::: "memory");
  if (warp >= 8 && warp < 11 && elect()) asm volatile("prefetch.tensormap [%0];" :: "l"(&tm.x + (warp - 8)) : "memory");
  auto pf_slice = [&](int ks) {
    pf_l2(lane < 16 ? (const char*)x + ((bid * 16 + lane) * 1280 + ks * 128) : (const char*)wqkv + ((bid * 15 + min(lane, 30) - 16) * 128 + ks * 245760));
  };
  if (warp == 4) pf_slice(0);
  const int rank = bid & 1, cl = bid >> 1;
  const int q7 = ((cl - 36) * 37) >> 8;
  const int P = cl < 4 ? 0 : cl < 36 ? (cl - 4) & 7 : cl - 35 - 7 * q7;
  const int g = cl < 4 ? 4 + cl : cl < 36 ? (cl - 4) >> 3 : 4 + q7;
  const int mt = 2 * P + rank, cid = mt * 8 + g;
  const bool ffn1 = g >= 5;
  const int fj = ffn1 ? mt * 3 + g - 5 : (P * 5 + g) * 2 + rank;
  const int ord = ((g >> 2) ^ P) & 1;
  auto ks_of = [&](int it) { return !ORDX || ord == 0 || it == 0 ? it : it <= 5 ? it + 4 : it - 5; };
  auto load_w = [&](int it, uint32_t a, uint32_t full) {
    tma_3d_mc(a + 16384 + rank * 16384, &tm.w, full, g * 80, it * 64, rank * 2);
    tma_3d_mc(a + (rank ? 40960 : 24576), rank ? &tm.wr : &tm.w, full, g * 80 + rank * 64, it * 64, 1 - rank);
  };
  if (warp == 0 && elect()) {
    mbar_expect_tx(bar_full + 16, SLOT);
    tma_3d(sb + 2 * SLOT, &tm.x, bar_full + 16, 0, mt * 64, 0);
  }
  asm volatile("barrier.cluster.wait.aligned;" ::: "memory");
  if (warp == 0) {
    if (elect()) load_w(0, sb + 2 * SLOT, bar_full + 16);
    asm volatile("bar.arrive 4, 64;" ::: "memory");
  }

  if (warp >= 8) {
    asm volatile("setmaxnreg.dec.sync.aligned.u32 %0;" :: "n"(REG_P));
#define TS_T 0
    if (warp == 8) {
      TS(8);
      bar_sync(4, 64);
      if (elect()) {
        TS(10);
        int fjn = 0;
#pragma unroll 1
        for (int it = 1; it < 17; it++) {
          const int s = (it + 2) & 3;
          const uint32_t full = bar_full + 8 * s, a = sb + s * SLOT;
          if (it >= 13) { mbar_wait(bar_oc + 8 * (it - 13), 0); mbar_wait(bar_oc + 56 + 8 * (it - 13), 0); }
          else if (it >= 4) mbar_wait(bar_empty + 8 * s, ((it >> 2) - 1) & 1);
          else if (it >= THR) mbar_wait(bar_full + 8 * ((it - THR + 2) & 3), 0);
          if (it < 10) {
            const int ks = ks_of(it);
            mbar_expect_tx(full, SLOT);
            tma_3d(a, &tm.x, full, ks * 64, mt * 64, 0);
            load_w(ks, a, full);
            TS(12 + it);
            if ((unsigned)(it - RST_IT) < 3u) {
              mbar_wait(bar_rst, 0);
              char* const d = it == RST_IT ? (char*)(g_own + cid) : it == RST_IT + 1 ? (char*)(g_own + cid) + 2688 : (char*)((uint4*)&g_x + cid * GLOB_PER_CTA);
              asm volatile("cp.async.bulk.global.shared::cta.bulk_group [%0], [%1], %2;\ncp.async.bulk.commit_group;"
                           :: "l"(d), "r"(sb + OFF_CS), "r"(it == RST_IT ? 2688 : it == RST_IT + 1 ? 3584 : GLOB_PER_CTA * 16) : "memory");
            }
            if (it == RST_IT + 3) { asm volatile("cp.async.bulk.wait_group 0;" ::: "memory"); mbar_arrive(bar_rst); }
          } else if (it < 13) {
            const int g0 = 3 * (it - 10), g1 = min(g0 + 3, 8);
            mbar_expect_tx(full, (g1 - g0) * 12800);
#pragma unroll 1
            for (int gp = g0 + ((g0 ^ rank) & 1); gp < g1; gp += 2) {
              tma_3d_mc(sb + gp * 15360, &tm.wo, full, 0, gp * 80, g * 2);
              tma_3d_mc(sb + gp * 15360 + 10240, &tm.wor, full, 512 + g * 16, gp * 80, 0);
            }
          }
          if (it == 4) mbar_expect_tx(bar_ffn, ffn1 ? 81920 : 24576);
          const int j1 = ffn1 ? (it >= 13 ? min(2 * it - 21, 10) : min(max(it - F_IT + 1, 0), 4)) : (it >= 13 ? (it == 16 ? 12 : min(F_MAX + (it - 12) * F_LATE, 12)) : min(max((it - F_IT + 1) * F_PER, 0), F_MAX));
#pragma unroll 1
          for (; fjn < j1; fjn++) {
            const int j = fjn < 4 ? fjn + 6 : fjn - 4;
            if (ffn1) tma_3d(sb + (j < 6 ? 0 : OFF_W2 - 49152) + j * 8192, j < 5 ? &tm.gate : &tm.up, bar_ffn, fj * 32, (j < 5 ? j : j - 5) * 128, 0);
            else tma_3d(sb + OFF_W2 + fjn * 2048, &tm.down, bar_ffn, fj * 8, fjn * 128, 0);
          }
        }
        TS(11);
      }
#undef TS_T
#define TS_T 0
    } else if (warp >= 12) {
      const int l7 = lane & 7, j = warp - 12, ch = min((P >> 1) * 4 + rank * 2 + (j >> 1), 14);
      const uint32_t sxo = ((g & 3) * 32 + j * 8 + l7) * 128 + (((lane >> 3) ^ l7) * 16);
      const uint32_t swo = ch < 12 ? 16384 + (ch >> 2) * 8192 + lane * 128 + ((((ch & 3) * 2 + (j & 1)) ^ l7) * 16)
                                   : 40960 + (ch - 12) * 2048 + lane * 32 + (((j & 1) ^ (l7 >> 2)) * 16);
      float ps = 0.f, pq = 0.f, pq1 = 0.f, pc = 0.f;
#pragma unroll 1
      for (int it = ord; it < ord + 5; it++) {
        const int sl = (it + 2) & 3;
        mbar_wait(bar_full + 8 * sl, (it >> 2) & 1);
        TS(it);
        const uint32_t a = sb + sl * SLOT;
        const uint4 v0 = ldsm4(a + sxo), v1 = ldsm4((a + sxo) ^ 64), w0 = ldsm4t(a + swo), w1 = ldsm4t(a + swo + (ch < 12 ? 4096 : 1024));
        if (lane + (int)((v0.x & v1.x & w0.x & w1.x) == 0x7fc17fc1u && (v0.x | v1.x) == 0u) < 2) mbar_arrive_cta(bar_empty + 8 * sl, lane);
        const uint32_t vv[8] = {v0.x, v0.y, v0.z, v0.w, v1.x, v1.y, v1.z, v1.w}, ww[8] = {w0.x, w0.y, w0.z, w0.w, w1.x, w1.y, w1.z, w1.w};
#pragma unroll
        for (int i = 0; i < 8; i++) {
          const float d = bf_lo(vv[i]), e = bf_hi(vv[i]);
          ps += d + e; pq = fmaf(d, d, pq); pq1 = fmaf(e, e, pq1); pc += bf_lo(ww[i]) + bf_hi(ww[i]);
        }
      }
      pq += pq1;
      ps += shx(ps, 1); pq += shx(pq, 1); pc += shx(pc, 1);
      ps += shx(ps, 2); pq += shx(pq, 2); pc += shx(pc, 2);
      const int c = lane & 3;
      if (c < 3) sts32f(sb + OFF_PT + (c * 32 + j * 8 + (lane >> 2)) * 4, c == 0 ? ps : c == 1 ? pq : pc);
      asm volatile("bar.arrive 2, 224;" ::: "memory");
#undef TS_T
#define TS_T 32
    } else if (warp < 11) {
      Own* const own = g_own + cid;
      const int l7 = lane & 7, hk = lane >> 4, idx = lane;
      if (warp == 10 && elect()) {
#pragma unroll 1
        for (int i = 0; i < 32; i++) mbar_init(bar_o + 8 * i, i < 14 ? 1 : i < 30 ? 4 : 128);
      }
      {
        const int t0 = clk();
#pragma unroll 1
        for (int i = PF_FIRST; i < 6; i++) {
          while (clk() - t0 < PF_T0 + (i - PF_FIRST) * PF_CLK) __nanosleep(20);
          pf_slice(warp == 9 ? min(i, 4) : i + 4);
        }
      }
      bar_sync(2, 224);
      mbar_wait(bar_rst, 1);
      TS(0);
      const uint32_t tag = __float_as_uint(lds32f(sb + OFF_WR + 324));
      const float s0 = lds32f(sb + OFF_PT + lane * 4 + (warp - 9) * 256), q0 = lds32f(sb + OFF_PT + 128 + lane * 4);
      int guard = SPIN_MAX;
      if (warp == 9) {
        stg_pkt(&own->st1[idx], __float_as_uint(s0), __float_as_uint(q0), tag, 0u);
        TS(1);
        const uint4* sp = &g_own[mt * 8].st1[lane];
        const uint4* hp = &g_own[max(mt - 1, 0) * 8 + hk * 2 + 1].st1[24 + l7];
        uint4 a[5], b[5];
        bool bad;
        do {
          __nanosleep(AUX_NS);
          bad = false;
#pragma unroll
          for (int i = 0; i < 5; i++) {
            const uint4* q = i < 4 ? sp + i * (sizeof(Own) / 16) : hp;
            a[i] = ldg_pkt(q); b[i] = ldg_pkt(q + 4 * sizeof(Own) / 16);
          }
#pragma unroll
          for (int i = 0; i < 5; i++) bad |= a[i].z != tag || b[i].z != tag;
        } while (anyw(bad) && --guard);
#pragma unroll
        for (int i = 0; i < 5; i++) {
          const float m = (__uint_as_float(a[i].x) + __uint_as_float(b[i].x)) * (1.f / 640.f);
          const float rs = rsq(fmaxf(fmaf(-m, m, (__uint_as_float(a[i].y) + __uint_as_float(b[i].y)) * (1.f / 640.f)), 0.f) + 1e-5f);
          ((float*)(smem + OFF_RS))[i < 4 ? 8 + lane + 32 * i + 8 * (i >> 1) : hk * 72 + l7] = rs;
          const uint32_t mh = pack_bf16(-m, -m);
          const float ml = -m - bf_lo(mh);
          if (i < 4) ((uint2*)(smem + OFF_MN))[lane + 32 * i] = make_uint2(mh, pack_bf16(ml, ml));
        }
      } else {
        stg_rlx64(&own->cs[idx], __float_as_uint(s0), tag);
        const uint4* cp = (const uint4*)g_own[hk * 8 + g].cs + (lane & 15);
        uint4 a[4], b[4];
        bool bad;
        do {
          __nanosleep(AUX_NS);
          bad = false;
#pragma unroll
          for (int i = 0; i < 4; i++) { a[i] = ldg_pkt(cp + i * 32 * sizeof(Own) / 16); b[i] = ldg_pkt(cp + (i * 32 + 16) * sizeof(Own) / 16); }
#pragma unroll
          for (int i = 0; i < 4; i++) bad |= a[i].y != tag || a[i].w != tag || b[i].y != tag || b[i].w != tag;
        } while (anyw(bad) && --guard);
#pragma unroll
        for (int i = 0; i < 4; i++)
          if (i < 3 || lane < 24) {
            const float c0 = __uint_as_float(a[i].x) + __uint_as_float(b[i].x), c1 = __uint_as_float(a[i].z) + __uint_as_float(b[i].z);
            const uint32_t hi = pack_bf16(c0, c1), w0 = pack_bf16(c0, c0 - bf_lo(hi)), w1 = pack_bf16(c1, c1 - bf_hi(hi));
            uint4* const d = (uint4*)(smem + OFF_CS) + 2 * (lane + 32 * i);
            d[0] = make_uint4(w0, w0, 0, 0); d[1] = make_uint4(w1, w1, 0, 0);
          }
        asm volatile("fence.proxy.async.shared::cta;" ::: "memory");
      }
      mbar_arrive(bar_aux);
      TS(2);
      const int fo = warp - 9, wq = fo ? 1 - LEAD : LEAD;
      const uint4* const fp = hold(g_own[mt * 8 + wq * 4].cnt);
      const char* src = hold((const char*)g_o[mt * 2 + wq]);
      if (elect()) {
        const uint32_t bo = bar_o + fo * 56;
#pragma unroll
        for (int i = 0; i < 7; i++) mbar_expect_tx(bo + 8 * i, 10240);
        mbar_wait(bar_st + 8 * fo, 0);
        while (ldg_rlx32(fp) != 32u && --guard > 0) {}
        asm volatile("fence.proxy.async.global;" ::: "memory");
        TS(6);
#pragma unroll
        for (int i = 0; i < 7; i++) {
          if (fo || i == 6) mbar_wait(bo + 64 + 8 * i, 0);
          else if (i == 4) mbar_wait(bar_st + 8, 0);
          if (i == g) src += 10240;
          asm volatile("cp.async.bulk.shared::cluster.global.mbarrier::complete_tx::bytes [%0], [%1], 10240, [%2];"
                       :: "r"(sb + OFF_O + ((i + 2) % 6) * 10240 + fo * (i == 3 ? -51200 : 10240)), "l"(src + i * 10240), "r"(bo + 8 * i) : "memory");
        }
      }
#undef TS_T
#define TS_T 96
    } else {
      if ((sb & 0x3FFFF) != D0 * 16) __trap();
#pragma unroll 1
      for (int i = lane; i < 224; i += 32) { const uint32_t f = i < 200 ? SENT : 0u; ((uint4*)(smem + OFF_CS))[i] = make_uint4(f, f, f, f); }
      asm volatile("fence.proxy.async.shared::cta;" ::: "memory");
      if (elect()) mbar_arrive(bar_rst);
      mbar_wait(bar_full + 8 * ((HK_IT + 2) & 3), 0);
      TS(4);
      const uint32_t epoch = ldg_rlx32(g_epoch + cid) + 1;
      uint32_t wv[10];
#pragma unroll
      for (int i = 0; i < 10; i++) wv[i] = __ldg((const uint32_t*)w_r + lane + 32 * i);
      float s = 0.f;
#pragma unroll
      for (int i = 0; i < 10; i++) {
        s += bf_lo(wv[i]) + bf_hi(wv[i]);
        const unsigned u = i < 8 ? lane + 32 * (i - g) : lane + 32 * (i - 7) - g * 8;
        if (i < 8 ? u < 32u : u - 32u < 8u) *(float2*)(smem + OFF_WR + ((u & 3) * 10 + (u >> 2)) * 8) = make_float2(bf_lo(wv[i]), bf_hi(wv[i]));
      }
#pragma unroll
      for (int m = 1; m < 32; m <<= 1) s += shx(s, m);
      *(float2*)(smem + OFF_WR + 320) = make_float2(s, __uint_as_float(epoch * 0x9E3779B8u));
      g_epoch[cid] = epoch;
      TS(3);
      TS(5);
      asm volatile("bar.arrive 2, 224;" ::: "memory");
#pragma unroll 1
      for (int i = 0; i < 14; i++) {
        const int m = (i + 2) >> 2, n = m == 0 ? 50 : 120, t = (m == 0 ? i : (i + 2) & 3) * 32 + lane;
        const char* b = (const char*)(m == 0 ? wo : m == 1 ? w_up : m == 2 ? w_down : w_gate);
        if (t < n) pf_l2(b + (bid * n + t) * 128);
        __nanosleep(PFW_NS);
      }
      bar_sync(3, 64);
      const uint4* const kp = g_own[1].cnt;
      const uint4* const cb = &g_x.cand[0][lane >> 2][lane & 3];
      uint4 k = ldg_pkt(kp), c0 = make_uint4(0, 0, 0, 0), c1 = c0; uint2 c2 = make_uint2(0, 0);
      int guard = SPIN_MAX, ws;
      while (true) {
        const uint32_t tk = 2047u - (k.x & 2047u);
        ws = (tk >> 7) * 8 + (tk & 1) * 4 + ((tk >> 5) & 3);
        const uint32_t prev = k.x;
        if (ffn1) { const uint4* q = cb + ws * 192; c0 = ldg_pkt(q); c1 = ldg_pkt(q + 4); c2 = ldg_rlx64(q + 8); }
        if (k.z != 128u) k = ldg_pkt(kp);
        if ((k.z == 128u && k.x == prev && !anyw(c0.x == SENT || c1.x == SENT || c2.x == SENT)) || --guard <= 0) break;
      }
      *(uint4*)(smem + OFF_HN + lane * 16) = c0; *(uint4*)(smem + OFF_HN + 512 + lane * 16) = c1; *(uint2*)(smem + OFF_HN + 1024 + lane * 16) = c2;
      const float rw = __uint_as_float(k.y ^ ((uint32_t)((int32_t)~k.y >> 31) | 0x80000000u));
      *(uint4*)(smem + OFF_WR + 336) = make_uint4(ws, 2047u - (k.x & 2047u), __float_as_uint(rcp(1.f + ex2(-1.4426950408889634f * rw))), 0);
      mbar_arrive(bar_win);
      TS(7);
    }
#undef TS_T
  } else {
#define TS_T 0
    TS(23);
    asm volatile("setmaxnreg.inc.sync.aligned.u32 %0;" :: "n"(REG_C));
    const int wg = warp >> 2, w4 = warp & 3, r = lane >> 2, c = lane & 3;
    float acc[120];
    uint4 xr[5] = {};
    const uint32_t xa = pin(sb + (warp * 16 + (lane & 15)) * 128 + ((lane >> 4) ^ (lane & 7)) * 16);
    const int fol = wg != LEAD;
    const bool first = (mt == 0) && (w4 == 0);
    uint4* const kvd = pin(w4 < 3 ? (uint4*)(smem + OFF_O + fol * 10240 + w4 * 2560) + lane : &g_own[cid].halo[wg][0][lane]);
    const uint4* const kvs = pin(first ? kvd : w4 > 0 ? (const uint4*)(smem + OFF_O + fol * 10240 + (w4 - 1) * 2560) + lane : &g_own[cid - 8].halo[wg][0][lane]);
    uint4* const odst = hold(&g_o[mt * 2 + wg][g][w4 * 160]);
    uint4* const ocnt = hold(g_own[mt * 8 + wg * 4].cnt);
    uint32_t m0 = 0, m1 = 0;
    const uint32_t mna = pin(sb + OFF_MN + (warp * 16 + r) * 8 + c * 4);
    const int itx = ord == 0 || g == 0 ? g : g < 5 ? g + 5 : g - 4, ity = (ord ? 4 : 8) + (g >> 2);
    uint32_t rel;
    asm volatile("mapa.shared::cluster.u32 %0, %1, %2;" : "=r"(rel) : "r"(bar_empty), "r"(tid & 1));
    const uint32_t xa1 = pin(xa ^ 32), xa2 = pin(xa ^ 64), xa3 = pin(xa ^ 96), xb = pin(xa ^ ((g & 3) * 32));
    const uint32_t da0 = wg * 512;
    const bool rel2 = lane < 2, rel6 = lane < 2 + 2 * (warp & 1);
    const uint32_t zero = (uint32_t)(uintptr_t)x & 8u;
    TS(0);
    mbar_wait(bar_full + 16, 0);
    TS(13);
    wgmma_fence();
#pragma unroll
    for (int it = 0; it < 10; it++) {
      const int s = (it + 2) & 3;
      if (it == 9) bar_sync(10 + wg, 256);
#pragma unroll
      for (int kk = 0; kk < 4; kk++) {
        if (kk == 2 && it > 0) {
          wgmma_commit();
          wgmma_wait<1>();
          const uint32_t ra = ((xr[0].x ^ xr[1].x ^ xr[2].x ^ xr[3].x ^ xr[4].x) & zero) | rel;
          if (it == 1 ? (ord ? rel6 : rel2) : it == 6 ? (ord ? rel2 : rel6) : it < 6 ? rel2 : rel6)
            asm volatile("mbarrier.arrive.shared::cluster.b64 _, [%0];" :: "r"(ra + 8 * ((it + 1) & 3)) : "memory");
        }
        if (kk == 2) {
          ldsm4_if(xr[0], xa, s * SLOT, it == itx); ldsm4_if(xr[1], xa1, s * SLOT, it == itx);
          ldsm4_if(xr[2], xa2, s * SLOT, it == itx); ldsm4_if(xr[3], xa3, s * SLOT, it == itx);
          if ((it & 6) == 4 || it >= 8) ldsm4_if(xr[4], xb, s * SLOT, it == ity);
        }
        if (kk == 3 && it < 9) {
          mbar_wait(bar_full + 8 * ((it + 3) & 3), ((it + 1) >> 2) & 1);
          TS(14 + it);
        }
        if (kk == LK && it >= 8 && it == (wg == LEAD ? 9 : 8)) asm volatile("bar.arrive %0, 256;" :: "r"(11 - wg) : "memory");
        const uint64_t da = mk64(da0 + (D0 + s * (SLOT >> 4) + kk * 2 + (1 << 16)), 0x40000040u);
        wgmma_n48hi_ss(acc, da, mk64(D0 + s * (SLOT >> 4) + 2560 + kk * 32 + (128 << 16), 0xC0000010u), (it | kk) != 0);
        wgmma_n192lo_ss(acc, da, mk64(D0 + s * (SLOT >> 4) + 1024 + kk * 128 + (512 << 16), 0x40000040u), (it | kk) != 0);
      }
      wgmma_commit();
      if (LK >= 4 && it >= 8 && it == (wg == LEAD ? (LK == 4 ? 9 : 10) : 8)) asm volatile("bar.arrive %0, 256;" :: "r"(11 - wg) : "memory");
      if (it == 8) {
        mbar_wait(bar_aux, 0);
        TS(3);
        if (c < 2) { m0 = __float_as_uint(lds32f(mna)); m1 = __float_as_uint(lds32f(mna + 64)); }
      }
    }
    {
      const uint64_t dc = make_desc(D0 * 16 + OFF_CS, 0, 128, 0);
      wgmma_fence();
      wgmma_n48hi_rk(acc, m0, m1, 0u, 0u, dc + 192, 1);
      wgmma_n192lo_rk(acc, m0, m1, 0u, 0u, dc, 1);
      wgmma_commit();
      if (LK == 5 && wg == LEAD) asm volatile("bar.arrive %0, 256;" :: "r"(11 - LEAD) : "memory");
    }
    const uint32_t stb = sb + OFF_RS + (wg * 72 + 16 * w4) * 4;
    const float rlo = lds32f(stb + (8 + r) * 4), rhi = lds32f(stb + (16 + r) * 4);
    wgmma_wait<0>();
#pragma unroll
    for (int i = 0; i < 120; i++) asm volatile("" : "+f"(acc[i]) :: "memory");
    if (wg != LEAD) asm volatile("bar.arrive 9, 256;" ::: "memory");
    TS(2);
    uint32_t Qlo[10], Qhi[10], Klo[10], Khi[10], Vlo[10], Vhi[10];
#pragma unroll
    for (int t = 0; t < 10; t++) {
      const int k = KT(t), v = VT(t);
      Khi[t] = pack_bf16(acc[4 * k + 2], acc[4 * k + 3]);
      Vhi[t] = pack_bf16(acc[4 * v + 2] * rhi, acc[4 * v + 3] * rhi);
    }
    st_pkt(kvd, Khi[0], Khi[1], Khi[3], Khi[4]);
    st_pkt(kvd + 32, Khi[5], Khi[6], Khi[8], Khi[9]);
    st_pkt(kvd + 64, Khi[2], Khi[7], Vhi[0], Vhi[1]);
    st_pkt(kvd + 96, Vhi[2], Vhi[3], Vhi[4], Vhi[5]);
    st_pkt(kvd + 128, Vhi[6], Vhi[7], Vhi[8], Vhi[9]);
    mbar_arrive(bar_kv + wg * 8);
    if (HOLD == 1 && fol) bar_sync(12, 256);
    mbar_wait(bar_aux, 0);
#pragma unroll
    for (int t = 0; t < 10; t++) {
      const int q = QT(t), k = KT(t), v = VT(t);
      Vhi[t] = movm(Vhi[t]);
      Klo[t] = pack_bf16(acc[4 * k], acc[4 * k + 1]);
      Vlo[t] = movm(pack_bf16(acc[4 * v] * rlo, acc[4 * v + 1] * rlo));
      Qlo[t] = pack_bf16(acc[4 * q], acc[4 * q + 1]);
      Qhi[t] = pack_bf16(acc[4 * q + 2], acc[4 * q + 3]);
    }
    const bool in0 = 2 * c <= r, in1 = 2 * c + 1 <= r;
    const uint32_t mL = (in0 ? 0xffffu : 0u) | (in1 ? 0xffff0000u : 0u);
    const float qs = 0.22360679774997896f * 1.4426950408889634f;
    const uint32_t kb0 = stb + (2 * c + (in0 ? 8 : 0)) * 4, kb1 = stb + (2 * c + 1 + (in1 ? 8 : 0)) * 4;
    const float scl0 = lds32f(kb0) * rlo * qs, scl1 = lds32f(kb1) * rlo * qs;
    const float sch0 = lds32f(kb0 + 32) * rhi * qs, sch1 = lds32f(kb1 + 32) * rhi * qs;
    const float bias0 = (first && !in0) ? -INFINITY : 0.f, bias1 = (first && !in1) ? -INFINITY : 0.f;
    const int slot = mt * 8 + warp;
    int guard = SPIN_MAX;
    uint4 pv[5];
    const bool cA = c < 2, nA = r < 4;
    if (HOLD == 2 && fol) bar_sync(12, 256);
    mbar_wait(bar_kv + wg * 8, 0);
#pragma unroll
    for (int j = 0; j < 5; j++) pv[j] = ld_pkt(kvs + 32 * j);
    if (wg == LEAD) bar_sync(9, 256);
    uint32_t Ph[4], qe[4][2];
    float sl0[4], sl1[4];
#pragma unroll
    for (int hd = 0; hd < 4; hd++) {
      const int ta = 5 * (hd >> 1) + 3 * (hd & 1), ts = 5 * (hd >> 1) + 2;
      const bool mine = (hd & 1) ? !cA : cA;
      qe[hd][0] = mine ? Qlo[ts] : 0u; qe[hd][1] = mine ? Qhi[ts] : 0u;
      float sl[4], sh[4];
      mma_k24(sl, Qlo[ta], Qhi[ta], Qlo[ta + 1], Qhi[ta + 1], Klo[ta], Klo[ta + 1], qe[hd][0], qe[hd][1], Klo[ts]);
      mma_k24(sh, Qlo[ta], Qhi[ta], Qlo[ta + 1], Qhi[ta + 1], Khi[ta], Khi[ta + 1], qe[hd][0], qe[hd][1], Khi[ts]);
      const float th0 = (in0 ? sh[2] : sl[2]) * sch0, th1 = (in1 ? sh[3] : sl[3]) * sch1;
      float mh = fmaxf(th0, th1);
      mh = fmaxf(mh, shx(mh, 1)); mh = fmaxf(mh, shx(mh, 2));
      Ph[hd] = pin(pack_bf16(ex2(th0 - mh), ex2(th1 - mh)));
      sl0[hd] = sl[0]; sl1[hd] = sl[1];
    }
    while (anyw(pv[0].x == SENT || pv[1].x == SENT || pv[2].x == SENT || pv[3].x == SENT || pv[4].x == SENT) && --guard > 0) {
#pragma unroll
      for (int j = 0; j < 5; j++) pv[j] = ld_pkt(kvs + 32 * j);
    }
    TS(4);
    const uint32_t Kp[10] = {pv[0].x, pv[0].y, pv[2].x, pv[0].z, pv[0].w, pv[1].x, pv[1].y, pv[2].y, pv[1].z, pv[1].w};
    const uint32_t Vp[10] = {movm(pv[2].z), movm(pv[2].w), movm(pv[3].x), movm(pv[3].y), movm(pv[3].z), movm(pv[3].w), movm(pv[4].x), movm(pv[4].y), movm(pv[4].z), movm(pv[4].w)};
    const uint32_t ONES = 0x3f803f80u;
    uint32_t of[20];
#pragma unroll
    for (int hp = 0; hp < 2; hp++) {
      float o[6][4];
#pragma unroll
      for (int hh = 0; hh < 2; hh++) {
        const int hd = 2 * hp + hh, ta = 5 * hp + 3 * hh, ts = 5 * hp + 2;
        float sp[4];
        mma_k24(sp, Qlo[ta], Qhi[ta], Qlo[ta + 1], Qhi[ta + 1], Kp[ta], Kp[ta + 1], qe[hd][0], qe[hd][1], Kp[ts]);
        const float tl0 = fmaf(in0 ? sl0[hd] : sp[0], scl0, bias0), tl1 = fmaf(in1 ? sl1[hd] : sp[1], scl1, bias1);
        float ml = fmaxf(tl0, tl1);
        ml = fmaxf(ml, shx(ml, 1)); ml = fmaxf(ml, shx(ml, 2));
        const uint32_t Pl = pack_bf16(ex2(tl0 - ml), ex2(tl1 - ml));
        const uint32_t a0 = Pl & mL, a1 = Ph[hd] & ~mL, a3 = Ph[hd] & mL, ap = Pl & ~mL;
        const bool vm = hh == 0 ? nA : !nA;
        mma_k24(o[3 * hh], a0, a1, 0u, a3, Vlo[ta], Vhi[ta], ap, 0u, Vp[ta]);
        mma_k24(o[3 * hh + 1], a0, a1, 0u, a3, Vlo[ta + 1], Vhi[ta + 1], ap, 0u, Vp[ta + 1]);
        mma_k24(o[3 * hh + 2], a0, a1, 0u, a3, vm ? Vlo[ts] : ONES, vm ? Vhi[ts] : ONES, ap, 0u, vm ? Vp[ts] : ONES);
      }
      const float il = rcp(cA ? o[5][0] : o[2][0]), ih = rcp(cA ? o[5][2] : o[2][2]);
      const float jl = shx(il, 2), jh = shx(ih, 2);
      const float al = cA ? jl : il, ah = cA ? jh : ih, bl = cA ? il : jl, bh = cA ? ih : jh;
      const int t0 = 5 * hp;
      of[2 * t0]     = pack_bf16(o[0][0] * al, o[0][1] * al); of[2 * t0 + 1] = pack_bf16(o[0][2] * ah, o[0][3] * ah);
      of[2 * t0 + 2] = pack_bf16(o[1][0] * al, o[1][1] * al); of[2 * t0 + 3] = pack_bf16(o[1][2] * ah, o[1][3] * ah);
      of[2 * t0 + 4] = pack_bf16((cA ? o[2][0] : o[5][0]) * jl, (cA ? o[2][1] : o[5][1]) * jl);
      of[2 * t0 + 5] = pack_bf16((cA ? o[2][2] : o[5][2]) * jh, (cA ? o[2][3] : o[5][3]) * jh);
      of[2 * t0 + 6] = pack_bf16(o[3][0] * bl, o[3][1] * bl); of[2 * t0 + 7] = pack_bf16(o[3][2] * bh, o[3][3] * bh);
      of[2 * t0 + 8] = pack_bf16(o[4][0] * bl, o[4][1] * bl); of[2 * t0 + 9] = pack_bf16(o[4][2] * bh, o[4][3] * bh);
    }
    {
      const uint32_t os = sb + OFF_O + (fol ? 0 : 20480) + w4 * 2560, oa = os + ((lane >> 3) & 1) * 1280 + (lane >> 4) * 128 + (lane & 7) * 16;
#pragma unroll
      for (int s = 0; s < 5; s++) {
        if (s == 0 && HOLD == 0 && fol) bar_sync(12, 256);
        stsm4(oa + s * 256, of[4 * s], of[4 * s + 1], of[4 * s + 2], of[4 * s + 3]);
        if (s == 0) asm volatile("bar.arrive %0, 256;" :: "r"(fol ? 1 : 12) : "memory");
      }
      asm volatile("fence.proxy.async.shared::cta;" ::: "memory");
      __syncwarp();
      if (elect()) {
        asm volatile("cp.async.bulk.global.shared::cta.bulk_group [%0], [%1], 2560;\ncp.async.bulk.commit_group;" :: "l"(odst), "r"(os) : "memory");
      }
    }
    TS(5);
    float h[40];
#pragma unroll
    for (int s = 0; s < 5; s++) {
      const uint4 v = xr[s];
      h[8 * s] = bf_lo(v.x); h[8 * s + 1] = bf_hi(v.x); h[8 * s + 2] = bf_lo(v.y); h[8 * s + 3] = bf_hi(v.y);
      h[8 * s + 4] = bf_lo(v.z); h[8 * s + 5] = bf_hi(v.z); h[8 * s + 6] = bf_lo(v.w); h[8 * s + 7] = bf_hi(v.w);
    }
    if (elect()) {
      asm volatile("cp.async.bulk.wait_group 0;" ::: "memory");
      asm volatile("red.relaxed.gpu.global.add.u32 [%0], 1;" :: "l"(ocnt) : "memory");
      mbar_arrive(bar_st + 8 * fol);
    }
    __syncwarp();
    mbar_wait(bar_full, 0); mbar_wait(bar_full + 8, 0); mbar_wait(bar_full + 16, 1);
    if (!fol) bar_sync(1, 256);
    const uint64_t dwo = make_desc(D0 * 16, 5120, 512, 2);
    wgmma_fence();
#pragma unroll
    for (int s = 0; s < 5; s++) wgmma_n80_rs(h, of[4 * s], of[4 * s + 1], of[4 * s + 2], of[4 * s + 3], dwo + g * 960 + s * 64, 1);
    wgmma_commit();
    TS(6);
    const uint32_t bo = bar_o + fol * 56;
#pragma unroll
    for (int i = 0; i < 7; i++) {
      mbar_wait(bo + 8 * i, 0);
      if (i == 0) TS(1);
      const uint32_t da = D0 + OFF_O / 16 + (8 << 16) + ((i + 2) % 6) * 640 + fol * (i == 3 ? -3200 : 640), db = D0 + (320 << 16) + (i >= g ? i + 1 : i) * 960;
      wgmma_fence();
#pragma unroll
      for (int s = 0; s < 5; s++) wgmma_n80_ss(h, mk64(da + s * 16, 80u), mk64(db + s * 64, 0x80000020u), 1);
      wgmma_commit();
      wgmma_wait<1>();
      if (lane == 0 && i > 0) mbar_arrive(bo + 104 + 8 * i);
    }
    const bool odd = c & 1;
    float wr[20];
#pragma unroll
    for (int j = 0; j < 5; j++) {
      const uint4 v = lds128(sb + OFF_WR + c * 80 + j * 16);
      wr[4 * j] = __uint_as_float(v.x); wr[4 * j + 1] = __uint_as_float(v.y); wr[4 * j + 2] = __uint_as_float(v.z); wr[4 * j + 3] = __uint_as_float(v.w);
    }
    const float wsum = lds32f(sb + OFF_WR + 320);
    uint4* const sp = hold(&g_own[slot].st2[r + (odd ? 8 : 0)]);
    uint4* const cdp = hold(&g_x.cand[slot][g][0]);
    const int tok0 = mt * 128 + 32 * w4 + wg;
    wgmma_wait<0>();
#pragma unroll
    for (int i = 0; i < 40; i++) asm volatile("" : "+f"(h[i]) :: "memory");
    if (lane == 0) mbar_arrive(bo + 160);
    TS(7);
    float mean, rstd, rr;
    {
      float l1 = 0.f, l2 = 0.f, l3 = 0.f, h1 = 0.f, h2 = 0.f, h3 = 0.f;
#pragma unroll
      for (int j = 0; j < 10; j++) {
        l1 += h[4 * j] + h[4 * j + 1]; h1 += h[4 * j + 2] + h[4 * j + 3];
        l2 = fmaf(h[4 * j], h[4 * j], l2); l2 = fmaf(h[4 * j + 1], h[4 * j + 1], l2);
        h2 = fmaf(h[4 * j + 2], h[4 * j + 2], h2); h2 = fmaf(h[4 * j + 3], h[4 * j + 3], h2);
        l3 = fmaf(h[4 * j], wr[2 * j], l3); l3 = fmaf(h[4 * j + 1], wr[2 * j + 1], l3);
        h3 = fmaf(h[4 * j + 2], wr[2 * j], h3); h3 = fmaf(h[4 * j + 3], wr[2 * j + 1], h3);
      }
      float s1 = (odd ? h1 : l1) + shx(odd ? l1 : h1, 1), s2 = (odd ? h2 : l2) + shx(odd ? l2 : h2, 1), s3 = (odd ? h3 : l3) + shx(odd ? l3 : h3, 1);
      s1 += shx(s1, 2); s2 += shx(s2, 2); s3 += shx(s3, 2);
      if (cA) asm volatile("red.relaxed.gpu.global.add.v4.f32 [%0], {%1, %2, %3, %4};" :: "l"(sp), "f"(s1), "f"(s2), "f"(s3), "f"(1.f) : "memory");
      uint4 p0;
      do { p0 = ldg_pkt(sp); } while (anyw(p0.w != 0x41000000u) && --guard > 0);
      mean = __uint_as_float(p0.x) * (1.f / 640.f);
      rstd = rsq(fmaxf(fmaf(-mean, mean, __uint_as_float(p0.y) * (1.f / 640.f)), 0.f) + 1e-5f);
      rr = fmaf(-mean, wsum, __uint_as_float(p0.z)) * rstd;
    }
    TS(8);
    const uint32_t kk = ord_key(rr), kmax = __reduce_max_sync(0xffffffffu, kk);
    const int L = __ffs(__ballot_sync(0xffffffffu, kk == kmax)) - 1;
    const int crow = (L >> 2) + 8 * (L & 1);
    if (warp == g) {
      if (elect()) {
        asm volatile("red.relaxed.gpu.global.max.u64 [%0], %1;" :: "l"(g_own[1].cnt), "l"(((uint64_t)kmax << 32) | (uint32_t)(2047 - tok0 - 2 * crow)) : "memory");
        asm volatile("red.relaxed.gpu.global.add.u32 [%0], 1;" :: "l"(&g_own[1].cnt[0].z) : "memory");
      }
      asm volatile("bar.arrive 3, 64;" ::: "memory");
    }
    const uint32_t stg = sb + (fol ? OFF_O : g * 15360) + w4 * 2560;
    uint4 held;
    {
      const float om = shx(mean, 1), os = shx(rstd, 1);
      const float rl = odd ? os : rstd, rh = odd ? rstd : os;
      const float bl = -(odd ? om : mean) * rl, bh = -(odd ? mean : om) * rh, al = 1.f + rl, ah = 1.f + rh;
      if ((L >> 2) == r) {
        const bool chi = L & 1;
        const float rc = chi ? rh : rl, bc = chi ? bh : bl;
        uint32_t n[10];
#pragma unroll
        for (int j = 0; j < 10; j++) n[j] = pack_bf16(fmaf(chi ? h[4 * j + 2] : h[4 * j], rc, bc), fmaf(chi ? h[4 * j + 3] : h[4 * j + 1], rc, bc));
        uint4* d = cdp + c;
        stg_pkt(d, n[0], n[1], n[2], n[3]); stg_pkt(d + 4, n[4], n[5], n[6], n[7]); stg_rlx64(d + 8, n[8], n[9]);
      }
      mbar_wait(bar_oc + 56, 0);
      const uint32_t fa = stg + (lane & 15) * 160 + (lane >> 4) * 16;
#pragma unroll
      for (int s = 0; s < 5; s++)
        stsm4(fa + s * 32, pack_bf16(fmaf(h[8 * s], al, bl), fmaf(h[8 * s + 1], al, bl)), pack_bf16(fmaf(h[8 * s + 2], ah, bh), fmaf(h[8 * s + 3], ah, bh)),
              pack_bf16(fmaf(h[8 * s + 4], al, bl), fmaf(h[8 * s + 5], al, bl)), pack_bf16(fmaf(h[8 * s + 6], ah, bh), fmaf(h[8 * s + 7], ah, bh)));
      __syncwarp();
      held = lds128(stg + crow * 160 + min(lane, 9) * 16);
      if (lane < 10) stg_pkt(cdp + 12 + lane, held.x, held.y, held.z, held.w);
    }
    TS(9);
    mbar_wait(bar_ffn, 0);
    const uint32_t red = sb + OFF_RED;
    if (ffn1) {
      uint4 w1[4][5];
      {
        const int k = (lane & 7) + (lane >> 4) * 8;
        const uint32_t a1 = sb + k * 64, sw = ((lane >> 3) & 1) ^ ((lane >> 1) & 3);
#pragma unroll
        for (int s = 0; s < 5; s++)
#pragma unroll
          for (int u = 0; u < 4; u++)
            w1[u][s] = ldsm4t(a1 + (s < 4 ? warp * 4096 + s * 1024 : 32768 + warp * 1024) + (u >> 1) * (40960 + (s == 4 || warp >= 2 ? OFF_W2 - 49152 : 0)) + ((sw ^ (2 * (u & 1))) * 16));
      }
      uint32_t* const ap = hold(g_x.act + fj * 16 + (lane >> 1));
      mbar_wait(bar_win, 0);
      const uint32_t hp = sb + OFF_HN + (warp * 4 + c) * 16;
      const uint4 c0 = lds128(hp), c1 = lds128(hp + 512), c2 = lds128(hp + 1024);
      TS(10);
      float a[4][4];
#pragma unroll
      for (int u = 0; u < 4; u++) {
        a[u][0] = a[u][1] = a[u][2] = a[u][3] = 0.f;
        mma_acc(a[u], w1[u][0], c0.x, c0.y); mma_acc(a[u], w1[u][1], c0.z, c0.w); mma_acc(a[u], w1[u][2], c1.x, c1.y);
        mma_acc(a[u], w1[u][3], c1.z, c1.w); mma_acc(a[u], w1[u][4], c2.x, c2.y);
      }
      asm volatile("st.shared.v2.f32 [%0], {%1, %2};" :: "r"(red + (warp * 32 + c * 8 + r) * 8),
                   "f"(cA ? (odd ? a[0][2] : a[0][0]) : (odd ? a[1][2] : a[1][0])), "f"(cA ? (odd ? a[2][2] : a[2][0]) : (odd ? a[3][2] : a[3][0])) : "memory");
      bar_sync(1, 256);
      if (warp == 0) {
        float2 t[8];
#pragma unroll
        for (int i = 0; i < 8; i++) t[i] = lds64f(red + (i * 32 + lane) * 8);
        const float s = ((t[0].x + t[1].x) + (t[2].x + t[3].x)) + ((t[4].x + t[5].x) + (t[6].x + t[7].x));
        const float u = ((t[0].y + t[1].y) + (t[2].y + t[3].y)) + ((t[4].y + t[5].y) + (t[6].y + t[7].y));
        const float av = s * u * rcp(1.f + ex2(-1.4426950408889634f * s));
        const float an = shx(av, 1);
        if (!odd) stg_rlx32(ap, pack_bf16(av, an));
      }
      bar_sync(1, 256);
      TS(11);
    }
    if (OUT_LATE) mbar_wait(bar_win, 0);
    char* const ob2 = (char*)(out + tok0 * 640 + g * 64);
    const int remo = 896 - 96 * g;
#pragma unroll
    for (int s = 0; s < 5; s++) {
      const int row = s < 4 ? 4 * s + (lane >> 3) : lane >> 1, pc = s < 4 ? lane & 7 : 8 + (lane & 1);
      const uint4 v = lds128(stg + row * 160 + pc * 16);
      if (row != crow) stg128(ob2 + row * 2560 + pc * 16 + (s < 4 ? 0 : remo), v);
    }
    mbar_wait(bar_win, 0);
    const uint4 win = lds128(sb + OFF_WR + 336);
    if (win.x != slot && lane < 10) stg128(ob2 + crow * 2560 + lane * 16 + (lane < 8 ? 0 : remo), held);
    if (!ffn1) {
      TS(10);
      uint4 w2[6];
      const uint32_t a2 = sb + OFF_W2 + (warp * 192 + 8 * (((lane >> 3) & 1) * 4 + ((lane & 7) >> 1)) + 2 * (lane >> 4) + (lane & 1)) * 16;
#pragma unroll
      for (int s = 0; s < 6; s++) w2[s] = ldsm4t(a2 + (s >> 1) * 1024 + (s & 1) * 64);
      const uint4* p = (const uint4*)(g_x.act + warp * 96) + (r & 1) * 4 + c;
      const uint32_t* pb = (const uint32_t*)&g_x.cand[win.x][fj < 64 ? fj >> 3 : (fj - 64) >> 1][fj < 64 ? 12 + (fj & 7) : 20 + (fj & 1)] + c;
      uint32_t* const op = hold((uint32_t*)(out + win.y * 640 + fj * 8) + c);
      uint4 c0, c1, c2; uint32_t bw;
      if (ACT_NS) __nanosleep(ACT_NS);
      do {
        c0 = ldg_pkt(p); c1 = ldg_pkt(p + 8); c2 = ldg_pkt(p + 16); bw = ldg_rlx32(pb);
      } while (anyw(max(max(max(max(c0.x, c0.y), max(c0.z, c0.w)), max(max(c1.x, c1.y), max(c1.z, c1.w))), max(max(max(c2.x, c2.y), max(c2.z, c2.w)), bw)) == SENT) && --guard > 0);
      TS(11);
      float a[4] = {0.f, 0.f, 0.f, 0.f}, b[4] = {0.f, 0.f, 0.f, 0.f}, d[4] = {0.f, 0.f, 0.f, 0.f};
      mma_acc(a, w2[0], c0.x, c0.y); mma_acc(b, w2[2], c1.x, c1.y); mma_acc(d, w2[4], c2.x, c2.y);
      mma_acc(a, w2[1], c0.z, c0.w); mma_acc(b, w2[3], c1.z, c1.w); mma_acc(d, w2[5], c2.z, c2.w);
      if (c == 0) sts32f(red + (warp * 8 + r) * 4, ((a[0] + a[3]) + (b[0] + b[3])) + (d[0] + d[3]));
      bar_sync(1, 256);
      if (tid < 4) {
        float2 t[8];
#pragma unroll
        for (int i = 0; i < 8; i++) t[i] = lds64f(red + (i * 4 + tid) * 8);
        const float y0 = ((t[0].x + t[1].x) + (t[2].x + t[3].x)) + ((t[4].x + t[5].x) + (t[6].x + t[7].x));
        const float y1 = ((t[0].y + t[1].y) + (t[2].y + t[3].y)) + ((t[4].y + t[5].y) + (t[6].y + t[7].y));
        const float sg = __uint_as_float(win.z);
        *op = pack_bf16(fmaf(y0, sg, bf_lo(bw)), fmaf(y1, sg, bf_hi(bw)));
      }
    }
    TS(12);
#undef TS_T
  }
}

typedef CUresult (*EncodeFn)(CUtensorMap*, CUtensorMapDataType, cuuint32_t, void*, const cuuint64_t*, const cuuint64_t*, const cuuint32_t*,
                             const cuuint32_t*, CUtensorMapInterleave, CUtensorMapSwizzle, CUtensorMapL2promotion, CUtensorMapFloatOOBfill);

void make_map(EncodeFn enc, CUtensorMap* m, const void* base, const cuuint64_t* dims, const cuuint64_t* strides, const cuuint32_t* box,
              CUtensorMapSwizzle swz) {
  const cuuint32_t es[3] = {1, 1, 1};
  enc(m, CU_TENSOR_MAP_DATA_TYPE_BFLOAT16, 3, (void*)base, dims, strides, box, es, CU_TENSOR_MAP_INTERLEAVE_NONE, swz,
      CU_TENSOR_MAP_L2_PROMOTION_L2_128B, CU_TENSOR_MAP_FLOAT_OOB_FILL_NONE);
}

}

extern "C" void kernel_launch(void* const* d_in, const int* in_sizes, int n_in, void* d_out, int out_size) {
  const __nv_bfloat16* x = (const __nv_bfloat16*)d_in[0];
  const __nv_bfloat16* wqkv = (const __nv_bfloat16*)d_in[1];
  const __nv_bfloat16* wo = (const __nv_bfloat16*)d_in[2];
  void* fn = nullptr;
  cudaDriverEntryPointQueryResult st;
  cudaGetDriverEntryPoint("cuTensorMapEncodeTiled", &fn, cudaEnableDefault, &st);
  EncodeFn enc = (EncodeFn)fn;
  void* scp = nullptr;
  cudaGetSymbolAddress(&scp, g_scratch);
  Maps tm;
  { const cuuint64_t d[3] = {640, 1024, 2}, s[2] = {2560, 1280}; const cuuint32_t b[3] = {64, 64, 2}; make_map(enc, &tm.x, x, d, s, b, CU_TENSOR_MAP_SWIZZLE_128B); }
  { const cuuint64_t d[3] = {640, 640, 3}, s[2] = {3840, 1280}; const cuuint32_t b[3] = {64, 64, 1}; make_map(enc, &tm.w, wqkv, d, s, b, CU_TENSOR_MAP_SWIZZLE_128B); }
  { const cuuint64_t d[3] = {640, 640, 3}, s[2] = {3840, 1280}; const cuuint32_t b[3] = {16, 64, 3}; make_map(enc, &tm.wr, wqkv, d, s, b, CU_TENSOR_MAP_SWIZZLE_32B); }
  { const cuuint64_t d[3] = {32, 640, 20}, s[2] = {1280, 64}; const cuuint32_t b[3] = {32, 80, 2}; make_map(enc, &tm.wo, wo, d, s, b, CU_TENSOR_MAP_SWIZZLE_64B); }
  { const cuuint64_t d[3] = {640, 640, 1}, s[2] = {1280, 819200}; const cuuint32_t b[3] = {16, 80, 1}; make_map(enc, &tm.wor, wo, d, s, b, CU_TENSOR_MAP_SWIZZLE_64B); }
  { const cuuint64_t d[3] = {1536, 640, 1}, s[2] = {3072, 1966080}; const cuuint32_t b[3] = {32, 128, 1};
    make_map(enc, &tm.gate, d_in[5], d, s, b, CU_TENSOR_MAP_SWIZZLE_64B); make_map(enc, &tm.up, d_in[6], d, s, b, CU_TENSOR_MAP_SWIZZLE_64B); }
  { const cuuint64_t d[3] = {640, 1536, 1}, s[2] = {1280, 1966080}; const cuuint32_t b[3] = {8, 128, 1}; make_map(enc, &tm.down, d_in[7], d, s, b, CU_TENSOR_MAP_SWIZZLE_NONE); }
  cudaFuncSetAttribute(fused_kernel, cudaFuncAttributeMaxDynamicSharedMemorySize, SMEM_BYTES);
  fused_kernel<<<128, 512, SMEM_BYTES, cudaStreamPerThread>>>(x, wqkv, wo, (const __nv_bfloat16*)d_in[4], (const __nv_bfloat16*)d_in[5],
                                                              (const __nv_bfloat16*)d_in[6], (const __nv_bfloat16*)d_in[7], (__nv_bfloat16*)d_out, (Scratch*)scp, tm);
}
```

```cpp
#include <cuda_runtime.h>
#include <cuda_bf16.h>
#include <cuda.h>
#include <stdint.h>

#define PFW_NS 100
#define ACT_NS 0
#define OUT_LATE 0
#define REG_P 72
#define REG_C 184
#define AUX_NS 50
#define LEAD 1
#define RST_IT 3
#define ORDX 1
#define THR 3
#define PF_FIRST 4
#define PF_T0 2500
#define PF_CLK 500
#define HK_IT 1
#define F_IT 9
#define F_PER 2
#define F_MAX 8
#define LK 5
#define HOLD 2
#define F_LATE 12
#define HALO_NS 0

namespace {

constexpr int SLOT    = 47104;
constexpr int OFF_O   = 122880;
constexpr int OFF_W2  = 4 * SLOT;
constexpr int OFF_CS  = OFF_W2 + 32768;
constexpr int OFF_RS  = OFF_CS + 3840;
constexpr int OFF_MN  = OFF_RS + 576;
constexpr int OFF_WR  = OFF_MN + 1024;
constexpr int OFF_RED = OFF_CS;
constexpr int OFF_HN  = OFF_CS + 2048;
constexpr int OFF_PT  = OFF_WR + 352;
constexpr int OFF_BAR = OFF_PT + 768;
constexpr int SMEM_BYTES = OFF_BAR + 384 + 384;
constexpr uint32_t D0 = 1024 >> 4;
constexpr uint32_t SENT = 0xFFFFFFFFu;
constexpr int SPIN_MAX = 1 << 20;

struct Glob {
  uint4 cand[128][8][24];
  uint32_t act[768];
  uint32_t pad[256];
};
constexpr int GLOB_PER_CTA = sizeof(Glob) / 16 / 128;
static_assert(GLOB_PER_CTA * 128 * 16 == sizeof(Glob), "glob size");
struct Own {
  uint4 halo[5][32];
  uint4 st1[32];
  uint2 cs[32];
  uint4 st2[16];
  uint4 cnt[8];
};
struct Scratch {
  Glob x;
  Own own[128];
  uint4 o[32][8][640];
  uint32_t epoch[128];
};
__device__ __align__(128) Scratch g_scratch;
#define g_x (sc->x)
#define g_own (sc->own)
#define g_o (sc->o)
#define g_epoch (sc->epoch)
#define TS(i)

__device__ __forceinline__ void mbar_init(uint32_t bar, uint32_t cnt) { asm volatile("mbarrier.init.shared::cta.b64 [%0], %1;" :: "r"(bar), "r"(cnt) : "memory"); }
__device__ __forceinline__ void mbar_expect_tx(uint32_t bar, uint32_t bytes) { asm volatile("mbarrier.arrive.expect_tx.shared::cta.b64 _, [%0], %1;" :: "r"(bar), "r"(bytes) : "memory"); }
__device__ __forceinline__ void mbar_arrive(uint32_t bar) { asm volatile("mbarrier.arrive.shared::cta.b64 _, [%0];" :: "r"(bar) : "memory"); }
__device__ __forceinline__ void mbar_arrive_cta(uint32_t bar, uint32_t cta) {
  asm volatile("{\n.reg .b32 ra;\nmapa.shared::cluster.u32 ra, %0, %1;\nmbarrier.arrive.shared::cluster.b64 _, [ra];\n}\n" :: "r"(bar), "r"(cta) : "memory");
}
__device__ __forceinline__ void mbar_wait(uint32_t bar, uint32_t parity) {
  asm volatile("{\n.reg .pred p;\n.reg .u32 n;\nmov.u32 n, 0;\nW:\nmbarrier.try_wait.parity.shared::cta.b64 p, [%0], %1;\n@p bra.uni D;\n"
               "add.u32 n, n, 1;\nsetp.lt.u32 p, n, %2;\n@p bra.uni W;\nD:\n}\n" :: "r"(bar), "r"(parity), "n"(SPIN_MAX) : "memory");
}
__device__ __forceinline__ void tma_3d(uint32_t dst, const void* tm, uint32_t bar, int c0, int c1, int c2) {
  asm volatile("cp.async.bulk.tensor.3d.shared::cluster.global.mbarrier::complete_tx::bytes [%0], [%1, {%3, %4, %5}], [%2];" :: "r"(dst), "l"(tm), "r"(bar), "r"(c0), "r"(c1), "r"(c2) : "memory");
}
__device__ __forceinline__ void tma_3d_mc(uint32_t dst, const void* tm, uint32_t bar, int c0, int c1, int c2) {
  asm volatile("cp.async.bulk.tensor.3d.shared::cluster.global.mbarrier::complete_tx::bytes.multicast::cluster [%0], [%1, {%3, %4, %5}], [%2], %6;" :: "r"(dst), "l"(tm), "r"(bar), "r"(c0), "r"(c1), "r"(c2), "h"((uint16_t)3) : "memory");
}
__device__ __forceinline__ void wgmma_fence() { asm volatile("wgmma.fence.sync.aligned;" ::: "memory"); }
__device__ __forceinline__ void wgmma_commit() { asm volatile("wgmma.commit_group.sync.aligned;" ::: "memory"); }
template <int N> __device__ __forceinline__ void wgmma_wait() { asm volatile("wgmma.wait_group.sync.aligned %0;" :: "n"(N) : "memory"); }
__device__ __forceinline__ uint64_t make_desc(uint32_t addr, uint32_t lbo, uint32_t sbo, uint32_t swz) {
  return (uint64_t)(((addr & 0x3FFFF) >> 4) | ((lbo >> 4) << 16)) | ((uint64_t)((sbo >> 4) | (swz << 30)) << 32);
}
__device__ __forceinline__ void bar_sync(int id, int n) { asm volatile("bar.sync %0, %1;" :: "r"(id), "r"(n) : "memory"); }
__device__ __forceinline__ void st_pkt(void* p, uint32_t a, uint32_t b, uint32_t c, uint32_t d) {
  asm volatile("st.relaxed.gpu.v4.u32 [%0], {%1, %2, %3, %4};" :: "l"(p), "r"(a), "r"(b), "r"(c), "r"(d) : "memory");
}
__device__ __forceinline__ uint4 ldg_pkt(const void* p) {
  uint4 v; asm volatile("ld.relaxed.gpu.global.v4.u32 {%0, %1, %2, %3}, [%4];" : "=r"(v.x), "=r"(v.y), "=r"(v.z), "=r"(v.w) : "l"(p) : "memory"); return v;
}
__device__ __forceinline__ void stg_pkt(void* p, uint32_t a, uint32_t b, uint32_t c, uint32_t d) {
  asm volatile("st.relaxed.gpu.global.v4.u32 [%0], {%1, %2, %3, %4};" :: "l"(p), "r"(a), "r"(b), "r"(c), "r"(d) : "memory");
}
__device__ __forceinline__ uint32_t ldg_rlx32(const void* p) { uint32_t v; asm volatile("ld.relaxed.gpu.global.u32 %0, [%1];" : "=r"(v) : "l"(p) : "memory"); return v; }
__device__ __forceinline__ uint2 ldg_rlx64(const void* p) { uint2 v; asm volatile("ld.relaxed.gpu.global.v2.u32 {%0, %1}, [%2];" : "=r"(v.x), "=r"(v.y) : "l"(p) : "memory"); return v; }
__device__ __forceinline__ void stg128(void* p, const uint4& v) { asm volatile("st.global.v4.u32 [%0], {%1, %2, %3, %4};" :: "l"(p), "r"(v.x), "r"(v.y), "r"(v.z), "r"(v.w) : "memory"); }
__device__ __forceinline__ uint32_t pin(uint32_t v) { asm volatile("" : "+r"(v)); return v; }
__device__ __forceinline__ uint64_t mk64(uint32_t lo, uint32_t hi) { return ((uint64_t)hi << 32) | lo; }
template <class T> __device__ __forceinline__ T* hold(T* p) { return (T*)__shfl_sync(0xffffffffu, (unsigned long long)p, threadIdx.x & 31); }
template <class T> __device__ __forceinline__ T* pin(T* p) { asm volatile("" : "+l"(p)); return p; }
__device__ __forceinline__ void stg_rlx32(void* p, uint32_t v) { asm volatile("st.relaxed.gpu.global.u32 [%0], %1;" :: "l"(p), "r"(v) : "memory"); }
__device__ __forceinline__ void stg_rlx64(void* p, uint32_t a, uint32_t b) { asm volatile("st.relaxed.gpu.global.v2.u32 [%0], {%1, %2};" :: "l"(p), "r"(a), "r"(b) : "memory"); }
__device__ __forceinline__ uint4 ldsm4(uint32_t a) { uint4 v; asm volatile("ldmatrix.sync.aligned.m8n8.x4.shared.b16 {%0, %1, %2, %3}, [%4];" : "=r"(v.x), "=r"(v.y), "=r"(v.z), "=r"(v.w) : "r"(a) : "memory"); return v; }
__device__ __forceinline__ void ldsm4_if(uint4& v, uint32_t a, int off, bool p) {
  asm volatile("{\n.reg .pred q;\nsetp.ne.u32 q, %5, 0;\n@q ldmatrix.sync.aligned.m8n8.x4.shared.b16 {%0, %1, %2, %3}, [%4];\n}\n"
               : "+r"(v.x), "+r"(v.y), "+r"(v.z), "+r"(v.w) : "r"(a + off), "r"((int)p) : "memory");
}
__device__ __forceinline__ uint4 ldsm4t(uint32_t a) { uint4 v; asm volatile("ldmatrix.sync.aligned.m8n8.x4.trans.shared.b16 {%0, %1, %2, %3}, [%4];" : "=r"(v.x), "=r"(v.y), "=r"(v.z), "=r"(v.w) : "r"(a) : "memory"); return v; }
__device__ __forceinline__ void stsm4(uint32_t a, uint32_t x, uint32_t y, uint32_t z, uint32_t w) { asm volatile("stmatrix.sync.aligned.m8n8.x4.shared.b16 [%0], {%1, %2, %3, %4};" :: "r"(a), "r"(x), "r"(y), "r"(z), "r"(w) : "memory"); }
__device__ __forceinline__ void mma_acc(float (&c)[4], const uint4& a, uint32_t b0, uint32_t b1) {
  asm("mma.sync.aligned.m16n8k16.row.col.f32.bf16.bf16.f32 {%0,%1,%2,%3}, {%4,%5,%6,%7}, {%8,%9}, {%0,%1,%2,%3};"
      : "+f"(c[0]), "+f"(c[1]), "+f"(c[2]), "+f"(c[3]) : "r"(a.x), "r"(a.y), "r"(a.z), "r"(a.w), "r"(b0), "r"(b1));
}
__device__ __forceinline__ uint4 lds128(uint32_t a) { uint4 v; asm volatile("ld.shared.v4.u32 {%0, %1, %2, %3}, [%4];" : "=r"(v.x), "=r"(v.y), "=r"(v.z), "=r"(v.w) : "r"(a) : "memory"); return v; }
__device__ __forceinline__ float2 lds64f(uint32_t a) { float2 v; asm volatile("ld.shared.v2.f32 {%0, %1}, [%2];" : "=f"(v.x), "=f"(v.y) : "r"(a)); return v; }
__device__ __forceinline__ float lds32f(uint32_t a) { float v; asm volatile("ld.shared.f32 %0, [%1];" : "=f"(v) : "r"(a)); return v; }
__device__ __forceinline__ void sts32f(uint32_t a, float v) { asm volatile("st.shared.f32 [%0], %1;" :: "r"(a), "f"(v) : "memory"); }
__device__ __forceinline__ uint32_t pack_bf16(float lo, float hi) { uint32_t r; asm("cvt.rn.bf16x2.f32 %0, %1, %2;" : "=r"(r) : "f"(hi), "f"(lo)); return r; }
__device__ __forceinline__ float bf_lo(uint32_t v) { return __uint_as_float(v << 16); }
__device__ __forceinline__ float bf_hi(uint32_t v) { return __uint_as_float(v & 0xffff0000u); }
__device__ __forceinline__ uint32_t movm(uint32_t a) { uint32_t d; asm("movmatrix.sync.aligned.m8n8.trans.b16 %0, %1;" : "=r"(d) : "r"(a)); return d; }
__device__ __forceinline__ float ex2(float x) { float y; asm("ex2.approx.ftz.f32 %0, %1;" : "=f"(y) : "f"(x)); return y; }
__device__ __forceinline__ float rsq(float x) { float y; asm("rsqrt.approx.ftz.f32 %0, %1;" : "=f"(y) : "f"(x)); return y; }
__device__ __forceinline__ float rcp(float x) { float y; asm("rcp.approx.ftz.f32 %0, %1;" : "=f"(y) : "f"(x)); return y; }
__device__ __forceinline__ bool elect() { uint32_t p; asm volatile("{\n.reg .pred q;\nelect.sync _|q, 0xffffffff;\nselp.u32 %0, 1, 0, q;\n}\n" : "=r"(p)); return p; }
__device__ __forceinline__ int clk() { int c; asm volatile("mov.u32 %0, %%clock;" : "=r"(c) :: "memory"); return c; }
__device__ __forceinline__ void pf_l2(const void* p) { asm volatile("prefetch.global.L2 [%0];" :: "l"(p)); }
__device__ __forceinline__ bool anyw(bool p) { return __any_sync(0xffffffffu, p); }
__device__ __forceinline__ float shx(float v, int m) { return __shfl_xor_sync(0xffffffffu, v, m); }
__device__ __forceinline__ void mma_k24(float (&c)[4], uint32_t a0, uint32_t a1, uint32_t a2, uint32_t a3, uint32_t b0, uint32_t b1,
                                        uint32_t e0, uint32_t e1, uint32_t f0) {
  asm("mma.sync.aligned.m16n8k16.row.col.f32.bf16.bf16.f32 {%0,%1,%2,%3}, {%4,%5,%6,%7}, {%8,%9}, {%10,%10,%10,%10};"
      : "=f"(c[0]), "=f"(c[1]), "=f"(c[2]), "=f"(c[3]) : "r"(a0), "r"(a1), "r"(a2), "r"(a3), "r"(b0), "r"(b1), "f"(0.f));
  asm("mma.sync.aligned.m16n8k8.row.col.f32.bf16.bf16.f32 {%0,%1,%2,%3}, {%4,%5}, {%6}, {%0,%1,%2,%3};"
      : "+f"(c[0]), "+f"(c[1]), "+f"(c[2]), "+f"(c[3]) : "r"(e0), "r"(e1), "r"(f0));
}
__device__ __forceinline__ uint32_t ord_key(float r) { uint32_t u = __float_as_uint(r); return u ^ ((uint32_t)((int32_t)u >> 31) | 0x80000000u); }

__device__ __forceinline__ void wgmma_n48hi_ss(float (&d)[120], uint64_t da, uint64_t db, int scale_d) {
  asm volatile("{\n.reg .pred p;\nsetp.ne.b32 p, %26, 0;\n"
    "wgmma.mma_async.sync.aligned.m64n48k16.f32.bf16.bf16 "
    "{%0, %1, %2, %3, %4, %5, %6, %7, %8, %9, %10, %11, %12, %13, %14, %15, "
    "%16, %17, %18, %19, %20, %21, %22, %23}, "
    "%24, %25, p, 1, 1, 0, 1;\n}\n"
    : "+f"(d[96]), "+f"(d[97]), "+f"(d[98]), "+f"(d[99]), "+f"(d[100]), "+f"(d[101]), "+f"(d[102]), "+f"(d[103]),
      "+f"(d[104]), "+f"(d[105]), "+f"(d[106]), "+f"(d[107]), "+f"(d[108]), "+f"(d[109]), "+f"(d[110]), "+f"(d[111]),
      "+f"(d[112]), "+f"(d[113]), "+f"(d[114]), "+f"(d[115]), "+f"(d[116]), "+f"(d[117]), "+f"(d[118]), "+f"(d[119])
    : "l"(da), "l"(db), "r"(scale_d));
}
__device__ __forceinline__ void wgmma_n192lo_ss(float (&d)[120], uint64_t da, uint64_t db, int scale_d) {
  asm volatile("{\n.reg .pred p;\nsetp.ne.b32 p, %98, 0;\n"
    "wgmma.mma_async.sync.aligned.m64n192k16.f32.bf16.bf16 "
    "{%0, %1, %2, %3, %4, %5, %6, %7, %8, %9, %10, %11, %12, %13, %14, %15, "
    "%16, %17, %18, %19, %20, %21, %22, %23, %24, %25, %26, %27, %28, %29, %30, %31, "
    "%32, %33, %34, %35, %36, %37, %38, %39, %40, %41, %42, %43, %44, %45, %46, %47, "
    "%48, %49, %50, %51, %52, %53, %54, %55, %56, %57, %58, %59, %60, %61, %62, %63, "
    "%64, %65, %66, %67, %68, %69, %70, %71, %72, %73, %74, %75, %76, %77, %78, %79, "
    "%80, %81, %82, %83, %84, %85, %86, %87, %88, %89, %90, %91, %92, %93, %94, %95}, "
    "%96, %97, p, 1, 1, 0, 1;\n}\n"
    : "+f"(d[0]), "+f"(d[1]), "+f"(d[2]), "+f"(d[3]), "+f"(d[4]), "+f"(d[5]), "+f"(d[6]), "+f"(d[7]),
      "+f"(d[8]), "+f"(d[9]), "+f"(d[10]), "+f"(d[11]), "+f"(d[12]), "+f"(d[13]), "+f"(d[14]), "+f"(d[15]),
      "+f"(d[16]), "+f"(d[17]), "+f"(d[18]), "+f"(d[19]), "+f"(d[20]), "+f"(d[21]), "+f"(d[22]), "+f"(d[23]),
      "+f"(d[24]), "+f"(d[25]), "+f"(d[26]), "+f"(d[27]), "+f"(d[28]), "+f"(d[29]), "+f"(d[30]), "+f"(d[31]),
      "+f"(d[32]), "+f"(d[33]), "+f"(d[34]), "+f"(d[35]), "+f"(d[36]), "+f"(d[37]), "+f"(d[38]), "+f"(d[39]),
      "+f"(d[40]), "+f"(d[41]), "+f"(d[42]), "+f"(d[43]), "+f"(d[44]), "+f"(d[45]), "+f"(d[46]), "+f"(d[47]),
      "+f"(d[48]), "+f"(d[49]), "+f"(d[50]), "+f"(d[51]), "+f"(d[52]), "+f"(d[53]), "+f"(d[54]), "+f"(d[55]),
      "+f"(d[56]), "+f"(d[57]), "+f"(d[58]), "+f"(d[59]), "+f"(d[60]), "+f"(d[61]), "+f"(d[62]), "+f"(d[63]),
      "+f"(d[64]), "+f"(d[65]), "+f"(d[66]), "+f"(d[67]), "+f"(d[68]), "+f"(d[69]), "+f"(d[70]), "+f"(d[71]),
      "+f"(d[72]), "+f"(d[73]), "+f"(d[74]), "+f"(d[75]), "+f"(d[76]), "+f"(d[77]), "+f"(d[78]), "+f"(d[79]),
      "+f"(d[80]), "+f"(d[81]), "+f"(d[82]), "+f"(d[83]), "+f"(d[84]), "+f"(d[85]), "+f"(d[86]), "+f"(d[87]),
      "+f"(d[88]), "+f"(d[89]), "+f"(d[90]), "+f"(d[91]), "+f"(d[92]), "+f"(d[93]), "+f"(d[94]), "+f"(d[95])
    : "l"(da), "l"(db), "r"(scale_d));
}
__device__ __forceinline__ void wgmma_n48hi_rk(float (&d)[120], uint32_t a0, uint32_t a1, uint32_t a2, uint32_t a3, uint64_t db, int scale_d) {
  asm volatile("{\n.reg .pred p;\nsetp.ne.b32 p, %29, 0;\n"
    "wgmma.mma_async.sync.aligned.m64n48k16.f32.bf16.bf16 "
    "{%0, %1, %2, %3, %4, %5, %6, %7, %8, %9, %10, %11, %12, %13, %14, %15, "
    "%16, %17, %18, %19, %20, %21, %22, %23}, "
    "{%24, %25, %26, %27}, %28, p, 1, 1, 0;\n}\n"
    : "+f"(d[96]), "+f"(d[97]), "+f"(d[98]), "+f"(d[99]), "+f"(d[100]), "+f"(d[101]), "+f"(d[102]), "+f"(d[103]),
      "+f"(d[104]), "+f"(d[105]), "+f"(d[106]), "+f"(d[107]), "+f"(d[108]), "+f"(d[109]), "+f"(d[110]), "+f"(d[111]),
      "+f"(d[112]), "+f"(d[113]), "+f"(d[114]), "+f"(d[115]), "+f"(d[116]), "+f"(d[117]), "+f"(d[118]), "+f"(d[119])
    : "r"(a0), "r"(a1), "r"(a2), "r"(a3), "l"(db), "r"(scale_d));
}
__device__ __forceinline__ void wgmma_n192lo_rk(float (&d)[120], uint32_t a0, uint32_t a1, uint32_t a2, uint32_t a3, uint64_t db, int scale_d) {
  asm volatile("{\n.reg .pred p;\nsetp.ne.b32 p, %101, 0;\n"
    "wgmma.mma_async.sync.aligned.m64n192k16.f32.bf16.bf16 "
    "{%0, %1, %2, %3, %4, %5, %6, %7, %8, %9, %10, %11, %12, %13, %14, %15, "
    "%16, %17, %18, %19, %20, %21, %22, %23, %24, %25, %26, %27, %28, %29, %30, %31, "
    "%32, %33, %34, %35, %36, %37, %38, %39, %40, %41, %42, %43, %44, %45, %46, %47, "
    "%48, %49, %50, %51, %52, %53, %54, %55, %56, %57, %58, %59, %60, %61, %62, %63, "
    "%64, %65, %66, %67, %68, %69, %70, %71, %72, %73, %74, %75, %76, %77, %78, %79, "
    "%80, %81, %82, %83, %84, %85, %86, %87, %88, %89, %90, %91, %92, %93, %94, %95}, "
    "{%96, %97, %98, %99}, %100, p, 1, 1, 0;\n}\n"
    : "+f"(d[0]), "+f"(d[1]), "+f"(d[2]), "+f"(d[3]), "+f"(d[4]), "+f"(d[5]), "+f"(d[6]), "+f"(d[7]),
      "+f"(d[8]), "+f"(d[9]), "+f"(d[10]), "+f"(d[11]), "+f"(d[12]), "+f"(d[13]), "+f"(d[14]), "+f"(d[15]),
      "+f"(d[16]), "+f"(d[17]), "+f"(d[18]), "+f"(d[19]), "+f"(d[20]), "+f"(d[21]), "+f"(d[22]), "+f"(d[23]),
      "+f"(d[24]), "+f"(d[25]), "+f"(d[26]), "+f"(d[27]), "+f"(d[28]), "+f"(d[29]), "+f"(d[30]), "+f"(d[31]),
      "+f"(d[32]), "+f"(d[33]), "+f"(d[34]), "+f"(d[35]), "+f"(d[36]), "+f"(d[37]), "+f"(d[38]), "+f"(d[39]),
      "+f"(d[40]), "+f"(d[41]), "+f"(d[42]), "+f"(d[43]), "+f"(d[44]), "+f"(d[45]), "+f"(d[46]), "+f"(d[47]),
      "+f"(d[48]), "+f"(d[49]), "+f"(d[50]), "+f"(d[51]), "+f"(d[52]), "+f"(d[53]), "+f"(d[54]), "+f"(d[55]),
      "+f"(d[56]), "+f"(d[57]), "+f"(d[58]), "+f"(d[59]), "+f"(d[60]), "+f"(d[61]), "+f"(d[62]), "+f"(d[63]),
      "+f"(d[64]), "+f"(d[65]), "+f"(d[66]), "+f"(d[67]), "+f"(d[68]), "+f"(d[69]), "+f"(d[70]), "+f"(d[71]),
      "+f"(d[72]), "+f"(d[73]), "+f"(d[74]), "+f"(d[75]), "+f"(d[76]), "+f"(d[77]), "+f"(d[78]), "+f"(d[79]),
      "+f"(d[80]), "+f"(d[81]), "+f"(d[82]), "+f"(d[83]), "+f"(d[84]), "+f"(d[85]), "+f"(d[86]), "+f"(d[87]),
      "+f"(d[88]), "+f"(d[89]), "+f"(d[90]), "+f"(d[91]), "+f"(d[92]), "+f"(d[93]), "+f"(d[94]), "+f"(d[95])
    : "r"(a0), "r"(a1), "r"(a2), "r"(a3), "l"(db), "r"(scale_d));
}
__device__ __forceinline__ void wgmma_n80_rs(float (&d)[40], uint32_t a0, uint32_t a1, uint32_t a2, uint32_t a3, uint64_t db, int scale_d) {
  asm volatile("{\n.reg .pred p;\nsetp.ne.b32 p, %45, 0;\n"
    "wgmma.mma_async.sync.aligned.m64n80k16.f32.bf16.bf16 "
    "{%0, %1, %2, %3, %4, %5, %6, %7, %8, %9, %10, %11, %12, %13, %14, %15, "
    "%16, %17, %18, %19, %20, %21, %22, %23, %24, %25, %26, %27, %28, %29, %30, %31, "
    "%32, %33, %34, %35, %36, %37, %38, %39}, "
    "{%40, %41, %42, %43}, %44, p, 1, 1, 1;\n}\n"
    : "+f"(d[0]), "+f"(d[1]), "+f"(d[2]), "+f"(d[3]), "+f"(d[4]), "+f"(d[5]), "+f"(d[6]), "+f"(d[7]),
      "+f"(d[8]), "+f"(d[9]), "+f"(d[10]), "+f"(d[11]), "+f"(d[12]), "+f"(d[13]), "+f"(d[14]), "+f"(d[15]),
      "+f"(d[16]), "+f"(d[17]), "+f"(d[18]), "+f"(d[19]), "+f"(d[20]), "+f"(d[21]), "+f"(d[22]), "+f"(d[23]),
      "+f"(d[24]), "+f"(d[25]), "+f"(d[26]), "+f"(d[27]), "+f"(d[28]), "+f"(d[29]), "+f"(d[30]), "+f"(d[31]),
      "+f"(d[32]), "+f"(d[33]), "+f"(d[34]), "+f"(d[35]), "+f"(d[36]), "+f"(d[37]), "+f"(d[38]), "+f"(d[39])
    : "r"(a0), "r"(a1), "r"(a2), "r"(a3), "l"(db), "r"(scale_d));
}
__device__ __forceinline__ void wgmma_n80_ss(float (&d)[40], uint64_t da, uint64_t db, int scale_d) {
  asm volatile("{\n.reg .pred p;\nsetp.ne.b32 p, %42, 0;\n"
    "wgmma.mma_async.sync.aligned.m64n80k16.f32.bf16.bf16 "
    "{%0, %1, %2, %3, %4, %5, %6, %7, %8, %9, %10, %11, %12, %13, %14, %15, "
    "%16, %17, %18, %19, %20, %21, %22, %23, %24, %25, %26, %27, %28, %29, %30, %31, "
    "%32, %33, %34, %35, %36, %37, %38, %39}, "
    "%40, %41, p, 1, 1, 0, 1;\n}\n"
    : "+f"(d[0]), "+f"(d[1]), "+f"(d[2]), "+f"(d[3]), "+f"(d[4]), "+f"(d[5]), "+f"(d[6]), "+f"(d[7]),
      "+f"(d[8]), "+f"(d[9]), "+f"(d[10]), "+f"(d[11]), "+f"(d[12]), "+f"(d[13]), "+f"(d[14]), "+f"(d[15]),
      "+f"(d[16]), "+f"(d[17]), "+f"(d[18]), "+f"(d[19]), "+f"(d[20]), "+f"(d[21]), "+f"(d[22]), "+f"(d[23]),
      "+f"(d[24]), "+f"(d[25]), "+f"(d[26]), "+f"(d[27]), "+f"(d[28]), "+f"(d[29]), "+f"(d[30]), "+f"(d[31]),
      "+f"(d[32]), "+f"(d[33]), "+f"(d[34]), "+f"(d[35]), "+f"(d[36]), "+f"(d[37]), "+f"(d[38]), "+f"(d[39])
    : "l"(da), "l"(db), "r"(scale_d));
}

__device__ __forceinline__ constexpr int QT(int t) { return t < 8 ? t : 16 + t; }
__device__ __forceinline__ constexpr int KT(int t) { return t < 8 ? 8 + t : 18 + t; }
__device__ __forceinline__ constexpr int VT(int t) { return t < 8 ? 16 + t : 20 + t; }

struct Maps { CUtensorMap x, w, wr, wo, wor, gate, up, down; };

__global__ void __cluster_dims__(2, 1, 1) __launch_bounds__(512, 1)
fused_kernel(const __nv_bfloat16* __restrict__ x, const __nv_bfloat16* __restrict__ wqkv,
             const __nv_bfloat16* __restrict__ wo, const __nv_bfloat16* __restrict__ w_r, const __nv_bfloat16* __restrict__ w_gate,
             const __nv_bfloat16* __restrict__ w_up, const __nv_bfloat16* __restrict__ w_down, __nv_bfloat16* __restrict__ out,
             Scratch* __restrict__ sc, const __grid_constant__ Maps tm) {
  extern __shared__ __align__(1024) uint8_t smem[];
  const int tid = threadIdx.x, warp = __shfl_sync(0xffffffffu, tid >> 5, 0), lane = tid & 31, bid = blockIdx.x;
  const uint32_t sb = (uint32_t)__cvta_generic_to_shared(smem);
  const uint32_t bar_full = sb + OFF_BAR, bar_empty = bar_full + 32, bar_aux = bar_full + 64, bar_ffn = bar_full + 72, bar_win = bar_full + 80, bar_rst = bar_full + 88,
                 bar_o = bar_full + 96, bar_oc = bar_o + 112, bar_st = bar_o + 224, bar_go = bar_o + 248, bar_kv = bar_o + 272;
  if (warp < 4 && elect()) {
    mbar_init(bar_full + 8 * (warp ^ 2), 1);
    mbar_init(bar_empty + 8 * warp, 24);
    mbar_init(bar_aux + 8 * warp, warp == 0 ? 64 : warp == 2 ? 32 : 1);
    asm volatile("fence.mbarrier_init.release.cluster;" ::: "memory");
  }
  asm volatile("barrier.cluster.arrive.relaxed.aligned;" ::: "memory");
  if (warp >= 8 && warp < 11 && elect()) asm volatile("prefetch.tensormap [%0];" :: "l"(&tm.x + (warp - 8)) : "memory");
  auto pf_slice = [&](int ks) {
    pf_l2(lane < 16 ? (const char*)x + ((bid * 16 + lane) * 1280 + ks * 128) : (const char*)wqkv + ((bid * 15 + min(lane, 30) - 16) * 128 + ks * 245760));
  };
  if (warp == 4) pf_slice(0);
  const int rank = bid & 1, cl = bid >> 1;
  const int q7 = ((cl - 36) * 37) >> 8;
  const int P = cl < 4 ? 0 : cl < 36 ? (cl - 4) & 7 : cl - 35 - 7 * q7;
  const int g = cl < 4 ? 4 + cl : cl < 36 ? (cl - 4) >> 3 : 4 + q7;
  const int mt = 2 * P + rank, cid = mt * 8 + g;
  const bool ffn1 = g >= 5;
  const int fj = ffn1 ? mt * 3 + g - 5 : (P * 5 + g) * 2 + rank;
  const int ord = ((g >> 2) ^ P) & 1;
  auto ks_of = [&](int it) { return !ORDX || ord == 0 || it == 0 ? it : it <= 5 ? it + 4 : it - 5; };
  auto load_w = [&](int it, uint32_t a, uint32_t full) {
    tma_3d_mc(a + 16384 + rank * 16384, &tm.w, full, g * 80, it * 64, rank * 2);
    tma_3d_mc(a + (rank ? 40960 : 24576), rank ? &tm.wr : &tm.w, full, g * 80 + rank * 64, it * 64, 1 - rank);
  };
  if (warp == 0 && elect()) {
    mbar_expect_tx(bar_full + 16, SLOT);
    tma_3d(sb + 2 * SLOT, &tm.x, bar_full + 16, 0, P * 128, rank);
  }
  asm volatile("barrier.cluster.wait.aligned;" ::: "memory");
  if (warp == 0) {
    if (elect()) load_w(0, sb + 2 * SLOT, bar_full + 16);
    asm volatile("bar.arrive 4, 64;" ::: "memory");
  }

  if (warp >= 8) {
    asm volatile("setmaxnreg.dec.sync.aligned.u32 %0;" :: "n"(REG_P));
#define TS_T 0
    if (warp == 8) {
      TS(8);
      bar_sync(4, 64);
      if (elect()) {
        TS(10);
        int fjn = 0;
#pragma unroll 1
        for (int it = 1; it < 17; it++) {
          const int s = (it + 2) & 3;
          const uint32_t full = bar_full + 8 * s, a = sb + s * SLOT;
          if (it >= 13) { mbar_wait(bar_oc + 8 * (it - 13), 0); mbar_wait(bar_oc + 56 + 8 * (it - 13), 0); }
          else if (it >= 4) mbar_wait(bar_empty + 8 * s, ((it >> 2) - 1) & 1);
          else if (it >= THR) mbar_wait(bar_full + 8 * ((it - THR + 2) & 3), 0);
          if (it < 10) {
            const int ks = ks_of(it);
            mbar_expect_tx(full, SLOT);
            tma_3d(a, &tm.x, full, ks * 64, P * 128, rank);
            load_w(ks, a, full);
            TS(12 + it);
            if ((unsigned)(it - RST_IT) < 2u) {
              mbar_wait(bar_rst, 0);
              asm volatile("cp.async.bulk.global.shared::cta.bulk_group [%0], [%1], %2;\ncp.async.bulk.commit_group;"
                           :: "l"(it == RST_IT ? (uint4*)(g_own + cid) : (uint4*)&g_x + cid * GLOB_PER_CTA), "r"(sb + OFF_CS),
                              "r"(it == RST_IT ? (int)sizeof(Own) : GLOB_PER_CTA * 16) : "memory");
            }
            if (it == RST_IT + 2) { asm volatile("cp.async.bulk.wait_group 0;" ::: "memory"); mbar_arrive(bar_rst); }
          } else if (it < 13) {
            const int g0 = 3 * (it - 10), g1 = min(g0 + 3, 8);
            mbar_expect_tx(full, (g1 - g0) * 12800);
#pragma unroll 1
            for (int gp = g0 + ((g0 ^ rank) & 1); gp < g1; gp += 2) {
              tma_3d_mc(sb + gp * 15360, &tm.wo, full, 0, gp * 80, g * 2);
              tma_3d_mc(sb + gp * 15360 + 10240, &tm.wor, full, 512 + g * 16, gp * 80, 0);
            }
          }
          if (it == 4) mbar_expect_tx(bar_ffn, ffn1 ? 81920 : 24576);
          const int j1 = ffn1 ? (it >= 13 ? min(2 * it - 21, 10) : min(max(it - F_IT + 1, 0), 4)) : (it >= 13 ? (it == 16 ? 12 : min(F_MAX + (it - 12) * F_LATE, 12)) : min(max((it - F_IT + 1) * F_PER, 0), F_MAX));
#pragma unroll 1
          for (; fjn < j1; fjn++) {
            const int j = fjn < 4 ? fjn + 6 : fjn - 4;
            if (ffn1) tma_3d(sb + (j < 6 ? 0 : OFF_W2 - 49152) + j * 8192, j < 5 ? &tm.gate : &tm.up, bar_ffn, fj * 32, (j < 5 ? j : j - 5) * 128, 0);
            else tma_3d(sb + OFF_W2 + fjn * 2048, &tm.down, bar_ffn, fj * 8, fjn * 128, 0);
          }
        }
        TS(11);
      }
#undef TS_T
#define TS_T 64
    } else if (warp >= 12) {
      const int l7 = lane & 7, j = warp - 12, ch = min((P >> 1) * 4 + rank * 2 + (j >> 1), 14);
      const uint32_t sxo = ((g & 3) * 32 + j * 8 + l7) * 128 + (((lane >> 3) ^ l7) * 16);
      const uint32_t swo = ch < 12 ? 16384 + (ch >> 2) * 8192 + lane * 128 + ((((ch & 3) * 2 + (j & 1)) ^ l7) * 16)
                                   : 40960 + (ch - 12) * 2048 + lane * 32 + (((j & 1) ^ (l7 >> 2)) * 16);
      float ps = 0.f, pq = 0.f, pq1 = 0.f, pc = 0.f;
#pragma unroll 1
      for (int it = ord; it < ord + 5; it++) {
        const int sl = (it + 2) & 3;
        mbar_wait(bar_full + 8 * sl, (it >> 2) & 1);
        TS(it);
        const uint32_t a = sb + sl * SLOT;
        const uint4 v0 = ldsm4(a + sxo), v1 = ldsm4((a + sxo) ^ 64), w0 = ldsm4t(a + swo), w1 = ldsm4t(a + swo + (ch < 12 ? 4096 : 1024));
        if (lane + (int)((v0.x & v1.x & w0.x & w1.x) == 0x7fc17fc1u && (v0.x | v1.x) == 0u) < 2) mbar_arrive_cta(bar_empty + 8 * sl, lane);
        const uint32_t vv[8] = {v0.x, v0.y, v0.z, v0.w, v1.x, v1.y, v1.z, v1.w}, ww[8] = {w0.x, w0.y, w0.z, w0.w, w1.x, w1.y, w1.z, w1.w};
#pragma unroll
        for (int i = 0; i < 8; i++) {
          const float d = bf_lo(vv[i]), e = bf_hi(vv[i]);
          ps += d + e; pq = fmaf(d, d, pq); pq1 = fmaf(e, e, pq1); pc += bf_lo(ww[i]) + bf_hi(ww[i]);
        }
      }
      pq += pq1;
      ps += shx(ps, 1); pq += shx(pq, 1); pc += shx(pc, 1);
      ps += shx(ps, 2); pq += shx(pq, 2); pc += shx(pc, 2);
      const int c = lane & 3;
      if (c < 3) sts32f(sb + OFF_PT + (c * 32 + j * 8 + (lane >> 2)) * 4, c == 0 ? ps : c == 1 ? pq : pc);
      asm volatile("bar.arrive 2, 224;" ::: "memory");
      if (warp == 12) {
        const uint4* const hp = hold(&g_own[max(cid - 16, 0)].halo[0][lane]);
        mbar_wait(bar_aux, 0);
        mbar_wait(bar_go, 0);
        uint4 v[5] = {};
        int guard = SPIN_MAX;
        if (P > 0) {
          do {
#pragma unroll
            for (int i = 0; i < 5; i++) v[i] = ldg_pkt(hp + 32 * i);
          } while (anyw(v[0].x == SENT || v[1].x == SENT || v[2].x == SENT || v[3].x == SENT || v[4].x == SENT) && --guard > 0);
        }
#pragma unroll
        for (int i = 0; i < 5; i++) *(uint4*)(smem + OFF_O + 10240 + i * 512 + lane * 16) = v[i];
        mbar_arrive(bar_kv);
      }
#undef TS_T
#define TS_T 32
    } else if (warp < 11) {
      Own* const own = g_own + cid;
      const int l7 = lane & 7, hk = lane >> 4, idx = lane;
      if (warp == 10 && elect()) {
#pragma unroll 1
        for (int i = 0; i < 36; i++) mbar_init(bar_o + 8 * i, i < 14 ? 1 : i < 34 ? 4 : 128);
      }
      {
        const int t0 = clk();
#pragma unroll 1
        for (int i = PF_FIRST; i < 6; i++) {
          while (clk() - t0 < PF_T0 + (i - PF_FIRST) * PF_CLK) __nanosleep(20);
          pf_slice(warp == 9 ? min(i, 4) : i + 4);
        }
      }
      bar_sync(2, 224);
      mbar_wait(bar_rst, 1);
      TS(0);
      const uint32_t tag = __float_as_uint(lds32f(sb + OFF_WR + 324));
      const float s0 = lds32f(sb + OFF_PT + lane * 4 + (warp - 9) * 256), q0 = lds32f(sb + OFF_PT + 128 + lane * 4);
      int guard = SPIN_MAX;
      if (warp == 9) {
        stg_pkt(&own->st1[idx], __float_as_uint(s0), __float_as_uint(q0), tag, 0u);
        TS(1);
        const uint4* sp = &g_own[mt * 8].st1[lane];
        const uint4* hp = &g_own[max(mt - 2, 0) * 8 + 3].st1[24 + l7];
        uint4 a[5], b[5];
        bool bad;
        do {
          __nanosleep(AUX_NS);
          bad = false;
#pragma unroll
          for (int i = 0; i < 5; i++) {
            const uint4* q = i < 4 ? sp + i * (sizeof(Own) / 16) : hp;
            a[i] = ldg_pkt(q); b[i] = ldg_pkt(q + 4 * sizeof(Own) / 16);
          }
#pragma unroll
          for (int i = 0; i < 5; i++) bad |= a[i].z != tag || b[i].z != tag;
        } while (anyw(bad) && --guard);
#pragma unroll
        for (int i = 0; i < 5; i++) {
          const float m = (__uint_as_float(a[i].x) + __uint_as_float(b[i].x)) * (1.f / 640.f);
          const float rs = rsq(fmaxf(fmaf(-m, m, (__uint_as_float(a[i].y) + __uint_as_float(b[i].y)) * (1.f / 640.f)), 0.f) + 1e-5f);
          ((float*)(smem + OFF_RS))[i < 4 ? 8 + lane + 32 * i : l7] = rs;
          const uint32_t mh = pack_bf16(-m, -m);
          const float ml = -m - bf_lo(mh);
          if (i < 4) ((uint2*)(smem + OFF_MN))[lane + 32 * i] = make_uint2(mh, pack_bf16(ml, ml));
        }
      } else {
        stg_rlx64(&own->cs[idx], __float_as_uint(s0), tag);
        const uint4* cp = (const uint4*)g_own[hk * 8 + g].cs + (lane & 15);
        uint4 a[4], b[4];
        bool bad;
        do {
          __nanosleep(AUX_NS);
          bad = false;
#pragma unroll
          for (int i = 0; i < 4; i++) { a[i] = ldg_pkt(cp + i * 32 * sizeof(Own) / 16); b[i] = ldg_pkt(cp + (i * 32 + 16) * sizeof(Own) / 16); }
#pragma unroll
          for (int i = 0; i < 4; i++) bad |= a[i].y != tag || a[i].w != tag || b[i].y != tag || b[i].w != tag;
        } while (anyw(bad) && --guard);
#pragma unroll
        for (int i = 0; i < 4; i++)
          if (i < 3 || lane < 24) {
            const float c0 = __uint_as_float(a[i].x) + __uint_as_float(b[i].x), c1 = __uint_as_float(a[i].z) + __uint_as_float(b[i].z);
            const uint32_t hi = pack_bf16(c0, c1), w0 = pack_bf16(c0, c0 - bf_lo(hi)), w1 = pack_bf16(c1, c1 - bf_hi(hi));
            uint4* const d = (uint4*)(smem + OFF_CS) + 2 * (lane + 32 * i);
            d[0] = make_uint4(w0, w0, 0, 0); d[1] = make_uint4(w1, w1, 0, 0);
          }
        asm volatile("fence.proxy.async.shared::cta;" ::: "memory");
      }
      mbar_arrive(bar_aux);
      TS(2);
      const int fo = warp - 9, wq = fo ? 1 - LEAD : LEAD;
      const uint4* const fp = hold(g_own[mt * 8 + wq * 4].cnt);
      const char* src = hold((const char*)g_o[mt * 2 + wq]);
      if (elect()) {
        const uint32_t bo = bar_o + fo * 56;
#pragma unroll
        for (int i = 0; i < 7; i++) mbar_expect_tx(bo + 8 * i, 10240);
        mbar_wait(bar_st + 8 * fo, 0);
        while (ldg_rlx32(fp) != 32u && --guard > 0) {}
        asm volatile("fence.proxy.async.global;" ::: "memory");
        TS(6);
#pragma unroll
        for (int i = 0; i < 7; i++) {
          if (fo || i == 6) mbar_wait(bo + 64 + 8 * i, 0);
          else if (i == 4) mbar_wait(bar_st + 8, 0);
          if (i == g) src += 10240;
          asm volatile("cp.async.bulk.shared::cluster.global.mbarrier::complete_tx::bytes [%0], [%1], 10240, [%2];"
                       :: "r"(sb + OFF_O + ((i + 2) % 6) * 10240 + fo * (i == 3 ? -51200 : 10240)), "l"(src + i * 10240), "r"(bo + 8 * i) : "memory");
        }
      }
#undef TS_T
#define TS_T 96
    } else {
      if ((sb & 0x3FFFF) != D0 * 16) __trap();
#pragma unroll 1
      for (int i = lane; i < 232; i += 32) { const uint32_t f = i < 208 ? SENT : 0u; ((uint4*)(smem + OFF_CS))[i] = make_uint4(f, f, f, f); }
      asm volatile("fence.proxy.async.shared::cta;" ::: "memory");
      if (elect()) mbar_arrive(bar_rst);
      mbar_wait(bar_full + 8 * ((HK_IT + 2) & 3), 0);
      TS(4);
      const uint32_t epoch = ldg_rlx32(g_epoch + cid) + 1;
      uint32_t wv[10];
#pragma unroll
      for (int i = 0; i < 10; i++) wv[i] = __ldg((const uint32_t*)w_r + lane + 32 * i);
      float s = 0.f;
#pragma unroll
      for (int i = 0; i < 10; i++) {
        s += bf_lo(wv[i]) + bf_hi(wv[i]);
        const unsigned u = i < 8 ? lane + 32 * (i - g) : lane + 32 * (i - 7) - g * 8;
        if (i < 8 ? u < 32u : u - 32u < 8u) *(float2*)(smem + OFF_WR + ((u & 3) * 10 + (u >> 2)) * 8) = make_float2(bf_lo(wv[i]), bf_hi(wv[i]));
      }
#pragma unroll
      for (int m = 1; m < 32; m <<= 1) s += shx(s, m);
      *(float2*)(smem + OFF_WR + 320) = make_float2(s, __uint_as_float(epoch * 0x9E3779B8u));
      g_epoch[cid] = epoch;
      TS(3);
      TS(5);
      asm volatile("bar.arrive 2, 224;" ::: "memory");
#pragma unroll 1
      for (int i = 0; i < 14; i++) {
        const int m = (i + 2) >> 2, n = m == 0 ? 50 : 120, t = (m == 0 ? i : (i + 2) & 3) * 32 + lane;
        const char* b = (const char*)(m == 0 ? wo : m == 1 ? w_up : m == 2 ? w_down : w_gate);
        if (t < n) pf_l2(b + (bid * n + t) * 128);
        __nanosleep(PFW_NS);
      }
      bar_sync(3, 64);
      const uint4* const kp = g_own[1].cnt;
      const uint4* const cb = &g_x.cand[0][lane >> 2][lane & 3];
      uint4 k = ldg_pkt(kp), c0 = make_uint4(0, 0, 0, 0), c1 = c0; uint2 c2 = make_uint2(0, 0);
      int guard = SPIN_MAX, ws;
      while (true) {
        const uint32_t tk = 2047u - (k.x & 2047u);
        ws = (tk >> 8) * 16 + (tk & 1) * 8 + ((tk >> 5) & 7);
        const uint32_t prev = k.x;
        if (ffn1) { const uint4* q = cb + ws * 192; c0 = ldg_pkt(q); c1 = ldg_pkt(q + 4); c2 = ldg_rlx64(q + 8); }
        if (k.z != 128u) k = ldg_pkt(kp);
        if ((k.z == 128u && k.x == prev && !anyw(c0.x == SENT || c1.x == SENT || c2.x == SENT)) || --guard <= 0) break;
      }
      *(uint4*)(smem + OFF_HN + lane * 16) = c0; *(uint4*)(smem + OFF_HN + 512 + lane * 16) = c1; *(uint2*)(smem + OFF_HN + 1024 + lane * 16) = c2;
      const float rw = __uint_as_float(k.y ^ ((uint32_t)((int32_t)~k.y >> 31) | 0x80000000u));
      *(uint4*)(smem + OFF_WR + 336) = make_uint4(ws, 2047u - (k.x & 2047u), __float_as_uint(rcp(1.f + ex2(-1.4426950408889634f * rw))), 0);
      mbar_arrive(bar_win);
      TS(7);
    }
#undef TS_T
  } else {
#define TS_T 0
    asm volatile("setmaxnreg.inc.sync.aligned.u32 %0;" :: "n"(REG_C));
    const int wg = warp >> 2, w4 = warp & 3, r = lane >> 2, c = lane & 3;
    float acc[120];
    uint4 xr[5] = {};
    const uint32_t xa = pin(sb + (warp * 16 + (lane & 15)) * 128 + ((lane >> 4) ^ (lane & 7)) * 16);
    const int fol = wg != LEAD;
    const bool first = (P == 0) && (warp == 0);
    const uint32_t kvs = sb + OFF_O + fol * 10240 + w4 * 2560 + lane * 16;
    uint4* const kvd = hold(warp == 7 ? &g_own[cid].halo[0][lane] : (uint4*)(smem + (warp == 3 ? OFF_O + lane * 16 : kvs - sb + 2560)));
    uint4* const odst = hold(&g_o[mt * 2 + wg][g][w4 * 160]);
    uint4* const ocnt = hold(g_own[mt * 8 + wg * 4].cnt);
    uint32_t m0 = 0, m1 = 0;
    const uint32_t mna = pin(sb + OFF_MN + (warp * 16 + r) * 8 + c * 4);
    const int itx = ord == 0 || g == 0 ? g : g < 5 ? g + 5 : g - 4, ity = (ord ? 4 : 8) + (g >> 2);
    uint32_t rel;
    asm volatile("mapa.shared::cluster.u32 %0, %1, %2;" : "=r"(rel) : "r"(bar_empty), "r"(tid & 1));
    const uint32_t xa1 = pin(xa ^ 32), xa2 = pin(xa ^ 64), xa3 = pin(xa ^ 96), xb = pin(xa ^ ((g & 3) * 32));
    const uint32_t da0 = wg * 512;
    const bool rel2 = lane < 2, rel6 = lane < 2 + 2 * (warp & 1);
    const uint32_t zero = (uint32_t)(uintptr_t)x & 8u;
    mbar_wait(bar_full + 16, 0);
    TS(13);
    wgmma_fence();
#pragma unroll
    for (int it = 0; it < 10; it++) {
      const int s = (it + 2) & 3;
      if (it == 9) bar_sync(10 + wg, 256);
#pragma unroll
      for (int kk = 0; kk < 4; kk++) {
        if (kk == 2 && it > 0) {
          wgmma_commit();
          wgmma_wait<1>();
          const uint32_t ra = ((xr[0].x ^ xr[1].x ^ xr[2].x ^ xr[3].x ^ xr[4].x) & zero) | rel;
          if (it == 1 ? (ord ? rel6 : rel2) : it == 6 ? (ord ? rel2 : rel6) : it < 6 ? rel2 : rel6)
            asm volatile("mbarrier.arrive.shared::cluster.b64 _, [%0];" :: "r"(ra + 8 * ((it + 1) & 3)) : "memory");
        }
        if (kk == 2) {
          ldsm4_if(xr[0], xa, s * SLOT, it == itx); ldsm4_if(xr[1], xa1, s * SLOT, it == itx);
          ldsm4_if(xr[2], xa2, s * SLOT, it == itx); ldsm4_if(xr[3], xa3, s * SLOT, it == itx);
          if ((it & 6) == 4 || it >= 8) ldsm4_if(xr[4], xb, s * SLOT, it == ity);
        }
        if (kk == 3 && it < 9) {
          mbar_wait(bar_full + 8 * ((it + 3) & 3), ((it + 1) >> 2) & 1);
          TS(14 + it);
        }
        if (kk == LK && it >= 8 && it == (wg == LEAD ? 9 : 8)) asm volatile("bar.arrive %0, 256;" :: "r"(11 - wg) : "memory");
        const uint64_t da = mk64(da0 + (D0 + s * (SLOT >> 4) + kk * 2 + (1 << 16)), 0x40000040u);
        wgmma_n48hi_ss(acc, da, mk64(D0 + s * (SLOT >> 4) + 2560 + kk * 32 + (128 << 16), 0xC0000010u), (it | kk) != 0);
        wgmma_n192lo_ss(acc, da, mk64(D0 + s * (SLOT >> 4) + 1024 + kk * 128 + (512 << 16), 0x40000040u), (it | kk) != 0);
      }
      wgmma_commit();
      if (LK >= 4 && it >= 8 && it == (wg == LEAD ? (LK == 4 ? 9 : 10) : 8)) asm volatile("bar.arrive %0, 256;" :: "r"(11 - wg) : "memory");
      if (it == 8) {
        mbar_wait(bar_aux, 0);
        TS(3);
        if (c < 2) { m0 = __float_as_uint(lds32f(mna)); m1 = __float_as_uint(lds32f(mna + 64)); }
      }
    }
    {
      const uint64_t dc = make_desc(D0 * 16 + OFF_CS, 0, 128, 0);
      wgmma_fence();
      wgmma_n48hi_rk(acc, m0, m1, 0u, 0u, dc + 192, 1);
      wgmma_n192lo_rk(acc, m0, m1, 0u, 0u, dc, 1);
      wgmma_commit();
      if (LK == 5 && wg == LEAD) asm volatile("bar.arrive %0, 256;" :: "r"(11 - LEAD) : "memory");
    }
    const uint32_t stb = sb + OFF_RS + warp * 64;
    const float rlo = lds32f(stb + (8 + r) * 4), rhi = lds32f(stb + (16 + r) * 4);
    wgmma_wait<0>();
#pragma unroll
    for (int i = 0; i < 120; i++) asm volatile("" : "+f"(acc[i]) :: "memory");
    if (fol && lane == 0) mbar_arrive(bar_go);
    TS(2);
    uint32_t Qlo[10], Qhi[10], Klo[10], Khi[10], Vlo[10], Vhi[10];
#pragma unroll
    for (int t = 0; t < 10; t++) {
      const int k = KT(t), v = VT(t);
      Khi[t] = pack_bf16(acc[4 * k + 2], acc[4 * k + 3]);
      Vhi[t] = pack_bf16(acc[4 * v + 2] * rhi, acc[4 * v + 3] * rhi);
    }
    st_pkt(kvd, Khi[0], Khi[1], Khi[3], Khi[4]);
    st_pkt(kvd + 32, Khi[5], Khi[6], Khi[8], Khi[9]);
    st_pkt(kvd + 64, Khi[2], Khi[7], Vhi[0], Vhi[1]);
    st_pkt(kvd + 96, Vhi[2], Vhi[3], Vhi[4], Vhi[5]);
    st_pkt(kvd + 128, Vhi[6], Vhi[7], Vhi[8], Vhi[9]);
    if (warp < 7) mbar_arrive(bar_kv + ((warp + 1) >> 2) * 8);
    mbar_wait(bar_aux, 0);
#pragma unroll
    for (int t = 0; t < 10; t++) {
      const int q = QT(t), k = KT(t), v = VT(t);
      Vhi[t] = movm(Vhi[t]);
      Klo[t] = pack_bf16(acc[4 * k], acc[4 * k + 1]);
      Vlo[t] = movm(pack_bf16(acc[4 * v] * rlo, acc[4 * v + 1] * rlo));
      Qlo[t] = pack_bf16(acc[4 * q], acc[4 * q + 1]);
      Qhi[t] = pack_bf16(acc[4 * q + 2], acc[4 * q + 3]);
    }
    const bool in0 = 2 * c <= r, in1 = 2 * c + 1 <= r;
    const uint32_t mL = (in0 ? 0xffffu : 0u) | (in1 ? 0xffff0000u : 0u);
    const float qs = 0.22360679774997896f * 1.4426950408889634f;
    const uint32_t kb0 = stb + (2 * c + (in0 ? 8 : 0)) * 4, kb1 = stb + (2 * c + 1 + (in1 ? 8 : 0)) * 4;
    const float scl0 = lds32f(kb0) * rlo * qs, scl1 = lds32f(kb1) * rlo * qs;
    const float sch0 = lds32f(kb0 + 32) * rhi * qs, sch1 = lds32f(kb1 + 32) * rhi * qs;
    const float bias0 = (first && !in0) ? -INFINITY : 0.f, bias1 = (first && !in1) ? -INFINITY : 0.f;
    const int slot = mt * 8 + warp;
    int guard = SPIN_MAX;
    uint4 pv[5];
    const bool cA = c < 2, nA = r < 4;
    TS(0);
    mbar_wait(bar_kv + wg * 8, 0);
#pragma unroll
    for (int j = 0; j < 5; j++) pv[j] = lds128(kvs + 512 * j);
    TS(23);
    const uint32_t Kp[10] = {pv[0].x, pv[0].y, pv[2].x, pv[0].z, pv[0].w, pv[1].x, pv[1].y, pv[2].y, pv[1].z, pv[1].w};
    const uint32_t Vp[10] = {movm(pv[2].z), movm(pv[2].w), movm(pv[3].x), movm(pv[3].y), movm(pv[3].z), movm(pv[3].w), movm(pv[4].x), movm(pv[4].y), movm(pv[4].z), movm(pv[4].w)};
    mbar_wait(bar_go + fol * 8, 0);
    TS(4);
    const uint32_t ONES = 0x3f803f80u;
    uint32_t of[20];
#pragma unroll
    for (int hp = 0; hp < 2; hp++) {
      float o[6][4];
#pragma unroll
      for (int hh = 0; hh < 2; hh++) {
        const int ta = 5 * hp + 3 * hh, ts = 5 * hp + 2;
        const bool mine = hh == 0 ? cA : !cA;
        const uint32_t e0 = mine ? Qlo[ts] : 0u, e1 = mine ? Qhi[ts] : 0u;
        float sp[4], sl[4], sh[4];
        mma_k24(sp, Qlo[ta], Qhi[ta], Qlo[ta + 1], Qhi[ta + 1], Kp[ta], Kp[ta + 1], e0, e1, Kp[ts]);
        mma_k24(sl, Qlo[ta], Qhi[ta], Qlo[ta + 1], Qhi[ta + 1], Klo[ta], Klo[ta + 1], e0, e1, Klo[ts]);
        mma_k24(sh, Qlo[ta], Qhi[ta], Qlo[ta + 1], Qhi[ta + 1], Khi[ta], Khi[ta + 1], e0, e1, Khi[ts]);
        const float tl0 = fmaf(in0 ? sl[0] : sp[0], scl0, bias0), tl1 = fmaf(in1 ? sl[1] : sp[1], scl1, bias1);
        const float th0 = (in0 ? sh[2] : sl[2]) * sch0, th1 = (in1 ? sh[3] : sl[3]) * sch1;
        float ml = fmaxf(tl0, tl1), mh = fmaxf(th0, th1);
        ml = fmaxf(ml, shx(ml, 1)); mh = fmaxf(mh, shx(mh, 1));
        ml = fmaxf(ml, shx(ml, 2)); mh = fmaxf(mh, shx(mh, 2));
        if (HOLD == 1 && hp == 1 && hh == 1 && !fol && lane == 0) mbar_arrive(bar_go + 8);
        const uint32_t Pl = pack_bf16(ex2(tl0 - ml), ex2(tl1 - ml)), Ph = pack_bf16(ex2(th0 - mh), ex2(th1 - mh));
        const uint32_t a0 = Pl & mL, a1 = Ph & ~mL, a3 = Ph & mL, ap = Pl & ~mL;
        const bool vm = hh == 0 ? nA : !nA;
        mma_k24(o[3 * hh], a0, a1, 0u, a3, Vlo[ta], Vhi[ta], ap, 0u, Vp[ta]);
        mma_k24(o[3 * hh + 1], a0, a1, 0u, a3, Vlo[ta + 1], Vhi[ta + 1], ap, 0u, Vp[ta + 1]);
        mma_k24(o[3 * hh + 2], a0, a1, 0u, a3, vm ? Vlo[ts] : ONES, vm ? Vhi[ts] : ONES, ap, 0u, vm ? Vp[ts] : ONES);
      }
      const float il = rcp(cA ? o[5][0] : o[2][0]), ih = rcp(cA ? o[5][2] : o[2][2]);
      const float jl = shx(il, 2), jh = shx(ih, 2);
      const float al = cA ? jl : il, ah = cA ? jh : ih, bl = cA ? il : jl, bh = cA ? ih : jh;
      const int t0 = 5 * hp;
      of[2 * t0]     = pack_bf16(o[0][0] * al, o[0][1] * al); of[2 * t0 + 1] = pack_bf16(o[0][2] * ah, o[0][3] * ah);
      of[2 * t0 + 2] = pack_bf16(o[1][0] * al, o[1][1] * al); of[2 * t0 + 3] = pack_bf16(o[1][2] * ah, o[1][3] * ah);
      of[2 * t0 + 4] = pack_bf16((cA ? o[2][0] : o[5][0]) * jl, (cA ? o[2][1] : o[5][1]) * jl);
      of[2 * t0 + 5] = pack_bf16((cA ? o[2][2] : o[5][2]) * jh, (cA ? o[2][3] : o[5][3]) * jh);
      of[2 * t0 + 6] = pack_bf16(o[3][0] * bl, o[3][1] * bl); of[2 * t0 + 7] = pack_bf16(o[3][2] * bh, o[3][3] * bh);
      of[2 * t0 + 8] = pack_bf16(o[4][0] * bl, o[4][1] * bl); of[2 * t0 + 9] = pack_bf16(o[4][2] * bh, o[4][3] * bh);
    }
    {
      const uint32_t os = sb + OFF_O + (fol ? 0 : 20480) + w4 * 2560, oa = os + ((lane >> 3) & 1) * 1280 + (lane >> 4) * 128 + (lane & 7) * 16;
#pragma unroll
      for (int s = 0; s < 5; s++) {
        stsm4(oa + s * 256, of[4 * s], of[4 * s + 1], of[4 * s + 2], of[4 * s + 3]);
        if (s == 0 && (fol || HOLD == 2) && lane == 0) mbar_arrive(bar_go + 8 + 8 * fol);
      }
      asm volatile("fence.proxy.async.shared::cta;" ::: "memory");
      __syncwarp();
      if (elect()) {
        asm volatile("cp.async.bulk.global.shared::cta.bulk_group [%0], [%1], 2560;\ncp.async.bulk.commit_group;" :: "l"(odst), "r"(os) : "memory");
      }
    }
    TS(5);
    float h[40];
#pragma unroll
    for (int s = 0; s < 5; s++) {
      const uint4 v = xr[s];
      h[8 * s] = bf_lo(v.x); h[8 * s + 1] = bf_hi(v.x); h[8 * s + 2] = bf_lo(v.y); h[8 * s + 3] = bf_hi(v.y);
      h[8 * s + 4] = bf_lo(v.z); h[8 * s + 5] = bf_hi(v.z); h[8 * s + 6] = bf_lo(v.w); h[8 * s + 7] = bf_hi(v.w);
    }
    if (elect()) {
      asm volatile("cp.async.bulk.wait_group 0;" ::: "memory");
      asm volatile("red.relaxed.gpu.global.add.u32 [%0], 1;" :: "l"(ocnt) : "memory");
      mbar_arrive(bar_st + 8 * fol);
    }
    __syncwarp();
    mbar_wait(bar_full, 0); mbar_wait(bar_full + 8, 0); mbar_wait(bar_full + 16, 1);
    mbar_wait(bar_go + 16, 0);
    const uint64_t dwo = make_desc(D0 * 16, 5120, 512, 2);
    wgmma_fence();
#pragma unroll
    for (int s = 0; s < 5; s++) wgmma_n80_rs(h, of[4 * s], of[4 * s + 1], of[4 * s + 2], of[4 * s + 3], dwo + g * 960 + s * 64, 1);
    wgmma_commit();
    TS(6);
    const uint32_t bo = bar_o + fol * 56;
#pragma unroll
    for (int i = 0; i < 7; i++) {
      mbar_wait(bo + 8 * i, 0);
      if (i == 0) TS(1);
      const uint32_t da = D0 + OFF_O / 16 + (8 << 16) + ((i + 2) % 6) * 640 + fol * (i == 3 ? -3200 : 640), db = D0 + (320 << 16) + (i >= g ? i + 1 : i) * 960;
      wgmma_fence();
#pragma unroll
      for (int s = 0; s < 5; s++) wgmma_n80_ss(h, mk64(da + s * 16, 80u), mk64(db + s * 64, 0x80000020u), 1);
      wgmma_commit();
      wgmma_wait<1>();
      if (lane == 0 && i > 0) mbar_arrive(bo + 104 + 8 * i);
    }
    const bool odd = c & 1;
    float wr[20];
#pragma unroll
    for (int j = 0; j < 5; j++) {
      const uint4 v = lds128(sb + OFF_WR + c * 80 + j * 16);
      wr[4 * j] = __uint_as_float(v.x); wr[4 * j + 1] = __uint_as_float(v.y); wr[4 * j + 2] = __uint_as_float(v.z); wr[4 * j + 3] = __uint_as_float(v.w);
    }
    const float wsum = lds32f(sb + OFF_WR + 320);
    uint4* const sp = hold(&g_own[slot].st2[r + (odd ? 8 : 0)]);
    uint4* const cdp = hold(&g_x.cand[slot][g][0]);
    const int tok0 = P * 256 + 32 * warp + rank;
    wgmma_wait<0>();
#pragma unroll
    for (int i = 0; i < 40; i++) asm volatile("" : "+f"(h[i]) :: "memory");
    if (lane == 0) mbar_arrive(bo + 160);
    TS(7);
    float mean, rstd, rr;
    {
      float l1 = 0.f, l2 = 0.f, l3 = 0.f, h1 = 0.f, h2 = 0.f, h3 = 0.f;
#pragma unroll
      for (int j = 0; j < 10; j++) {
        l1 += h[4 * j] + h[4 * j + 1]; h1 += h[4 * j + 2] + h[4 * j + 3];
        l2 = fmaf(h[4 * j], h[4 * j], l2); l2 = fmaf(h[4 * j + 1], h[4 * j + 1], l2);
        h2 = fmaf(h[4 * j + 2], h[4 * j + 2], h2); h2 = fmaf(h[4 * j + 3], h[4 * j + 3], h2);
        l3 = fmaf(h[4 * j], wr[2 * j], l3); l3 = fmaf(h[4 * j + 1], wr[2 * j + 1], l3);
        h3 = fmaf(h[4 * j + 2], wr[2 * j], h3); h3 = fmaf(h[4 * j + 3], wr[2 * j + 1], h3);
      }
      float s1 = (odd ? h1 : l1) + shx(odd ? l1 : h1, 1), s2 = (odd ? h2 : l2) + shx(odd ? l2 : h2, 1), s3 = (odd ? h3 : l3) + shx(odd ? l3 : h3, 1);
      s1 += shx(s1, 2); s2 += shx(s2, 2); s3 += shx(s3, 2);
      if (cA) asm volatile("red.relaxed.gpu.global.add.v4.f32 [%0], {%1, %2, %3, %4};" :: "l"(sp), "f"(s1), "f"(s2), "f"(s3), "f"(1.f) : "memory");
      uint4 p0;
      do { p0 = ldg_pkt(sp); } while (anyw(p0.w != 0x41000000u) && --guard > 0);
      mean = __uint_as_float(p0.x) * (1.f / 640.f);
      rstd = rsq(fmaxf(fmaf(-mean, mean, __uint_as_float(p0.y) * (1.f / 640.f)), 0.f) + 1e-5f);
      rr = fmaf(-mean, wsum, __uint_as_float(p0.z)) * rstd;
    }
    TS(8);
    const uint32_t kk = ord_key(rr), kmax = __reduce_max_sync(0xffffffffu, kk);
    const int L = __ffs(__ballot_sync(0xffffffffu, kk == kmax)) - 1;
    const int crow = (L >> 2) + 8 * (L & 1);
    if (warp == g) {
      if (elect()) {
        asm volatile("red.relaxed.gpu.global.max.u64 [%0], %1;" :: "l"(g_own[1].cnt), "l"(((uint64_t)kmax << 32) | (uint32_t)(2047 - tok0 - 2 * crow)) : "memory");
        asm volatile("red.relaxed.gpu.global.add.u32 [%0], 1;" :: "l"(&g_own[1].cnt[0].z) : "memory");
      }
      asm volatile("bar.arrive 3, 64;" ::: "memory");
    }
    const uint32_t stg = sb + (fol ? OFF_O : g * 15360) + w4 * 2560;
    uint4 held;
    {
      const float om = shx(mean, 1), os = shx(rstd, 1);
      const float rl = odd ? os : rstd, rh = odd ? rstd : os;
      const float bl = -(odd ? om : mean) * rl, bh = -(odd ? mean : om) * rh, al = 1.f + rl, ah = 1.f + rh;
      if ((L >> 2) == r) {
        const bool chi = L & 1;
        const float rc = chi ? rh : rl, bc = chi ? bh : bl;
        uint32_t n[10];
#pragma unroll
        for (int j = 0; j < 10; j++) n[j] = pack_bf16(fmaf(chi ? h[4 * j + 2] : h[4 * j], rc, bc), fmaf(chi ? h[4 * j + 3] : h[4 * j + 1], rc, bc));
        uint4* d = cdp + c;
        stg_pkt(d, n[0], n[1], n[2], n[3]); stg_pkt(d + 4, n[4], n[5], n[6], n[7]); stg_rlx64(d + 8, n[8], n[9]);
      }
      mbar_wait(bar_oc + 56, 0);
      const uint32_t fa = stg + (lane & 15) * 160 + (lane >> 4) * 16;
#pragma unroll
      for (int s = 0; s < 5; s++)
        stsm4(fa + s * 32, pack_bf16(fmaf(h[8 * s], al, bl), fmaf(h[8 * s + 1], al, bl)), pack_bf16(fmaf(h[8 * s + 2], ah, bh), fmaf(h[8 * s + 3], ah, bh)),
              pack_bf16(fmaf(h[8 * s + 4], al, bl), fmaf(h[8 * s + 5], al, bl)), pack_bf16(fmaf(h[8 * s + 6], ah, bh), fmaf(h[8 * s + 7], ah, bh)));
      __syncwarp();
      held = lds128(stg + crow * 160 + min(lane, 9) * 16);
      if (lane < 10) stg_pkt(cdp + 12 + lane, held.x, held.y, held.z, held.w);
    }
    TS(9);
    mbar_wait(bar_ffn, 0);
    const uint32_t red = sb + OFF_RED;
    if (ffn1) {
      uint4 w1[4][5];
      {
        const int k = (lane & 7) + (lane >> 4) * 8;
        const uint32_t a1 = sb + k * 64, sw = ((lane >> 3) & 1) ^ ((lane >> 1) & 3);
#pragma unroll
        for (int s = 0; s < 5; s++)
#pragma unroll
          for (int u = 0; u < 4; u++)
            w1[u][s] = ldsm4t(a1 + (s < 4 ? warp * 4096 + s * 1024 : 32768 + warp * 1024) + (u >> 1) * (40960 + (s == 4 || warp >= 2 ? OFF_W2 - 49152 : 0)) + ((sw ^ (2 * (u & 1))) * 16));
      }
      uint32_t* const ap = hold(g_x.act + fj * 16 + (lane >> 1));
      mbar_wait(bar_win, 0);
      const uint32_t hp = sb + OFF_HN + (warp * 4 + c) * 16;
      const uint4 c0 = lds128(hp), c1 = lds128(hp + 512), c2 = lds128(hp + 1024);
      TS(10);
      float a[4][4];
#pragma unroll
      for (int u = 0; u < 4; u++) {
        a[u][0] = a[u][1] = a[u][2] = a[u][3] = 0.f;
        mma_acc(a[u], w1[u][0], c0.x, c0.y); mma_acc(a[u], w1[u][1], c0.z, c0.w); mma_acc(a[u], w1[u][2], c1.x, c1.y);
        mma_acc(a[u], w1[u][3], c1.z, c1.w); mma_acc(a[u], w1[u][4], c2.x, c2.y);
      }
      asm volatile("st.shared.v2.f32 [%0], {%1, %2};" :: "r"(red + (warp * 32 + c * 8 + r) * 8),
                   "f"(cA ? (odd ? a[0][2] : a[0][0]) : (odd ? a[1][2] : a[1][0])), "f"(cA ? (odd ? a[2][2] : a[2][0]) : (odd ? a[3][2] : a[3][0])) : "memory");
      bar_sync(1, 256);
      if (warp == 0) {
        float2 t[8];
#pragma unroll
        for (int i = 0; i < 8; i++) t[i] = lds64f(red + (i * 32 + lane) * 8);
        const float s = ((t[0].x + t[1].x) + (t[2].x + t[3].x)) + ((t[4].x + t[5].x) + (t[6].x + t[7].x));
        const float u = ((t[0].y + t[1].y) + (t[2].y + t[3].y)) + ((t[4].y + t[5].y) + (t[6].y + t[7].y));
        const float av = s * u * rcp(1.f + ex2(-1.4426950408889634f * s));
        const float an = shx(av, 1);
        if (!odd) stg_rlx32(ap, pack_bf16(av, an));
      }
      bar_sync(1, 256);
      TS(11);
    }
    if (OUT_LATE) mbar_wait(bar_win, 0);
    char* const ob2 = (char*)(out + tok0 * 640 + g * 64);
    const int remo = 896 - 96 * g;
#pragma unroll
    for (int s = 0; s < 5; s++) {
      const int row = s < 4 ? 4 * s + (lane >> 3) : lane >> 1, pc = s < 4 ? lane & 7 : 8 + (lane & 1);
      const uint4 v = lds128(stg + row * 160 + pc * 16);
      if (row != crow) stg128(ob2 + row * 2560 + pc * 16 + (s < 4 ? 0 : remo), v);
    }
    mbar_wait(bar_win, 0);
    const uint4 win = lds128(sb + OFF_WR + 336);
    if (win.x != slot && lane < 10) stg128(ob2 + crow * 2560 + lane * 16 + (lane < 8 ? 0 : remo), held);
    if (!ffn1) {
      TS(10);
      uint4 w2[6];
      const uint32_t a2 = sb + OFF_W2 + (warp * 192 + 8 * (((lane >> 3) & 1) * 4 + ((lane & 7) >> 1)) + 2 * (lane >> 4) + (lane & 1)) * 16;
#pragma unroll
      for (int s = 0; s < 6; s++) w2[s] = ldsm4t(a2 + (s >> 1) * 1024 + (s & 1) * 64);
      const uint4* p = (const uint4*)(g_x.act + warp * 96) + (r & 1) * 4 + c;
      const uint32_t* pb = (const uint32_t*)&g_x.cand[win.x][fj < 64 ? fj >> 3 : (fj - 64) >> 1][fj < 64 ? 12 + (fj & 7) : 20 + (fj & 1)] + c;
      uint32_t* const op = hold((uint32_t*)(out + win.y * 640 + fj * 8) + c);
      uint4 c0, c1, c2; uint32_t bw;
      if (ACT_NS) __nanosleep(ACT_NS);
      do {
        c0 = ldg_pkt(p); c1 = ldg_pkt(p + 8); c2 = ldg_pkt(p + 16); bw = ldg_rlx32(pb);
      } while (anyw(max(max(max(max(c0.x, c0.y), max(c0.z, c0.w)), max(max(c1.x, c1.y), max(c1.z, c1.w))), max(max(max(c2.x, c2.y), max(c2.z, c2.w)), bw)) == SENT) && --guard > 0);
      TS(11);
      float a[4] = {0.f, 0.f, 0.f, 0.f}, b[4] = {0.f, 0.f, 0.f, 0.f}, d[4] = {0.f, 0.f, 0.f, 0.f};
      mma_acc(a, w2[0], c0.x, c0.y); mma_acc(b, w2[2], c1.x, c1.y); mma_acc(d, w2[4], c2.x, c2.y);
      mma_acc(a, w2[1], c0.z, c0.w); mma_acc(b, w2[3], c1.z, c1.w); mma_acc(d, w2[5], c2.z, c2.w);
      if (c == 0) sts32f(red + (warp * 8 + r) * 4, ((a[0] + a[3]) + (b[0] + b[3])) + (d[0] + d[3]));
      bar_sync(1, 256);
      if (tid < 4) {
        float2 t[8];
#pragma unroll
        for (int i = 0; i < 8; i++) t[i] = lds64f(red + (i * 4 + tid) * 8);
        const float y0 = ((t[0].x + t[1].x) + (t[2].x + t[3].x)) + ((t[4].x + t[5].x) + (t[6].x + t[7].x));
        const float y1 = ((t[0].y + t[1].y) + (t[2].y + t[3].y)) + ((t[4].y + t[5].y) + (t[6].y + t[7].y));
        const float sg = __uint_as_float(win.z);
        *op = pack_bf16(fmaf(y0, sg, bf_lo(bw)), fmaf(y1, sg, bf_hi(bw)));
      }
    }
    TS(12);
#undef TS_T
  }
}

typedef CUresult (*EncodeFn)(CUtensorMap*, CUtensorMapDataType, cuuint32_t, void*, const cuuint64_t*, const cuuint64_t*, const cuuint32_t*,
                             const cuuint32_t*, CUtensorMapInterleave, CUtensorMapSwizzle, CUtensorMapL2promotion, CUtensorMapFloatOOBfill);

void make_map(EncodeFn enc, CUtensorMap* m, const void* base, const cuuint64_t* dims, const cuuint64_t* strides, const cuuint32_t* box,
              CUtensorMapSwizzle swz) {
  const cuuint32_t es[3] = {1, 1, 1};
  enc(m, CU_TENSOR_MAP_DATA_TYPE_BFLOAT16, 3, (void*)base, dims, strides, box, es, CU_TENSOR_MAP_INTERLEAVE_NONE, swz,
      CU_TENSOR_MAP_L2_PROMOTION_L2_128B, CU_TENSOR_MAP_FLOAT_OOB_FILL_NONE);
}

}

extern "C" void kernel_launch(void* const* d_in, const int* in_sizes, int n_in, void* d_out, int out_size) {
  const __nv_bfloat16* x = (const __nv_bfloat16*)d_in[0];
  const __nv_bfloat16* wqkv = (const __nv_bfloat16*)d_in[1];
  const __nv_bfloat16* wo = (const __nv_bfloat16*)d_in[2];
  void* fn = nullptr;
  cudaDriverEntryPointQueryResult st;
  cudaGetDriverEntryPoint("cuTensorMapEncodeTiled", &fn, cudaEnableDefault, &st);
  EncodeFn enc = (EncodeFn)fn;
  void* scp = nullptr;
  cudaGetSymbolAddress(&scp, g_scratch);
  Maps tm;
  { const cuuint64_t d[3] = {640, 1024, 2}, s[2] = {2560, 1280}; const cuuint32_t b[3] = {64, 128, 1}; make_map(enc, &tm.x, x, d, s, b, CU_TENSOR_MAP_SWIZZLE_128B); }
  { const cuuint64_t d[3] = {640, 640, 3}, s[2] = {3840, 1280}; const cuuint32_t b[3] = {64, 64, 1}; make_map(enc, &tm.w, wqkv, d, s, b, CU_TENSOR_MAP_SWIZZLE_128B); }
  { const cuuint64_t d[3] = {640, 640, 3}, s[2] = {3840, 1280}; const cuuint32_t b[3] = {16, 64, 3}; make_map(enc, &tm.wr, wqkv, d, s, b, CU_TENSOR_MAP_SWIZZLE_32B); }
  { const cuuint64_t d[3] = {32, 640, 20}, s[2] = {1280, 64}; const cuuint32_t b[3] = {32, 80, 2}; make_map(enc, &tm.wo, wo, d, s, b, CU_TENSOR_MAP_SWIZZLE_64B); }
  { const cuuint64_t d[3] = {640, 640, 1}, s[2] = {1280, 819200}; const cuuint32_t b[3] = {16, 80, 1}; make_map(enc, &tm.wor, wo, d, s, b, CU_TENSOR_MAP_SWIZZLE_64B); }
  { const cuuint64_t d[3] = {1536, 640, 1}, s[2] = {3072, 1966080}; const cuuint32_t b[3] = {32, 128, 1};
    make_map(enc, &tm.gate, d_in[5], d, s, b, CU_TENSOR_MAP_SWIZZLE_64B); make_map(enc, &tm.up, d_in[6], d, s, b, CU_TENSOR_MAP_SWIZZLE_64B); }
  { const cuuint64_t d[3] = {640, 1536, 1}, s[2] = {1280, 1966080}; const cuuint32_t b[3] = {8, 128, 1}; make_map(enc, &tm.down, d_in[7], d, s, b, CU_TENSOR_MAP_SWIZZLE_NONE); }
  cudaFuncSetAttribute(fused_kernel, cudaFuncAttributeMaxDynamicSharedMemorySize, SMEM_BYTES);
  fused_kernel<<<128, 512, SMEM_BYTES, cudaStreamPerThread>>>(x, wqkv, wo, (const __nv_bfloat16*)d_in[4], (const __nv_bfloat16*)d_in[5],
                                                              (const __nv_bfloat16*)d_in[6], (const __nv_bfloat16*)d_in[7], (__nv_bfloat16*)d_out, (Scratch*)scp, tm);
}
```

```cpp
#include <cuda_runtime.h>
#include <cuda_bf16.h>
#include <cuda.h>
#include <stdint.h>

#define PFW_NS 100
#define ACT_NS 0
#define OUT_LATE 0
#define REG_P 72
#define REG_C 184
#define AUX_NS 50
#define LEAD 1
#define RST_IT 4
#define ORDX 1
#define THR 2
#define PF_FIRST 3
#define PF_T0 2000
#define PF_CLK 500
#define HK_IT 1
#define F_IT 9
#define F_PER 2
#define F_MAX 8
#define HOLD 2
#define F_LATE 12
#define HALO_NS 0
#define AK 3

namespace {

constexpr int SLOT    = 47104;
constexpr int OFF_O   = 122880;
constexpr int OFF_W2  = 4 * SLOT;
constexpr int OFF_CS  = OFF_W2 + 32768;
constexpr int OFF_RS  = OFF_CS + 3840;
constexpr int OFF_MN  = OFF_RS + 576;
constexpr int OFF_WR  = OFF_MN + 1024;
constexpr int OFF_RED = OFF_CS;
constexpr int OFF_HN  = OFF_CS + 2048;
constexpr int OFF_PT  = OFF_WR + 352;
constexpr int OFF_BAR = OFF_PT + 768;
constexpr int SMEM_BYTES = OFF_BAR + 384 + 384;
constexpr uint32_t D0 = 1024 >> 4;
constexpr uint32_t SENT = 0xFFFFFFFFu;
constexpr int SPIN_MAX = 1 << 20;

struct Glob {
  uint4 cand[128][8][24];
  uint32_t act[768];
  uint32_t pad[256];
};
constexpr int GLOB_PER_CTA = sizeof(Glob) / 16 / 128;
static_assert(GLOB_PER_CTA * 128 * 16 == sizeof(Glob), "glob size");
struct Own {
  uint4 halo[5][32];
  uint4 st1[32];
  uint2 cs[32];
  uint4 st2[16];
  uint4 cnt[8];
};
struct Scratch {
  Glob x;
  Own own[128];
  uint4 o[32][8][640];
  uint32_t epoch[128];
};
__device__ __align__(128) Scratch g_scratch;
#define g_x (sc->x)
#define g_own (sc->own)
#define g_o (sc->o)
#define g_epoch (sc->epoch)
#define TS(i)

__device__ __forceinline__ void mbar_init(uint32_t bar, uint32_t cnt) { asm volatile("mbarrier.init.shared::cta.b64 [%0], %1;" :: "r"(bar), "r"(cnt) : "memory"); }
__device__ __forceinline__ void mbar_expect_tx(uint32_t bar, uint32_t bytes) { asm volatile("mbarrier.arrive.expect_tx.shared::cta.b64 _, [%0], %1;" :: "r"(bar), "r"(bytes) : "memory"); }
__device__ __forceinline__ void mbar_arrive(uint32_t bar) { asm volatile("mbarrier.arrive.shared::cta.b64 _, [%0];" :: "r"(bar) : "memory"); }
__device__ __forceinline__ void mbar_arrive_cta(uint32_t bar, uint32_t cta) {
  asm volatile("{\n.reg .b32 ra;\nmapa.shared::cluster.u32 ra, %0, %1;\nmbarrier.arrive.shared::cluster.b64 _, [ra];\n}\n" :: "r"(bar), "r"(cta) : "memory");
}
__device__ __forceinline__ void mbar_wait(uint32_t bar, uint32_t parity) {
  asm volatile("{\n.reg .pred p;\n.reg .u32 n;\nmov.u32 n, 0;\nW:\nmbarrier.try_wait.parity.shared::cta.b64 p, [%0], %1;\n@p bra.uni D;\n"
               "add.u32 n, n, 1;\nsetp.lt.u32 p, n, %2;\n@p bra.uni W;\nD:\n}\n" :: "r"(bar), "r"(parity), "n"(SPIN_MAX) : "memory");
}
__device__ __forceinline__ void tma_3d(uint32_t dst, const void* tm, uint32_t bar, int c0, int c1, int c2) {
  asm volatile("cp.async.bulk.tensor.3d.shared::cluster.global.mbarrier::complete_tx::bytes [%0], [%1, {%3, %4, %5}], [%2];" :: "r"(dst), "l"(tm), "r"(bar), "r"(c0), "r"(c1), "r"(c2) : "memory");
}
__device__ __forceinline__ void tma_3d_mc(uint32_t dst, const void* tm, uint32_t bar, int c0, int c1, int c2) {
  asm volatile("cp.async.bulk.tensor.3d.shared::cluster.global.mbarrier::complete_tx::bytes.multicast::cluster [%0], [%1, {%3, %4, %5}], [%2], %6;" :: "r"(dst), "l"(tm), "r"(bar), "r"(c0), "r"(c1), "r"(c2), "h"((uint16_t)3) : "memory");
}
__device__ __forceinline__ void wgmma_fence() { asm volatile("wgmma.fence.sync.aligned;" ::: "memory"); }
__device__ __forceinline__ void wgmma_commit() { asm volatile("wgmma.commit_group.sync.aligned;" ::: "memory"); }
template <int N> __device__ __forceinline__ void wgmma_wait() { asm volatile("wgmma.wait_group.sync.aligned %0;" :: "n"(N) : "memory"); }
__device__ __forceinline__ uint64_t make_desc(uint32_t addr, uint32_t lbo, uint32_t sbo, uint32_t swz) {
  return (uint64_t)(((addr & 0x3FFFF) >> 4) | ((lbo >> 4) << 16)) | ((uint64_t)((sbo >> 4) | (swz << 30)) << 32);
}
__device__ __forceinline__ void bar_sync(int id, int n) { asm volatile("bar.sync %0, %1;" :: "r"(id), "r"(n) : "memory"); }
__device__ __forceinline__ void st_pkt(void* p, uint32_t a, uint32_t b, uint32_t c, uint32_t d) {
  asm volatile("st.relaxed.gpu.v4.u32 [%0], {%1, %2, %3, %4};" :: "l"(p), "r"(a), "r"(b), "r"(c), "r"(d) : "memory");
}
__device__ __forceinline__ uint4 ldg_pkt(const void* p) {
  uint4 v; asm volatile("ld.relaxed.gpu.global.v4.u32 {%0, %1, %2, %3}, [%4];" : "=r"(v.x), "=r"(v.y), "=r"(v.z), "=r"(v.w) : "l"(p) : "memory"); return v;
}
__device__ __forceinline__ void stg_pkt(void* p, uint32_t a, uint32_t b, uint32_t c, uint32_t d) {
  asm volatile("st.relaxed.gpu.global.v4.u32 [%0], {%1, %2, %3, %4};" :: "l"(p), "r"(a), "r"(b), "r"(c), "r"(d) : "memory");
}
__device__ __forceinline__ uint32_t ldg_rlx32(const void* p) { uint32_t v; asm volatile("ld.relaxed.gpu.global.u32 %0, [%1];" : "=r"(v) : "l"(p) : "memory"); return v; }
__device__ __forceinline__ uint2 ldg_rlx64(const void* p) { uint2 v; asm volatile("ld.relaxed.gpu.global.v2.u32 {%0, %1}, [%2];" : "=r"(v.x), "=r"(v.y) : "l"(p) : "memory"); return v; }
__device__ __forceinline__ void stg128(void* p, const uint4& v) { asm volatile("st.global.v4.u32 [%0], {%1, %2, %3, %4};" :: "l"(p), "r"(v.x), "r"(v.y), "r"(v.z), "r"(v.w) : "memory"); }
__device__ __forceinline__ uint32_t pin(uint32_t v) { asm volatile("" : "+r"(v)); return v; }
__device__ __forceinline__ uint64_t mk64(uint32_t lo, uint32_t hi) { return ((uint64_t)hi << 32) | lo; }
template <class T> __device__ __forceinline__ T* hold(T* p) { return (T*)__shfl_sync(0xffffffffu, (unsigned long long)p, threadIdx.x & 31); }
template <class T> __device__ __forceinline__ T* pin(T* p) { asm volatile("" : "+l"(p)); return p; }
__device__ __forceinline__ void stg_rlx32(void* p, uint32_t v) { asm volatile("st.relaxed.gpu.global.u32 [%0], %1;" :: "l"(p), "r"(v) : "memory"); }
__device__ __forceinline__ void stg_rlx64(void* p, uint32_t a, uint32_t b) { asm volatile("st.relaxed.gpu.global.v2.u32 [%0], {%1, %2};" :: "l"(p), "r"(a), "r"(b) : "memory"); }
__device__ __forceinline__ uint4 ldsm4(uint32_t a) { uint4 v; asm volatile("ldmatrix.sync.aligned.m8n8.x4.shared.b16 {%0, %1, %2, %3}, [%4];" : "=r"(v.x), "=r"(v.y), "=r"(v.z), "=r"(v.w) : "r"(a) : "memory"); return v; }
__device__ __forceinline__ void ldsm4_if(uint4& v, uint32_t a, int off, bool p) {
  asm volatile("{\n.reg .pred q;\nsetp.ne.u32 q, %5, 0;\n@q ldmatrix.sync.aligned.m8n8.x4.shared.b16 {%0, %1, %2, %3}, [%4];\n}\n"
               : "+r"(v.x), "+r"(v.y), "+r"(v.z), "+r"(v.w) : "r"(a + off), "r"((int)p) : "memory");
}
__device__ __forceinline__ uint4 ldsm4t(uint32_t a) { uint4 v; asm volatile("ldmatrix.sync.aligned.m8n8.x4.trans.shared.b16 {%0, %1, %2, %3}, [%4];" : "=r"(v.x), "=r"(v.y), "=r"(v.z), "=r"(v.w) : "r"(a) : "memory"); return v; }
__device__ __forceinline__ void stsm4(uint32_t a, uint32_t x, uint32_t y, uint32_t z, uint32_t w) { asm volatile("stmatrix.sync.aligned.m8n8.x4.shared.b16 [%0], {%1, %2, %3, %4};" :: "r"(a), "r"(x), "r"(y), "r"(z), "r"(w) : "memory"); }
__device__ __forceinline__ void mma_acc(float (&c)[4], const uint4& a, uint32_t b0, uint32_t b1) {
  asm("mma.sync.aligned.m16n8k16.row.col.f32.bf16.bf16.f32 {%0,%1,%2,%3}, {%4,%5,%6,%7}, {%8,%9}, {%0,%1,%2,%3};"
      : "+f"(c[0]), "+f"(c[1]), "+f"(c[2]), "+f"(c[3]) : "r"(a.x), "r"(a.y), "r"(a.z), "r"(a.w), "r"(b0), "r"(b1));
}
__device__ __forceinline__ uint4 lds128(uint32_t a) { uint4 v; asm volatile("ld.shared.v4.u32 {%0, %1, %2, %3}, [%4];" : "=r"(v.x), "=r"(v.y), "=r"(v.z), "=r"(v.w) : "r"(a) : "memory"); return v; }
__device__ __forceinline__ float2 lds64f(uint32_t a) { float2 v; asm volatile("ld.shared.v2.f32 {%0, %1}, [%2];" : "=f"(v.x), "=f"(v.y) : "r"(a)); return v; }
__device__ __forceinline__ float lds32f(uint32_t a) { float v; asm volatile("ld.shared.f32 %0, [%1];" : "=f"(v) : "r"(a)); return v; }
__device__ __forceinline__ void sts32f(uint32_t a, float v) { asm volatile("st.shared.f32 [%0], %1;" :: "r"(a), "f"(v) : "memory"); }
__device__ __forceinline__ uint32_t pack_bf16(float lo, float hi) { uint32_t r; asm("cvt.rn.bf16x2.f32 %0, %1, %2;" : "=r"(r) : "f"(hi), "f"(lo)); return r; }
__device__ __forceinline__ float bf_lo(uint32_t v) { return __uint_as_float(v << 16); }
__device__ __forceinline__ float bf_hi(uint32_t v) { return __uint_as_float(v & 0xffff0000u); }
__device__ __forceinline__ uint32_t movm(uint32_t a) { uint32_t d; asm("movmatrix.sync.aligned.m8n8.trans.b16 %0, %1;" : "=r"(d) : "r"(a)); return d; }
__device__ __forceinline__ float ex2(float x) { float y; asm("ex2.approx.ftz.f32 %0, %1;" : "=f"(y) : "f"(x)); return y; }
__device__ __forceinline__ float rsq(float x) { float y; asm("rsqrt.approx.ftz.f32 %0, %1;" : "=f"(y) : "f"(x)); return y; }
__device__ __forceinline__ float rcp(float x) { float y; asm("rcp.approx.ftz.f32 %0, %1;" : "=f"(y) : "f"(x)); return y; }
__device__ __forceinline__ bool elect() { uint32_t p; asm volatile("{\n.reg .pred q;\nelect.sync _|q, 0xffffffff;\nselp.u32 %0, 1, 0, q;\n}\n" : "=r"(p)); return p; }
__device__ __forceinline__ int clk() { int c; asm volatile("mov.u32 %0, %%clock;" : "=r"(c) :: "memory"); return c; }
__device__ __forceinline__ void pf_l2(const void* p) { asm volatile("prefetch.global.L2 [%0];" :: "l"(p)); }
__device__ __forceinline__ bool anyw(bool p) { return __any_sync(0xffffffffu, p); }
__device__ __forceinline__ float shx(float v, int m) { return __shfl_xor_sync(0xffffffffu, v, m); }
__device__ __forceinline__ void mma_k24(float (&c)[4], uint32_t a0, uint32_t a1, uint32_t a2, uint32_t a3, uint32_t b0, uint32_t b1,
                                        uint32_t e0, uint32_t e1, uint32_t f0) {
  asm("mma.sync.aligned.m16n8k16.row.col.f32.bf16.bf16.f32 {%0,%1,%2,%3}, {%4,%5,%6,%7}, {%8,%9}, {%10,%10,%10,%10};"
      : "=f"(c[0]), "=f"(c[1]), "=f"(c[2]), "=f"(c[3]) : "r"(a0), "r"(a1), "r"(a2), "r"(a3), "r"(b0), "r"(b1), "f"(0.f));
  asm("mma.sync.aligned.m16n8k8.row.col.f32.bf16.bf16.f32 {%0,%1,%2,%3}, {%4,%5}, {%6}, {%0,%1,%2,%3};"
      : "+f"(c[0]), "+f"(c[1]), "+f"(c[2]), "+f"(c[3]) : "r"(e0), "r"(e1), "r"(f0));
}
__device__ __forceinline__ uint32_t ord_key(float r) { uint32_t u = __float_as_uint(r); return u ^ ((uint32_t)((int32_t)u >> 31) | 0x80000000u); }

__device__ __forceinline__ void wgmma_n48hi_ss(float (&d)[120], uint64_t da, uint64_t db, int scale_d) {
  asm volatile("{\n.reg .pred p;\nsetp.ne.b32 p, %26, 0;\n"
    "wgmma.mma_async.sync.aligned.m64n48k16.f32.bf16.bf16 "
    "{%0, %1, %2, %3, %4, %5, %6, %7, %8, %9, %10, %11, %12, %13, %14, %15, "
    "%16, %17, %18, %19, %20, %21, %22, %23}, "
    "%24, %25, p, 1, 1, 0, 1;\n}\n"
    : "+f"(d[96]), "+f"(d[97]), "+f"(d[98]), "+f"(d[99]), "+f"(d[100]), "+f"(d[101]), "+f"(d[102]), "+f"(d[103]),
      "+f"(d[104]), "+f"(d[105]), "+f"(d[106]), "+f"(d[107]), "+f"(d[108]), "+f"(d[109]), "+f"(d[110]), "+f"(d[111]),
      "+f"(d[112]), "+f"(d[113]), "+f"(d[114]), "+f"(d[115]), "+f"(d[116]), "+f"(d[117]), "+f"(d[118]), "+f"(d[119])
    : "l"(da), "l"(db), "r"(scale_d));
}
__device__ __forceinline__ void wgmma_n192lo_ss(float (&d)[120], uint64_t da, uint64_t db, int scale_d) {
  asm volatile("{\n.reg .pred p;\nsetp.ne.b32 p, %98, 0;\n"
    "wgmma.mma_async.sync.aligned.m64n192k16.f32.bf16.bf16 "
    "{%0, %1, %2, %3, %4, %5, %6, %7, %8, %9, %10, %11, %12, %13, %14, %15, "
    "%16, %17, %18, %19, %20, %21, %22, %23, %24, %25, %26, %27, %28, %29, %30, %31, "
    "%32, %33, %34, %35, %36, %37, %38, %39, %40, %41, %42, %43, %44, %45, %46, %47, "
    "%48, %49, %50, %51, %52, %53, %54, %55, %56, %57, %58, %59, %60, %61, %62, %63, "
    "%64, %65, %66, %67, %68, %69, %70, %71, %72, %73, %74, %75, %76, %77, %78, %79, "
    "%80, %81, %82, %83, %84, %85, %86, %87, %88, %89, %90, %91, %92, %93, %94, %95}, "
    "%96, %97, p, 1, 1, 0, 1;\n}\n"
    : "+f"(d[0]), "+f"(d[1]), "+f"(d[2]), "+f"(d[3]), "+f"(d[4]), "+f"(d[5]), "+f"(d[6]), "+f"(d[7]),
      "+f"(d[8]), "+f"(d[9]), "+f"(d[10]), "+f"(d[11]), "+f"(d[12]), "+f"(d[13]), "+f"(d[14]), "+f"(d[15]),
      "+f"(d[16]), "+f"(d[17]), "+f"(d[18]), "+f"(d[19]), "+f"(d[20]), "+f"(d[21]), "+f"(d[22]), "+f"(d[23]),
      "+f"(d[24]), "+f"(d[25]), "+f"(d[26]), "+f"(d[27]), "+f"(d[28]), "+f"(d[29]), "+f"(d[30]), "+f"(d[31]),
      "+f"(d[32]), "+f"(d[33]), "+f"(d[34]), "+f"(d[35]), "+f"(d[36]), "+f"(d[37]), "+f"(d[38]), "+f"(d[39]),
      "+f"(d[40]), "+f"(d[41]), "+f"(d[42]), "+f"(d[43]), "+f"(d[44]), "+f"(d[45]), "+f"(d[46]), "+f"(d[47]),
      "+f"(d[48]), "+f"(d[49]), "+f"(d[50]), "+f"(d[51]), "+f"(d[52]), "+f"(d[53]), "+f"(d[54]), "+f"(d[55]),
      "+f"(d[56]), "+f"(d[57]), "+f"(d[58]), "+f"(d[59]), "+f"(d[60]), "+f"(d[61]), "+f"(d[62]), "+f"(d[63]),
      "+f"(d[64]), "+f"(d[65]), "+f"(d[66]), "+f"(d[67]), "+f"(d[68]), "+f"(d[69]), "+f"(d[70]), "+f"(d[71]),
      "+f"(d[72]), "+f"(d[73]), "+f"(d[74]), "+f"(d[75]), "+f"(d[76]), "+f"(d[77]), "+f"(d[78]), "+f"(d[79]),
      "+f"(d[80]), "+f"(d[81]), "+f"(d[82]), "+f"(d[83]), "+f"(d[84]), "+f"(d[85]), "+f"(d[86]), "+f"(d[87]),
      "+f"(d[88]), "+f"(d[89]), "+f"(d[90]), "+f"(d[91]), "+f"(d[92]), "+f"(d[93]), "+f"(d[94]), "+f"(d[95])
    : "l"(da), "l"(db), "r"(scale_d));
}
__device__ __forceinline__ void wgmma_n48hi_rk(float (&d)[120], uint32_t a0, uint32_t a1, uint32_t a2, uint32_t a3, uint64_t db, int scale_d) {
  asm volatile("{\n.reg .pred p;\nsetp.ne.b32 p, %29, 0;\n"
    "wgmma.mma_async.sync.aligned.m64n48k16.f32.bf16.bf16 "
    "{%0, %1, %2, %3, %4, %5, %6, %7, %8, %9, %10, %11, %12, %13, %14, %15, "
    "%16, %17, %18, %19, %20, %21, %22, %23}, "
    "{%24, %25, %26, %27}, %28, p, 1, 1, 0;\n}\n"
    : "+f"(d[96]), "+f"(d[97]), "+f"(d[98]), "+f"(d[99]), "+f"(d[100]), "+f"(d[101]), "+f"(d[102]), "+f"(d[103]),
      "+f"(d[104]), "+f"(d[105]), "+f"(d[106]), "+f"(d[107]), "+f"(d[108]), "+f"(d[109]), "+f"(d[110]), "+f"(d[111]),
      "+f"(d[112]), "+f"(d[113]), "+f"(d[114]), "+f"(d[115]), "+f"(d[116]), "+f"(d[117]), "+f"(d[118]), "+f"(d[119])
    : "r"(a0), "r"(a1), "r"(a2), "r"(a3), "l"(db), "r"(scale_d));
}
__device__ __forceinline__ void wgmma_n192lo_rk(float (&d)[120], uint32_t a0, uint32_t a1, uint32_t a2, uint32_t a3, uint64_t db, int scale_d) {
  asm volatile("{\n.reg .pred p;\nsetp.ne.b32 p, %101, 0;\n"
    "wgmma.mma_async.sync.aligned.m64n192k16.f32.bf16.bf16 "
    "{%0, %1, %2, %3, %4, %5, %6, %7, %8, %9, %10, %11, %12, %13, %14, %15, "
    "%16, %17, %18, %19, %20, %21, %22, %23, %24, %25, %26, %27, %28, %29, %30, %31, "
    "%32, %33, %34, %35, %36, %37, %38, %39, %40, %41, %42, %43, %44, %45, %46, %47, "
    "%48, %49, %50, %51, %52, %53, %54, %55, %56, %57, %58, %59, %60, %61, %62, %63, "
    "%64, %65, %66, %67, %68, %69, %70, %71, %72, %73, %74, %75, %76, %77, %78, %79, "
    "%80, %81, %82, %83, %84, %85, %86, %87, %88, %89, %90, %91, %92, %93, %94, %95}, "
    "{%96, %97, %98, %99}, %100, p, 1, 1, 0;\n}\n"
    : "+f"(d[0]), "+f"(d[1]), "+f"(d[2]), "+f"(d[3]), "+f"(d[4]), "+f"(d[5]), "+f"(d[6]), "+f"(d[7]),
      "+f"(d[8]), "+f"(d[9]), "+f"(d[10]), "+f"(d[11]), "+f"(d[12]), "+f"(d[13]), "+f"(d[14]), "+f"(d[15]),
      "+f"(d[16]), "+f"(d[17]), "+f"(d[18]), "+f"(d[19]), "+f"(d[20]), "+f"(d[21]), "+f"(d[22]), "+f"(d[23]),
      "+f"(d[24]), "+f"(d[25]), "+f"(d[26]), "+f"(d[27]), "+f"(d[28]), "+f"(d[29]), "+f"(d[30]), "+f"(d[31]),
      "+f"(d[32]), "+f"(d[33]), "+f"(d[34]), "+f"(d[35]), "+f"(d[36]), "+f"(d[37]), "+f"(d[38]), "+f"(d[39]),
      "+f"(d[40]), "+f"(d[41]), "+f"(d[42]), "+f"(d[43]), "+f"(d[44]), "+f"(d[45]), "+f"(d[46]), "+f"(d[47]),
      "+f"(d[48]), "+f"(d[49]), "+f"(d[50]), "+f"(d[51]), "+f"(d[52]), "+f"(d[53]), "+f"(d[54]), "+f"(d[55]),
      "+f"(d[56]), "+f"(d[57]), "+f"(d[58]), "+f"(d[59]), "+f"(d[60]), "+f"(d[61]), "+f"(d[62]), "+f"(d[63]),
      "+f"(d[64]), "+f"(d[65]), "+f"(d[66]), "+f"(d[67]), "+f"(d[68]), "+f"(d[69]), "+f"(d[70]), "+f"(d[71]),
      "+f"(d[72]), "+f"(d[73]), "+f"(d[74]), "+f"(d[75]), "+f"(d[76]), "+f"(d[77]), "+f"(d[78]), "+f"(d[79]),
      "+f"(d[80]), "+f"(d[81]), "+f"(d[82]), "+f"(d[83]), "+f"(d[84]), "+f"(d[85]), "+f"(d[86]), "+f"(d[87]),
      "+f"(d[88]), "+f"(d[89]), "+f"(d[90]), "+f"(d[91]), "+f"(d[92]), "+f"(d[93]), "+f"(d[94]), "+f"(d[95])
    : "r"(a0), "r"(a1), "r"(a2), "r"(a3), "l"(db), "r"(scale_d));
}
__device__ __forceinline__ void wgmma_n80_rs(float (&d)[40], uint32_t a0, uint32_t a1, uint32_t a2, uint32_t a3, uint64_t db, int scale_d) {
  asm volatile("{\n.reg .pred p;\nsetp.ne.b32 p, %45, 0;\n"
    "wgmma.mma_async.sync.aligned.m64n80k16.f32.bf16.bf16 "
    "{%0, %1, %2, %3, %4, %5, %6, %7, %8, %9, %10, %11, %12, %13, %14, %15, "
    "%16, %17, %18, %19, %20, %21, %22, %23, %24, %25, %26, %27, %28, %29, %30, %31, "
    "%32, %33, %34, %35, %36, %37, %38, %39}, "
    "{%40, %41, %42, %43}, %44, p, 1, 1, 1;\n}\n"
    : "+f"(d[0]), "+f"(d[1]), "+f"(d[2]), "+f"(d[3]), "+f"(d[4]), "+f"(d[5]), "+f"(d[6]), "+f"(d[7]),
      "+f"(d[8]), "+f"(d[9]), "+f"(d[10]), "+f"(d[11]), "+f"(d[12]), "+f"(d[13]), "+f"(d[14]), "+f"(d[15]),
      "+f"(d[16]), "+f"(d[17]), "+f"(d[18]), "+f"(d[19]), "+f"(d[20]), "+f"(d[21]), "+f"(d[22]), "+f"(d[23]),
      "+f"(d[24]), "+f"(d[25]), "+f"(d[26]), "+f"(d[27]), "+f"(d[28]), "+f"(d[29]), "+f"(d[30]), "+f"(d[31]),
      "+f"(d[32]), "+f"(d[33]), "+f"(d[34]), "+f"(d[35]), "+f"(d[36]), "+f"(d[37]), "+f"(d[38]), "+f"(d[39])
    : "r"(a0), "r"(a1), "r"(a2), "r"(a3), "l"(db), "r"(scale_d));
}
__device__ __forceinline__ void wgmma_n80_ss(float (&d)[40], uint64_t da, uint64_t db, int scale_d) {
  asm volatile("{\n.reg .pred p;\nsetp.ne.b32 p, %42, 0;\n"
    "wgmma.mma_async.sync.aligned.m64n80k16.f32.bf16.bf16 "
    "{%0, %1, %2, %3, %4, %5, %6, %7, %8, %9, %10, %11, %12, %13, %14, %15, "
    "%16, %17, %18, %19, %20, %21, %22, %23, %24, %25, %26, %27, %28, %29, %30, %31, "
    "%32, %33, %34, %35, %36, %37, %38, %39}, "
    "%40, %41, p, 1, 1, 0, 1;\n}\n"
    : "+f"(d[0]), "+f"(d[1]), "+f"(d[2]), "+f"(d[3]), "+f"(d[4]), "+f"(d[5]), "+f"(d[6]), "+f"(d[7]),
      "+f"(d[8]), "+f"(d[9]), "+f"(d[10]), "+f"(d[11]), "+f"(d[12]), "+f"(d[13]), "+f"(d[14]), "+f"(d[15]),
      "+f"(d[16]), "+f"(d[17]), "+f"(d[18]), "+f"(d[19]), "+f"(d[20]), "+f"(d[21]), "+f"(d[22]), "+f"(d[23]),
      "+f"(d[24]), "+f"(d[25]), "+f"(d[26]), "+f"(d[27]), "+f"(d[28]), "+f"(d[29]), "+f"(d[30]), "+f"(d[31]),
      "+f"(d[32]), "+f"(d[33]), "+f"(d[34]), "+f"(d[35]), "+f"(d[36]), "+f"(d[37]), "+f"(d[38]), "+f"(d[39])
    : "l"(da), "l"(db), "r"(scale_d));
}

__device__ __forceinline__ constexpr int QT(int t) { return t < 8 ? t : 16 + t; }
__device__ __forceinline__ constexpr int KT(int t) { return t < 8 ? 8 + t : 18 + t; }
__device__ __forceinline__ constexpr int VT(int t) { return t < 8 ? 16 + t : 20 + t; }

struct Maps { CUtensorMap x, w, wr, wo, wor, gate, up, down; };

__global__ void __cluster_dims__(2, 1, 1) __launch_bounds__(512, 1)
fused_kernel(const __nv_bfloat16* __restrict__ x, const __nv_bfloat16* __restrict__ wqkv,
             const __nv_bfloat16* __restrict__ wo, const __nv_bfloat16* __restrict__ w_r, const __nv_bfloat16* __restrict__ w_gate,
             const __nv_bfloat16* __restrict__ w_up, const __nv_bfloat16* __restrict__ w_down, __nv_bfloat16* __restrict__ out,
             Scratch* __restrict__ sc, const __grid_constant__ Maps tm) {
  extern __shared__ __align__(1024) uint8_t smem[];
  const int tid = threadIdx.x, warp = __shfl_sync(0xffffffffu, tid >> 5, 0), lane = tid & 31, bid = blockIdx.x;
  const uint32_t sb = (uint32_t)__cvta_generic_to_shared(smem);
  const uint32_t bar_full = sb + OFF_BAR, bar_empty = bar_full + 32, bar_aux = bar_full + 64, bar_ffn = bar_full + 72, bar_win = bar_full + 80, bar_rst = bar_full + 88,
                 bar_o = bar_full + 96, bar_oc = bar_o + 112, bar_st = bar_o + 224, bar_go = bar_o + 248, bar_kv = bar_o + 272;
  if (warp < 4 && elect()) {
    mbar_init(bar_full + 8 * (warp ^ 2), 1);
    mbar_init(bar_empty + 8 * warp, 24);
    mbar_init(bar_aux + 8 * warp, warp == 0 ? 64 : warp == 2 ? 32 : 1);
    asm volatile("fence.mbarrier_init.release.cluster;" ::: "memory");
  }
  asm volatile("barrier.cluster.arrive.relaxed.aligned;" ::: "memory");
  if (warp >= 8 && warp < 11 && elect()) asm volatile("prefetch.tensormap [%0];" :: "l"(&tm.x + (warp - 8)) : "memory");
  auto pf_slice = [&](int ks) {
    pf_l2(lane < 16 ? (const char*)x + ((bid * 16 + lane) * 1280 + ks * 128) : (const char*)wqkv + ((bid * 15 + min(lane, 30) - 16) * 128 + ks * 245760));
  };
  if (warp == 4) pf_slice(0);
  const int rank = bid & 1, cl = bid >> 1;
  const int q7 = ((cl - 36) * 37) >> 8;
  const int P = cl < 4 ? 0 : cl < 36 ? (cl - 4) & 7 : cl - 35 - 7 * q7;
  const int g = cl < 4 ? 4 + cl : cl < 36 ? (cl - 4) >> 3 : 4 + q7;
  const int mt = 2 * P + rank, cid = mt * 8 + g;
  const bool ffn1 = g >= 5;
  const int fj = ffn1 ? mt * 3 + g - 5 : (P * 5 + g) * 2 + rank;
  const int ord = ((g >> 2) ^ P) & 1;
  auto ks_of = [&](int it) { return !ORDX || ord == 0 || it == 0 ? it : it <= 5 ? it + 4 : it - 5; };
  auto load_w = [&](int it, uint32_t a, uint32_t full) {
    tma_3d_mc(a + 16384 + rank * 16384, &tm.w, full, g * 80, it * 64, rank * 2);
    tma_3d_mc(a + (rank ? 40960 : 24576), rank ? &tm.wr : &tm.w, full, g * 80 + rank * 64, it * 64, 1 - rank);
  };
  if (warp == 0 && elect()) {
    mbar_expect_tx(bar_full + 16, SLOT);
    tma_3d(sb + 2 * SLOT, &tm.x, bar_full + 16, 0, P * 128, rank);
  }
  asm volatile("barrier.cluster.wait.aligned;" ::: "memory");
  if (warp == 0) {
    if (elect()) load_w(0, sb + 2 * SLOT, bar_full + 16);
    asm volatile("bar.arrive 4, 64;" ::: "memory");
  }

  if (warp >= 8) {
    asm volatile("setmaxnreg.dec.sync.aligned.u32 %0;" :: "n"(REG_P));
#define TS_T 0
    if (warp == 8) {
      TS(8);
      bar_sync(4, 64);
      if (elect()) {
        TS(10);
        int fjn = 0;
#pragma unroll 1
        for (int it = 1; it < 17; it++) {
          const int s = (it + 2) & 3;
          const uint32_t full = bar_full + 8 * s, a = sb + s * SLOT;
          if (it >= 13) { mbar_wait(bar_oc + 8 * (it - 13), 0); mbar_wait(bar_oc + 56 + 8 * (it - 13), 0); }
          else if (it >= 4) mbar_wait(bar_empty + 8 * s, ((it >> 2) - 1) & 1);
          else if (it >= THR) mbar_wait(bar_full + 8 * ((it - THR + 2) & 3), 0);
          if (it < 10) {
            const int ks = ks_of(it);
            mbar_expect_tx(full, SLOT);
            tma_3d(a, &tm.x, full, ks * 64, P * 128, rank);
            load_w(ks, a, full);
            TS(12 + it);
            if ((unsigned)(it - RST_IT) < 2u) {
              mbar_wait(bar_rst, 0);
              asm volatile("cp.async.bulk.global.shared::cta.bulk_group [%0], [%1], %2;\ncp.async.bulk.commit_group;"
                           :: "l"(it == RST_IT ? (uint4*)(g_own + cid) : (uint4*)&g_x + cid * GLOB_PER_CTA), "r"(sb + OFF_CS),
                              "r"(it == RST_IT ? (int)sizeof(Own) : GLOB_PER_CTA * 16) : "memory");
            }
            if (it == RST_IT + 2) { asm volatile("cp.async.bulk.wait_group 0;" ::: "memory"); mbar_arrive(bar_rst); }
          } else if (it < 13) {
            const int g0 = 3 * (it - 10), g1 = min(g0 + 3, 8);
            mbar_expect_tx(full, (g1 - g0) * 12800);
#pragma unroll 1
            for (int gp = g0 + ((g0 ^ rank) & 1); gp < g1; gp += 2) {
              tma_3d_mc(sb + gp * 15360, &tm.wo, full, 0, gp * 80, g * 2);
              tma_3d_mc(sb + gp * 15360 + 10240, &tm.wor, full, 512 + g * 16, gp * 80, 0);
            }
          }
          if (it == 4) mbar_expect_tx(bar_ffn, ffn1 ? 81920 : 24576);
          const int j1 = ffn1 ? (it >= 13 ? min(2 * it - 21, 10) : min(max(it - F_IT + 1, 0), 4)) : (it >= 13 ? (it == 16 ? 12 : min(F_MAX + (it - 12) * F_LATE, 12)) : min(max((it - F_IT + 1) * F_PER, 0), F_MAX));
#pragma unroll 1
          for (; fjn < j1; fjn++) {
            const int j = fjn < 4 ? fjn + 6 : fjn - 4;
            if (ffn1) tma_3d(sb + (j < 6 ? 0 : OFF_W2 - 49152) + j * 8192, j < 5 ? &tm.gate : &tm.up, bar_ffn, fj * 32, (j < 5 ? j : j - 5) * 128, 0);
            else tma_3d(sb + OFF_W2 + fjn * 2048, &tm.down, bar_ffn, fj * 8, fjn * 128, 0);
          }
        }
        TS(11);
      }
#undef TS_T
#define TS_T 64
    } else if (warp >= 12) {
      const int l7 = lane & 7, j = warp - 12, ch = min((P >> 1) * 4 + rank * 2 + (j >> 1), 14);
      const uint32_t sxo = ((g & 3) * 32 + j * 8 + l7) * 128 + (((lane >> 3) ^ l7) * 16);
      const uint32_t swo = ch < 12 ? 16384 + (ch >> 2) * 8192 + lane * 128 + ((((ch & 3) * 2 + (j & 1)) ^ l7) * 16)
                                   : 40960 + (ch - 12) * 2048 + lane * 32 + (((j & 1) ^ (l7 >> 2)) * 16);
      float ps = 0.f, pq = 0.f, pq1 = 0.f, pc = 0.f;
#pragma unroll 1
      for (int it = ord; it < ord + 5; it++) {
        const int sl = (it + 2) & 3;
        mbar_wait(bar_full + 8 * sl, (it >> 2) & 1);
        TS(it);
        const uint32_t a = sb + sl * SLOT;
        const uint4 v0 = ldsm4(a + sxo), v1 = ldsm4((a + sxo) ^ 64), w0 = ldsm4t(a + swo), w1 = ldsm4t(a + swo + (ch < 12 ? 4096 : 1024));
        if (lane + (int)((v0.x & v1.x & w0.x & w1.x) == 0x7fc17fc1u && (v0.x | v1.x) == 0u) < 2) mbar_arrive_cta(bar_empty + 8 * sl, lane);
        const uint32_t vv[8] = {v0.x, v0.y, v0.z, v0.w, v1.x, v1.y, v1.z, v1.w}, ww[8] = {w0.x, w0.y, w0.z, w0.w, w1.x, w1.y, w1.z, w1.w};
#pragma unroll
        for (int i = 0; i < 8; i++) {
          const float d = bf_lo(vv[i]), e = bf_hi(vv[i]);
          ps += d + e; pq = fmaf(d, d, pq); pq1 = fmaf(e, e, pq1); pc += bf_lo(ww[i]) + bf_hi(ww[i]);
        }
      }
      pq += pq1;
      ps += shx(ps, 1); pq += shx(pq, 1); pc += shx(pc, 1);
      ps += shx(ps, 2); pq += shx(pq, 2); pc += shx(pc, 2);
      const int c = lane & 3;
      if (c < 3) sts32f(sb + OFF_PT + (c * 32 + j * 8 + (lane >> 2)) * 4, c == 0 ? ps : c == 1 ? pq : pc);
      asm volatile("bar.arrive 2, 224;" ::: "memory");
      if (warp == 12) {
        const uint4* const hp = hold(&g_own[max(cid - 16, 0)].halo[0][lane]);
        mbar_wait(bar_aux, 0);
        mbar_wait(bar_go, 0);
        uint4 v[5] = {};
        int guard = SPIN_MAX;
        if (P > 0) {
          do {
#pragma unroll
            for (int i = 0; i < 5; i++) v[i] = ldg_pkt(hp + 32 * i);
          } while (anyw(v[0].x == SENT || v[1].x == SENT || v[2].x == SENT || v[3].x == SENT || v[4].x == SENT) && --guard > 0);
        }
#pragma unroll
        for (int i = 0; i < 5; i++) *(uint4*)(smem + OFF_O + 10240 + i * 512 + lane * 16) = v[i];
        mbar_arrive(bar_kv);
      }
#undef TS_T
#define TS_T 32
    } else if (warp < 11) {
      Own* const own = g_own + cid;
      const int l7 = lane & 7, hk = lane >> 4, idx = lane;
      if (warp == 10 && elect()) {
#pragma unroll 1
        for (int i = 0; i < 36; i++) mbar_init(bar_o + 8 * i, i < 14 ? 1 : i < 34 ? 4 : 128);
      }
      {
        const int t0 = clk();
#pragma unroll 1
        for (int i = PF_FIRST; i < 6; i++) {
          while (clk() - t0 < PF_T0 + (i - PF_FIRST) * PF_CLK) __nanosleep(20);
          pf_slice(warp == 9 ? min(i, 4) : i + 4);
        }
      }
      bar_sync(2, 224);
      mbar_wait(bar_rst, 1);
      TS(0);
      const uint32_t tag = __float_as_uint(lds32f(sb + OFF_WR + 324));
      const float s0 = lds32f(sb + OFF_PT + lane * 4 + (warp - 9) * 256), q0 = lds32f(sb + OFF_PT + 128 + lane * 4);
      int guard = SPIN_MAX;
      if (warp == 9) {
        stg_pkt(&own->st1[idx], __float_as_uint(s0), __float_as_uint(q0), tag, 0u);
        TS(1);
        const uint4* sp = &g_own[mt * 8].st1[lane];
        const uint4* hp = &g_own[max(mt - 2, 0) * 8 + 3].st1[24 + l7];
        uint4 a[5], b[5];
        bool bad;
        do {
          __nanosleep(AUX_NS);
          bad = false;
#pragma unroll
          for (int i = 0; i < 5; i++) {
            const uint4* q = i < 4 ? sp + i * (sizeof(Own) / 16) : hp;
            a[i] = ldg_pkt(q); b[i] = ldg_pkt(q + 4 * sizeof(Own) / 16);
          }
#pragma unroll
          for (int i = 0; i < 5; i++) bad |= a[i].z != tag || b[i].z != tag;
        } while (anyw(bad) && --guard);
#pragma unroll
        for (int i = 0; i < 5; i++) {
          const float m = (__uint_as_float(a[i].x) + __uint_as_float(b[i].x)) * (1.f / 640.f);
          const float rs = rsq(fmaxf(fmaf(-m, m, (__uint_as_float(a[i].y) + __uint_as_float(b[i].y)) * (1.f / 640.f)), 0.f) + 1e-5f);
          ((float*)(smem + OFF_RS))[i < 4 ? 8 + lane + 32 * i : l7] = rs;
          const uint32_t mh = pack_bf16(-m, -m);
          const float ml = -m - bf_lo(mh);
          if (i < 4) ((uint2*)(smem + OFF_MN))[lane + 32 * i] = make_uint2(mh, pack_bf16(ml, ml));
        }
      } else {
        stg_rlx64(&own->cs[idx], __float_as_uint(s0), tag);
        const uint4* cp = (const uint4*)g_own[hk * 8 + g].cs + (lane & 15);
        uint4 a[4], b[4];
        bool bad;
        do {
          __nanosleep(AUX_NS);
          bad = false;
#pragma unroll
          for (int i = 0; i < 4; i++) { a[i] = ldg_pkt(cp + i * 32 * sizeof(Own) / 16); b[i] = ldg_pkt(cp + (i * 32 + 16) * sizeof(Own) / 16); }
#pragma unroll
          for (int i = 0; i < 4; i++) bad |= a[i].y != tag || a[i].w != tag || b[i].y != tag || b[i].w != tag;
        } while (anyw(bad) && --guard);
#pragma unroll
        for (int i = 0; i < 4; i++)
          if (i < 3 || lane < 24) {
            const float c0 = __uint_as_float(a[i].x) + __uint_as_float(b[i].x), c1 = __uint_as_float(a[i].z) + __uint_as_float(b[i].z);
            const uint32_t hi = pack_bf16(c0, c1), w0 = pack_bf16(c0, c0 - bf_lo(hi)), w1 = pack_bf16(c1, c1 - bf_hi(hi));
            uint4* const d = (uint4*)(smem + OFF_CS) + 2 * (lane + 32 * i);
            d[0] = make_uint4(w0, w0, 0, 0); d[1] = make_uint4(w1, w1, 0, 0);
          }
        asm volatile("fence.proxy.async.shared::cta;" ::: "memory");
      }
      mbar_arrive(bar_aux);
      TS(2);
      const int fo = warp - 9, wq = fo ? 1 - LEAD : LEAD;
      const uint4* const fp = hold(g_own[mt * 8 + wq * 4].cnt);
      const char* src = hold((const char*)g_o[mt * 2 + wq]);
      if (elect()) {
        const uint32_t bo = bar_o + fo * 56;
#pragma unroll
        for (int i = 0; i < 7; i++) mbar_expect_tx(bo + 8 * i, 10240);
        mbar_wait(bar_st + 8 * fo, 0);
        while (ldg_rlx32(fp) != 32u && --guard > 0) {}
        asm volatile("fence.proxy.async.global;" ::: "memory");
        TS(6);
#pragma unroll
        for (int i = 0; i < 7; i++) {
          if (fo || i == 6) mbar_wait(bo + 64 + 8 * i, 0);
          else if (i == 4) mbar_wait(bar_st + 8, 0);
          if (i == g) src += 10240;
          asm volatile("cp.async.bulk.shared::cluster.global.mbarrier::complete_tx::bytes [%0], [%1], 10240, [%2];"
                       :: "r"(sb + OFF_O + ((i + 2) % 6) * 10240 + fo * (i == 3 ? -51200 : 10240)), "l"(src + i * 10240), "r"(bo + 8 * i) : "memory");
        }
      }
#undef TS_T
#define TS_T 96
    } else {
      if ((sb & 0x3FFFF) != D0 * 16) __trap();
#pragma unroll 1
      for (int i = lane; i < 232; i += 32) { const uint32_t f = i < 208 ? SENT : 0u; ((uint4*)(smem + OFF_CS))[i] = make_uint4(f, f, f, f); }
      asm volatile("fence.proxy.async.shared::cta;" ::: "memory");
      if (elect()) mbar_arrive(bar_rst);
      mbar_wait(bar_full + 8 * ((HK_IT + 2) & 3), 0);
      TS(4);
      const uint32_t epoch = ldg_rlx32(g_epoch + cid) + 1;
      uint32_t wv[10];
#pragma unroll
      for (int i = 0; i < 10; i++) wv[i] = __ldg((const uint32_t*)w_r + lane + 32 * i);
      float s = 0.f;
#pragma unroll
      for (int i = 0; i < 10; i++) {
        s += bf_lo(wv[i]) + bf_hi(wv[i]);
        const unsigned u = i < 8 ? lane + 32 * (i - g) : lane + 32 * (i - 7) - g * 8;
        if (i < 8 ? u < 32u : u - 32u < 8u) *(float2*)(smem + OFF_WR + ((u & 3) * 10 + (u >> 2)) * 8) = make_float2(bf_lo(wv[i]), bf_hi(wv[i]));
      }
#pragma unroll
      for (int m = 1; m < 32; m <<= 1) s += shx(s, m);
      *(float2*)(smem + OFF_WR + 320) = make_float2(s, __uint_as_float(epoch * 0x9E3779B8u));
      g_epoch[cid] = epoch;
      TS(3);
      TS(5);
      asm volatile("bar.arrive 2, 224;" ::: "memory");
#pragma unroll 1
      for (int i = 0; i < 14; i++) {
        const int m = (i + 2) >> 2, n = m == 0 ? 50 : 120, t = (m == 0 ? i : (i + 2) & 3) * 32 + lane;
        const char* b = (const char*)(m == 0 ? wo : m == 1 ? w_up : m == 2 ? w_down : w_gate);
        if (t < n) pf_l2(b + (bid * n + t) * 128);
        __nanosleep(PFW_NS);
      }
      bar_sync(3, 64);
      const uint4* const kp = g_own[1].cnt;
      const uint4* const cb = &g_x.cand[0][lane >> 2][lane & 3];
      uint4 k = ldg_pkt(kp), c0 = make_uint4(0, 0, 0, 0), c1 = c0; uint2 c2 = make_uint2(0, 0);
      int guard = SPIN_MAX, ws;
      while (true) {
        const uint32_t tk = 2047u - (k.x & 2047u);
        ws = (tk >> 8) * 16 + (tk & 1) * 8 + ((tk >> 5) & 7);
        const uint32_t prev = k.x;
        if (ffn1) { const uint4* q = cb + ws * 192; c0 = ldg_pkt(q); c1 = ldg_pkt(q + 4); c2 = ldg_rlx64(q + 8); }
        if (k.z != 128u) k = ldg_pkt(kp);
        if ((k.z == 128u && k.x == prev && !anyw(c0.x == SENT || c1.x == SENT || c2.x == SENT)) || --guard <= 0) break;
      }
      *(uint4*)(smem + OFF_HN + lane * 16) = c0; *(uint4*)(smem + OFF_HN + 512 + lane * 16) = c1; *(uint2*)(smem + OFF_HN + 1024 + lane * 16) = c2;
      *(uint4*)(smem + OFF_WR + 336) = make_uint4(ws, 2047u - (k.x & 2047u), k.y, 0);
      mbar_arrive(bar_win);
      TS(7);
    }
#undef TS_T
  } else {
#define TS_T 0
    asm volatile("setmaxnreg.inc.sync.aligned.u32 %0;" :: "n"(REG_C));
    const int wg = warp >> 2, w4 = warp & 3, r = lane >> 2, c = lane & 3;
    float acc[120];
    uint4 xr[5] = {};
    const uint32_t xa = pin(sb + (warp * 16 + (lane & 15)) * 128 + ((lane >> 4) ^ (lane & 7)) * 16);
    const int fol = wg != LEAD;
    const bool first = (P == 0) && (warp == 0);
    const uint32_t kvs = sb + OFF_O + fol * 10240 + w4 * 2560 + lane * 16;
    uint4* const kvd = hold(warp == 7 ? &g_own[cid].halo[0][lane] : (uint4*)(smem + (warp == 3 ? OFF_O + lane * 16 : kvs - sb + 2560)));
    uint4* const odst = hold(&g_o[mt * 2 + wg][g][w4 * 160]);
    uint4* const ocnt = hold(g_own[mt * 8 + wg * 4].cnt);
    uint32_t m0 = 0, m1 = 0;
    const uint32_t mna = pin(sb + OFF_MN + (warp * 16 + r) * 8 + c * 4);
    const int itx = ord == 0 || g == 0 ? g : g < 5 ? g + 5 : g - 4, ity = (ord ? 4 : 8) + (g >> 2);
    uint32_t rel;
    asm volatile("mapa.shared::cluster.u32 %0, %1, %2;" : "=r"(rel) : "r"(bar_empty), "r"(tid & 1));
    const uint32_t xa1 = pin(xa ^ 32), xa2 = pin(xa ^ 64), xa3 = pin(xa ^ 96), xb = pin(xa ^ ((g & 3) * 32));
    const uint32_t da0 = wg * 512;
    const bool rel2 = lane < 2, rel6 = lane < 2 + 2 * (warp & 1);
    const uint32_t zero = (uint32_t)(uintptr_t)x & 8u;
    mbar_wait(bar_full + 16, 0);
    TS(13);
    wgmma_fence();
#pragma unroll
    for (int it = 0; it < 10; it++) {
      const int s = (it + 2) & 3;
      if (it == 9 && fol) bar_sync(10, 256);
#pragma unroll
      for (int kk = 0; kk < 4; kk++) {
        if (kk == 2 && it > 0) {
          wgmma_commit();
          wgmma_wait<1>();
          const uint32_t ra = ((xr[0].x ^ xr[1].x ^ xr[2].x ^ xr[3].x ^ xr[4].x) & zero) | rel;
          if (it == 1 ? (ord ? rel6 : rel2) : it == 6 ? (ord ? rel2 : rel6) : it < 6 ? rel2 : rel6)
            asm volatile("mbarrier.arrive.shared::cluster.b64 _, [%0];" :: "r"(ra + 8 * ((it + 1) & 3)) : "memory");
        }
        if (kk == 2) {
          ldsm4_if(xr[0], xa, s * SLOT, it == itx); ldsm4_if(xr[1], xa1, s * SLOT, it == itx);
          ldsm4_if(xr[2], xa2, s * SLOT, it == itx); ldsm4_if(xr[3], xa3, s * SLOT, it == itx);
          if ((it & 6) == 4 || it >= 8) ldsm4_if(xr[4], xb, s * SLOT, it == ity);
        }
        if (kk == AK && it == 9) {
          mbar_wait(bar_aux, 0);
          TS(3);
          if (c < 2) { m0 = __float_as_uint(lds32f(mna)); m1 = __float_as_uint(lds32f(mna + 64)); }
          if (!fol) bar_sync(11, 256);
        }
        if (kk == 3 && it < 9) {
          mbar_wait(bar_full + 8 * ((it + 3) & 3), ((it + 1) >> 2) & 1);
          TS(14 + it);
        }
        const uint64_t da = mk64(da0 + (D0 + s * (SLOT >> 4) + kk * 2 + (1 << 16)), 0x40000040u);
        wgmma_n48hi_ss(acc, da, mk64(D0 + s * (SLOT >> 4) + 2560 + kk * 32 + (128 << 16), 0xC0000010u), (it | kk) != 0);
        wgmma_n192lo_ss(acc, da, mk64(D0 + s * (SLOT >> 4) + 1024 + kk * 128 + (512 << 16), 0x40000040u), (it | kk) != 0);
      }
      wgmma_commit();
      if (it == 8 && fol) asm volatile("bar.arrive 11, 256;" ::: "memory");
    }
    {
      const uint64_t dc = make_desc(D0 * 16 + OFF_CS, 0, 128, 0);
      wgmma_fence();
      wgmma_n48hi_rk(acc, m0, m1, 0u, 0u, dc + 192, 1);
      wgmma_n192lo_rk(acc, m0, m1, 0u, 0u, dc, 1);
      wgmma_commit();
      if (!fol) asm volatile("bar.arrive 10, 256;" ::: "memory");
    }
    const uint32_t stb = sb + OFF_RS + warp * 64;
    const float rlo = lds32f(stb + (8 + r) * 4), rhi = lds32f(stb + (16 + r) * 4);
    wgmma_wait<0>();
#pragma unroll
    for (int i = 0; i < 120; i++) asm volatile("" : "+f"(acc[i]) :: "memory");
    if (fol && lane == 0) mbar_arrive(bar_go);
    TS(2);
    uint32_t Qlo[10], Qhi[10], Klo[10], Khi[10], Vlo[10], Vhi[10];
#pragma unroll
    for (int t = 0; t < 10; t++) {
      const int k = KT(t), v = VT(t);
      Khi[t] = pack_bf16(acc[4 * k + 2], acc[4 * k + 3]);
      Vhi[t] = pack_bf16(acc[4 * v + 2] * rhi, acc[4 * v + 3] * rhi);
    }
    st_pkt(kvd, Khi[0], Khi[1], Khi[3], Khi[4]);
    st_pkt(kvd + 32, Khi[5], Khi[6], Khi[8], Khi[9]);
    st_pkt(kvd + 64, Khi[2], Khi[7], Vhi[0], Vhi[1]);
    st_pkt(kvd + 96, Vhi[2], Vhi[3], Vhi[4], Vhi[5]);
    st_pkt(kvd + 128, Vhi[6], Vhi[7], Vhi[8], Vhi[9]);
    if (warp < 7) mbar_arrive(bar_kv + ((warp + 1) >> 2) * 8);
    mbar_wait(bar_aux, 0);
#pragma unroll
    for (int t = 0; t < 10; t++) {
      const int q = QT(t), k = KT(t), v = VT(t);
      Vhi[t] = movm(Vhi[t]);
      Klo[t] = pack_bf16(acc[4 * k], acc[4 * k + 1]);
      Vlo[t] = movm(pack_bf16(acc[4 * v] * rlo, acc[4 * v + 1] * rlo));
      Qlo[t] = pack_bf16(acc[4 * q], acc[4 * q + 1]);
      Qhi[t] = pack_bf16(acc[4 * q + 2], acc[4 * q + 3]);
    }
    const bool in0 = 2 * c <= r, in1 = 2 * c + 1 <= r;
    const uint32_t mL = (in0 ? 0xffffu : 0u) | (in1 ? 0xffff0000u : 0u);
    const float qs = 0.22360679774997896f * 1.4426950408889634f;
    const uint32_t kb0 = stb + (2 * c + (in0 ? 8 : 0)) * 4, kb1 = stb + (2 * c + 1 + (in1 ? 8 : 0)) * 4;
    const float scl0 = lds32f(kb0) * rlo * qs, scl1 = lds32f(kb1) * rlo * qs;
    const float sch0 = lds32f(kb0 + 32) * rhi * qs, sch1 = lds32f(kb1 + 32) * rhi * qs;
    const float bias0 = (first && !in0) ? -INFINITY : 0.f, bias1 = (first && !in1) ? -INFINITY : 0.f;
    const int slot = mt * 8 + warp;
    int guard = SPIN_MAX;
    uint4 pv[5];
    const bool cA = c < 2, nA = r < 4;
    TS(0);
    mbar_wait(bar_go + fol * 8, 0);
    TS(23);
    uint32_t qe[4][2];
    float sl0[4], sl1[4], th0[4], th1[4];
#pragma unroll
    for (int hd = 0; hd < 4; hd++) {
      const int ta = 5 * (hd >> 1) + 3 * (hd & 1), ts = 5 * (hd >> 1) + 2;
      const bool mine = (hd & 1) ? !cA : cA;
      qe[hd][0] = mine ? Qlo[ts] : 0u; qe[hd][1] = mine ? Qhi[ts] : 0u;
      float sl[4], sh[4];
      mma_k24(sl, Qlo[ta], Qhi[ta], Qlo[ta + 1], Qhi[ta + 1], Klo[ta], Klo[ta + 1], qe[hd][0], qe[hd][1], Klo[ts]);
      mma_k24(sh, Qlo[ta], Qhi[ta], Qlo[ta + 1], Qhi[ta + 1], Khi[ta], Khi[ta + 1], qe[hd][0], qe[hd][1], Khi[ts]);
      th0[hd] = (in0 ? sh[2] : sl[2]) * sch0; th1[hd] = (in1 ? sh[3] : sl[3]) * sch1;
      float mh = fmaxf(th0[hd], th1[hd]);
      mh = fmaxf(mh, shx(mh, 1)); mh = fmaxf(mh, shx(mh, 2));
      th0[hd] -= mh; th1[hd] -= mh;
      sl0[hd] = sl[0]; sl1[hd] = sl[1];
    }
    mbar_wait(bar_kv + wg * 8, 0);
    TS(4);
#pragma unroll
    for (int j = 0; j < 5; j++) pv[j] = lds128(kvs + 512 * j);
    const uint32_t Kp[10] = {pv[0].x, pv[0].y, pv[2].x, pv[0].z, pv[0].w, pv[1].x, pv[1].y, pv[2].y, pv[1].z, pv[1].w};
    const uint32_t Vp[10] = {movm(pv[2].z), movm(pv[2].w), movm(pv[3].x), movm(pv[3].y), movm(pv[3].z), movm(pv[3].w), movm(pv[4].x), movm(pv[4].y), movm(pv[4].z), movm(pv[4].w)};
    const uint32_t ONES = 0x3f803f80u;
    uint32_t of[20];
#pragma unroll
    for (int hp = 0; hp < 2; hp++) {
      float o[6][4];
#pragma unroll
      for (int hh = 0; hh < 2; hh++) {
        const int hd = 2 * hp + hh, ta = 5 * hp + 3 * hh, ts = 5 * hp + 2;
        float sp[4];
        mma_k24(sp, Qlo[ta], Qhi[ta], Qlo[ta + 1], Qhi[ta + 1], Kp[ta], Kp[ta + 1], qe[hd][0], qe[hd][1], Kp[ts]);
        const float tl0 = fmaf(in0 ? sl0[hd] : sp[0], scl0, bias0), tl1 = fmaf(in1 ? sl1[hd] : sp[1], scl1, bias1);
        float ml = fmaxf(tl0, tl1);
        ml = fmaxf(ml, shx(ml, 1)); ml = fmaxf(ml, shx(ml, 2));
        if (HOLD == 1 && hd == 3 && !fol && lane == 0) mbar_arrive(bar_go + 8);
        const uint32_t Pl = pack_bf16(ex2(tl0 - ml), ex2(tl1 - ml)), Ph = pack_bf16(ex2(th0[hd]), ex2(th1[hd]));
        const uint32_t a0 = Pl & mL, a1 = Ph & ~mL, a3 = Ph & mL, ap = Pl & ~mL;
        const bool vm = hh == 0 ? nA : !nA;
        mma_k24(o[3 * hh], a0, a1, 0u, a3, Vlo[ta], Vhi[ta], ap, 0u, Vp[ta]);
        mma_k24(o[3 * hh + 1], a0, a1, 0u, a3, Vlo[ta + 1], Vhi[ta + 1], ap, 0u, Vp[ta + 1]);
        mma_k24(o[3 * hh + 2], a0, a1, 0u, a3, vm ? Vlo[ts] : ONES, vm ? Vhi[ts] : ONES, ap, 0u, vm ? Vp[ts] : ONES);
      }
      const float il = rcp(cA ? o[5][0] : o[2][0]), ih = rcp(cA ? o[5][2] : o[2][2]);
      const float jl = shx(il, 2), jh = shx(ih, 2);
      const float al = cA ? jl : il, ah = cA ? jh : ih, bl = cA ? il : jl, bh = cA ? ih : jh;
      const int t0 = 5 * hp;
      of[2 * t0]     = pack_bf16(o[0][0] * al, o[0][1] * al); of[2 * t0 + 1] = pack_bf16(o[0][2] * ah, o[0][3] * ah);
      of[2 * t0 + 2] = pack_bf16(o[1][0] * al, o[1][1] * al); of[2 * t0 + 3] = pack_bf16(o[1][2] * ah, o[1][3] * ah);
      of[2 * t0 + 4] = pack_bf16((cA ? o[2][0] : o[5][0]) * jl, (cA ? o[2][1] : o[5][1]) * jl);
      of[2 * t0 + 5] = pack_bf16((cA ? o[2][2] : o[5][2]) * jh, (cA ? o[2][3] : o[5][3]) * jh);
      of[2 * t0 + 6] = pack_bf16(o[3][0] * bl, o[3][1] * bl); of[2 * t0 + 7] = pack_bf16(o[3][2] * bh, o[3][3] * bh);
      of[2 * t0 + 8] = pack_bf16(o[4][0] * bl, o[4][1] * bl); of[2 * t0 + 9] = pack_bf16(o[4][2] * bh, o[4][3] * bh);
    }
    {
      const uint32_t os = sb + OFF_O + (fol ? 0 : 20480) + w4 * 2560, oa = os + ((lane >> 3) & 1) * 1280 + (lane >> 4) * 128 + (lane & 7) * 16;
#pragma unroll
      for (int s = 0; s < 5; s++) {
        stsm4(oa + s * 256, of[4 * s], of[4 * s + 1], of[4 * s + 2], of[4 * s + 3]);
        if (s == 0 && (fol || HOLD == 2) && lane == 0) mbar_arrive(bar_go + 8 + 8 * fol);
      }
      asm volatile("fence.proxy.async.shared::cta;" ::: "memory");
      __syncwarp();
      if (elect()) {
        asm volatile("cp.async.bulk.global.shared::cta.bulk_group [%0], [%1], 2560;\ncp.async.bulk.commit_group;" :: "l"(odst), "r"(os) : "memory");
      }
    }
    TS(5);
    float h[40];
#pragma unroll
    for (int s = 0; s < 5; s++) {
      const uint4 v = xr[s];
      h[8 * s] = bf_lo(v.x); h[8 * s + 1] = bf_hi(v.x); h[8 * s + 2] = bf_lo(v.y); h[8 * s + 3] = bf_hi(v.y);
      h[8 * s + 4] = bf_lo(v.z); h[8 * s + 5] = bf_hi(v.z); h[8 * s + 6] = bf_lo(v.w); h[8 * s + 7] = bf_hi(v.w);
    }
    if (elect()) {
      asm volatile("cp.async.bulk.wait_group 0;" ::: "memory");
      asm volatile("red.relaxed.gpu.global.add.u32 [%0], 1;" :: "l"(ocnt) : "memory");
      mbar_arrive(bar_st + 8 * fol);
    }
    __syncwarp();
    mbar_wait(bar_full, 0); mbar_wait(bar_full + 8, 0); mbar_wait(bar_full + 16, 1);
    mbar_wait(bar_go + 16, 0);
    const uint64_t dwo = make_desc(D0 * 16, 5120, 512, 2);
    wgmma_fence();
#pragma unroll
    for (int s = 0; s < 5; s++) wgmma_n80_rs(h, of[4 * s], of[4 * s + 1], of[4 * s + 2], of[4 * s + 3], dwo + g * 960 + s * 64, 1);
    wgmma_commit();
    TS(6);
    const uint32_t bo = bar_o + fol * 56;
#pragma unroll
    for (int i = 0; i < 7; i++) {
      mbar_wait(bo + 8 * i, 0);
      if (i == 0) TS(1);
      const uint32_t da = D0 + OFF_O / 16 + (8 << 16) + ((i + 2) % 6) * 640 + fol * (i == 3 ? -3200 : 640), db = D0 + (320 << 16) + (i >= g ? i + 1 : i) * 960;
      wgmma_fence();
#pragma unroll
      for (int s = 0; s < 5; s++) wgmma_n80_ss(h, mk64(da + s * 16, 80u), mk64(db + s * 64, 0x80000020u), 1);
      wgmma_commit();
      wgmma_wait<1>();
      if (lane == 0 && i > 0) mbar_arrive(bo + 104 + 8 * i);
    }
    const bool odd = c & 1;
    float wr[20];
#pragma unroll
    for (int j = 0; j < 5; j++) {
      const uint4 v = lds128(sb + OFF_WR + c * 80 + j * 16);
      wr[4 * j] = __uint_as_float(v.x); wr[4 * j + 1] = __uint_as_float(v.y); wr[4 * j + 2] = __uint_as_float(v.z); wr[4 * j + 3] = __uint_as_float(v.w);
    }
    const float wsum = lds32f(sb + OFF_WR + 320);
    uint4* const sp = hold(&g_own[slot].st2[r + (odd ? 8 : 0)]);
    uint4* const cdp = hold(&g_x.cand[slot][g][0]);
    const int tok0 = P * 256 + 32 * warp + rank;
    wgmma_wait<0>();
#pragma unroll
    for (int i = 0; i < 40; i++) asm volatile("" : "+f"(h[i]) :: "memory");
    if (lane == 0) mbar_arrive(bo + 160);
    TS(7);
    float mean, rstd, rr;
    {
      float l1 = 0.f, l2 = 0.f, l3 = 0.f, h1 = 0.f, h2 = 0.f, h3 = 0.f;
#pragma unroll
      for (int j = 0; j < 10; j++) {
        l1 += h[4 * j] + h[4 * j + 1]; h1 += h[4 * j + 2] + h[4 * j + 3];
        l2 = fmaf(h[4 * j], h[4 * j], l2); l2 = fmaf(h[4 * j + 1], h[4 * j + 1], l2);
        h2 = fmaf(h[4 * j + 2], h[4 * j + 2], h2); h2 = fmaf(h[4 * j + 3], h[4 * j + 3], h2);
        l3 = fmaf(h[4 * j], wr[2 * j], l3); l3 = fmaf(h[4 * j + 1], wr[2 * j + 1], l3);
        h3 = fmaf(h[4 * j + 2], wr[2 * j], h3); h3 = fmaf(h[4 * j + 3], wr[2 * j + 1], h3);
      }
      float s1 = (odd ? h1 : l1) + shx(odd ? l1 : h1, 1), s2 = (odd ? h2 : l2) + shx(odd ? l2 : h2, 1), s3 = (odd ? h3 : l3) + shx(odd ? l3 : h3, 1);
      s1 += shx(s1, 2); s2 += shx(s2, 2); s3 += shx(s3, 2);
      if (cA) asm volatile("red.relaxed.gpu.global.add.v4.f32 [%0], {%1, %2, %3, %4};" :: "l"(sp), "f"(s1), "f"(s2), "f"(s3), "f"(1.f) : "memory");
      uint4 p0;
      do { p0 = ldg_pkt(sp); } while (anyw(p0.w != 0x41000000u) && --guard > 0);
      mean = __uint_as_float(p0.x) * (1.f / 640.f);
      rstd = rsq(fmaxf(fmaf(-mean, mean, __uint_as_float(p0.y) * (1.f / 640.f)), 0.f) + 1e-5f);
      rr = fmaf(-mean, wsum, __uint_as_float(p0.z)) * rstd;
    }
    TS(8);
    const uint32_t kk = ord_key(rr), kmax = __reduce_max_sync(0xffffffffu, kk);
    const int L = __ffs(__ballot_sync(0xffffffffu, kk == kmax)) - 1;
    const int crow = (L >> 2) + 8 * (L & 1);
    if (warp == g) {
      if (elect()) {
        asm volatile("red.relaxed.gpu.global.max.u64 [%0], %1;" :: "l"(g_own[1].cnt), "l"(((uint64_t)kmax << 32) | (uint32_t)(2047 - tok0 - 2 * crow)) : "memory");
        asm volatile("red.relaxed.gpu.global.add.u32 [%0], 1;" :: "l"(&g_own[1].cnt[0].z) : "memory");
      }
      asm volatile("bar.arrive 3, 64;" ::: "memory");
    }
    const uint32_t stg = sb + (fol ? OFF_O : g * 15360) + w4 * 2560;
    uint4 held;
    {
      const float om = shx(mean, 1), os = shx(rstd, 1);
      const float rl = odd ? os : rstd, rh = odd ? rstd : os;
      const float bl = -(odd ? om : mean) * rl, bh = -(odd ? mean : om) * rh, al = 1.f + rl, ah = 1.f + rh;
      if ((L >> 2) == r) {
        const bool chi = L & 1;
        const float rc = chi ? rh : rl, bc = chi ? bh : bl;
        uint32_t n[10];
#pragma unroll
        for (int j = 0; j < 10; j++) n[j] = pack_bf16(fmaf(chi ? h[4 * j + 2] : h[4 * j], rc, bc), fmaf(chi ? h[4 * j + 3] : h[4 * j + 1], rc, bc));
        uint4* d = cdp + c;
        stg_pkt(d, n[0], n[1], n[2], n[3]); stg_pkt(d + 4, n[4], n[5], n[6], n[7]); stg_rlx64(d + 8, n[8], n[9]);
      }
      mbar_wait(bar_oc + 56, 0);
      const uint32_t fa = stg + (lane & 15) * 160 + (lane >> 4) * 16;
#pragma unroll
      for (int s = 0; s < 5; s++)
        stsm4(fa + s * 32, pack_bf16(fmaf(h[8 * s], al, bl), fmaf(h[8 * s + 1], al, bl)), pack_bf16(fmaf(h[8 * s + 2], ah, bh), fmaf(h[8 * s + 3], ah, bh)),
              pack_bf16(fmaf(h[8 * s + 4], al, bl), fmaf(h[8 * s + 5], al, bl)), pack_bf16(fmaf(h[8 * s + 6], ah, bh), fmaf(h[8 * s + 7], ah, bh)));
      __syncwarp();
      held = lds128(stg + crow * 160 + min(lane, 9) * 16);
      if (lane < 10) stg_pkt(cdp + 12 + lane, held.x, held.y, held.z, held.w);
    }
    TS(9);
    mbar_wait(bar_ffn, 0);
    const uint32_t red = sb + OFF_RED;
    if (ffn1) {
      uint4 w1[4][5];
      {
        const int k = (lane & 7) + (lane >> 4) * 8;
        const uint32_t a1 = sb + k * 64, sw = ((lane >> 3) & 1) ^ ((lane >> 1) & 3);
#pragma unroll
        for (int s = 0; s < 5; s++)
#pragma unroll
          for (int u = 0; u < 4; u++)
            w1[u][s] = ldsm4t(a1 + (s < 4 ? warp * 4096 + s * 1024 : 32768 + warp * 1024) + (u >> 1) * (40960 + (s == 4 || warp >= 2 ? OFF_W2 - 49152 : 0)) + ((sw ^ (2 * (u & 1))) * 16));
      }
      uint32_t* const ap = hold(g_x.act + fj * 16 + (lane >> 1));
      mbar_wait(bar_win, 0);
      const uint32_t hp = sb + OFF_HN + (warp * 4 + c) * 16;
      const uint4 c0 = lds128(hp), c1 = lds128(hp + 512), c2 = lds128(hp + 1024);
      TS(10);
      float a[4][4];
#pragma unroll
      for (int u = 0; u < 4; u++) {
        a[u][0] = a[u][1] = a[u][2] = a[u][3] = 0.f;
        mma_acc(a[u], w1[u][0], c0.x, c0.y); mma_acc(a[u], w1[u][1], c0.z, c0.w); mma_acc(a[u], w1[u][2], c1.x, c1.y);
        mma_acc(a[u], w1[u][3], c1.z, c1.w); mma_acc(a[u], w1[u][4], c2.x, c2.y);
      }
      asm volatile("st.shared.v2.f32 [%0], {%1, %2};" :: "r"(red + (warp * 32 + c * 8 + r) * 8),
                   "f"(cA ? (odd ? a[0][2] : a[0][0]) : (odd ? a[1][2] : a[1][0])), "f"(cA ? (odd ? a[2][2] : a[2][0]) : (odd ? a[3][2] : a[3][0])) : "memory");
      bar_sync(1, 256);
      if (warp == 0) {
        float2 t[8];
#pragma unroll
        for (int i = 0; i < 8; i++) t[i] = lds64f(red + (i * 32 + lane) * 8);
        const float s = ((t[0].x + t[1].x) + (t[2].x + t[3].x)) + ((t[4].x + t[5].x) + (t[6].x + t[7].x));
        const float u = ((t[0].y + t[1].y) + (t[2].y + t[3].y)) + ((t[4].y + t[5].y) + (t[6].y + t[7].y));
        const float av = s * u * rcp(1.f + ex2(-1.4426950408889634f * s));
        const float an = shx(av, 1);
        if (!odd) stg_rlx32(ap, pack_bf16(av, an));
      }
      bar_sync(1, 256);
      TS(11);
    }
    if (OUT_LATE) mbar_wait(bar_win, 0);
    char* const ob2 = (char*)(out + tok0 * 640 + g * 64);
    const int remo = 896 - 96 * g;
#pragma unroll
    for (int s = 0; s < 5; s++) {
      const int row = s < 4 ? 4 * s + (lane >> 3) : lane >> 1, pc = s < 4 ? lane & 7 : 8 + (lane & 1);
      const uint4 v = lds128(stg + row * 160 + pc * 16);
      if (row != crow) stg128(ob2 + row * 2560 + pc * 16 + (s < 4 ? 0 : remo), v);
    }
    mbar_wait(bar_win, 0);
    const uint4 win = lds128(sb + OFF_WR + 336);
    if (win.x != slot && lane < 10) stg128(ob2 + crow * 2560 + lane * 16 + (lane < 8 ? 0 : remo), held);
    if (!ffn1) {
      TS(10);
      uint4 w2[6];
      const uint32_t a2 = sb + OFF_W2 + (warp * 192 + 8 * (((lane >> 3) & 1) * 4 + ((lane & 7) >> 1)) + 2 * (lane >> 4) + (lane & 1)) * 16;
#pragma unroll
      for (int s = 0; s < 6; s++) w2[s] = ldsm4t(a2 + (s >> 1) * 1024 + (s & 1) * 64);
      const uint4* p = (const uint4*)(g_x.act + warp * 96) + (r & 1) * 4 + c;
      const uint32_t* pb = (const uint32_t*)&g_x.cand[win.x][fj < 64 ? fj >> 3 : (fj - 64) >> 1][fj < 64 ? 12 + (fj & 7) : 20 + (fj & 1)] + c;
      uint32_t* const op = hold((uint32_t*)(out + win.y * 640 + fj * 8) + c);
      const float sg = rcp(1.f + ex2(-1.4426950408889634f * __uint_as_float(win.z ^ ((uint32_t)((int32_t)~win.z >> 31) | 0x80000000u))));
      uint4 c0, c1, c2; uint32_t bw;
      if (ACT_NS) __nanosleep(ACT_NS);
      do {
        c0 = ldg_pkt(p); c1 = ldg_pkt(p + 8); c2 = ldg_pkt(p + 16); bw = ldg_rlx32(pb);
      } while (anyw(max(max(max(max(c0.x, c0.y), max(c0.z, c0.w)), max(max(c1.x, c1.y), max(c1.z, c1.w))), max(max(max(c2.x, c2.y), max(c2.z, c2.w)), bw)) == SENT) && --guard > 0);
      TS(11);
      float a[4] = {0.f, 0.f, 0.f, 0.f}, b[4] = {0.f, 0.f, 0.f, 0.f}, d[4] = {0.f, 0.f, 0.f, 0.f};
      mma_acc(a, w2[0], c0.x, c0.y); mma_acc(b, w2[2], c1.x, c1.y); mma_acc(d, w2[4], c2.x, c2.y);
      mma_acc(a, w2[1], c0.z, c0.w); mma_acc(b, w2[3], c1.z, c1.w); mma_acc(d, w2[5], c2.z, c2.w);
      if (c == 0) sts32f(red + (warp * 8 + r) * 4, ((a[0] + a[3]) + (b[0] + b[3])) + (d[0] + d[3]));
      bar_sync(1, 256);
      if (tid < 4) {
        float2 t[8];
#pragma unroll
        for (int i = 0; i < 8; i++) t[i] = lds64f(red + (i * 4 + tid) * 8);
        const float y0 = ((t[0].x + t[1].x) + (t[2].x + t[3].x)) + ((t[4].x + t[5].x) + (t[6].x + t[7].x));
        const float y1 = ((t[0].y + t[1].y) + (t[2].y + t[3].y)) + ((t[4].y + t[5].y) + (t[6].y + t[7].y));
        *op = pack_bf16(fmaf(y0, sg, bf_lo(bw)), fmaf(y1, sg, bf_hi(bw)));
      }
    }
    TS(12);
#undef TS_T
  }
}

typedef CUresult (*EncodeFn)(CUtensorMap*, CUtensorMapDataType, cuuint32_t, void*, const cuuint64_t*, const cuuint64_t*, const cuuint32_t*,
                             const cuuint32_t*, CUtensorMapInterleave, CUtensorMapSwizzle, CUtensorMapL2promotion, CUtensorMapFloatOOBfill);

void make_map(EncodeFn enc, CUtensorMap* m, const void* base, const cuuint64_t* dims, const cuuint64_t* strides, const cuuint32_t* box,
              CUtensorMapSwizzle swz) {
  const cuuint32_t es[3] = {1, 1, 1};
  enc(m, CU_TENSOR_MAP_DATA_TYPE_BFLOAT16, 3, (void*)base, dims, strides, box, es, CU_TENSOR_MAP_INTERLEAVE_NONE, swz,
      CU_TENSOR_MAP_L2_PROMOTION_L2_128B, CU_TENSOR_MAP_FLOAT_OOB_FILL_NONE);
}

}

extern "C" void kernel_launch(void* const* d_in, const int* in_sizes, int n_in, void* d_out, int out_size) {
  const __nv_bfloat16* x = (const __nv_bfloat16*)d_in[0];
  const __nv_bfloat16* wqkv = (const __nv_bfloat16*)d_in[1];
  const __nv_bfloat16* wo = (const __nv_bfloat16*)d_in[2];
  void* fn = nullptr;
  cudaDriverEntryPointQueryResult st;
  cudaGetDriverEntryPoint("cuTensorMapEncodeTiled", &fn, cudaEnableDefault, &st);
  EncodeFn enc = (EncodeFn)fn;
  void* scp = nullptr;
  cudaGetSymbolAddress(&scp, g_scratch);
  Maps tm;
  { const cuuint64_t d[3] = {640, 1024, 2}, s[2] = {2560, 1280}; const cuuint32_t b[3] = {64, 128, 1}; make_map(enc, &tm.x, x, d, s, b, CU_TENSOR_MAP_SWIZZLE_128B); }
  { const cuuint64_t d[3] = {640, 640, 3}, s[2] = {3840, 1280}; const cuuint32_t b[3] = {64, 64, 1}; make_map(enc, &tm.w, wqkv, d, s, b, CU_TENSOR_MAP_SWIZZLE_128B); }
  { const cuuint64_t d[3] = {640, 640, 3}, s[2] = {3840, 1280}; const cuuint32_t b[3] = {16, 64, 3}; make_map(enc, &tm.wr, wqkv, d, s, b, CU_TENSOR_MAP_SWIZZLE_32B); }
  { const cuuint64_t d[3] = {32, 640, 20}, s[2] = {1280, 64}; const cuuint32_t b[3] = {32, 80, 2}; make_map(enc, &tm.wo, wo, d, s, b, CU_TENSOR_MAP_SWIZZLE_64B); }
  { const cuuint64_t d[3] = {640, 640, 1}, s[2] = {1280, 819200}; const cuuint32_t b[3] = {16, 80, 1}; make_map(enc, &tm.wor, wo, d, s, b, CU_TENSOR_MAP_SWIZZLE_64B); }
  { const cuuint64_t d[3] = {1536, 640, 1}, s[2] = {3072, 1966080}; const cuuint32_t b[3] = {32, 128, 1};
    make_map(enc, &tm.gate, d_in[5], d, s, b, CU_TENSOR_MAP_SWIZZLE_64B); make_map(enc, &tm.up, d_in[6], d, s, b, CU_TENSOR_MAP_SWIZZLE_64B); }
  { const cuuint64_t d[3] = {640, 1536, 1}, s[2] = {1280, 1966080}; const cuuint32_t b[3] = {8, 128, 1}; make_map(enc, &tm.down, d_in[7], d, s, b, CU_TENSOR_MAP_SWIZZLE_NONE); }
  cudaFuncSetAttribute(fused_kernel, cudaFuncAttributeMaxDynamicSharedMemorySize, SMEM_BYTES);
  fused_kernel<<<128, 512, SMEM_BYTES, cudaStreamPerThread>>>(x, wqkv, wo, (const __nv_bfloat16*)d_in[4], (const __nv_bfloat16*)d_in[5],
                                                              (const __nv_bfloat16*)d_in[6], (const __nv_bfloat16*)d_in[7], (__nv_bfloat16*)d_out, (Scratch*)scp, tm);
}
```

```cpp
#include <cuda_runtime.h>
#include <cuda_bf16.h>
#include <cuda.h>
#include <stdint.h>

#define PFW_NS 100
#define ACT_NS 100
#define OUT_LATE 0
#define REG_P 72
#define REG_C 184
#define AUX_NS 50
#define LEAD 1
#define RST_IT 4
#define ORDX 1
#define THR 2
#define PF_FIRST 3
#define PF_T0 2000
#define PF_CLK 500
#define HK_IT 1
#define F_IT 9
#define F_PER 2
#define F_MAX 8
#define HOLD 2
#define F_LATE 12
#define HALO_NS 0
#define AK 3
#define KEY_NS 60

namespace {

constexpr int SLOT    = 47104;
constexpr int OFF_O   = 122880;
constexpr int OFF_W2  = 4 * SLOT;
constexpr int OFF_CS  = OFF_W2 + 32768;
constexpr int OFF_RS  = OFF_CS + 3840;
constexpr int OFF_MN  = OFF_RS + 576;
constexpr int OFF_WR  = OFF_MN + 1024;
constexpr int OFF_RED = OFF_CS;
constexpr int OFF_HN  = OFF_CS + 2048;
constexpr int OFF_PT  = OFF_WR + 352;
constexpr int OFF_BAR = OFF_PT + 768;
constexpr int SMEM_BYTES = OFF_BAR + 384 + 384;
constexpr uint32_t D0 = 1024 >> 4;
constexpr uint32_t SENT = 0xFFFFFFFFu;
constexpr int SPIN_MAX = 1 << 20;

struct Glob {
  uint4 cand[128][8][24];
  uint32_t act[768];
  uint32_t pad[256];
};
constexpr int GLOB_PER_CTA = sizeof(Glob) / 16 / 128;
static_assert(GLOB_PER_CTA * 128 * 16 == sizeof(Glob), "glob size");
struct Own {
  uint4 halo[5][32];
  uint4 st1[32];
  uint2 cs[32];
  uint4 st2[16];
  uint4 cnt[8];
};
struct Scratch {
  Glob x;
  Own own[128];
  uint4 o[32][8][640];
  uint32_t epoch[128];
};
__device__ __align__(128) Scratch g_scratch;
#define g_x (sc->x)
#define g_own (sc->own)
#define g_o (sc->o)
#define g_epoch (sc->epoch)
#define TS(i)

__device__ __forceinline__ void mbar_init(uint32_t bar, uint32_t cnt) { asm volatile("mbarrier.init.shared::cta.b64 [%0], %1;" :: "r"(bar), "r"(cnt) : "memory"); }
__device__ __forceinline__ void mbar_expect_tx(uint32_t bar, uint32_t bytes) { asm volatile("mbarrier.arrive.expect_tx.shared::cta.b64 _, [%0], %1;" :: "r"(bar), "r"(bytes) : "memory"); }
__device__ __forceinline__ void mbar_arrive(uint32_t bar) { asm volatile("mbarrier.arrive.shared::cta.b64 _, [%0];" :: "r"(bar) : "memory"); }
__device__ __forceinline__ void mbar_arrive_cta(uint32_t bar, uint32_t cta) {
  asm volatile("{\n.reg .b32 ra;\nmapa.shared::cluster.u32 ra, %0, %1;\nmbarrier.arrive.shared::cluster.b64 _, [ra];\n}\n" :: "r"(bar), "r"(cta) : "memory");
}
__device__ __forceinline__ void mbar_wait(uint32_t bar, uint32_t parity) {
  asm volatile("{\n.reg .pred p;\n.reg .u32 n;\nmov.u32 n, 0;\nW:\nmbarrier.try_wait.parity.shared::cta.b64 p, [%0], %1;\n@p bra.uni D;\n"
               "add.u32 n, n, 1;\nsetp.lt.u32 p, n, %2;\n@p bra.uni W;\nD:\n}\n" :: "r"(bar), "r"(parity), "n"(SPIN_MAX) : "memory");
}
__device__ __forceinline__ void tma_3d(uint32_t dst, const void* tm, uint32_t bar, int c0, int c1, int c2) {
  asm volatile("cp.async.bulk.tensor.3d.shared::cluster.global.mbarrier::complete_tx::bytes [%0], [%1, {%3, %4, %5}], [%2];" :: "r"(dst), "l"(tm), "r"(bar), "r"(c0), "r"(c1), "r"(c2) : "memory");
}
__device__ __forceinline__ void tma_3d_mc(uint32_t dst, const void* tm, uint32_t bar, int c0, int c1, int c2) {
  asm volatile("cp.async.bulk.tensor.3d.shared::cluster.global.mbarrier::complete_tx::bytes.multicast::cluster [%0], [%1, {%3, %4, %5}], [%2], %6;" :: "r"(dst), "l"(tm), "r"(bar), "r"(c0), "r"(c1), "r"(c2), "h"((uint16_t)3) : "memory");
}
__device__ __forceinline__ void wgmma_fence() { asm volatile("wgmma.fence.sync.aligned;" ::: "memory"); }
__device__ __forceinline__ void wgmma_commit() { asm volatile("wgmma.commit_group.sync.aligned;" ::: "memory"); }
template <int N> __device__ __forceinline__ void wgmma_wait() { asm volatile("wgmma.wait_group.sync.aligned %0;" :: "n"(N) : "memory"); }
__device__ __forceinline__ uint64_t make_desc(uint32_t addr, uint32_t lbo, uint32_t sbo, uint32_t swz) {
  return (uint64_t)(((addr & 0x3FFFF) >> 4) | ((lbo >> 4) << 16)) | ((uint64_t)((sbo >> 4) | (swz << 30)) << 32);
}
__device__ __forceinline__ void bar_sync(int id, int n) { asm volatile("bar.sync %0, %1;" :: "r"(id), "r"(n) : "memory"); }
__device__ __forceinline__ void st_pkt(void* p, uint32_t a, uint32_t b, uint32_t c, uint32_t d) {
  asm volatile("st.relaxed.gpu.v4.u32 [%0], {%1, %2, %3, %4};" :: "l"(p), "r"(a), "r"(b), "r"(c), "r"(d) : "memory");
}
__device__ __forceinline__ uint4 ldg_pkt(const void* p) {
  uint4 v; asm volatile("ld.relaxed.gpu.global.v4.u32 {%0, %1, %2, %3}, [%4];" : "=r"(v.x), "=r"(v.y), "=r"(v.z), "=r"(v.w) : "l"(p) : "memory"); return v;
}
__device__ __forceinline__ void stg_pkt(void* p, uint32_t a, uint32_t b, uint32_t c, uint32_t d) {
  asm volatile("st.relaxed.gpu.global.v4.u32 [%0], {%1, %2, %3, %4};" :: "l"(p), "r"(a), "r"(b), "r"(c), "r"(d) : "memory");
}
__device__ __forceinline__ uint32_t ldg_rlx32(const void* p) { uint32_t v; asm volatile("ld.relaxed.gpu.global.u32 %0, [%1];" : "=r"(v) : "l"(p) : "memory"); return v; }
__device__ __forceinline__ uint2 ldg_rlx64(const void* p) { uint2 v; asm volatile("ld.relaxed.gpu.global.v2.u32 {%0, %1}, [%2];" : "=r"(v.x), "=r"(v.y) : "l"(p) : "memory"); return v; }
__device__ __forceinline__ void stg128(void* p, const uint4& v) { asm volatile("st.global.v4.u32 [%0], {%1, %2, %3, %4};" :: "l"(p), "r"(v.x), "r"(v.y), "r"(v.z), "r"(v.w) : "memory"); }
__device__ __forceinline__ uint32_t pin(uint32_t v) { asm volatile("" : "+r"(v)); return v; }
__device__ __forceinline__ uint64_t mk64(uint32_t lo, uint32_t hi) { return ((uint64_t)hi << 32) | lo; }
template <class T> __device__ __forceinline__ T* hold(T* p) { return (T*)__shfl_sync(0xffffffffu, (unsigned long long)p, threadIdx.x & 31); }
template <class T> __device__ __forceinline__ T* pin(T* p) { asm volatile("" : "+l"(p)); return p; }
__device__ __forceinline__ void stg_rlx32(void* p, uint32_t v) { asm volatile("st.relaxed.gpu.global.u32 [%0], %1;" :: "l"(p), "r"(v) : "memory"); }
__device__ __forceinline__ void stg_rlx64(void* p, uint32_t a, uint32_t b) { asm volatile("st.relaxed.gpu.global.v2.u32 [%0], {%1, %2};" :: "l"(p), "r"(a), "r"(b) : "memory"); }
__device__ __forceinline__ uint4 ldsm4(uint32_t a) { uint4 v; asm volatile("ldmatrix.sync.aligned.m8n8.x4.shared.b16 {%0, %1, %2, %3}, [%4];" : "=r"(v.x), "=r"(v.y), "=r"(v.z), "=r"(v.w) : "r"(a) : "memory"); return v; }
__device__ __forceinline__ void ldsm4_if(uint4& v, uint32_t a, int off, bool p) {
  asm volatile("{\n.reg .pred q;\nsetp.ne.u32 q, %5, 0;\n@q ldmatrix.sync.aligned.m8n8.x4.shared.b16 {%0, %1, %2, %3}, [%4];\n}\n"
               : "+r"(v.x), "+r"(v.y), "+r"(v.z), "+r"(v.w) : "r"(a + off), "r"((int)p) : "memory");
}
__device__ __forceinline__ uint4 ldsm4t(uint32_t a) { uint4 v; asm volatile("ldmatrix.sync.aligned.m8n8.x4.trans.shared.b16 {%0, %1, %2, %3}, [%4];" : "=r"(v.x), "=r"(v.y), "=r"(v.z), "=r"(v.w) : "r"(a) : "memory"); return v; }
__device__ __forceinline__ void stsm4(uint32_t a, uint32_t x, uint32_t y, uint32_t z, uint32_t w) { asm volatile("stmatrix.sync.aligned.m8n8.x4.shared.b16 [%0], {%1, %2, %3, %4};" :: "r"(a), "r"(x), "r"(y), "r"(z), "r"(w) : "memory"); }
__device__ __forceinline__ void mma_acc(float (&c)[4], const uint4& a, uint32_t b0, uint32_t b1) {
  asm("mma.sync.aligned.m16n8k16.row.col.f32.bf16.bf16.f32 {%0,%1,%2,%3}, {%4,%5,%6,%7}, {%8,%9}, {%0,%1,%2,%3};"
      : "+f"(c[0]), "+f"(c[1]), "+f"(c[2]), "+f"(c[3]) : "r"(a.x), "r"(a.y), "r"(a.z), "r"(a.w), "r"(b0), "r"(b1));
}
__device__ __forceinline__ uint4 lds128(uint32_t a) { uint4 v; asm volatile("ld.shared.v4.u32 {%0, %1, %2, %3}, [%4];" : "=r"(v.x), "=r"(v.y), "=r"(v.z), "=r"(v.w) : "r"(a) : "memory"); return v; }
__device__ __forceinline__ float2 lds64f(uint32_t a) { float2 v; asm volatile("ld.shared.v2.f32 {%0, %1}, [%2];" : "=f"(v.x), "=f"(v.y) : "r"(a)); return v; }
__device__ __forceinline__ float lds32f(uint32_t a) { float v; asm volatile("ld.shared.f32 %0, [%1];" : "=f"(v) : "r"(a)); return v; }
__device__ __forceinline__ void sts32f(uint32_t a, float v) { asm volatile("st.shared.f32 [%0], %1;" :: "r"(a), "f"(v) : "memory"); }
__device__ __forceinline__ uint32_t pack_bf16(float lo, float hi) { uint32_t r; asm("cvt.rn.bf16x2.f32 %0, %1, %2;" : "=r"(r) : "f"(hi), "f"(lo)); return r; }
__device__ __forceinline__ float bf_lo(uint32_t v) { return __uint_as_float(v << 16); }
__device__ __forceinline__ float bf_hi(uint32_t v) { return __uint_as_float(v & 0xffff0000u); }
__device__ __forceinline__ uint32_t movm(uint32_t a) { uint32_t d; asm("movmatrix.sync.aligned.m8n8.trans.b16 %0, %1;" : "=r"(d) : "r"(a)); return d; }
__device__ __forceinline__ float ex2(float x) { float y; asm("ex2.approx.ftz.f32 %0, %1;" : "=f"(y) : "f"(x)); return y; }
__device__ __forceinline__ float rsq(float x) { float y; asm("rsqrt.approx.ftz.f32 %0, %1;" : "=f"(y) : "f"(x)); return y; }
__device__ __forceinline__ float rcp(float x) { float y; asm("rcp.approx.ftz.f32 %0, %1;" : "=f"(y) : "f"(x)); return y; }
__device__ __forceinline__ bool elect() { uint32_t p; asm volatile("{\n.reg .pred q;\nelect.sync _|q, 0xffffffff;\nselp.u32 %0, 1, 0, q;\n}\n" : "=r"(p)); return p; }
__device__ __forceinline__ int clk() { int c; asm volatile("mov.u32 %0, %%clock;" : "=r"(c) :: "memory"); return c; }
__device__ __forceinline__ void pf_l2(const void* p) { asm volatile("prefetch.global.L2 [%0];" :: "l"(p)); }
__device__ __forceinline__ bool anyw(bool p) { return __any_sync(0xffffffffu, p); }
__device__ __forceinline__ float shx(float v, int m) { return __shfl_xor_sync(0xffffffffu, v, m); }
__device__ __forceinline__ void mma_k24(float (&c)[4], uint32_t a0, uint32_t a1, uint32_t a2, uint32_t a3, uint32_t b0, uint32_t b1,
                                        uint32_t e0, uint32_t e1, uint32_t f0) {
  asm("mma.sync.aligned.m16n8k16.row.col.f32.bf16.bf16.f32 {%0,%1,%2,%3}, {%4,%5,%6,%7}, {%8,%9}, {%10,%10,%10,%10};"
      : "=f"(c[0]), "=f"(c[1]), "=f"(c[2]), "=f"(c[3]) : "r"(a0), "r"(a1), "r"(a2), "r"(a3), "r"(b0), "r"(b1), "f"(0.f));
  asm("mma.sync.aligned.m16n8k8.row.col.f32.bf16.bf16.f32 {%0,%1,%2,%3}, {%4,%5}, {%6}, {%0,%1,%2,%3};"
      : "+f"(c[0]), "+f"(c[1]), "+f"(c[2]), "+f"(c[3]) : "r"(e0), "r"(e1), "r"(f0));
}
__device__ __forceinline__ uint32_t ord_key(float r) { uint32_t u = __float_as_uint(r); return u ^ ((uint32_t)((int32_t)u >> 31) | 0x80000000u); }

__device__ __forceinline__ void wgmma_n48hi_ss(float (&d)[120], uint64_t da, uint64_t db, int scale_d) {
  asm volatile("{\n.reg .pred p;\nsetp.ne.b32 p, %26, 0;\n"
    "wgmma.mma_async.sync.aligned.m64n48k16.f32.bf16.bf16 "
    "{%0, %1, %2, %3, %4, %5, %6, %7, %8, %9, %10, %11, %12, %13, %14, %15, "
    "%16, %17, %18, %19, %20, %21, %22, %23}, "
    "%24, %25, p, 1, 1, 0, 1;\n}\n"
    : "+f"(d[96]), "+f"(d[97]), "+f"(d[98]), "+f"(d[99]), "+f"(d[100]), "+f"(d[101]), "+f"(d[102]), "+f"(d[103]),
      "+f"(d[104]), "+f"(d[105]), "+f"(d[106]), "+f"(d[107]), "+f"(d[108]), "+f"(d[109]), "+f"(d[110]), "+f"(d[111]),
      "+f"(d[112]), "+f"(d[113]), "+f"(d[114]), "+f"(d[115]), "+f"(d[116]), "+f"(d[117]), "+f"(d[118]), "+f"(d[119])
    : "l"(da), "l"(db), "r"(scale_d));
}
__device__ __forceinline__ void wgmma_n192lo_ss(float (&d)[120], uint64_t da, uint64_t db, int scale_d) {
  asm volatile("{\n.reg .pred p;\nsetp.ne.b32 p, %98, 0;\n"
    "wgmma.mma_async.sync.aligned.m64n192k16.f32.bf16.bf16 "
    "{%0, %1, %2, %3, %4, %5, %6, %7, %8, %9, %10, %11, %12, %13, %14, %15, "
    "%16, %17, %18, %19, %20, %21, %22, %23, %24, %25, %26, %27, %28, %29, %30, %31, "
    "%32, %33, %34, %35, %36, %37, %38, %39, %40, %41, %42, %43, %44, %45, %46, %47, "
    "%48, %49, %50, %51, %52, %53, %54, %55, %56, %57, %58, %59, %60, %61, %62, %63, "
    "%64, %65, %66, %67, %68, %69, %70, %71, %72, %73, %74, %75, %76, %77, %78, %79, "
    "%80, %81, %82, %83, %84, %85, %86, %87, %88, %89, %90, %91, %92, %93, %94, %95}, "
    "%96, %97, p, 1, 1, 0, 1;\n}\n"
    : "+f"(d[0]), "+f"(d[1]), "+f"(d[2]), "+f"(d[3]), "+f"(d[4]), "+f"(d[5]), "+f"(d[6]), "+f"(d[7]),
      "+f"(d[8]), "+f"(d[9]), "+f"(d[10]), "+f"(d[11]), "+f"(d[12]), "+f"(d[13]), "+f"(d[14]), "+f"(d[15]),
      "+f"(d[16]), "+f"(d[17]), "+f"(d[18]), "+f"(d[19]), "+f"(d[20]), "+f"(d[21]), "+f"(d[22]), "+f"(d[23]),
      "+f"(d[24]), "+f"(d[25]), "+f"(d[26]), "+f"(d[27]), "+f"(d[28]), "+f"(d[29]), "+f"(d[30]), "+f"(d[31]),
      "+f"(d[32]), "+f"(d[33]), "+f"(d[34]), "+f"(d[35]), "+f"(d[36]), "+f"(d[37]), "+f"(d[38]), "+f"(d[39]),
      "+f"(d[40]), "+f"(d[41]), "+f"(d[42]), "+f"(d[43]), "+f"(d[44]), "+f"(d[45]), "+f"(d[46]), "+f"(d[47]),
      "+f"(d[48]), "+f"(d[49]), "+f"(d[50]), "+f"(d[51]), "+f"(d[52]), "+f"(d[53]), "+f"(d[54]), "+f"(d[55]),
      "+f"(d[56]), "+f"(d[57]), "+f"(d[58]), "+f"(d[59]), "+f"(d[60]), "+f"(d[61]), "+f"(d[62]), "+f"(d[63]),
      "+f"(d[64]), "+f"(d[65]), "+f"(d[66]), "+f"(d[67]), "+f"(d[68]), "+f"(d[69]), "+f"(d[70]), "+f"(d[71]),
      "+f"(d[72]), "+f"(d[73]), "+f"(d[74]), "+f"(d[75]), "+f"(d[76]), "+f"(d[77]), "+f"(d[78]), "+f"(d[79]),
      "+f"(d[80]), "+f"(d[81]), "+f"(d[82]), "+f"(d[83]), "+f"(d[84]), "+f"(d[85]), "+f"(d[86]), "+f"(d[87]),
      "+f"(d[88]), "+f"(d[89]), "+f"(d[90]), "+f"(d[91]), "+f"(d[92]), "+f"(d[93]), "+f"(d[94]), "+f"(d[95])
    : "l"(da), "l"(db), "r"(scale_d));
}
__device__ __forceinline__ void wgmma_n48hi_rk(float (&d)[120], uint32_t a0, uint32_t a1, uint32_t a2, uint32_t a3, uint64_t db, int scale_d) {
  asm volatile("{\n.reg .pred p;\nsetp.ne.b32 p, %29, 0;\n"
    "wgmma.mma_async.sync.aligned.m64n48k16.f32.bf16.bf16 "
    "{%0, %1, %2, %3, %4, %5, %6, %7, %8, %9, %10, %11, %12, %13, %14, %15, "
    "%16, %17, %18, %19, %20, %21, %22, %23}, "
    "{%24, %25, %26, %27}, %28, p, 1, 1, 0;\n}\n"
    : "+f"(d[96]), "+f"(d[97]), "+f"(d[98]), "+f"(d[99]), "+f"(d[100]), "+f"(d[101]), "+f"(d[102]), "+f"(d[103]),
      "+f"(d[104]), "+f"(d[105]), "+f"(d[106]), "+f"(d[107]), "+f"(d[108]), "+f"(d[109]), "+f"(d[110]), "+f"(d[111]),
      "+f"(d[112]), "+f"(d[113]), "+f"(d[114]), "+f"(d[115]), "+f"(d[116]), "+f"(d[117]), "+f"(d[118]), "+f"(d[119])
    : "r"(a0), "r"(a1), "r"(a2), "r"(a3), "l"(db), "r"(scale_d));
}
__device__ __forceinline__ void wgmma_n192lo_rk(float (&d)[120], uint32_t a0, uint32_t a1, uint32_t a2, uint32_t a3, uint64_t db, int scale_d) {
  asm volatile("{\n.reg .pred p;\nsetp.ne.b32 p, %101, 0;\n"
    "wgmma.mma_async.sync.aligned.m64n192k16.f32.bf16.bf16 "
    "{%0, %1, %2, %3, %4, %5, %6, %7, %8, %9, %10, %11, %12, %13, %14, %15, "
    "%16, %17, %18, %19, %20, %21, %22, %23, %24, %25, %26, %27, %28, %29, %30, %31, "
    "%32, %33, %34, %35, %36, %37, %38, %39, %40, %41, %42, %43, %44, %45, %46, %47, "
    "%48, %49, %50, %51, %52, %53, %54, %55, %56, %57, %58, %59, %60, %61, %62, %63, "
    "%64, %65, %66, %67, %68, %69, %70, %71, %72, %73, %74, %75, %76, %77, %78, %79, "
    "%80, %81, %82, %83, %84, %85, %86, %87, %88, %89, %90, %91, %92, %93, %94, %95}, "
    "{%96, %97, %98, %99}, %100, p, 1, 1, 0;\n}\n"
    : "+f"(d[0]), "+f"(d[1]), "+f"(d[2]), "+f"(d[3]), "+f"(d[4]), "+f"(d[5]), "+f"(d[6]), "+f"(d[7]),
      "+f"(d[8]), "+f"(d[9]), "+f"(d[10]), "+f"(d[11]), "+f"(d[12]), "+f"(d[13]), "+f"(d[14]), "+f"(d[15]),
      "+f"(d[16]), "+f"(d[17]), "+f"(d[18]), "+f"(d[19]), "+f"(d[20]), "+f"(d[21]), "+f"(d[22]), "+f"(d[23]),
      "+f"(d[24]), "+f"(d[25]), "+f"(d[26]), "+f"(d[27]), "+f"(d[28]), "+f"(d[29]), "+f"(d[30]), "+f"(d[31]),
      "+f"(d[32]), "+f"(d[33]), "+f"(d[34]), "+f"(d[35]), "+f"(d[36]), "+f"(d[37]), "+f"(d[38]), "+f"(d[39]),
      "+f"(d[40]), "+f"(d[41]), "+f"(d[42]), "+f"(d[43]), "+f"(d[44]), "+f"(d[45]), "+f"(d[46]), "+f"(d[47]),
      "+f"(d[48]), "+f"(d[49]), "+f"(d[50]), "+f"(d[51]), "+f"(d[52]), "+f"(d[53]), "+f"(d[54]), "+f"(d[55]),
      "+f"(d[56]), "+f"(d[57]), "+f"(d[58]), "+f"(d[59]), "+f"(d[60]), "+f"(d[61]), "+f"(d[62]), "+f"(d[63]),
      "+f"(d[64]), "+f"(d[65]), "+f"(d[66]), "+f"(d[67]), "+f"(d[68]), "+f"(d[69]), "+f"(d[70]), "+f"(d[71]),
      "+f"(d[72]), "+f"(d[73]), "+f"(d[74]), "+f"(d[75]), "+f"(d[76]), "+f"(d[77]), "+f"(d[78]), "+f"(d[79]),
      "+f"(d[80]), "+f"(d[81]), "+f"(d[82]), "+f"(d[83]), "+f"(d[84]), "+f"(d[85]), "+f"(d[86]), "+f"(d[87]),
      "+f"(d[88]), "+f"(d[89]), "+f"(d[90]), "+f"(d[91]), "+f"(d[92]), "+f"(d[93]), "+f"(d[94]), "+f"(d[95])
    : "r"(a0), "r"(a1), "r"(a2), "r"(a3), "l"(db), "r"(scale_d));
}
__device__ __forceinline__ void wgmma_n80_rs(float (&d)[40], uint32_t a0, uint32_t a1, uint32_t a2, uint32_t a3, uint64_t db, int scale_d) {
  asm volatile("{\n.reg .pred p;\nsetp.ne.b32 p, %45, 0;\n"
    "wgmma.mma_async.sync.aligned.m64n80k16.f32.bf16.bf16 "
    "{%0, %1, %2, %3, %4, %5, %6, %7, %8, %9, %10, %11, %12, %13, %14, %15, "
    "%16, %17, %18, %19, %20, %21, %22, %23, %24, %25, %26, %27, %28, %29, %30, %31, "
    "%32, %33, %34, %35, %36, %37, %38, %39}, "
    "{%40, %41, %42, %43}, %44, p, 1, 1, 1;\n}\n"
    : "+f"(d[0]), "+f"(d[1]), "+f"(d[2]), "+f"(d[3]), "+f"(d[4]), "+f"(d[5]), "+f"(d[6]), "+f"(d[7]),
      "+f"(d[8]), "+f"(d[9]), "+f"(d[10]), "+f"(d[11]), "+f"(d[12]), "+f"(d[13]), "+f"(d[14]), "+f"(d[15]),
      "+f"(d[16]), "+f"(d[17]), "+f"(d[18]), "+f"(d[19]), "+f"(d[20]), "+f"(d[21]), "+f"(d[22]), "+f"(d[23]),
      "+f"(d[24]), "+f"(d[25]), "+f"(d[26]), "+f"(d[27]), "+f"(d[28]), "+f"(d[29]), "+f"(d[30]), "+f"(d[31]),
      "+f"(d[32]), "+f"(d[33]), "+f"(d[34]), "+f"(d[35]), "+f"(d[36]), "+f"(d[37]), "+f"(d[38]), "+f"(d[39])
    : "r"(a0), "r"(a1), "r"(a2), "r"(a3), "l"(db), "r"(scale_d));
}
__device__ __forceinline__ void wgmma_n80_ss(float (&d)[40], uint64_t da, uint64_t db, int scale_d) {
  asm volatile("{\n.reg .pred p;\nsetp.ne.b32 p, %42, 0;\n"
    "wgmma.mma_async.sync.aligned.m64n80k16.f32.bf16.bf16 "
    "{%0, %1, %2, %3, %4, %5, %6, %7, %8, %9, %10, %11, %12, %13, %14, %15, "
    "%16, %17, %18, %19, %20, %21, %22, %23, %24, %25, %26, %27, %28, %29, %30, %31, "
    "%32, %33, %34, %35, %36, %37, %38, %39}, "
    "%40, %41, p, 1, 1, 0, 1;\n}\n"
    : "+f"(d[0]), "+f"(d[1]), "+f"(d[2]), "+f"(d[3]), "+f"(d[4]), "+f"(d[5]), "+f"(d[6]), "+f"(d[7]),
      "+f"(d[8]), "+f"(d[9]), "+f"(d[10]), "+f"(d[11]), "+f"(d[12]), "+f"(d[13]), "+f"(d[14]), "+f"(d[15]),
      "+f"(d[16]), "+f"(d[17]), "+f"(d[18]), "+f"(d[19]), "+f"(d[20]), "+f"(d[21]), "+f"(d[22]), "+f"(d[23]),
      "+f"(d[24]), "+f"(d[25]), "+f"(d[26]), "+f"(d[27]), "+f"(d[28]), "+f"(d[29]), "+f"(d[30]), "+f"(d[31]),
      "+f"(d[32]), "+f"(d[33]), "+f"(d[34]), "+f"(d[35]), "+f"(d[36]), "+f"(d[37]), "+f"(d[38]), "+f"(d[39])
    : "l"(da), "l"(db), "r"(scale_d));
}

__device__ __forceinline__ constexpr int QT(int t) { return t < 8 ? t : 16 + t; }
__device__ __forceinline__ constexpr int KT(int t) { return t < 8 ? 8 + t : 18 + t; }
__device__ __forceinline__ constexpr int VT(int t) { return t < 8 ? 16 + t : 20 + t; }

struct Maps { CUtensorMap x, w, wr, wo, wor, gate, up, down; };

__global__ void __cluster_dims__(2, 1, 1) __launch_bounds__(512, 1)
fused_kernel(const __nv_bfloat16* __restrict__ x, const __nv_bfloat16* __restrict__ wqkv,
             const __nv_bfloat16* __restrict__ wo, const __nv_bfloat16* __restrict__ w_r, const __nv_bfloat16* __restrict__ w_gate,
             const __nv_bfloat16* __restrict__ w_up, const __nv_bfloat16* __restrict__ w_down, __nv_bfloat16* __restrict__ out,
             Scratch* __restrict__ sc, const __grid_constant__ Maps tm) {
  extern __shared__ __align__(1024) uint8_t smem[];
  const int tid = threadIdx.x, warp = __shfl_sync(0xffffffffu, tid >> 5, 0), lane = tid & 31, bid = blockIdx.x;
  const uint32_t sb = (uint32_t)__cvta_generic_to_shared(smem);
  const uint32_t bar_full = sb + OFF_BAR, bar_empty = bar_full + 32, bar_aux = bar_full + 64, bar_ffn = bar_full + 72, bar_win = bar_full + 80, bar_rst = bar_full + 88,
                 bar_o = bar_full + 96, bar_oc = bar_o + 112, bar_st = bar_o + 224, bar_go = bar_o + 248, bar_kv = bar_o + 272;
  if (warp < 4 && elect()) {
    mbar_init(bar_full + 8 * (warp ^ 2), 1);
    mbar_init(bar_empty + 8 * warp, 24);
    mbar_init(bar_aux + 8 * warp, warp == 0 ? 64 : warp == 2 ? 32 : 1);
    asm volatile("fence.mbarrier_init.release.cluster;" ::: "memory");
  }
  asm volatile("barrier.cluster.arrive.relaxed.aligned;" ::: "memory");
  if (warp >= 8 && warp < 11 && elect()) asm volatile("prefetch.tensormap [%0];" :: "l"(&tm.x + (warp - 8)) : "memory");
  auto pf_slice = [&](int ks) {
    pf_l2(lane < 16 ? (const char*)x + ((bid * 16 + lane) * 1280 + ks * 128) : (const char*)wqkv + ((bid * 15 + min(lane, 30) - 16) * 128 + ks * 245760));
  };
  if (warp == 4) pf_slice(0);
  const int rank = bid & 1, cl = bid >> 1;
  const int q7 = ((cl - 36) * 37) >> 8;
  const int P = cl < 4 ? 0 : cl < 36 ? (cl - 4) & 7 : cl - 35 - 7 * q7;
  const int g = cl < 4 ? 4 + cl : cl < 36 ? (cl - 4) >> 3 : 4 + q7;
  const int mt = 2 * P + rank, cid = mt * 8 + g;
  const bool ffn1 = g >= 5;
  const int fj = ffn1 ? mt * 3 + g - 5 : (P * 5 + g) * 2 + rank;
  const int ord = ((g >> 2) ^ P) & 1;
  auto ks_of = [&](int it) { return !ORDX || ord == 0 || it == 0 ? it : it <= 5 ? it + 4 : it - 5; };
  auto load_w = [&](int it, uint32_t a, uint32_t full) {
    tma_3d_mc(a + 16384 + rank * 16384, &tm.w, full, g * 80, it * 64, rank * 2);
    tma_3d_mc(a + (rank ? 40960 : 24576), rank ? &tm.wr : &tm.w, full, g * 80 + rank * 64, it * 64, 1 - rank);
  };
  if (warp == 0 && elect()) {
    mbar_expect_tx(bar_full + 16, SLOT);
    tma_3d(sb + 2 * SLOT, &tm.x, bar_full + 16, 0, P * 128, rank);
  }
  asm volatile("barrier.cluster.wait.aligned;" ::: "memory");
  if (warp == 0) {
    if (elect()) load_w(0, sb + 2 * SLOT, bar_full + 16);
    asm volatile("bar.arrive 4, 64;" ::: "memory");
  }

  if (warp >= 8) {
    asm volatile("setmaxnreg.dec.sync.aligned.u32 %0;" :: "n"(REG_P));
#define TS_T 0
    if (warp == 8) {
      TS(8);
      bar_sync(4, 64);
      if (elect()) {
        TS(10);
        int fjn = 0;
#pragma unroll 1
        for (int it = 1; it < 17; it++) {
          const int s = (it + 2) & 3;
          const uint32_t full = bar_full + 8 * s, a = sb + s * SLOT;
          if (it >= 13) { mbar_wait(bar_oc + 8 * (it - 13), 0); mbar_wait(bar_oc + 56 + 8 * (it - 13), 0); }
          else if (it >= 4) mbar_wait(bar_empty + 8 * s, ((it >> 2) - 1) & 1);
          else if (it >= THR) mbar_wait(bar_full + 8 * ((it - THR + 2) & 3), 0);
          if (it < 10) {
            const int ks = ks_of(it);
            mbar_expect_tx(full, SLOT);
            tma_3d(a, &tm.x, full, ks * 64, P * 128, rank);
            load_w(ks, a, full);
            TS(12 + it);
            if ((unsigned)(it - RST_IT) < 2u) {
              mbar_wait(bar_rst, 0);
              asm volatile("cp.async.bulk.global.shared::cta.bulk_group [%0], [%1], %2;\ncp.async.bulk.commit_group;"
                           :: "l"(it == RST_IT ? (uint4*)(g_own + cid) : (uint4*)&g_x + cid * GLOB_PER_CTA), "r"(sb + OFF_CS),
                              "r"(it == RST_IT ? (int)sizeof(Own) : GLOB_PER_CTA * 16) : "memory");
            }
            if (it == RST_IT + 2) { asm volatile("cp.async.bulk.wait_group 0;" ::: "memory"); mbar_arrive(bar_rst); }
          } else if (it < 13) {
            const int g0 = 3 * (it - 10), g1 = min(g0 + 3, 8);
            mbar_expect_tx(full, (g1 - g0) * 12800);
#pragma unroll 1
            for (int gp = g0 + ((g0 ^ rank) & 1); gp < g1; gp += 2) {
              tma_3d_mc(sb + gp * 15360, &tm.wo, full, 0, gp * 80, g * 2);
              tma_3d_mc(sb + gp * 15360 + 10240, &tm.wor, full, 512 + g * 16, gp * 80, 0);
            }
          }
          if (it == 4) mbar_expect_tx(bar_ffn, ffn1 ? 81920 : 24576);
          const int j1 = ffn1 ? (it >= 13 ? min(2 * it - 21, 10) : min(max(it - F_IT + 1, 0), 4)) : (it >= 13 ? (it == 16 ? 12 : min(F_MAX + (it - 12) * F_LATE, 12)) : min(max((it - F_IT + 1) * F_PER, 0), F_MAX));
#pragma unroll 1
          for (; fjn < j1; fjn++) {
            const int j = fjn < 4 ? fjn + 6 : fjn - 4;
            if (ffn1) tma_3d(sb + (j < 6 ? 0 : OFF_W2 - 49152) + j * 8192, j < 5 ? &tm.gate : &tm.up, bar_ffn, fj * 32, (j < 5 ? j : j - 5) * 128, 0);
            else tma_3d(sb + OFF_W2 + fjn * 2048, &tm.down, bar_ffn, fj * 8, fjn * 128, 0);
          }
        }
        TS(11);
      }
#undef TS_T
#define TS_T 64
    } else if (warp >= 12) {
      const int l7 = lane & 7, j = warp - 12, ch = min((P >> 1) * 4 + rank * 2 + (j >> 1), 14);
      const uint32_t sxo = ((g & 3) * 32 + j * 8 + l7) * 128 + (((lane >> 3) ^ l7) * 16);
      const uint32_t swo = ch < 12 ? 16384 + (ch >> 2) * 8192 + lane * 128 + ((((ch & 3) * 2 + (j & 1)) ^ l7) * 16)
                                   : 40960 + (ch - 12) * 2048 + lane * 32 + (((j & 1) ^ (l7 >> 2)) * 16);
      float ps = 0.f, pq = 0.f, pq1 = 0.f, pc = 0.f;
#pragma unroll 1
      for (int it = ord; it < ord + 5; it++) {
        const int sl = (it + 2) & 3;
        mbar_wait(bar_full + 8 * sl, (it >> 2) & 1);
        TS(it);
        const uint32_t a = sb + sl * SLOT;
        const uint4 v0 = ldsm4(a + sxo), v1 = ldsm4((a + sxo) ^ 64), w0 = ldsm4t(a + swo), w1 = ldsm4t(a + swo + (ch < 12 ? 4096 : 1024));
        if (lane + (int)((v0.x & v1.x & w0.x & w1.x) == 0x7fc17fc1u && (v0.x | v1.x) == 0u) < 2) mbar_arrive_cta(bar_empty + 8 * sl, lane);
        const uint32_t vv[8] = {v0.x, v0.y, v0.z, v0.w, v1.x, v1.y, v1.z, v1.w}, ww[8] = {w0.x, w0.y, w0.z, w0.w, w1.x, w1.y, w1.z, w1.w};
#pragma unroll
        for (int i = 0; i < 8; i++) {
          const float d = bf_lo(vv[i]), e = bf_hi(vv[i]);
          ps += d + e; pq = fmaf(d, d, pq); pq1 = fmaf(e, e, pq1); pc += bf_lo(ww[i]) + bf_hi(ww[i]);
        }
      }
      pq += pq1;
      ps += shx(ps, 1); pq += shx(pq, 1); pc += shx(pc, 1);
      ps += shx(ps, 2); pq += shx(pq, 2); pc += shx(pc, 2);
      const int c = lane & 3;
      if (c < 3) sts32f(sb + OFF_PT + (c * 32 + j * 8 + (lane >> 2)) * 4, c == 0 ? ps : c == 1 ? pq : pc);
      asm volatile("bar.arrive 2, 224;" ::: "memory");
      if (warp == 12) {
        const uint4* const hp = hold(&g_own[max(cid - 16, 0)].halo[0][lane]);
        mbar_wait(bar_aux, 0);
        mbar_wait(bar_go, 0);
        uint4 v[5] = {};
        int guard = SPIN_MAX;
        if (P > 0) {
          do {
#pragma unroll
            for (int i = 0; i < 5; i++) v[i] = ldg_pkt(hp + 32 * i);
          } while (anyw(v[0].x == SENT || v[1].x == SENT || v[2].x == SENT || v[3].x == SENT || v[4].x == SENT) && --guard > 0);
        }
#pragma unroll
        for (int i = 0; i < 5; i++) *(uint4*)(smem + OFF_O + 10240 + i * 512 + lane * 16) = v[i];
        mbar_arrive(bar_kv);
      }
#undef TS_T
#define TS_T 32
    } else if (warp < 11) {
      Own* const own = g_own + cid;
      const int l7 = lane & 7, hk = lane >> 4, idx = lane;
      if (warp == 10 && elect()) {
#pragma unroll 1
        for (int i = 0; i < 36; i++) mbar_init(bar_o + 8 * i, i < 14 ? 1 : i < 34 ? 4 : 128);
      }
      {
        const int t0 = clk();
#pragma unroll 1
        for (int i = PF_FIRST; i < 6; i++) {
          while (clk() - t0 < PF_T0 + (i - PF_FIRST) * PF_CLK) __nanosleep(20);
          pf_slice(warp == 9 ? min(i, 4) : i + 4);
        }
      }
      bar_sync(2, 224);
      mbar_wait(bar_rst, 1);
      TS(0);
      const uint32_t tag = __float_as_uint(lds32f(sb + OFF_WR + 324));
      const float s0 = lds32f(sb + OFF_PT + lane * 4 + (warp - 9) * 256), q0 = lds32f(sb + OFF_PT + 128 + lane * 4);
      int guard = SPIN_MAX;
      if (warp == 9) {
        stg_pkt(&own->st1[idx], __float_as_uint(s0), __float_as_uint(q0), tag, 0u);
        TS(1);
        const uint4* sp = &g_own[mt * 8].st1[lane];
        const uint4* hp = &g_own[max(mt - 2, 0) * 8 + 3].st1[24 + l7];
        uint4 a[5], b[5];
        bool bad;
        do {
          __nanosleep(AUX_NS);
          bad = false;
#pragma unroll
          for (int i = 0; i < 5; i++) {
            const uint4* q = i < 4 ? sp + i * (sizeof(Own) / 16) : hp;
            a[i] = ldg_pkt(q); b[i] = ldg_pkt(q + 4 * sizeof(Own) / 16);
          }
#pragma unroll
          for (int i = 0; i < 5; i++) bad |= a[i].z != tag || b[i].z != tag;
        } while (anyw(bad) && --guard);
#pragma unroll
        for (int i = 0; i < 5; i++) {
          const float m = (__uint_as_float(a[i].x) + __uint_as_float(b[i].x)) * (1.f / 640.f);
          const float rs = rsq(fmaxf(fmaf(-m, m, (__uint_as_float(a[i].y) + __uint_as_float(b[i].y)) * (1.f / 640.f)), 0.f) + 1e-5f);
          ((float*)(smem + OFF_RS))[i < 4 ? 8 + lane + 32 * i : l7] = rs;
          const uint32_t mh = pack_bf16(-m, -m);
          const float ml = -m - bf_lo(mh);
          if (i < 4) ((uint2*)(smem + OFF_MN))[lane + 32 * i] = make_uint2(mh, pack_bf16(ml, ml));
        }
      } else {
        stg_rlx64(&own->cs[idx], __float_as_uint(s0), tag);
        const uint4* cp = (const uint4*)g_own[hk * 8 + g].cs + (lane & 15);
        uint4 a[4], b[4];
        bool bad;
        do {
          __nanosleep(AUX_NS);
          bad = false;
#pragma unroll
          for (int i = 0; i < 4; i++) { a[i] = ldg_pkt(cp + i * 32 * sizeof(Own) / 16); b[i] = ldg_pkt(cp + (i * 32 + 16) * sizeof(Own) / 16); }
#pragma unroll
          for (int i = 0; i < 4; i++) bad |= a[i].y != tag || a[i].w != tag || b[i].y != tag || b[i].w != tag;
        } while (anyw(bad) && --guard);
#pragma unroll
        for (int i = 0; i < 4; i++)
          if (i < 3 || lane < 24) {
            const float c0 = __uint_as_float(a[i].x) + __uint_as_float(b[i].x), c1 = __uint_as_float(a[i].z) + __uint_as_float(b[i].z);
            const uint32_t hi = pack_bf16(c0, c1), w0 = pack_bf16(c0, c0 - bf_lo(hi)), w1 = pack_bf16(c1, c1 - bf_hi(hi));
            uint4* const d = (uint4*)(smem + OFF_CS) + 2 * (lane + 32 * i);
            d[0] = make_uint4(w0, w0, 0, 0); d[1] = make_uint4(w1, w1, 0, 0);
          }
        asm volatile("fence.proxy.async.shared::cta;" ::: "memory");
      }
      mbar_arrive(bar_aux);
      TS(2);
      const int fo = warp - 9, wq = fo ? 1 - LEAD : LEAD;
      const uint4* const fp = hold(g_own[mt * 8 + wq * 4].cnt);
      const char* src = hold((const char*)g_o[mt * 2 + wq]);
      if (elect()) {
        const uint32_t bo = bar_o + fo * 56;
#pragma unroll
        for (int i = 0; i < 7; i++) mbar_expect_tx(bo + 8 * i, 10240);
        mbar_wait(bar_st + 8 * fo, 0);
        while (ldg_rlx32(fp) != 32u && --guard > 0) {}
        asm volatile("fence.proxy.async.global;" ::: "memory");
        TS(6);
#pragma unroll
        for (int i = 0; i < 7; i++) {
          if (fo || i == 6) mbar_wait(bo + 64 + 8 * i, 0);
          else if (i == 4) mbar_wait(bar_st + 8, 0);
          if (i == g) src += 10240;
          asm volatile("cp.async.bulk.shared::cluster.global.mbarrier::complete_tx::bytes [%0], [%1], 10240, [%2];"
                       :: "r"(sb + OFF_O + ((i + 2) % 6) * 10240 + fo * (i == 3 ? -51200 : 10240)), "l"(src + i * 10240), "r"(bo + 8 * i) : "memory");
        }
      }
#undef TS_T
#define TS_T 96
    } else {
      if ((sb & 0x3FFFF) != D0 * 16) __trap();
#pragma unroll 1
      for (int i = lane; i < 232; i += 32) { const uint32_t f = i < 208 ? SENT : 0u; ((uint4*)(smem + OFF_CS))[i] = make_uint4(f, f, f, f); }
      asm volatile("fence.proxy.async.shared::cta;" ::: "memory");
      if (elect()) mbar_arrive(bar_rst);
      mbar_wait(bar_full + 8 * ((HK_IT + 2) & 3), 0);
      TS(4);
      const uint32_t epoch = ldg_rlx32(g_epoch + cid) + 1;
      uint32_t wv[10];
#pragma unroll
      for (int i = 0; i < 10; i++) wv[i] = __ldg((const uint32_t*)w_r + lane + 32 * i);
      float s = 0.f;
#pragma unroll
      for (int i = 0; i < 10; i++) {
        s += bf_lo(wv[i]) + bf_hi(wv[i]);
        const unsigned u = i < 8 ? lane + 32 * (i - g) : lane + 32 * (i - 7) - g * 8;
        if (i < 8 ? u < 32u : u - 32u < 8u) *(float2*)(smem + OFF_WR + ((u & 3) * 10 + (u >> 2)) * 8) = make_float2(bf_lo(wv[i]), bf_hi(wv[i]));
      }
#pragma unroll
      for (int m = 1; m < 32; m <<= 1) s += shx(s, m);
      *(float2*)(smem + OFF_WR + 320) = make_float2(s, __uint_as_float(epoch * 0x9E3779B8u));
      g_epoch[cid] = epoch;
      TS(3);
      TS(5);
      asm volatile("bar.arrive 2, 224;" ::: "memory");
#pragma unroll 1
      for (int i = 0; i < 14; i++) {
        const int m = (i + 2) >> 2, n = m == 0 ? 50 : 120, t = (m == 0 ? i : (i + 2) & 3) * 32 + lane;
        const char* b = (const char*)(m == 0 ? wo : m == 1 ? w_up : m == 2 ? w_down : w_gate);
        if (t < n) pf_l2(b + (bid * n + t) * 128);
        __nanosleep(PFW_NS);
      }
      const uint4* const kp = hold(g_own[1].cnt);
      const uint4* const cb = hold(&g_x.cand[0][lane >> 2][lane & 3]);
      bar_sync(3, 64);
      uint4 k;
      uint32_t have = SENT;
      int guard = SPIN_MAX;
      while (true) {
        k = ldg_pkt(kp);
        if (ffn1) {
          while (k.x != have && --guard > 0) {
            const uint32_t tk = 2047u - (k.x & 2047u), want = k.x;
            const uint4* q = cb + ((tk >> 8) * 16 + (tk & 1) * 8 + ((tk >> 5) & 7)) * 192;
            const uint4 c0 = ldg_pkt(q), c1 = ldg_pkt(q + 4); const uint2 c2 = ldg_rlx64(q + 8);
            k = ldg_pkt(kp);
            *(uint4*)(smem + OFF_HN + lane * 16) = c0; *(uint4*)(smem + OFF_HN + 512 + lane * 16) = c1; *(uint2*)(smem + OFF_HN + 1024 + lane * 16) = c2;
            have = anyw(c0.x == SENT || c1.x == SENT || c2.x == SENT) ? SENT : want;
          }
        } else if (KEY_NS && k.z != 128u) __nanosleep(KEY_NS);
        if (k.z == 128u || --guard <= 0) break;
      }
      *(uint2*)(smem + OFF_WR + 336) = make_uint2(k.x, k.y);
      mbar_arrive(bar_win);
      TS(7);
    }
#undef TS_T
  } else {
#define TS_T 0
    asm volatile("setmaxnreg.inc.sync.aligned.u32 %0;" :: "n"(REG_C));
    const int wg = warp >> 2, w4 = warp & 3, r = lane >> 2, c = lane & 3;
    float acc[120];
    uint4 xr[5] = {};
    const uint32_t xa = pin(sb + (warp * 16 + (lane & 15)) * 128 + ((lane >> 4) ^ (lane & 7)) * 16);
    const int fol = wg != LEAD;
    const bool first = (P == 0) && (warp == 0);
    const uint32_t kvs = sb + OFF_O + fol * 10240 + w4 * 2560 + lane * 16;
    uint4* const kvd = hold(warp == 7 ? &g_own[cid].halo[0][lane] : (uint4*)(smem + (warp == 3 ? OFF_O + lane * 16 : kvs - sb + 2560)));
    uint4* const odst = hold(&g_o[mt * 2 + wg][g][w4 * 160]);
    uint4* const ocnt = hold(g_own[mt * 8 + wg * 4].cnt);
    uint32_t m0 = 0, m1 = 0;
    const uint32_t mna = pin(sb + OFF_MN + (warp * 16 + r) * 8 + c * 4);
    const int itx = ord == 0 || g == 0 ? g : g < 5 ? g + 5 : g - 4, ity = (ord ? 4 : 8) + (g >> 2);
    uint32_t rel;
    asm volatile("mapa.shared::cluster.u32 %0, %1, %2;" : "=r"(rel) : "r"(bar_empty), "r"(tid & 1));
    const uint32_t xa1 = pin(xa ^ 32), xa2 = pin(xa ^ 64), xa3 = pin(xa ^ 96), xb = pin(xa ^ ((g & 3) * 32));
    const uint32_t da0 = wg * 512;
    const bool rel2 = lane < 2, rel6 = lane < 2 + 2 * (warp & 1);
    const uint32_t zero = (uint32_t)(uintptr_t)x & 8u;
    mbar_wait(bar_full + 16, 0);
    TS(13);
    wgmma_fence();
#pragma unroll
    for (int it = 0; it < 10; it++) {
      const int s = (it + 2) & 3;
      if (it == 9 && fol) bar_sync(10, 256);
#pragma unroll
      for (int kk = 0; kk < 4; kk++) {
        if (kk == 2 && it > 0) {
          wgmma_commit();
          wgmma_wait<1>();
          const uint32_t ra = ((xr[0].x ^ xr[1].x ^ xr[2].x ^ xr[3].x ^ xr[4].x) & zero) | rel;
          if (it == 1 ? (ord ? rel6 : rel2) : it == 6 ? (ord ? rel2 : rel6) : it < 6 ? rel2 : rel6)
            asm volatile("mbarrier.arrive.shared::cluster.b64 _, [%0];" :: "r"(ra + 8 * ((it + 1) & 3)) : "memory");
        }
        if (kk == 2) {
          ldsm4_if(xr[0], xa, s * SLOT, it == itx); ldsm4_if(xr[1], xa1, s * SLOT, it == itx);
          ldsm4_if(xr[2], xa2, s * SLOT, it == itx); ldsm4_if(xr[3], xa3, s * SLOT, it == itx);
          if ((it & 6) == 4 || it >= 8) ldsm4_if(xr[4], xb, s * SLOT, it == ity);
        }
        if (kk == AK && it == 9) {
          mbar_wait(bar_aux, 0);
          TS(3);
          if (c < 2) { m0 = __float_as_uint(lds32f(mna)); m1 = __float_as_uint(lds32f(mna + 64)); }
          if (!fol) bar_sync(11, 256);
        }
        if (kk == 3 && it < 9) {
          mbar_wait(bar_full + 8 * ((it + 3) & 3), ((it + 1) >> 2) & 1);
          TS(14 + it);
        }
        const uint64_t da = mk64(da0 + (D0 + s * (SLOT >> 4) + kk * 2 + (1 << 16)), 0x40000040u);
        wgmma_n48hi_ss(acc, da, mk64(D0 + s * (SLOT >> 4) + 2560 + kk * 32 + (128 << 16), 0xC0000010u), (it | kk) != 0);
        wgmma_n192lo_ss(acc, da, mk64(D0 + s * (SLOT >> 4) + 1024 + kk * 128 + (512 << 16), 0x40000040u), (it | kk) != 0);
      }
      wgmma_commit();
      if (it == 8 && fol) asm volatile("bar.arrive 11, 256;" ::: "memory");
    }
    {
      const uint64_t dc = make_desc(D0 * 16 + OFF_CS, 0, 128, 0);
      wgmma_fence();
      wgmma_n48hi_rk(acc, m0, m1, 0u, 0u, dc + 192, 1);
      wgmma_n192lo_rk(acc, m0, m1, 0u, 0u, dc, 1);
      wgmma_commit();
      if (!fol) asm volatile("bar.arrive 10, 256;" ::: "memory");
    }
    const uint32_t stb = sb + OFF_RS + warp * 64;
    const float rlo = lds32f(stb + (8 + r) * 4), rhi = lds32f(stb + (16 + r) * 4);
    wgmma_wait<0>();
#pragma unroll
    for (int i = 0; i < 120; i++) asm volatile("" : "+f"(acc[i]) :: "memory");
    if (fol && lane == 0) mbar_arrive(bar_go);
    TS(2);
    uint32_t Qlo[10], Qhi[10], Klo[10], Khi[10], Vlo[10], Vhi[10];
#pragma unroll
    for (int t = 0; t < 10; t++) {
      const int k = KT(t), v = VT(t);
      Khi[t] = pack_bf16(acc[4 * k + 2], acc[4 * k + 3]);
      Vhi[t] = pack_bf16(acc[4 * v + 2] * rhi, acc[4 * v + 3] * rhi);
    }
    st_pkt(kvd, Khi[0], Khi[1], Khi[3], Khi[4]);
    st_pkt(kvd + 32, Khi[5], Khi[6], Khi[8], Khi[9]);
    st_pkt(kvd + 64, Khi[2], Khi[7], Vhi[0], Vhi[1]);
    st_pkt(kvd + 96, Vhi[2], Vhi[3], Vhi[4], Vhi[5]);
    st_pkt(kvd + 128, Vhi[6], Vhi[7], Vhi[8], Vhi[9]);
    if (warp < 7) mbar_arrive(bar_kv + ((warp + 1) >> 2) * 8);
    mbar_wait(bar_aux, 0);
#pragma unroll
    for (int t = 0; t < 10; t++) {
      const int q = QT(t), k = KT(t), v = VT(t);
      Vhi[t] = movm(Vhi[t]);
      Klo[t] = pack_bf16(acc[4 * k], acc[4 * k + 1]);
      Vlo[t] = movm(pack_bf16(acc[4 * v] * rlo, acc[4 * v + 1] * rlo));
      Qlo[t] = pack_bf16(acc[4 * q], acc[4 * q + 1]);
      Qhi[t] = pack_bf16(acc[4 * q + 2], acc[4 * q + 3]);
    }
    const bool in0 = 2 * c <= r, in1 = 2 * c + 1 <= r;
    const uint32_t mL = (in0 ? 0xffffu : 0u) | (in1 ? 0xffff0000u : 0u);
    const float qs = 0.22360679774997896f * 1.4426950408889634f;
    const uint32_t kb0 = stb + (2 * c + (in0 ? 8 : 0)) * 4, kb1 = stb + (2 * c + 1 + (in1 ? 8 : 0)) * 4;
    const float scl0 = lds32f(kb0) * rlo * qs, scl1 = lds32f(kb1) * rlo * qs;
    const float sch0 = lds32f(kb0 + 32) * rhi * qs, sch1 = lds32f(kb1 + 32) * rhi * qs;
    const float bias0 = (first && !in0) ? -INFINITY : 0.f, bias1 = (first && !in1) ? -INFINITY : 0.f;
    const int slot = mt * 8 + warp;
    int guard = SPIN_MAX;
    uint4 pv[5];
    const bool cA = c < 2, nA = r < 4;
    TS(0);
    mbar_wait(bar_go + fol * 8, 0);
    TS(23);
    uint32_t qe[4][2];
    float sl0[4], sl1[4], th0[4], th1[4];
#pragma unroll
    for (int hd = 0; hd < 4; hd++) {
      const int ta = 5 * (hd >> 1) + 3 * (hd & 1), ts = 5 * (hd >> 1) + 2;
      const bool mine = (hd & 1) ? !cA : cA;
      qe[hd][0] = mine ? Qlo[ts] : 0u; qe[hd][1] = mine ? Qhi[ts] : 0u;
      float sl[4], sh[4];
      mma_k24(sl, Qlo[ta], Qhi[ta], Qlo[ta + 1], Qhi[ta + 1], Klo[ta], Klo[ta + 1], qe[hd][0], qe[hd][1], Klo[ts]);
      mma_k24(sh, Qlo[ta], Qhi[ta], Qlo[ta + 1], Qhi[ta + 1], Khi[ta], Khi[ta + 1], qe[hd][0], qe[hd][1], Khi[ts]);
      th0[hd] = (in0 ? sh[2] : sl[2]) * sch0; th1[hd] = (in1 ? sh[3] : sl[3]) * sch1;
      float mh = fmaxf(th0[hd], th1[hd]);
      mh = fmaxf(mh, shx(mh, 1)); mh = fmaxf(mh, shx(mh, 2));
      th0[hd] -= mh; th1[hd] -= mh;
      sl0[hd] = sl[0]; sl1[hd] = sl[1];
    }
    mbar_wait(bar_kv + wg * 8, 0);
    TS(4);
#pragma unroll
    for (int j = 0; j < 5; j++) pv[j] = lds128(kvs + 512 * j);
    const uint32_t Kp[10] = {pv[0].x, pv[0].y, pv[2].x, pv[0].z, pv[0].w, pv[1].x, pv[1].y, pv[2].y, pv[1].z, pv[1].w};
    const uint32_t Vp[10] = {movm(pv[2].z), movm(pv[2].w), movm(pv[3].x), movm(pv[3].y), movm(pv[3].z), movm(pv[3].w), movm(pv[4].x), movm(pv[4].y), movm(pv[4].z), movm(pv[4].w)};
    const uint32_t ONES = 0x3f803f80u;
    uint32_t of[20];
#pragma unroll
    for (int hp = 0; hp < 2; hp++) {
      float o[6][4];
#pragma unroll
      for (int hh = 0; hh < 2; hh++) {
        const int hd = 2 * hp + hh, ta = 5 * hp + 3 * hh, ts = 5 * hp + 2;
        float sp[4];
        mma_k24(sp, Qlo[ta], Qhi[ta], Qlo[ta + 1], Qhi[ta + 1], Kp[ta], Kp[ta + 1], qe[hd][0], qe[hd][1], Kp[ts]);
        const float tl0 = fmaf(in0 ? sl0[hd] : sp[0], scl0, bias0), tl1 = fmaf(in1 ? sl1[hd] : sp[1], scl1, bias1);
        float ml = fmaxf(tl0, tl1);
        ml = fmaxf(ml, shx(ml, 1)); ml = fmaxf(ml, shx(ml, 2));
        if (HOLD == 1 && hd == 3 && !fol && lane == 0) mbar_arrive(bar_go + 8);
        const uint32_t Pl = pack_bf16(ex2(tl0 - ml), ex2(tl1 - ml)), Ph = pack_bf16(ex2(th0[hd]), ex2(th1[hd]));
        const uint32_t a0 = Pl & mL, a1 = Ph & ~mL, a3 = Ph & mL, ap = Pl & ~mL;
        const bool vm = hh == 0 ? nA : !nA;
        mma_k24(o[3 * hh], a0, a1, 0u, a3, Vlo[ta], Vhi[ta], ap, 0u, Vp[ta]);
        mma_k24(o[3 * hh + 1], a0, a1, 0u, a3, Vlo[ta + 1], Vhi[ta + 1], ap, 0u, Vp[ta + 1]);
        mma_k24(o[3 * hh + 2], a0, a1, 0u, a3, vm ? Vlo[ts] : ONES, vm ? Vhi[ts] : ONES, ap, 0u, vm ? Vp[ts] : ONES);
      }
      const float il = rcp(cA ? o[5][0] : o[2][0]), ih = rcp(cA ? o[5][2] : o[2][2]);
      const float jl = shx(il, 2), jh = shx(ih, 2);
      const float al = cA ? jl : il, ah = cA ? jh : ih, bl = cA ? il : jl, bh = cA ? ih : jh;
      const int t0 = 5 * hp;
      of[2 * t0]     = pack_bf16(o[0][0] * al, o[0][1] * al); of[2 * t0 + 1] = pack_bf16(o[0][2] * ah, o[0][3] * ah);
      of[2 * t0 + 2] = pack_bf16(o[1][0] * al, o[1][1] * al); of[2 * t0 + 3] = pack_bf16(o[1][2] * ah, o[1][3] * ah);
      of[2 * t0 + 4] = pack_bf16((cA ? o[2][0] : o[5][0]) * jl, (cA ? o[2][1] : o[5][1]) * jl);
      of[2 * t0 + 5] = pack_bf16((cA ? o[2][2] : o[5][2]) * jh, (cA ? o[2][3] : o[5][3]) * jh);
      of[2 * t0 + 6] = pack_bf16(o[3][0] * bl, o[3][1] * bl); of[2 * t0 + 7] = pack_bf16(o[3][2] * bh, o[3][3] * bh);
      of[2 * t0 + 8] = pack_bf16(o[4][0] * bl, o[4][1] * bl); of[2 * t0 + 9] = pack_bf16(o[4][2] * bh, o[4][3] * bh);
    }
    {
      const uint32_t os = sb + OFF_O + (fol ? 0 : 20480) + w4 * 2560, oa = os + ((lane >> 3) & 1) * 1280 + (lane >> 4) * 128 + (lane & 7) * 16;
#pragma unroll
      for (int s = 0; s < 5; s++) {
        stsm4(oa + s * 256, of[4 * s], of[4 * s + 1], of[4 * s + 2], of[4 * s + 3]);
        if (s == 0 && (fol || HOLD == 2) && lane == 0) mbar_arrive(bar_go + 8 + 8 * fol);
      }
      asm volatile("fence.proxy.async.shared::cta;" ::: "memory");
      __syncwarp();
      if (elect()) {
        asm volatile("cp.async.bulk.global.shared::cta.bulk_group [%0], [%1], 2560;\ncp.async.bulk.commit_group;" :: "l"(odst), "r"(os) : "memory");
      }
    }
    TS(5);
    float h[40];
#pragma unroll
    for (int s = 0; s < 5; s++) {
      const uint4 v = xr[s];
      h[8 * s] = bf_lo(v.x); h[8 * s + 1] = bf_hi(v.x); h[8 * s + 2] = bf_lo(v.y); h[8 * s + 3] = bf_hi(v.y);
      h[8 * s + 4] = bf_lo(v.z); h[8 * s + 5] = bf_hi(v.z); h[8 * s + 6] = bf_lo(v.w); h[8 * s + 7] = bf_hi(v.w);
    }
    if (elect()) {
      asm volatile("cp.async.bulk.wait_group 0;" ::: "memory");
      asm volatile("red.relaxed.gpu.global.add.u32 [%0], 1;" :: "l"(ocnt) : "memory");
      mbar_arrive(bar_st + 8 * fol);
    }
    __syncwarp();
    mbar_wait(bar_full, 0); mbar_wait(bar_full + 8, 0); mbar_wait(bar_full + 16, 1);
    mbar_wait(bar_go + 16, 0);
    const uint64_t dwo = make_desc(D0 * 16, 5120, 512, 2);
    wgmma_fence();
#pragma unroll
    for (int s = 0; s < 5; s++) wgmma_n80_rs(h, of[4 * s], of[4 * s + 1], of[4 * s + 2], of[4 * s + 3], dwo + g * 960 + s * 64, 1);
    wgmma_commit();
    TS(6);
    const uint32_t bo = bar_o + fol * 56;
#pragma unroll
    for (int i = 0; i < 7; i++) {
      mbar_wait(bo + 8 * i, 0);
      if (i == 0) TS(1);
      const uint32_t da = D0 + OFF_O / 16 + (8 << 16) + ((i + 2) % 6) * 640 + fol * (i == 3 ? -3200 : 640), db = D0 + (320 << 16) + (i >= g ? i + 1 : i) * 960;
      wgmma_fence();
#pragma unroll
      for (int s = 0; s < 5; s++) wgmma_n80_ss(h, mk64(da + s * 16, 80u), mk64(db + s * 64, 0x80000020u), 1);
      wgmma_commit();
      wgmma_wait<1>();
      if (lane == 0 && i > 0) mbar_arrive(bo + 104 + 8 * i);
    }
    const bool odd = c & 1;
    float wr[20];
#pragma unroll
    for (int j = 0; j < 5; j++) {
      const uint4 v = lds128(sb + OFF_WR + c * 80 + j * 16);
      wr[4 * j] = __uint_as_float(v.x); wr[4 * j + 1] = __uint_as_float(v.y); wr[4 * j + 2] = __uint_as_float(v.z); wr[4 * j + 3] = __uint_as_float(v.w);
    }
    const float wsum = lds32f(sb + OFF_WR + 320);
    uint4* const sp = hold(&g_own[slot].st2[r + (odd ? 8 : 0)]);
    uint4* const cdp = hold(&g_x.cand[slot][g][0]);
    const int tok0 = P * 256 + 32 * warp + rank;
    wgmma_wait<0>();
#pragma unroll
    for (int i = 0; i < 40; i++) asm volatile("" : "+f"(h[i]) :: "memory");
    if (lane == 0) mbar_arrive(bo + 160);
    TS(7);
    float mean, rstd, rr;
    {
      float l1 = 0.f, l2 = 0.f, l3 = 0.f, h1 = 0.f, h2 = 0.f, h3 = 0.f;
#pragma unroll
      for (int j = 0; j < 10; j++) {
        l1 += h[4 * j] + h[4 * j + 1]; h1 += h[4 * j + 2] + h[4 * j + 3];
        l2 = fmaf(h[4 * j], h[4 * j], l2); l2 = fmaf(h[4 * j + 1], h[4 * j + 1], l2);
        h2 = fmaf(h[4 * j + 2], h[4 * j + 2], h2); h2 = fmaf(h[4 * j + 3], h[4 * j + 3], h2);
        l3 = fmaf(h[4 * j], wr[2 * j], l3); l3 = fmaf(h[4 * j + 1], wr[2 * j + 1], l3);
        h3 = fmaf(h[4 * j + 2], wr[2 * j], h3); h3 = fmaf(h[4 * j + 3], wr[2 * j + 1], h3);
      }
      float s1 = (odd ? h1 : l1) + shx(odd ? l1 : h1, 1), s2 = (odd ? h2 : l2) + shx(odd ? l2 : h2, 1), s3 = (odd ? h3 : l3) + shx(odd ? l3 : h3, 1);
      s1 += shx(s1, 2); s2 += shx(s2, 2); s3 += shx(s3, 2);
      if (cA) asm volatile("red.relaxed.gpu.global.add.v4.f32 [%0], {%1, %2, %3, %4};" :: "l"(sp), "f"(s1), "f"(s2), "f"(s3), "f"(1.f) : "memory");
      uint4 p0;
      do { p0 = ldg_pkt(sp); } while (anyw(p0.w != 0x41000000u) && --guard > 0);
      mean = __uint_as_float(p0.x) * (1.f / 640.f);
      rstd = rsq(fmaxf(fmaf(-mean, mean, __uint_as_float(p0.y) * (1.f / 640.f)), 0.f) + 1e-5f);
      rr = fmaf(-mean, wsum, __uint_as_float(p0.z)) * rstd;
    }
    TS(8);
    const uint32_t kk = ord_key(rr), kmax = __reduce_max_sync(0xffffffffu, kk);
    const int L = __ffs(__ballot_sync(0xffffffffu, kk == kmax)) - 1;
    const int crow = (L >> 2) + 8 * (L & 1);
    if (warp == g) {
      if (elect()) {
        asm volatile("red.relaxed.gpu.global.max.u64 [%0], %1;" :: "l"(g_own[1].cnt), "l"(((uint64_t)kmax << 32) | (uint32_t)(2047 - tok0 - 2 * crow)) : "memory");
        asm volatile("red.relaxed.gpu.global.add.u32 [%0], 1;" :: "l"(&g_own[1].cnt[0].z) : "memory");
      }
      asm volatile("bar.arrive 3, 64;" ::: "memory");
    }
    const uint32_t stg = sb + (fol ? OFF_O : g * 15360) + w4 * 2560;
    uint4 held;
    {
      const float om = shx(mean, 1), os = shx(rstd, 1);
      const float rl = odd ? os : rstd, rh = odd ? rstd : os;
      const float bl = -(odd ? om : mean) * rl, bh = -(odd ? mean : om) * rh, al = 1.f + rl, ah = 1.f + rh;
      if ((L >> 2) == r) {
        const bool chi = L & 1;
        const float rc = chi ? rh : rl, bc = chi ? bh : bl;
        uint32_t n[10];
#pragma unroll
        for (int j = 0; j < 10; j++) n[j] = pack_bf16(fmaf(chi ? h[4 * j + 2] : h[4 * j], rc, bc), fmaf(chi ? h[4 * j + 3] : h[4 * j + 1], rc, bc));
        uint4* d = cdp + c;
        stg_pkt(d, n[0], n[1], n[2], n[3]); stg_pkt(d + 4, n[4], n[5], n[6], n[7]); stg_rlx64(d + 8, n[8], n[9]);
      }
      mbar_wait(bar_oc + 56, 0);
      const uint32_t fa = stg + (lane & 15) * 160 + (lane >> 4) * 16;
#pragma unroll
      for (int s = 0; s < 5; s++)
        stsm4(fa + s * 32, pack_bf16(fmaf(h[8 * s], al, bl), fmaf(h[8 * s + 1], al, bl)), pack_bf16(fmaf(h[8 * s + 2], ah, bh), fmaf(h[8 * s + 3], ah, bh)),
              pack_bf16(fmaf(h[8 * s + 4], al, bl), fmaf(h[8 * s + 5], al, bl)), pack_bf16(fmaf(h[8 * s + 6], ah, bh), fmaf(h[8 * s + 7], ah, bh)));
      __syncwarp();
      held = lds128(stg + crow * 160 + min(lane, 9) * 16);
      if (lane < 10) stg_pkt(cdp + 12 + lane, held.x, held.y, held.z, held.w);
    }
    TS(9);
    mbar_wait(bar_ffn, 0);
    const uint32_t red = sb + OFF_RED;
    if (ffn1) {
      uint4 w1[4][5];
      {
        const int k = (lane & 7) + (lane >> 4) * 8;
        const uint32_t a1 = sb + k * 64, sw = ((lane >> 3) & 1) ^ ((lane >> 1) & 3);
#pragma unroll
        for (int s = 0; s < 5; s++)
#pragma unroll
          for (int u = 0; u < 4; u++)
            w1[u][s] = ldsm4t(a1 + (s < 4 ? warp * 4096 + s * 1024 : 32768 + warp * 1024) + (u >> 1) * (40960 + (s == 4 || warp >= 2 ? OFF_W2 - 49152 : 0)) + ((sw ^ (2 * (u & 1))) * 16));
      }
      uint32_t* const ap = hold(g_x.act + fj * 16 + (lane >> 1));
      mbar_wait(bar_win, 0);
      const uint32_t hp = sb + OFF_HN + (warp * 4 + c) * 16;
      const uint4 c0 = lds128(hp), c1 = lds128(hp + 512), c2 = lds128(hp + 1024);
      TS(10);
      float a[4][4];
#pragma unroll
      for (int u = 0; u < 4; u++) {
        a[u][0] = a[u][1] = a[u][2] = a[u][3] = 0.f;
        mma_acc(a[u], w1[u][0], c0.x, c0.y); mma_acc(a[u], w1[u][1], c0.z, c0.w); mma_acc(a[u], w1[u][2], c1.x, c1.y);
        mma_acc(a[u], w1[u][3], c1.z, c1.w); mma_acc(a[u], w1[u][4], c2.x, c2.y);
      }
      asm volatile("st.shared.v2.f32 [%0], {%1, %2};" :: "r"(red + (warp * 32 + c * 8 + r) * 8),
                   "f"(cA ? (odd ? a[0][2] : a[0][0]) : (odd ? a[1][2] : a[1][0])), "f"(cA ? (odd ? a[2][2] : a[2][0]) : (odd ? a[3][2] : a[3][0])) : "memory");
      bar_sync(1, 256);
      if (warp == 0) {
        float2 t[8];
#pragma unroll
        for (int i = 0; i < 8; i++) t[i] = lds64f(red + (i * 32 + lane) * 8);
        const float s = ((t[0].x + t[1].x) + (t[2].x + t[3].x)) + ((t[4].x + t[5].x) + (t[6].x + t[7].x));
        const float u = ((t[0].y + t[1].y) + (t[2].y + t[3].y)) + ((t[4].y + t[5].y) + (t[6].y + t[7].y));
        const float av = s * u * rcp(1.f + ex2(-1.4426950408889634f * s));
        const float an = shx(av, 1);
        if (!odd) stg_rlx32(ap, pack_bf16(av, an));
      }
      bar_sync(1, 256);
      TS(11);
    }
    if (OUT_LATE) mbar_wait(bar_win, 0);
    char* const ob2 = (char*)(out + tok0 * 640 + g * 64);
    const int remo = 896 - 96 * g;
#pragma unroll
    for (int s = 0; s < 5; s++) {
      const int row = s < 4 ? 4 * s + (lane >> 3) : lane >> 1, pc = s < 4 ? lane & 7 : 8 + (lane & 1);
      const uint4 v = lds128(stg + row * 160 + pc * 16);
      if (row != crow) stg128(ob2 + row * 2560 + pc * 16 + (s < 4 ? 0 : remo), v);
    }
    mbar_wait(bar_win, 0);
    uint4 win = lds128(sb + OFF_WR + 336);
    win.z = win.y; win.y = 2047u - (win.x & 2047u); win.x = (win.y >> 8) * 16 + (win.y & 1) * 8 + ((win.y >> 5) & 7);
    if (win.x != slot && lane < 10) stg128(ob2 + crow * 2560 + lane * 16 + (lane < 8 ? 0 : remo), held);
    if (!ffn1) {
      TS(10);
      uint4 w2[6];
      const uint32_t a2 = sb + OFF_W2 + (warp * 192 + 8 * (((lane >> 3) & 1) * 4 + ((lane & 7) >> 1)) + 2 * (lane >> 4) + (lane & 1)) * 16;
#pragma unroll
      for (int s = 0; s < 6; s++) w2[s] = ldsm4t(a2 + (s >> 1) * 1024 + (s & 1) * 64);
      const uint4* p = (const uint4*)(g_x.act + warp * 96) + (r & 1) * 4 + c;
      const uint32_t* pb = (const uint32_t*)&g_x.cand[win.x][fj < 64 ? fj >> 3 : (fj - 64) >> 1][fj < 64 ? 12 + (fj & 7) : 20 + (fj & 1)] + c;
      uint32_t* const op = hold((uint32_t*)(out + win.y * 640 + fj * 8) + c);
      const float sg = rcp(1.f + ex2(-1.4426950408889634f * __uint_as_float(win.z ^ ((uint32_t)((int32_t)~win.z >> 31) | 0x80000000u))));
      uint4 c0, c1, c2; uint32_t bw;
      if (ACT_NS) __nanosleep(ACT_NS);
      do {
        c0 = ldg_pkt(p); c1 = ldg_pkt(p + 8); c2 = ldg_pkt(p + 16); bw = ldg_rlx32(pb);
      } while (anyw(max(max(max(max(c0.x, c0.y), max(c0.z, c0.w)), max(max(c1.x, c1.y), max(c1.z, c1.w))), max(max(max(c2.x, c2.y), max(c2.z, c2.w)), bw)) == SENT) && --guard > 0);
      TS(11);
      float a[4] = {0.f, 0.f, 0.f, 0.f}, b[4] = {0.f, 0.f, 0.f, 0.f}, d[4] = {0.f, 0.f, 0.f, 0.f};
      mma_acc(a, w2[0], c0.x, c0.y); mma_acc(b, w2[2], c1.x, c1.y); mma_acc(d, w2[4], c2.x, c2.y);
      mma_acc(a, w2[1], c0.z, c0.w); mma_acc(b, w2[3], c1.z, c1.w); mma_acc(d, w2[5], c2.z, c2.w);
      if (c == 0) sts32f(red + (warp * 8 + r) * 4, ((a[0] + a[3]) + (b[0] + b[3])) + (d[0] + d[3]));
      bar_sync(1, 256);
      if (tid < 4) {
        float2 t[8];
#pragma unroll
        for (int i = 0; i < 8; i++) t[i] = lds64f(red + (i * 4 + tid) * 8);
        const float y0 = ((t[0].x + t[1].x) + (t[2].x + t[3].x)) + ((t[4].x + t[5].x) + (t[6].x + t[7].x));
        const float y1 = ((t[0].y + t[1].y) + (t[2].y + t[3].y)) + ((t[4].y + t[5].y) + (t[6].y + t[7].y));
        *op = pack_bf16(fmaf(y0, sg, bf_lo(bw)), fmaf(y1, sg, bf_hi(bw)));
      }
    }
    TS(12);
#undef TS_T
  }
}

typedef CUresult (*EncodeFn)(CUtensorMap*, CUtensorMapDataType, cuuint32_t, void*, const cuuint64_t*, const cuuint64_t*, const cuuint32_t*,
                             const cuuint32_t*, CUtensorMapInterleave, CUtensorMapSwizzle, CUtensorMapL2promotion, CUtensorMapFloatOOBfill);

void make_map(EncodeFn enc, CUtensorMap* m, const void* base, const cuuint64_t* dims, const cuuint64_t* strides, const cuuint32_t* box,
              CUtensorMapSwizzle swz) {
  const cuuint32_t es[3] = {1, 1, 1};
  enc(m, CU_TENSOR_MAP_DATA_TYPE_BFLOAT16, 3, (void*)base, dims, strides, box, es, CU_TENSOR_MAP_INTERLEAVE_NONE, swz,
      CU_TENSOR_MAP_L2_PROMOTION_L2_128B, CU_TENSOR_MAP_FLOAT_OOB_FILL_NONE);
}

}

extern "C" void kernel_launch(void* const* d_in, const int* in_sizes, int n_in, void* d_out, int out_size) {
  const __nv_bfloat16* x = (const __nv_bfloat16*)d_in[0];
  const __nv_bfloat16* wqkv = (const __nv_bfloat16*)d_in[1];
  const __nv_bfloat16* wo = (const __nv_bfloat16*)d_in[2];
  void* fn = nullptr;
  cudaDriverEntryPointQueryResult st;
  cudaGetDriverEntryPoint("cuTensorMapEncodeTiled", &fn, cudaEnableDefault, &st);
  EncodeFn enc = (EncodeFn)fn;
  void* scp = nullptr;
  cudaGetSymbolAddress(&scp, g_scratch);
  Maps tm;
  { const cuuint64_t d[3] = {640, 1024, 2}, s[2] = {2560, 1280}; const cuuint32_t b[3] = {64, 128, 1}; make_map(enc, &tm.x, x, d, s, b, CU_TENSOR_MAP_SWIZZLE_128B); }
  { const cuuint64_t d[3] = {640, 640, 3}, s[2] = {3840, 1280}; const cuuint32_t b[3] = {64, 64, 1}; make_map(enc, &tm.w, wqkv, d, s, b, CU_TENSOR_MAP_SWIZZLE_128B); }
  { const cuuint64_t d[3] = {640, 640, 3}, s[2] = {3840, 1280}; const cuuint32_t b[3] = {16, 64, 3}; make_map(enc, &tm.wr, wqkv, d, s, b, CU_TENSOR_MAP_SWIZZLE_32B); }
  { const cuuint64_t d[3] = {32, 640, 20}, s[2] = {1280, 64}; const cuuint32_t b[3] = {32, 80, 2}; make_map(enc, &tm.wo, wo, d, s, b, CU_TENSOR_MAP_SWIZZLE_64B); }
  { const cuuint64_t d[3] = {640, 640, 1}, s[2] = {1280, 819200}; const cuuint32_t b[3] = {16, 80, 1}; make_map(enc, &tm.wor, wo, d, s, b, CU_TENSOR_MAP_SWIZZLE_64B); }
  { const cuuint64_t d[3] = {1536, 640, 1}, s[2] = {3072, 1966080}; const cuuint32_t b[3] = {32, 128, 1};
    make_map(enc, &tm.gate, d_in[5], d, s, b, CU_TENSOR_MAP_SWIZZLE_64B); make_map(enc, &tm.up, d_in[6], d, s, b, CU_TENSOR_MAP_SWIZZLE_64B); }
  { const cuuint64_t d[3] = {640, 1536, 1}, s[2] = {1280, 1966080}; const cuuint32_t b[3] = {8, 128, 1}; make_map(enc, &tm.down, d_in[7], d, s, b, CU_TENSOR_MAP_SWIZZLE_NONE); }
  cudaFuncSetAttribute(fused_kernel, cudaFuncAttributeMaxDynamicSharedMemorySize, SMEM_BYTES);
  fused_kernel<<<128, 512, SMEM_BYTES, cudaStreamPerThread>>>(x, wqkv, wo, (const __nv_bfloat16*)d_in[4], (const __nv_bfloat16*)d_in[5],
                                                              (const __nv_bfloat16*)d_in[6], (const __nv_bfloat16*)d_in[7], (__nv_bfloat16*)d_out, (Scratch*)scp, tm);
}
```

```cpp
#include <cuda_runtime.h>
#include <cuda_bf16.h>
#include <cuda.h>
#include <stdint.h>

#define PFW_NS 100
#define ACT_NS 100
#define OUT_LATE 0
#define REG_P 72
#define REG_C 184
#define AUX_NS 50
#define LEAD 1
#define RST_IT 4
#define ORDX 1
#define THR 2
#define PF_FIRST 3
#define PF_T0 2000
#define PF_CLK 500
#define HK_IT 1
#define F_IT 9
#define F_PER 2
#define F_MAX 8
#define HOLD 2
#define F_LATE 12
#define HALO_NS 0
#define AK 3
#define KEY_NS 60
#define FW 5
#define ONE_RED 2
#define CNT_NS 0

namespace {

constexpr int SLOT    = 47104;
constexpr int OFF_O   = 122880;
constexpr int OFF_W2  = 4 * SLOT;
constexpr int OFF_CS  = OFF_W2 + 32768;
constexpr int OFF_RS  = OFF_CS + 3840;
constexpr int OFF_MN  = OFF_RS + 576;
constexpr int OFF_WR  = OFF_MN + 1024;
constexpr int OFF_RED = OFF_CS;
constexpr int OFF_HN  = OFF_CS + 2048;
constexpr int OFF_PT  = OFF_WR + 352;
constexpr int OFF_BAR = OFF_PT + 768;
constexpr int SMEM_BYTES = OFF_BAR + 384 + 384;
constexpr uint32_t D0 = 1024 >> 4;
constexpr uint32_t SENT = 0xFFFFFFFFu;
constexpr int SPIN_MAX = 1 << 20;

struct Glob {
  uint4 cand[128][8][24];
  uint32_t act[768];
  uint32_t pad[256];
};
constexpr int GLOB_PER_CTA = sizeof(Glob) / 16 / 128;
static_assert(GLOB_PER_CTA * 128 * 16 == sizeof(Glob), "glob size");
struct Own {
  uint4 halo[5][32];
  uint4 st1[32];
  uint2 cs[32];
  uint4 st2[16];
  uint4 cnt[8];
};
struct Scratch {
  Glob x;
  Own own[128];
  uint4 o[32][8][640];
  uint32_t epoch[128];
};
__device__ __align__(128) Scratch g_scratch;
#define g_x (sc->x)
#define g_own (sc->own)
#define g_o (sc->o)
#define g_epoch (sc->epoch)
#define TS(i)

__device__ __forceinline__ void mbar_init(uint32_t bar, uint32_t cnt) { asm volatile("mbarrier.init.shared::cta.b64 [%0], %1;" :: "r"(bar), "r"(cnt) : "memory"); }
__device__ __forceinline__ void mbar_expect_tx(uint32_t bar, uint32_t bytes) { asm volatile("mbarrier.arrive.expect_tx.shared::cta.b64 _, [%0], %1;" :: "r"(bar), "r"(bytes) : "memory"); }
__device__ __forceinline__ void mbar_arrive(uint32_t bar) { asm volatile("mbarrier.arrive.shared::cta.b64 _, [%0];" :: "r"(bar) : "memory"); }
__device__ __forceinline__ void mbar_arrive_cta(uint32_t bar, uint32_t cta) {
  asm volatile("{\n.reg .b32 ra;\nmapa.shared::cluster.u32 ra, %0, %1;\nmbarrier.arrive.shared::cluster.b64 _, [ra];\n}\n" :: "r"(bar), "r"(cta) : "memory");
}
__device__ __forceinline__ void mbar_wait(uint32_t bar, uint32_t parity) {
  asm volatile("{\n.reg .pred p;\n.reg .u32 n;\nmov.u32 n, 0;\nW:\nmbarrier.try_wait.parity.shared::cta.b64 p, [%0], %1;\n@p bra.uni D;\n"
               "add.u32 n, n, 1;\nsetp.lt.u32 p, n, %2;\n@p bra.uni W;\nD:\n}\n" :: "r"(bar), "r"(parity), "n"(SPIN_MAX) : "memory");
}
__device__ __forceinline__ void tma_3d(uint32_t dst, const void* tm, uint32_t bar, int c0, int c1, int c2) {
  asm volatile("cp.async.bulk.tensor.3d.shared::cluster.global.mbarrier::complete_tx::bytes [%0], [%1, {%3, %4, %5}], [%2];" :: "r"(dst), "l"(tm), "r"(bar), "r"(c0), "r"(c1), "r"(c2) : "memory");
}
__device__ __forceinline__ void tma_3d_mc(uint32_t dst, const void* tm, uint32_t bar, int c0, int c1, int c2) {
  asm volatile("cp.async.bulk.tensor.3d.shared::cluster.global.mbarrier::complete_tx::bytes.multicast::cluster [%0], [%1, {%3, %4, %5}], [%2], %6;" :: "r"(dst), "l"(tm), "r"(bar), "r"(c0), "r"(c1), "r"(c2), "h"((uint16_t)3) : "memory");
}
__device__ __forceinline__ void wgmma_fence() { asm volatile("wgmma.fence.sync.aligned;" ::: "memory"); }
__device__ __forceinline__ void wgmma_commit() { asm volatile("wgmma.commit_group.sync.aligned;" ::: "memory"); }
template <int N> __device__ __forceinline__ void wgmma_wait() { asm volatile("wgmma.wait_group.sync.aligned %0;" :: "n"(N) : "memory"); }
__device__ __forceinline__ uint64_t make_desc(uint32_t addr, uint32_t lbo, uint32_t sbo, uint32_t swz) {
  return (uint64_t)(((addr & 0x3FFFF) >> 4) | ((lbo >> 4) << 16)) | ((uint64_t)((sbo >> 4) | (swz << 30)) << 32);
}
__device__ __forceinline__ void bar_sync(int id, int n) { asm volatile("bar.sync %0, %1;" :: "r"(id), "r"(n) : "memory"); }
__device__ __forceinline__ void st_pkt(void* p, uint32_t a, uint32_t b, uint32_t c, uint32_t d) {
  asm volatile("st.relaxed.gpu.v4.u32 [%0], {%1, %2, %3, %4};" :: "l"(p), "r"(a), "r"(b), "r"(c), "r"(d) : "memory");
}
__device__ __forceinline__ uint4 ldg_pkt(const void* p) {
  uint4 v; asm volatile("ld.relaxed.gpu.global.v4.u32 {%0, %1, %2, %3}, [%4];" : "=r"(v.x), "=r"(v.y), "=r"(v.z), "=r"(v.w) : "l"(p) : "memory"); return v;
}
__device__ __forceinline__ void stg_pkt(void* p, uint32_t a, uint32_t b, uint32_t c, uint32_t d) {
  asm volatile("st.relaxed.gpu.global.v4.u32 [%0], {%1, %2, %3, %4};" :: "l"(p), "r"(a), "r"(b), "r"(c), "r"(d) : "memory");
}
__device__ __forceinline__ uint32_t ldg_rlx32(const void* p) { uint32_t v; asm volatile("ld.relaxed.gpu.global.u32 %0, [%1];" : "=r"(v) : "l"(p) : "memory"); return v; }
__device__ __forceinline__ uint2 ldg_rlx64(const void* p) { uint2 v; asm volatile("ld.relaxed.gpu.global.v2.u32 {%0, %1}, [%2];" : "=r"(v.x), "=r"(v.y) : "l"(p) : "memory"); return v; }
__device__ __forceinline__ void stg128(void* p, const uint4& v) { asm volatile("st.global.v4.u32 [%0], {%1, %2, %3, %4};" :: "l"(p), "r"(v.x), "r"(v.y), "r"(v.z), "r"(v.w) : "memory"); }
__device__ __forceinline__ uint32_t pin(uint32_t v) { asm volatile("" : "+r"(v)); return v; }
__device__ __forceinline__ uint64_t mk64(uint32_t lo, uint32_t hi) { return ((uint64_t)hi << 32) | lo; }
template <class T> __device__ __forceinline__ T* hold(T* p) { return (T*)__shfl_sync(0xffffffffu, (unsigned long long)p, threadIdx.x & 31); }
template <class T> __device__ __forceinline__ T* pin(T* p) { asm volatile("" : "+l"(p)); return p; }
__device__ __forceinline__ void stg_rlx32(void* p, uint32_t v) { asm volatile("st.relaxed.gpu.global.u32 [%0], %1;" :: "l"(p), "r"(v) : "memory"); }
__device__ __forceinline__ void stg_rlx64(void* p, uint32_t a, uint32_t b) { asm volatile("st.relaxed.gpu.global.v2.u32 [%0], {%1, %2};" :: "l"(p), "r"(a), "r"(b) : "memory"); }
__device__ __forceinline__ uint4 ldsm4(uint32_t a) { uint4 v; asm volatile("ldmatrix.sync.aligned.m8n8.x4.shared.b16 {%0, %1, %2, %3}, [%4];" : "=r"(v.x), "=r"(v.y), "=r"(v.z), "=r"(v.w) : "r"(a) : "memory"); return v; }
__device__ __forceinline__ void ldsm4_if(uint4& v, uint32_t a, int off, bool p) {
  asm volatile("{\n.reg .pred q;\nsetp.ne.u32 q, %5, 0;\n@q ldmatrix.sync.aligned.m8n8.x4.shared.b16 {%0, %1, %2, %3}, [%4];\n}\n"
               : "+r"(v.x), "+r"(v.y), "+r"(v.z), "+r"(v.w) : "r"(a + off), "r"((int)p) : "memory");
}
__device__ __forceinline__ uint4 ldsm4t(uint32_t a) { uint4 v; asm volatile("ldmatrix.sync.aligned.m8n8.x4.trans.shared.b16 {%0, %1, %2, %3}, [%4];" : "=r"(v.x), "=r"(v.y), "=r"(v.z), "=r"(v.w) : "r"(a) : "memory"); return v; }
__device__ __forceinline__ void stsm4(uint32_t a, uint32_t x, uint32_t y, uint32_t z, uint32_t w) { asm volatile("stmatrix.sync.aligned.m8n8.x4.shared.b16 [%0], {%1, %2, %3, %4};" :: "r"(a), "r"(x), "r"(y), "r"(z), "r"(w) : "memory"); }
__device__ __forceinline__ void mma_acc(float (&c)[4], const uint4& a, uint32_t b0, uint32_t b1) {
  asm("mma.sync.aligned.m16n8k16.row.col.f32.bf16.bf16.f32 {%0,%1,%2,%3}, {%4,%5,%6,%7}, {%8,%9}, {%0,%1,%2,%3};"
      : "+f"(c[0]), "+f"(c[1]), "+f"(c[2]), "+f"(c[3]) : "r"(a.x), "r"(a.y), "r"(a.z), "r"(a.w), "r"(b0), "r"(b1));
}
__device__ __forceinline__ uint4 lds128(uint32_t a) { uint4 v; asm volatile("ld.shared.v4.u32 {%0, %1, %2, %3}, [%4];" : "=r"(v.x), "=r"(v.y), "=r"(v.z), "=r"(v.w) : "r"(a) : "memory"); return v; }
__device__ __forceinline__ float2 lds64f(uint32_t a) { float2 v; asm volatile("ld.shared.v2.f32 {%0, %1}, [%2];" : "=f"(v.x), "=f"(v.y) : "r"(a)); return v; }
__device__ __forceinline__ float lds32f(uint32_t a) { float v; asm volatile("ld.shared.f32 %0, [%1];" : "=f"(v) : "r"(a)); return v; }
__device__ __forceinline__ void sts32f(uint32_t a, float v) { asm volatile("st.shared.f32 [%0], %1;" :: "r"(a), "f"(v) : "memory"); }
__device__ __forceinline__ uint32_t pack_bf16(float lo, float hi) { uint32_t r; asm("cvt.rn.bf16x2.f32 %0, %1, %2;" : "=r"(r) : "f"(hi), "f"(lo)); return r; }
__device__ __forceinline__ float bf_lo(uint32_t v) { return __uint_as_float(v << 16); }
__device__ __forceinline__ float bf_hi(uint32_t v) { return __uint_as_float(v & 0xffff0000u); }
__device__ __forceinline__ uint32_t movm(uint32_t a) { uint32_t d; asm("movmatrix.sync.aligned.m8n8.trans.b16 %0, %1;" : "=r"(d) : "r"(a)); return d; }
__device__ __forceinline__ float ex2(float x) { float y; asm("ex2.approx.ftz.f32 %0, %1;" : "=f"(y) : "f"(x)); return y; }
__device__ __forceinline__ float rsq(float x) { float y; asm("rsqrt.approx.ftz.f32 %0, %1;" : "=f"(y) : "f"(x)); return y; }
__device__ __forceinline__ float rcp(float x) { float y; asm("rcp.approx.ftz.f32 %0, %1;" : "=f"(y) : "f"(x)); return y; }
__device__ __forceinline__ bool elect() { uint32_t p; asm volatile("{\n.reg .pred q;\nelect.sync _|q, 0xffffffff;\nselp.u32 %0, 1, 0, q;\n}\n" : "=r"(p)); return p; }
__device__ __forceinline__ int clk() { int c; asm volatile("mov.u32 %0, %%clock;" : "=r"(c) :: "memory"); return c; }
__device__ __forceinline__ void pf_l2(const void* p) { asm volatile("prefetch.global.L2 [%0];" :: "l"(p)); }
__device__ __forceinline__ bool anyw(bool p) { return __any_sync(0xffffffffu, p); }
__device__ __forceinline__ float shx(float v, int m) { return __shfl_xor_sync(0xffffffffu, v, m); }
__device__ __forceinline__ void mma_k24(float (&c)[4], uint32_t a0, uint32_t a1, uint32_t a2, uint32_t a3, uint32_t b0, uint32_t b1,
                                        uint32_t e0, uint32_t e1, uint32_t f0) {
  asm("mma.sync.aligned.m16n8k16.row.col.f32.bf16.bf16.f32 {%0,%1,%2,%3}, {%4,%5,%6,%7}, {%8,%9}, {%10,%10,%10,%10};"
      : "=f"(c[0]), "=f"(c[1]), "=f"(c[2]), "=f"(c[3]) : "r"(a0), "r"(a1), "r"(a2), "r"(a3), "r"(b0), "r"(b1), "f"(0.f));
  asm("mma.sync.aligned.m16n8k8.row.col.f32.bf16.bf16.f32 {%0,%1,%2,%3}, {%4,%5}, {%6}, {%0,%1,%2,%3};"
      : "+f"(c[0]), "+f"(c[1]), "+f"(c[2]), "+f"(c[3]) : "r"(e0), "r"(e1), "r"(f0));
}
__device__ __forceinline__ uint32_t ord_key(float r) { uint32_t u = __float_as_uint(r); return u ^ ((uint32_t)((int32_t)u >> 31) | 0x80000000u); }

__device__ __forceinline__ void wgmma_n48hi_ss(float (&d)[120], uint64_t da, uint64_t db, int scale_d) {
  asm volatile("{\n.reg .pred p;\nsetp.ne.b32 p, %26, 0;\n"
    "wgmma.mma_async.sync.aligned.m64n48k16.f32.bf16.bf16 "
    "{%0, %1, %2, %3, %4, %5, %6, %7, %8, %9, %10, %11, %12, %13, %14, %15, "
    "%16, %17, %18, %19, %20, %21, %22, %23}, "
    "%24, %25, p, 1, 1, 0, 1;\n}\n"
    : "+f"(d[96]), "+f"(d[97]), "+f"(d[98]), "+f"(d[99]), "+f"(d[100]), "+f"(d[101]), "+f"(d[102]), "+f"(d[103]),
      "+f"(d[104]), "+f"(d[105]), "+f"(d[106]), "+f"(d[107]), "+f"(d[108]), "+f"(d[109]), "+f"(d[110]), "+f"(d[111]),
      "+f"(d[112]), "+f"(d[113]), "+f"(d[114]), "+f"(d[115]), "+f"(d[116]), "+f"(d[117]), "+f"(d[118]), "+f"(d[119])
    : "l"(da), "l"(db), "r"(scale_d));
}
__device__ __forceinline__ void wgmma_n192lo_ss(float (&d)[120], uint64_t da, uint64_t db, int scale_d) {
  asm volatile("{\n.reg .pred p;\nsetp.ne.b32 p, %98, 0;\n"
    "wgmma.mma_async.sync.aligned.m64n192k16.f32.bf16.bf16 "
    "{%0, %1, %2, %3, %4, %5, %6, %7, %8, %9, %10, %11, %12, %13, %14, %15, "
    "%16, %17, %18, %19, %20, %21, %22, %23, %24, %25, %26, %27, %28, %29, %30, %31, "
    "%32, %33, %34, %35, %36, %37, %38, %39, %40, %41, %42, %43, %44, %45, %46, %47, "
    "%48, %49, %50, %51, %52, %53, %54, %55, %56, %57, %58, %59, %60, %61, %62, %63, "
    "%64, %65, %66, %67, %68, %69, %70, %71, %72, %73, %74, %75, %76, %77, %78, %79, "
    "%80, %81, %82, %83, %84, %85, %86, %87, %88, %89, %90, %91, %92, %93, %94, %95}, "
    "%96, %97, p, 1, 1, 0, 1;\n}\n"
    : "+f"(d[0]), "+f"(d[1]), "+f"(d[2]), "+f"(d[3]), "+f"(d[4]), "+f"(d[5]), "+f"(d[6]), "+f"(d[7]),
      "+f"(d[8]), "+f"(d[9]), "+f"(d[10]), "+f"(d[11]), "+f"(d[12]), "+f"(d[13]), "+f"(d[14]), "+f"(d[15]),
      "+f"(d[16]), "+f"(d[17]), "+f"(d[18]), "+f"(d[19]), "+f"(d[20]), "+f"(d[21]), "+f"(d[22]), "+f"(d[23]),
      "+f"(d[24]), "+f"(d[25]), "+f"(d[26]), "+f"(d[27]), "+f"(d[28]), "+f"(d[29]), "+f"(d[30]), "+f"(d[31]),
      "+f"(d[32]), "+f"(d[33]), "+f"(d[34]), "+f"(d[35]), "+f"(d[36]), "+f"(d[37]), "+f"(d[38]), "+f"(d[39]),
      "+f"(d[40]), "+f"(d[41]), "+f"(d[42]), "+f"(d[43]), "+f"(d[44]), "+f"(d[45]), "+f"(d[46]), "+f"(d[47]),
      "+f"(d[48]), "+f"(d[49]), "+f"(d[50]), "+f"(d[51]), "+f"(d[52]), "+f"(d[53]), "+f"(d[54]), "+f"(d[55]),
      "+f"(d[56]), "+f"(d[57]), "+f"(d[58]), "+f"(d[59]), "+f"(d[60]), "+f"(d[61]), "+f"(d[62]), "+f"(d[63]),
      "+f"(d[64]), "+f"(d[65]), "+f"(d[66]), "+f"(d[67]), "+f"(d[68]), "+f"(d[69]), "+f"(d[70]), "+f"(d[71]),
      "+f"(d[72]), "+f"(d[73]), "+f"(d[74]), "+f"(d[75]), "+f"(d[76]), "+f"(d[77]), "+f"(d[78]), "+f"(d[79]),
      "+f"(d[80]), "+f"(d[81]), "+f"(d[82]), "+f"(d[83]), "+f"(d[84]), "+f"(d[85]), "+f"(d[86]), "+f"(d[87]),
      "+f"(d[88]), "+f"(d[89]), "+f"(d[90]), "+f"(d[91]), "+f"(d[92]), "+f"(d[93]), "+f"(d[94]), "+f"(d[95])
    : "l"(da), "l"(db), "r"(scale_d));
}
__device__ __forceinline__ void wgmma_n48hi_rk(float (&d)[120], uint32_t a0, uint32_t a1, uint32_t a2, uint32_t a3, uint64_t db, int scale_d) {
  asm volatile("{\n.reg .pred p;\nsetp.ne.b32 p, %29, 0;\n"
    "wgmma.mma_async.sync.aligned.m64n48k16.f32.bf16.bf16 "
    "{%0, %1, %2, %3, %4, %5, %6, %7, %8, %9, %10, %11, %12, %13, %14, %15, "
    "%16, %17, %18, %19, %20, %21, %22, %23}, "
    "{%24, %25, %26, %27}, %28, p, 1, 1, 0;\n}\n"
    : "+f"(d[96]), "+f"(d[97]), "+f"(d[98]), "+f"(d[99]), "+f"(d[100]), "+f"(d[101]), "+f"(d[102]), "+f"(d[103]),
      "+f"(d[104]), "+f"(d[105]), "+f"(d[106]), "+f"(d[107]), "+f"(d[108]), "+f"(d[109]), "+f"(d[110]), "+f"(d[111]),
      "+f"(d[112]), "+f"(d[113]), "+f"(d[114]), "+f"(d[115]), "+f"(d[116]), "+f"(d[117]), "+f"(d[118]), "+f"(d[119])
    : "r"(a0), "r"(a1), "r"(a2), "r"(a3), "l"(db), "r"(scale_d));
}
__device__ __forceinline__ void wgmma_n192lo_rk(float (&d)[120], uint32_t a0, uint32_t a1, uint32_t a2, uint32_t a3, uint64_t db, int scale_d) {
  asm volatile("{\n.reg .pred p;\nsetp.ne.b32 p, %101, 0;\n"
    "wgmma.mma_async.sync.aligned.m64n192k16.f32.bf16.bf16 "
    "{%0, %1, %2, %3, %4, %5, %6, %7, %8, %9, %10, %11, %12, %13, %14, %15, "
    "%16, %17, %18, %19, %20, %21, %22, %23, %24, %25, %26, %27, %28, %29, %30, %31, "
    "%32, %33, %34, %35, %36, %37, %38, %39, %40, %41, %42, %43, %44, %45, %46, %47, "
    "%48, %49, %50, %51, %52, %53, %54, %55, %56, %57, %58, %59, %60, %61, %62, %63, "
    "%64, %65, %66, %67, %68, %69, %70, %71, %72, %73, %74, %75, %76, %77, %78, %79, "
    "%80, %81, %82, %83, %84, %85, %86, %87, %88, %89, %90, %91, %92, %93, %94, %95}, "
    "{%96, %97, %98, %99}, %100, p, 1, 1, 0;\n}\n"
    : "+f"(d[0]), "+f"(d[1]), "+f"(d[2]), "+f"(d[3]), "+f"(d[4]), "+f"(d[5]), "+f"(d[6]), "+f"(d[7]),
      "+f"(d[8]), "+f"(d[9]), "+f"(d[10]), "+f"(d[11]), "+f"(d[12]), "+f"(d[13]), "+f"(d[14]), "+f"(d[15]),
      "+f"(d[16]), "+f"(d[17]), "+f"(d[18]), "+f"(d[19]), "+f"(d[20]), "+f"(d[21]), "+f"(d[22]), "+f"(d[23]),
      "+f"(d[24]), "+f"(d[25]), "+f"(d[26]), "+f"(d[27]), "+f"(d[28]), "+f"(d[29]), "+f"(d[30]), "+f"(d[31]),
      "+f"(d[32]), "+f"(d[33]), "+f"(d[34]), "+f"(d[35]), "+f"(d[36]), "+f"(d[37]), "+f"(d[38]), "+f"(d[39]),
      "+f"(d[40]), "+f"(d[41]), "+f"(d[42]), "+f"(d[43]), "+f"(d[44]), "+f"(d[45]), "+f"(d[46]), "+f"(d[47]),
      "+f"(d[48]), "+f"(d[49]), "+f"(d[50]), "+f"(d[51]), "+f"(d[52]), "+f"(d[53]), "+f"(d[54]), "+f"(d[55]),
      "+f"(d[56]), "+f"(d[57]), "+f"(d[58]), "+f"(d[59]), "+f"(d[60]), "+f"(d[61]), "+f"(d[62]), "+f"(d[63]),
      "+f"(d[64]), "+f"(d[65]), "+f"(d[66]), "+f"(d[67]), "+f"(d[68]), "+f"(d[69]), "+f"(d[70]), "+f"(d[71]),
      "+f"(d[72]), "+f"(d[73]), "+f"(d[74]), "+f"(d[75]), "+f"(d[76]), "+f"(d[77]), "+f"(d[78]), "+f"(d[79]),
      "+f"(d[80]), "+f"(d[81]), "+f"(d[82]), "+f"(d[83]), "+f"(d[84]), "+f"(d[85]), "+f"(d[86]), "+f"(d[87]),
      "+f"(d[88]), "+f"(d[89]), "+f"(d[90]), "+f"(d[91]), "+f"(d[92]), "+f"(d[93]), "+f"(d[94]), "+f"(d[95])
    : "r"(a0), "r"(a1), "r"(a2), "r"(a3), "l"(db), "r"(scale_d));
}
__device__ __forceinline__ void wgmma_n80_rs(float (&d)[40], uint32_t a0, uint32_t a1, uint32_t a2, uint32_t a3, uint64_t db, int scale_d) {
  asm volatile("{\n.reg .pred p;\nsetp.ne.b32 p, %45, 0;\n"
    "wgmma.mma_async.sync.aligned.m64n80k16.f32.bf16.bf16 "
    "{%0, %1, %2, %3, %4, %5, %6, %7, %8, %9, %10, %11, %12, %13, %14, %15, "
    "%16, %17, %18, %19, %20, %21, %22, %23, %24, %25, %26, %27, %28, %29, %30, %31, "
    "%32, %33, %34, %35, %36, %37, %38, %39}, "
    "{%40, %41, %42, %43}, %44, p, 1, 1, 1;\n}\n"
    : "+f"(d[0]), "+f"(d[1]), "+f"(d[2]), "+f"(d[3]), "+f"(d[4]), "+f"(d[5]), "+f"(d[6]), "+f"(d[7]),
      "+f"(d[8]), "+f"(d[9]), "+f"(d[10]), "+f"(d[11]), "+f"(d[12]), "+f"(d[13]), "+f"(d[14]), "+f"(d[15]),
      "+f"(d[16]), "+f"(d[17]), "+f"(d[18]), "+f"(d[19]), "+f"(d[20]), "+f"(d[21]), "+f"(d[22]), "+f"(d[23]),
      "+f"(d[24]), "+f"(d[25]), "+f"(d[26]), "+f"(d[27]), "+f"(d[28]), "+f"(d[29]), "+f"(d[30]), "+f"(d[31]),
      "+f"(d[32]), "+f"(d[33]), "+f"(d[34]), "+f"(d[35]), "+f"(d[36]), "+f"(d[37]), "+f"(d[38]), "+f"(d[39])
    : "r"(a0), "r"(a1), "r"(a2), "r"(a3), "l"(db), "r"(scale_d));
}
__device__ __forceinline__ void wgmma_n80_ss(float (&d)[40], uint64_t da, uint64_t db, int scale_d) {
  asm volatile("{\n.reg .pred p;\nsetp.ne.b32 p, %42, 0;\n"
    "wgmma.mma_async.sync.aligned.m64n80k16.f32.bf16.bf16 "
    "{%0, %1, %2, %3, %4, %5, %6, %7, %8, %9, %10, %11, %12, %13, %14, %15, "
    "%16, %17, %18, %19, %20, %21, %22, %23, %24, %25, %26, %27, %28, %29, %30, %31, "
    "%32, %33, %34, %35, %36, %37, %38, %39}, "
    "%40, %41, p, 1, 1, 0, 1;\n}\n"
    : "+f"(d[0]), "+f"(d[1]), "+f"(d[2]), "+f"(d[3]), "+f"(d[4]), "+f"(d[5]), "+f"(d[6]), "+f"(d[7]),
      "+f"(d[8]), "+f"(d[9]), "+f"(d[10]), "+f"(d[11]), "+f"(d[12]), "+f"(d[13]), "+f"(d[14]), "+f"(d[15]),
      "+f"(d[16]), "+f"(d[17]), "+f"(d[18]), "+f"(d[19]), "+f"(d[20]), "+f"(d[21]), "+f"(d[22]), "+f"(d[23]),
      "+f"(d[24]), "+f"(d[25]), "+f"(d[26]), "+f"(d[27]), "+f"(d[28]), "+f"(d[29]), "+f"(d[30]), "+f"(d[31]),
      "+f"(d[32]), "+f"(d[33]), "+f"(d[34]), "+f"(d[35]), "+f"(d[36]), "+f"(d[37]), "+f"(d[38]), "+f"(d[39])
    : "l"(da), "l"(db), "r"(scale_d));
}

__device__ __forceinline__ constexpr int QT(int t) { return t < 8 ? t : 16 + t; }
__device__ __forceinline__ constexpr int KT(int t) { return t < 8 ? 8 + t : 18 + t; }
__device__ __forceinline__ constexpr int VT(int t) { return t < 8 ? 16 + t : 20 + t; }

struct Maps { CUtensorMap x, w, wr, wo, wor, gate, up, down; };

__global__ void __cluster_dims__(2, 1, 1) __launch_bounds__(512, 1)
fused_kernel(const __nv_bfloat16* __restrict__ x, const __nv_bfloat16* __restrict__ wqkv,
             const __nv_bfloat16* __restrict__ wo, const __nv_bfloat16* __restrict__ w_r, const __nv_bfloat16* __restrict__ w_gate,
             const __nv_bfloat16* __restrict__ w_up, const __nv_bfloat16* __restrict__ w_down, __nv_bfloat16* __restrict__ out,
             Scratch* __restrict__ sc, const __grid_constant__ Maps tm) {
  extern __shared__ __align__(1024) uint8_t smem[];
  const int tid = threadIdx.x, warp = __shfl_sync(0xffffffffu, tid >> 5, 0), lane = tid & 31, bid = blockIdx.x;
  const uint32_t sb = (uint32_t)__cvta_generic_to_shared(smem);
  const uint32_t bar_full = sb + OFF_BAR, bar_empty = bar_full + 32, bar_aux = bar_full + 64, bar_ffn = bar_full + 72, bar_win = bar_full + 80, bar_rst = bar_full + 88,
                 bar_o = bar_full + 96, bar_oc = bar_o + 112, bar_st = bar_o + 224, bar_go = bar_o + 248, bar_kv = bar_o + 272;
  if (warp < 4 && elect()) {
    mbar_init(bar_full + 8 * (warp ^ 2), 1);
    mbar_init(bar_empty + 8 * warp, 24);
    mbar_init(bar_aux + 8 * warp, warp == 0 ? 64 : warp == 2 ? 32 : 1);
    asm volatile("fence.mbarrier_init.release.cluster;" ::: "memory");
  }
  asm volatile("barrier.cluster.arrive.relaxed.aligned;" ::: "memory");
  if (warp >= 8 && warp < 11 && elect()) asm volatile("prefetch.tensormap [%0];" :: "l"(&tm.x + (warp - 8)) : "memory");
  auto pf_slice = [&](int ks) {
    pf_l2(lane < 16 ? (const char*)x + ((bid * 16 + lane) * 1280 + ks * 128) : (const char*)wqkv + ((bid * 15 + min(lane, 30) - 16) * 128 + ks * 245760));
  };
  if (warp == 4) pf_slice(0);
  const int rank = bid & 1, cl = bid >> 1;
  const int q7 = ((cl - 36) * 37) >> 8;
  const int P = cl < 4 ? 0 : cl < 36 ? (cl - 4) & 7 : cl - 35 - 7 * q7;
  const int g = cl < 4 ? 4 + cl : cl < 36 ? (cl - 4) >> 3 : 4 + q7;
  const int mt = 2 * P + rank, cid = mt * 8 + g;
  const bool ffn1 = g >= 5;
  const int fj = ffn1 ? mt * 3 + g - 5 : (P * 5 + g) * 2 + rank;
  const int ord = ((g >> 2) ^ P) & 1;
  auto ks_of = [&](int it) { return !ORDX || ord == 0 || it == 0 ? it : it <= 5 ? it + 4 : it - 5; };
  auto load_w = [&](int it, uint32_t a, uint32_t full) {
    tma_3d_mc(a + 16384 + rank * 16384, &tm.w, full, g * 80, it * 64, rank * 2);
    tma_3d_mc(a + (rank ? 40960 : 24576), rank ? &tm.wr : &tm.w, full, g * 80 + rank * 64, it * 64, 1 - rank);
  };
  if (warp == 0 && elect()) {
    mbar_expect_tx(bar_full + 16, SLOT);
    tma_3d(sb + 2 * SLOT, &tm.x, bar_full + 16, 0, P * 128, rank);
  }
  asm volatile("barrier.cluster.wait.aligned;" ::: "memory");
  if (warp == 0) {
    if (elect()) load_w(0, sb + 2 * SLOT, bar_full + 16);
    asm volatile("bar.arrive 4, 64;" ::: "memory");
  }

  if (warp >= 8) {
    asm volatile("setmaxnreg.dec.sync.aligned.u32 %0;" :: "n"(REG_P));
#define TS_T 0
    if (warp == 8) {
      TS(8);
      bar_sync(4, 64);
      if (elect()) {
        TS(10);
        int fjn = 0;
#pragma unroll 1
        for (int it = 1; it < 17; it++) {
          const int s = (it + 2) & 3;
          const uint32_t full = bar_full + 8 * s, a = sb + s * SLOT;
          if (it >= 13) { mbar_wait(bar_oc + 8 * (it - 13), 0); mbar_wait(bar_oc + 56 + 8 * (it - 13), 0); }
          else if (it >= 4) mbar_wait(bar_empty + 8 * s, ((it >> 2) - 1) & 1);
          else if (it >= THR) mbar_wait(bar_full + 8 * ((it - THR + 2) & 3), 0);
          if (it < 10) {
            const int ks = ks_of(it);
            mbar_expect_tx(full, SLOT);
            tma_3d(a, &tm.x, full, ks * 64, P * 128, rank);
            load_w(ks, a, full);
            TS(12 + it);
            if ((unsigned)(it - RST_IT) < 2u) {
              mbar_wait(bar_rst, 0);
              asm volatile("cp.async.bulk.global.shared::cta.bulk_group [%0], [%1], %2;\ncp.async.bulk.commit_group;"
                           :: "l"(it == RST_IT ? (uint4*)(g_own + cid) : (uint4*)&g_x + cid * GLOB_PER_CTA), "r"(sb + OFF_CS),
                              "r"(it == RST_IT ? (int)sizeof(Own) : GLOB_PER_CTA * 16) : "memory");
            }
            if (it == RST_IT + 2) { asm volatile("cp.async.bulk.wait_group 0;" ::: "memory"); mbar_arrive(bar_rst); }
          } else if (it < 13) {
            const int g0 = 3 * (it - 10), g1 = min(g0 + 3, 8);
            mbar_expect_tx(full, (g1 - g0) * 12800);
#pragma unroll 1
            for (int gp = g0 + ((g0 ^ rank) & 1); gp < g1; gp += 2) {
              tma_3d_mc(sb + gp * 15360, &tm.wo, full, 0, gp * 80, g * 2);
              tma_3d_mc(sb + gp * 15360 + 10240, &tm.wor, full, 512 + g * 16, gp * 80, 0);
            }
          }
          if (it == 4) mbar_expect_tx(bar_ffn, ffn1 ? 81920 : 24576);
          const int j1 = ffn1 ? (it >= 13 ? min(2 * it - 21, 10) : min(max(it - F_IT + 1, 0), 4)) : (it >= 13 ? (it == 16 ? 12 : min(F_MAX + (it - 12) * F_LATE, 12)) : min(max((it - F_IT + 1) * F_PER, 0), F_MAX));
#pragma unroll 1
          for (; fjn < j1; fjn++) {
            const int j = fjn < 4 ? fjn + 6 : fjn - 4;
            if (ffn1) tma_3d(sb + (j < 6 ? 0 : OFF_W2 - 49152) + j * 8192, j < 5 ? &tm.gate : &tm.up, bar_ffn, fj * 32, (j < 5 ? j : j - 5) * 128, 0);
            else tma_3d(sb + OFF_W2 + fjn * 2048, &tm.down, bar_ffn, fj * 8, fjn * 128, 0);
          }
        }
        TS(11);
      }
#undef TS_T
#define TS_T 64
    } else if (warp >= 12) {
      const int l7 = lane & 7, j = warp - 12, ch = min((P >> 1) * 4 + rank * 2 + (j >> 1), 14);
      const uint32_t sxo = ((g & 3) * 32 + j * 8 + l7) * 128 + (((lane >> 3) ^ l7) * 16);
      const uint32_t swo = ch < 12 ? 16384 + (ch >> 2) * 8192 + lane * 128 + ((((ch & 3) * 2 + (j & 1)) ^ l7) * 16)
                                   : 40960 + (ch - 12) * 2048 + lane * 32 + (((j & 1) ^ (l7 >> 2)) * 16);
      float ps = 0.f, pq = 0.f, pq1 = 0.f, pc = 0.f;
#pragma unroll 1
      for (int it = ord; it < ord + 5; it++) {
        const int sl = (it + 2) & 3;
        mbar_wait(bar_full + 8 * sl, (it >> 2) & 1);
        TS(it);
        const uint32_t a = sb + sl * SLOT;
        const uint4 v0 = ldsm4(a + sxo), v1 = ldsm4((a + sxo) ^ 64), w0 = ldsm4t(a + swo), w1 = ldsm4t(a + swo + (ch < 12 ? 4096 : 1024));
        if (lane + (int)((v0.x & v1.x & w0.x & w1.x) == 0x7fc17fc1u && (v0.x | v1.x) == 0u) < 2) mbar_arrive_cta(bar_empty + 8 * sl, lane);
        const uint32_t vv[8] = {v0.x, v0.y, v0.z, v0.w, v1.x, v1.y, v1.z, v1.w}, ww[8] = {w0.x, w0.y, w0.z, w0.w, w1.x, w1.y, w1.z, w1.w};
#pragma unroll
        for (int i = 0; i < 8; i++) {
          const float d = bf_lo(vv[i]), e = bf_hi(vv[i]);
          ps += d + e; pq = fmaf(d, d, pq); pq1 = fmaf(e, e, pq1); pc += bf_lo(ww[i]) + bf_hi(ww[i]);
        }
      }
      pq += pq1;
      ps += shx(ps, 1); pq += shx(pq, 1); pc += shx(pc, 1);
      ps += shx(ps, 2); pq += shx(pq, 2); pc += shx(pc, 2);
      const int c = lane & 3;
      if (c < 3) sts32f(sb + OFF_PT + (c * 32 + j * 8 + (lane >> 2)) * 4, c == 0 ? ps : c == 1 ? pq : pc);
      asm volatile("bar.arrive 2, 224;" ::: "memory");
      if (warp == 12) {
        const uint4* const hp = hold(&g_own[max(cid - 16, 0)].halo[0][lane]);
        mbar_wait(bar_aux, 0);
        mbar_wait(bar_go, 0);
        uint4 v[5] = {};
        int guard = SPIN_MAX;
        if (P > 0) {
          do {
#pragma unroll
            for (int i = 0; i < 5; i++) v[i] = ldg_pkt(hp + 32 * i);
          } while (anyw(v[0].x == SENT || v[1].x == SENT || v[2].x == SENT || v[3].x == SENT || v[4].x == SENT) && --guard > 0);
        }
#pragma unroll
        for (int i = 0; i < 5; i++) *(uint4*)(smem + OFF_O + 10240 + i * 512 + lane * 16) = v[i];
        mbar_arrive(bar_kv);
      }
#undef TS_T
#define TS_T 32
    } else if (warp < 11) {
      Own* const own = g_own + cid;
      const int l7 = lane & 7, hk = lane >> 4, idx = lane;
      if (warp == 10 && elect()) {
#pragma unroll 1
        for (int i = 0; i < 36; i++) mbar_init(bar_o + 8 * i, i < 14 || i == 30 ? 1 : i < 34 ? 4 : 128);
      }
      {
        const int t0 = clk();
#pragma unroll 1
        for (int i = PF_FIRST; i < 6; i++) {
          while (clk() - t0 < PF_T0 + (i - PF_FIRST) * PF_CLK) __nanosleep(20);
          pf_slice(warp == 9 ? min(i, 4) : i + 4);
        }
      }
      bar_sync(2, 224);
      mbar_wait(bar_rst, 1);
      TS(0);
      const uint32_t tag = __float_as_uint(lds32f(sb + OFF_WR + 324));
      const float s0 = lds32f(sb + OFF_PT + lane * 4 + (warp - 9) * 256), q0 = lds32f(sb + OFF_PT + 128 + lane * 4);
      int guard = SPIN_MAX;
      if (warp == 9) {
        stg_pkt(&own->st1[idx], __float_as_uint(s0), __float_as_uint(q0), tag, 0u);
        TS(1);
        const uint4* sp = &g_own[mt * 8].st1[lane];
        const uint4* hp = &g_own[max(mt - 2, 0) * 8 + 3].st1[24 + l7];
        uint4 a[5], b[5];
        bool bad;
        do {
          __nanosleep(AUX_NS);
          bad = false;
#pragma unroll
          for (int i = 0; i < 5; i++) {
            const uint4* q = i < 4 ? sp + i * (sizeof(Own) / 16) : hp;
            a[i] = ldg_pkt(q); b[i] = ldg_pkt(q + 4 * sizeof(Own) / 16);
          }
#pragma unroll
          for (int i = 0; i < 5; i++) bad |= a[i].z != tag || b[i].z != tag;
        } while (anyw(bad) && --guard);
#pragma unroll
        for (int i = 0; i < 5; i++) {
          const float m = (__uint_as_float(a[i].x) + __uint_as_float(b[i].x)) * (1.f / 640.f);
          const float rs = rsq(fmaxf(fmaf(-m, m, (__uint_as_float(a[i].y) + __uint_as_float(b[i].y)) * (1.f / 640.f)), 0.f) + 1e-5f);
          ((float*)(smem + OFF_RS))[i < 4 ? 8 + lane + 32 * i : l7] = rs;
          const uint32_t mh = pack_bf16(-m, -m);
          const float ml = -m - bf_lo(mh);
          if (i < 4) ((uint2*)(smem + OFF_MN))[lane + 32 * i] = make_uint2(mh, pack_bf16(ml, ml));
        }
      } else {
        stg_rlx64(&own->cs[idx], __float_as_uint(s0), tag);
        const uint4* cp = (const uint4*)g_own[hk * 8 + g].cs + (lane & 15);
        uint4 a[4], b[4];
        bool bad;
        do {
          __nanosleep(AUX_NS);
          bad = false;
#pragma unroll
          for (int i = 0; i < 4; i++) { a[i] = ldg_pkt(cp + i * 32 * sizeof(Own) / 16); b[i] = ldg_pkt(cp + (i * 32 + 16) * sizeof(Own) / 16); }
#pragma unroll
          for (int i = 0; i < 4; i++) bad |= a[i].y != tag || a[i].w != tag || b[i].y != tag || b[i].w != tag;
        } while (anyw(bad) && --guard);
#pragma unroll
        for (int i = 0; i < 4; i++)
          if (i < 3 || lane < 24) {
            const float c0 = __uint_as_float(a[i].x) + __uint_as_float(b[i].x), c1 = __uint_as_float(a[i].z) + __uint_as_float(b[i].z);
            const uint32_t hi = pack_bf16(c0, c1), w0 = pack_bf16(c0, c0 - bf_lo(hi)), w1 = pack_bf16(c1, c1 - bf_hi(hi));
            uint4* const d = (uint4*)(smem + OFF_CS) + 2 * (lane + 32 * i);
            d[0] = make_uint4(w0, w0, 0, 0); d[1] = make_uint4(w1, w1, 0, 0);
          }
        asm volatile("fence.proxy.async.shared::cta;" ::: "memory");
      }
      mbar_arrive(bar_aux);
      TS(2);
      const int fo = warp - 9, wq = fo ? 1 - LEAD : LEAD;
      const uint4* const fp = hold(g_own[mt * 8 + wq * 4].cnt);
      const char* src = hold((const char*)g_o[mt * 2 + wq]);
      if (elect()) {
        const uint32_t bo = bar_o + fo * 56;
#pragma unroll
        for (int i = 0; i < 7; i++) mbar_expect_tx(bo + 8 * i, 10240);
        mbar_wait(bar_st + 8 * fo, 0);
        if (ONE_RED == 1) {
          asm volatile("red.relaxed.gpu.global.add.u32 [%0], 4;" :: "l"(fp) : "memory");
          if (CNT_NS) __nanosleep(CNT_NS);
        }
        uint32_t cv = 0;
        if (ONE_RED == 2) { asm volatile("atom.relaxed.gpu.global.add.u32 %0, [%1], 4;" : "=r"(cv) : "l"(fp) : "memory"); cv += 4; }
        while (cv != 32u && --guard > 0) cv = ldg_rlx32(fp);
        asm volatile("fence.proxy.async.global;" ::: "memory");
        TS(6);
#pragma unroll
        for (int i = 0; i < 7; i++) {
          if (fo || i == 6) mbar_wait(bo + 64 + 8 * i, 0);
          else if (i == FW) mbar_arrive(bar_go - 8);
          if (!fo && i == 4) mbar_wait(bar_st + 8, 0);
          if (i == g) src += 10240;
          asm volatile("cp.async.bulk.shared::cluster.global.mbarrier::complete_tx::bytes [%0], [%1], 10240, [%2];"
                       :: "r"(sb + OFF_O + ((i + 2) % 6) * 10240 + fo * (i == 3 ? -51200 : 10240)), "l"(src + i * 10240), "r"(bo + 8 * i) : "memory");
        }
      }
#undef TS_T
#define TS_T 96
    } else {
      if ((sb & 0x3FFFF) != D0 * 16) __trap();
#pragma unroll 1
      for (int i = lane; i < 232; i += 32) { const uint32_t f = i < 208 ? SENT : 0u; ((uint4*)(smem + OFF_CS))[i] = make_uint4(f, f, f, f); }
      asm volatile("fence.proxy.async.shared::cta;" ::: "memory");
      if (elect()) mbar_arrive(bar_rst);
      mbar_wait(bar_full + 8 * ((HK_IT + 2) & 3), 0);
      TS(4);
      const uint32_t epoch = ldg_rlx32(g_epoch + cid) + 1;
      uint32_t wv[10];
#pragma unroll
      for (int i = 0; i < 10; i++) wv[i] = __ldg((const uint32_t*)w_r + lane + 32 * i);
      float s = 0.f;
#pragma unroll
      for (int i = 0; i < 10; i++) {
        s += bf_lo(wv[i]) + bf_hi(wv[i]);
        const unsigned u = i < 8 ? lane + 32 * (i - g) : lane + 32 * (i - 7) - g * 8;
        if (i < 8 ? u < 32u : u - 32u < 8u) *(float2*)(smem + OFF_WR + ((u & 3) * 10 + (u >> 2)) * 8) = make_float2(bf_lo(wv[i]), bf_hi(wv[i]));
      }
#pragma unroll
      for (int m = 1; m < 32; m <<= 1) s += shx(s, m);
      *(float2*)(smem + OFF_WR + 320) = make_float2(s, __uint_as_float(epoch * 0x9E3779B8u));
      g_epoch[cid] = epoch;
      TS(3);
      TS(5);
      asm volatile("bar.arrive 2, 224;" ::: "memory");
#pragma unroll 1
      for (int i = 0; i < 14; i++) {
        const int m = (i + 2) >> 2, n = m == 0 ? 50 : 120, t = (m == 0 ? i : (i + 2) & 3) * 32 + lane;
        const char* b = (const char*)(m == 0 ? wo : m == 1 ? w_up : m == 2 ? w_down : w_gate);
        if (t < n) pf_l2(b + (bid * n + t) * 128);
        __nanosleep(PFW_NS);
      }
      const uint4* const kp = hold(g_own[1].cnt);
      const uint4* const cb = hold(&g_x.cand[0][lane >> 2][lane & 3]);
      bar_sync(3, 64);
      uint4 k;
      uint32_t have = SENT;
      int guard = SPIN_MAX;
      while (true) {
        k = ldg_pkt(kp);
        if (ffn1) {
          while (k.x != have && --guard > 0) {
            const uint32_t tk = 2047u - (k.x & 2047u), want = k.x;
            const uint4* q = cb + ((tk >> 8) * 16 + (tk & 1) * 8 + ((tk >> 5) & 7)) * 192;
            const uint4 c0 = ldg_pkt(q), c1 = ldg_pkt(q + 4); const uint2 c2 = ldg_rlx64(q + 8);
            k = ldg_pkt(kp);
            *(uint4*)(smem + OFF_HN + lane * 16) = c0; *(uint4*)(smem + OFF_HN + 512 + lane * 16) = c1; *(uint2*)(smem + OFF_HN + 1024 + lane * 16) = c2;
            have = anyw(c0.x == SENT || c1.x == SENT || c2.x == SENT) ? SENT : want;
          }
        } else if (KEY_NS && k.z != 128u) __nanosleep(KEY_NS);
        if (k.z == 128u || --guard <= 0) break;
      }
      *(uint2*)(smem + OFF_WR + 336) = make_uint2(k.x, k.y);
      mbar_arrive(bar_win);
      TS(7);
    }
#undef TS_T
  } else {
#define TS_T 0
    asm volatile("setmaxnreg.inc.sync.aligned.u32 %0;" :: "n"(REG_C));
    const int wg = warp >> 2, w4 = warp & 3, r = lane >> 2, c = lane & 3;
    float acc[120];
    uint4 xr[5] = {};
    const uint32_t xa = pin(sb + (warp * 16 + (lane & 15)) * 128 + ((lane >> 4) ^ (lane & 7)) * 16);
    const int fol = wg != LEAD;
    const bool first = (P == 0) && (warp == 0);
    const uint32_t kvs = sb + OFF_O + fol * 10240 + w4 * 2560 + lane * 16;
    uint4* const kvd = hold(warp == 7 ? &g_own[cid].halo[0][lane] : (uint4*)(smem + (warp == 3 ? OFF_O + lane * 16 : kvs - sb + 2560)));
    uint4* const odst = hold(&g_o[mt * 2 + wg][g][w4 * 160]);
    uint4* const ocnt = hold(g_own[mt * 8 + wg * 4].cnt);
    uint32_t m0 = 0, m1 = 0;
    const uint32_t mna = pin(sb + OFF_MN + (warp * 16 + r) * 8 + c * 4);
    const int itx = ord == 0 || g == 0 ? g : g < 5 ? g + 5 : g - 4, ity = (ord ? 4 : 8) + (g >> 2);
    uint32_t rel;
    asm volatile("mapa.shared::cluster.u32 %0, %1, %2;" : "=r"(rel) : "r"(bar_empty), "r"(tid & 1));
    const uint32_t xa1 = pin(xa ^ 32), xa2 = pin(xa ^ 64), xa3 = pin(xa ^ 96), xb = pin(xa ^ ((g & 3) * 32));
    const uint32_t da0 = wg * 512;
    const bool rel2 = lane < 2, rel6 = lane < 2 + 2 * (warp & 1);
    const uint32_t zero = (uint32_t)(uintptr_t)x & 8u;
    mbar_wait(bar_full + 16, 0);
    TS(13);
    wgmma_fence();
#pragma unroll
    for (int it = 0; it < 10; it++) {
      const int s = (it + 2) & 3;
      if (it == 9 && fol) bar_sync(10, 256);
#pragma unroll
      for (int kk = 0; kk < 4; kk++) {
        if (kk == 2 && it > 0) {
          wgmma_commit();
          wgmma_wait<1>();
          const uint32_t ra = ((xr[0].x ^ xr[1].x ^ xr[2].x ^ xr[3].x ^ xr[4].x) & zero) | rel;
          if (it == 1 ? (ord ? rel6 : rel2) : it == 6 ? (ord ? rel2 : rel6) : it < 6 ? rel2 : rel6)
            asm volatile("mbarrier.arrive.shared::cluster.b64 _, [%0];" :: "r"(ra + 8 * ((it + 1) & 3)) : "memory");
        }
        if (kk == 2) {
          ldsm4_if(xr[0], xa, s * SLOT, it == itx); ldsm4_if(xr[1], xa1, s * SLOT, it == itx);
          ldsm4_if(xr[2], xa2, s * SLOT, it == itx); ldsm4_if(xr[3], xa3, s * SLOT, it == itx);
          if ((it & 6) == 4 || it >= 8) ldsm4_if(xr[4], xb, s * SLOT, it == ity);
        }
        if (kk == AK && it == 9) {
          mbar_wait(bar_aux, 0);
          TS(3);
          if (c < 2) { m0 = __float_as_uint(lds32f(mna)); m1 = __float_as_uint(lds32f(mna + 64)); }
          if (!fol) bar_sync(11, 256);
        }
        if (kk == 3 && it < 9) {
          mbar_wait(bar_full + 8 * ((it + 3) & 3), ((it + 1) >> 2) & 1);
          if (it < 8) TS(14 + it);
        }
        const uint64_t da = mk64(da0 + (D0 + s * (SLOT >> 4) + kk * 2 + (1 << 16)), 0x40000040u);
        wgmma_n48hi_ss(acc, da, mk64(D0 + s * (SLOT >> 4) + 2560 + kk * 32 + (128 << 16), 0xC0000010u), (it | kk) != 0);
        wgmma_n192lo_ss(acc, da, mk64(D0 + s * (SLOT >> 4) + 1024 + kk * 128 + (512 << 16), 0x40000040u), (it | kk) != 0);
      }
      wgmma_commit();
      if (it == 8 && fol) asm volatile("bar.arrive 11, 256;" ::: "memory");
    }
    {
      const uint64_t dc = make_desc(D0 * 16 + OFF_CS, 0, 128, 0);
      wgmma_fence();
      wgmma_n48hi_rk(acc, m0, m1, 0u, 0u, dc + 192, 1);
      wgmma_n192lo_rk(acc, m0, m1, 0u, 0u, dc, 1);
      wgmma_commit();
      if (!fol) asm volatile("bar.arrive 10, 256;" ::: "memory");
    }
    const uint32_t stb = sb + OFF_RS + warp * 64;
    const float rlo = lds32f(stb + (8 + r) * 4), rhi = lds32f(stb + (16 + r) * 4);
    wgmma_wait<0>();
#pragma unroll
    for (int i = 0; i < 120; i++) asm volatile("" : "+f"(acc[i]) :: "memory");
    if (fol && lane == 0) mbar_arrive(bar_go);
    TS(2);
    uint32_t Qlo[10], Qhi[10], Klo[10], Khi[10], Vlo[10], Vhi[10];
#pragma unroll
    for (int t = 0; t < 10; t++) {
      const int k = KT(t), v = VT(t);
      Khi[t] = pack_bf16(acc[4 * k + 2], acc[4 * k + 3]);
      Vhi[t] = pack_bf16(acc[4 * v + 2] * rhi, acc[4 * v + 3] * rhi);
    }
    st_pkt(kvd, Khi[0], Khi[1], Khi[3], Khi[4]);
    st_pkt(kvd + 32, Khi[5], Khi[6], Khi[8], Khi[9]);
    st_pkt(kvd + 64, Khi[2], Khi[7], Vhi[0], Vhi[1]);
    st_pkt(kvd + 96, Vhi[2], Vhi[3], Vhi[4], Vhi[5]);
    st_pkt(kvd + 128, Vhi[6], Vhi[7], Vhi[8], Vhi[9]);
    if (warp < 7) mbar_arrive(bar_kv + ((warp + 1) >> 2) * 8);
    mbar_wait(bar_aux, 0);
#pragma unroll
    for (int t = 0; t < 10; t++) {
      const int q = QT(t), k = KT(t), v = VT(t);
      Vhi[t] = movm(Vhi[t]);
      Klo[t] = pack_bf16(acc[4 * k], acc[4 * k + 1]);
      Vlo[t] = movm(pack_bf16(acc[4 * v] * rlo, acc[4 * v + 1] * rlo));
      Qlo[t] = pack_bf16(acc[4 * q], acc[4 * q + 1]);
      Qhi[t] = pack_bf16(acc[4 * q + 2], acc[4 * q + 3]);
    }
    const bool in0 = 2 * c <= r, in1 = 2 * c + 1 <= r;
    const uint32_t mL = (in0 ? 0xffffu : 0u) | (in1 ? 0xffff0000u : 0u);
    const float qs = 0.22360679774997896f * 1.4426950408889634f;
    const uint32_t kb0 = stb + (2 * c + (in0 ? 8 : 0)) * 4, kb1 = stb + (2 * c + 1 + (in1 ? 8 : 0)) * 4;
    const float scl0 = lds32f(kb0) * rlo * qs, scl1 = lds32f(kb1) * rlo * qs;
    const float sch0 = lds32f(kb0 + 32) * rhi * qs, sch1 = lds32f(kb1 + 32) * rhi * qs;
    const float bias0 = (first && !in0) ? -INFINITY : 0.f, bias1 = (first && !in1) ? -INFINITY : 0.f;
    const int slot = mt * 8 + warp;
    int guard = SPIN_MAX;
    uint4 pv[5];
    const bool cA = c < 2, nA = r < 4;
    TS(0);
    mbar_wait(bar_go + fol * 8, 0);
    TS(23);
    uint32_t qe[4][2];
    float sl0[4], sl1[4], th0[4], th1[4];
#pragma unroll
    for (int hd = 0; hd < 4; hd++) {
      const int ta = 5 * (hd >> 1) + 3 * (hd & 1), ts = 5 * (hd >> 1) + 2;
      const bool mine = (hd & 1) ? !cA : cA;
      qe[hd][0] = mine ? Qlo[ts] : 0u; qe[hd][1] = mine ? Qhi[ts] : 0u;
      float sl[4], sh[4];
      mma_k24(sl, Qlo[ta], Qhi[ta], Qlo[ta + 1], Qhi[ta + 1], Klo[ta], Klo[ta + 1], qe[hd][0], qe[hd][1], Klo[ts]);
      mma_k24(sh, Qlo[ta], Qhi[ta], Qlo[ta + 1], Qhi[ta + 1], Khi[ta], Khi[ta + 1], qe[hd][0], qe[hd][1], Khi[ts]);
      th0[hd] = (in0 ? sh[2] : sl[2]) * sch0; th1[hd] = (in1 ? sh[3] : sl[3]) * sch1;
      float mh = fmaxf(th0[hd], th1[hd]);
      mh = fmaxf(mh, shx(mh, 1)); mh = fmaxf(mh, shx(mh, 2));
      th0[hd] -= mh; th1[hd] -= mh;
      sl0[hd] = sl[0]; sl1[hd] = sl[1];
    }
    mbar_wait(bar_kv + wg * 8, 0);
    TS(4);
#pragma unroll
    for (int j = 0; j < 5; j++) pv[j] = lds128(kvs + 512 * j);
    const uint32_t Kp[10] = {pv[0].x, pv[0].y, pv[2].x, pv[0].z, pv[0].w, pv[1].x, pv[1].y, pv[2].y, pv[1].z, pv[1].w};
    const uint32_t Vp[10] = {movm(pv[2].z), movm(pv[2].w), movm(pv[3].x), movm(pv[3].y), movm(pv[3].z), movm(pv[3].w), movm(pv[4].x), movm(pv[4].y), movm(pv[4].z), movm(pv[4].w)};
    const uint32_t ONES = 0x3f803f80u;
    uint32_t of[20];
#pragma unroll
    for (int hp = 0; hp < 2; hp++) {
      float o[6][4];
#pragma unroll
      for (int hh = 0; hh < 2; hh++) {
        const int hd = 2 * hp + hh, ta = 5 * hp + 3 * hh, ts = 5 * hp + 2;
        float sp[4];
        mma_k24(sp, Qlo[ta], Qhi[ta], Qlo[ta + 1], Qhi[ta + 1], Kp[ta], Kp[ta + 1], qe[hd][0], qe[hd][1], Kp[ts]);
        const float tl0 = fmaf(in0 ? sl0[hd] : sp[0], scl0, bias0), tl1 = fmaf(in1 ? sl1[hd] : sp[1], scl1, bias1);
        float ml = fmaxf(tl0, tl1);
        ml = fmaxf(ml, shx(ml, 1)); ml = fmaxf(ml, shx(ml, 2));
        if (HOLD == 1 && hd == 3 && !fol && lane == 0) mbar_arrive(bar_go + 8);
        const uint32_t Pl = pack_bf16(ex2(tl0 - ml), ex2(tl1 - ml)), Ph = pack_bf16(ex2(th0[hd]), ex2(th1[hd]));
        const uint32_t a0 = Pl & mL, a1 = Ph & ~mL, a3 = Ph & mL, ap = Pl & ~mL;
        const bool vm = hh == 0 ? nA : !nA;
        mma_k24(o[3 * hh], a0, a1, 0u, a3, Vlo[ta], Vhi[ta], ap, 0u, Vp[ta]);
        mma_k24(o[3 * hh + 1], a0, a1, 0u, a3, Vlo[ta + 1], Vhi[ta + 1], ap, 0u, Vp[ta + 1]);
        mma_k24(o[3 * hh + 2], a0, a1, 0u, a3, vm ? Vlo[ts] : ONES, vm ? Vhi[ts] : ONES, ap, 0u, vm ? Vp[ts] : ONES);
      }
      const float il = rcp(cA ? o[5][0] : o[2][0]), ih = rcp(cA ? o[5][2] : o[2][2]);
      const float jl = shx(il, 2), jh = shx(ih, 2);
      const float al = cA ? jl : il, ah = cA ? jh : ih, bl = cA ? il : jl, bh = cA ? ih : jh;
      const int t0 = 5 * hp;
      of[2 * t0]     = pack_bf16(o[0][0] * al, o[0][1] * al); of[2 * t0 + 1] = pack_bf16(o[0][2] * ah, o[0][3] * ah);
      of[2 * t0 + 2] = pack_bf16(o[1][0] * al, o[1][1] * al); of[2 * t0 + 3] = pack_bf16(o[1][2] * ah, o[1][3] * ah);
      of[2 * t0 + 4] = pack_bf16((cA ? o[2][0] : o[5][0]) * jl, (cA ? o[2][1] : o[5][1]) * jl);
      of[2 * t0 + 5] = pack_bf16((cA ? o[2][2] : o[5][2]) * jh, (cA ? o[2][3] : o[5][3]) * jh);
      of[2 * t0 + 6] = pack_bf16(o[3][0] * bl, o[3][1] * bl); of[2 * t0 + 7] = pack_bf16(o[3][2] * bh, o[3][3] * bh);
      of[2 * t0 + 8] = pack_bf16(o[4][0] * bl, o[4][1] * bl); of[2 * t0 + 9] = pack_bf16(o[4][2] * bh, o[4][3] * bh);
    }
    {
      const uint32_t os = sb + OFF_O + (fol ? 0 : 20480) + w4 * 2560, oa = os + ((lane >> 3) & 1) * 1280 + (lane >> 4) * 128 + (lane & 7) * 16;
#pragma unroll
      for (int s = 0; s < 5; s++) {
        stsm4(oa + s * 256, of[4 * s], of[4 * s + 1], of[4 * s + 2], of[4 * s + 3]);
        if (s == 0 && (fol || HOLD == 2) && lane == 0) mbar_arrive(bar_go + 8 + 8 * fol);
      }
      asm volatile("fence.proxy.async.shared::cta;" ::: "memory");
      __syncwarp();
      if (FW < 5 && fol) mbar_wait(bar_go - 8, 0);
      if (elect()) {
        asm volatile("cp.async.bulk.global.shared::cta.bulk_group [%0], [%1], 2560;\ncp.async.bulk.commit_group;" :: "l"(odst), "r"(os) : "memory");
      }
    }
    TS(5);
    float h[40];
#pragma unroll
    for (int s = 0; s < 5; s++) {
      const uint4 v = xr[s];
      h[8 * s] = bf_lo(v.x); h[8 * s + 1] = bf_hi(v.x); h[8 * s + 2] = bf_lo(v.y); h[8 * s + 3] = bf_hi(v.y);
      h[8 * s + 4] = bf_lo(v.z); h[8 * s + 5] = bf_hi(v.z); h[8 * s + 6] = bf_lo(v.w); h[8 * s + 7] = bf_hi(v.w);
    }
    if (elect()) {
      asm volatile("cp.async.bulk.wait_group 0;" ::: "memory");
      if (!ONE_RED) asm volatile("red.relaxed.gpu.global.add.u32 [%0], 1;" :: "l"(ocnt) : "memory");
      mbar_arrive(bar_st + 8 * fol);
    }
    __syncwarp();
    TS(22);
    mbar_wait(bar_full, 0); mbar_wait(bar_full + 8, 0); mbar_wait(bar_full + 16, 1);
    mbar_wait(bar_go + 16, 0);
    const uint64_t dwo = make_desc(D0 * 16, 5120, 512, 2);
    wgmma_fence();
#pragma unroll
    for (int s = 0; s < 5; s++) wgmma_n80_rs(h, of[4 * s], of[4 * s + 1], of[4 * s + 2], of[4 * s + 3], dwo + g * 960 + s * 64, 1);
    wgmma_commit();
    TS(6);
    const uint32_t bo = bar_o + fol * 56;
#pragma unroll
    for (int i = 0; i < 7; i++) {
      mbar_wait(bo + 8 * i, 0);
      if (i == 0) TS(1);
      const uint32_t da = D0 + OFF_O / 16 + (8 << 16) + ((i + 2) % 6) * 640 + fol * (i == 3 ? -3200 : 640), db = D0 + (320 << 16) + (i >= g ? i + 1 : i) * 960;
      wgmma_fence();
#pragma unroll
      for (int s = 0; s < 5; s++) wgmma_n80_ss(h, mk64(da + s * 16, 80u), mk64(db + s * 64, 0x80000020u), 1);
      wgmma_commit();
      wgmma_wait<1>();
      if (lane == 0 && i > 0) mbar_arrive(bo + 104 + 8 * i);
    }
    const bool odd = c & 1;
    float wr[20];
#pragma unroll
    for (int j = 0; j < 5; j++) {
      const uint4 v = lds128(sb + OFF_WR + c * 80 + j * 16);
      wr[4 * j] = __uint_as_float(v.x); wr[4 * j + 1] = __uint_as_float(v.y); wr[4 * j + 2] = __uint_as_float(v.z); wr[4 * j + 3] = __uint_as_float(v.w);
    }
    const float wsum = lds32f(sb + OFF_WR + 320);
    uint4* const sp = hold(&g_own[slot].st2[r + (odd ? 8 : 0)]);
    uint4* const cdp = hold(&g_x.cand[slot][g][0]);
    const int tok0 = P * 256 + 32 * warp + rank;
    wgmma_wait<0>();
#pragma unroll
    for (int i = 0; i < 40; i++) asm volatile("" : "+f"(h[i]) :: "memory");
    if (lane == 0) mbar_arrive(bo + 160);
    TS(7);
    float mean, rstd, rr;
    {
      float l1 = 0.f, l2 = 0.f, l3 = 0.f, h1 = 0.f, h2 = 0.f, h3 = 0.f;
#pragma unroll
      for (int j = 0; j < 10; j++) {
        l1 += h[4 * j] + h[4 * j + 1]; h1 += h[4 * j + 2] + h[4 * j + 3];
        l2 = fmaf(h[4 * j], h[4 * j], l2); l2 = fmaf(h[4 * j + 1], h[4 * j + 1], l2);
        h2 = fmaf(h[4 * j + 2], h[4 * j + 2], h2); h2 = fmaf(h[4 * j + 3], h[4 * j + 3], h2);
        l3 = fmaf(h[4 * j], wr[2 * j], l3); l3 = fmaf(h[4 * j + 1], wr[2 * j + 1], l3);
        h3 = fmaf(h[4 * j + 2], wr[2 * j], h3); h3 = fmaf(h[4 * j + 3], wr[2 * j + 1], h3);
      }
      float s1 = (odd ? h1 : l1) + shx(odd ? l1 : h1, 1), s2 = (odd ? h2 : l2) + shx(odd ? l2 : h2, 1), s3 = (odd ? h3 : l3) + shx(odd ? l3 : h3, 1);
      s1 += shx(s1, 2); s2 += shx(s2, 2); s3 += shx(s3, 2);
      if (cA) asm volatile("red.relaxed.gpu.global.add.v4.f32 [%0], {%1, %2, %3, %4};" :: "l"(sp), "f"(s1), "f"(s2), "f"(s3), "f"(1.f) : "memory");
      uint4 p0;
      do { p0 = ldg_pkt(sp); } while (anyw(p0.w != 0x41000000u) && --guard > 0);
      mean = __uint_as_float(p0.x) * (1.f / 640.f);
      rstd = rsq(fmaxf(fmaf(-mean, mean, __uint_as_float(p0.y) * (1.f / 640.f)), 0.f) + 1e-5f);
      rr = fmaf(-mean, wsum, __uint_as_float(p0.z)) * rstd;
    }
    TS(8);
    const uint32_t kk = ord_key(rr), kmax = __reduce_max_sync(0xffffffffu, kk);
    const int L = __ffs(__ballot_sync(0xffffffffu, kk == kmax)) - 1;
    const int crow = (L >> 2) + 8 * (L & 1);
    if (warp == g) {
      if (elect()) {
        asm volatile("red.relaxed.gpu.global.max.u64 [%0], %1;" :: "l"(g_own[1].cnt), "l"(((uint64_t)kmax << 32) | (uint32_t)(2047 - tok0 - 2 * crow)) : "memory");
        asm volatile("red.relaxed.gpu.global.add.u32 [%0], 1;" :: "l"(&g_own[1].cnt[0].z) : "memory");
      }
      asm volatile("bar.arrive 3, 64;" ::: "memory");
    }
    const uint32_t stg = sb + (fol ? OFF_O : g * 15360) + w4 * 2560;
    uint4 held;
    {
      const float om = shx(mean, 1), os = shx(rstd, 1);
      const float rl = odd ? os : rstd, rh = odd ? rstd : os;
      const float bl = -(odd ? om : mean) * rl, bh = -(odd ? mean : om) * rh, al = 1.f + rl, ah = 1.f + rh;
      if ((L >> 2) == r) {
        const bool chi = L & 1;
        const float rc = chi ? rh : rl, bc = chi ? bh : bl;
        uint32_t n[10];
#pragma unroll
        for (int j = 0; j < 10; j++) n[j] = pack_bf16(fmaf(chi ? h[4 * j + 2] : h[4 * j], rc, bc), fmaf(chi ? h[4 * j + 3] : h[4 * j + 1], rc, bc));
        uint4* d = cdp + c;
        stg_pkt(d, n[0], n[1], n[2], n[3]); stg_pkt(d + 4, n[4], n[5], n[6], n[7]); stg_rlx64(d + 8, n[8], n[9]);
      }
      mbar_wait(bar_oc + 56, 0);
      const uint32_t fa = stg + (lane & 15) * 160 + (lane >> 4) * 16;
#pragma unroll
      for (int s = 0; s < 5; s++)
        stsm4(fa + s * 32, pack_bf16(fmaf(h[8 * s], al, bl), fmaf(h[8 * s + 1], al, bl)), pack_bf16(fmaf(h[8 * s + 2], ah, bh), fmaf(h[8 * s + 3], ah, bh)),
              pack_bf16(fmaf(h[8 * s + 4], al, bl), fmaf(h[8 * s + 5], al, bl)), pack_bf16(fmaf(h[8 * s + 6], ah, bh), fmaf(h[8 * s + 7], ah, bh)));
      __syncwarp();
      held = lds128(stg + crow * 160 + min(lane, 9) * 16);
      if (lane < 10) stg_pkt(cdp + 12 + lane, held.x, held.y, held.z, held.w);
    }
    TS(9);
    mbar_wait(bar_ffn, 0);
    const uint32_t red = sb + OFF_RED;
    if (ffn1) {
      uint4 w1[4][5];
      {
        const int k = (lane & 7) + (lane >> 4) * 8;
        const uint32_t a1 = sb + k * 64, sw = ((lane >> 3) & 1) ^ ((lane >> 1) & 3);
#pragma unroll
        for (int s = 0; s < 5; s++)
#pragma unroll
          for (int u = 0; u < 4; u++)
            w1[u][s] = ldsm4t(a1 + (s < 4 ? warp * 4096 + s * 1024 : 32768 + warp * 1024) + (u >> 1) * (40960 + (s == 4 || warp >= 2 ? OFF_W2 - 49152 : 0)) + ((sw ^ (2 * (u & 1))) * 16));
      }
      uint32_t* const ap = hold(g_x.act + fj * 16 + (lane >> 1));
      mbar_wait(bar_win, 0);
      const uint32_t hp = sb + OFF_HN + (warp * 4 + c) * 16;
      const uint4 c0 = lds128(hp), c1 = lds128(hp + 512), c2 = lds128(hp + 1024);
      TS(10);
      float a[4][4];
#pragma unroll
      for (int u = 0; u < 4; u++) {
        a[u][0] = a[u][1] = a[u][2] = a[u][3] = 0.f;
        mma_acc(a[u], w1[u][0], c0.x, c0.y); mma_acc(a[u], w1[u][1], c0.z, c0.w); mma_acc(a[u], w1[u][2], c1.x, c1.y);
        mma_acc(a[u], w1[u][3], c1.z, c1.w); mma_acc(a[u], w1[u][4], c2.x, c2.y);
      }
      asm volatile("st.shared.v2.f32 [%0], {%1, %2};" :: "r"(red + (warp * 32 + c * 8 + r) * 8),
                   "f"(cA ? (odd ? a[0][2] : a[0][0]) : (odd ? a[1][2] : a[1][0])), "f"(cA ? (odd ? a[2][2] : a[2][0]) : (odd ? a[3][2] : a[3][0])) : "memory");
      bar_sync(1, 256);
      if (warp == 0) {
        float2 t[8];
#pragma unroll
        for (int i = 0; i < 8; i++) t[i] = lds64f(red + (i * 32 + lane) * 8);
        const float s = ((t[0].x + t[1].x) + (t[2].x + t[3].x)) + ((t[4].x + t[5].x) + (t[6].x + t[7].x));
        const float u = ((t[0].y + t[1].y) + (t[2].y + t[3].y)) + ((t[4].y + t[5].y) + (t[6].y + t[7].y));
        const float av = s * u * rcp(1.f + ex2(-1.4426950408889634f * s));
        const float an = shx(av, 1);
        if (!odd) stg_rlx32(ap, pack_bf16(av, an));
      }
      bar_sync(1, 256);
      TS(11);
    }
    if (OUT_LATE) mbar_wait(bar_win, 0);
    char* const ob2 = (char*)(out + tok0 * 640 + g * 64);
    const int remo = 896 - 96 * g;
#pragma unroll
    for (int s = 0; s < 5; s++) {
      const int row = s < 4 ? 4 * s + (lane >> 3) : lane >> 1, pc = s < 4 ? lane & 7 : 8 + (lane & 1);
      const uint4 v = lds128(stg + row * 160 + pc * 16);
      if (row != crow) stg128(ob2 + row * 2560 + pc * 16 + (s < 4 ? 0 : remo), v);
    }
    mbar_wait(bar_win, 0);
    uint4 win = lds128(sb + OFF_WR + 336);
    win.z = win.y; win.y = 2047u - (win.x & 2047u); win.x = (win.y >> 8) * 16 + (win.y & 1) * 8 + ((win.y >> 5) & 7);
    if (win.x != slot && lane < 10) stg128(ob2 + crow * 2560 + lane * 16 + (lane < 8 ? 0 : remo), held);
    if (!ffn1) {
      TS(10);
      uint4 w2[6];
      const uint32_t a2 = sb + OFF_W2 + (warp * 192 + 8 * (((lane >> 3) & 1) * 4 + ((lane & 7) >> 1)) + 2 * (lane >> 4) + (lane & 1)) * 16;
#pragma unroll
      for (int s = 0; s < 6; s++) w2[s] = ldsm4t(a2 + (s >> 1) * 1024 + (s & 1) * 64);
      const uint4* p = (const uint4*)(g_x.act + warp * 96) + (r & 1) * 4 + c;
      const uint32_t* pb = (const uint32_t*)&g_x.cand[win.x][fj < 64 ? fj >> 3 : (fj - 64) >> 1][fj < 64 ? 12 + (fj & 7) : 20 + (fj & 1)] + c;
      uint32_t* const op = hold((uint32_t*)(out + win.y * 640 + fj * 8) + c);
      const float sg = rcp(1.f + ex2(-1.4426950408889634f * __uint_as_float(win.z ^ ((uint32_t)((int32_t)~win.z >> 31) | 0x80000000u))));
      uint4 c0, c1, c2; uint32_t bw;
      if (ACT_NS) __nanosleep(ACT_NS);
      do {
        c0 = ldg_pkt(p); c1 = ldg_pkt(p + 8); c2 = ldg_pkt(p + 16); bw = ldg_rlx32(pb);
      } while (anyw(max(max(max(max(c0.x, c0.y), max(c0.z, c0.w)), max(max(c1.x, c1.y), max(c1.z, c1.w))), max(max(max(c2.x, c2.y), max(c2.z, c2.w)), bw)) == SENT) && --guard > 0);
      TS(11);
      float a[4] = {0.f, 0.f, 0.f, 0.f}, b[4] = {0.f, 0.f, 0.f, 0.f}, d[4] = {0.f, 0.f, 0.f, 0.f};
      mma_acc(a, w2[0], c0.x, c0.y); mma_acc(b, w2[2], c1.x, c1.y); mma_acc(d, w2[4], c2.x, c2.y);
      mma_acc(a, w2[1], c0.z, c0.w); mma_acc(b, w2[3], c1.z, c1.w); mma_acc(d, w2[5], c2.z, c2.w);
      if (c == 0) sts32f(red + (warp * 8 + r) * 4, ((a[0] + a[3]) + (b[0] + b[3])) + (d[0] + d[3]));
      bar_sync(1, 256);
      if (tid < 4) {
        float2 t[8];
#pragma unroll
        for (int i = 0; i < 8; i++) t[i] = lds64f(red + (i * 4 + tid) * 8);
        const float y0 = ((t[0].x + t[1].x) + (t[2].x + t[3].x)) + ((t[4].x + t[5].x) + (t[6].x + t[7].x));
        const float y1 = ((t[0].y + t[1].y) + (t[2].y + t[3].y)) + ((t[4].y + t[5].y) + (t[6].y + t[7].y));
        *op = pack_bf16(fmaf(y0, sg, bf_lo(bw)), fmaf(y1, sg, bf_hi(bw)));
      }
    }
    TS(12);
#undef TS_T
  }
}

typedef CUresult (*EncodeFn)(CUtensorMap*, CUtensorMapDataType, cuuint32_t, void*, const cuuint64_t*, const cuuint64_t*, const cuuint32_t*,
                             const cuuint32_t*, CUtensorMapInterleave, CUtensorMapSwizzle, CUtensorMapL2promotion, CUtensorMapFloatOOBfill);

void make_map(EncodeFn enc, CUtensorMap* m, const void* base, const cuuint64_t* dims, const cuuint64_t* strides, const cuuint32_t* box,
              CUtensorMapSwizzle swz) {
  const cuuint32_t es[3] = {1, 1, 1};
  enc(m, CU_TENSOR_MAP_DATA_TYPE_BFLOAT16, 3, (void*)base, dims, strides, box, es, CU_TENSOR_MAP_INTERLEAVE_NONE, swz,
      CU_TENSOR_MAP_L2_PROMOTION_L2_128B, CU_TENSOR_MAP_FLOAT_OOB_FILL_NONE);
}

}

extern "C" void kernel_launch(void* const* d_in, const int* in_sizes, int n_in, void* d_out, int out_size) {
  const __nv_bfloat16* x = (const __nv_bfloat16*)d_in[0];
  const __nv_bfloat16* wqkv = (const __nv_bfloat16*)d_in[1];
  const __nv_bfloat16* wo = (const __nv_bfloat16*)d_in[2];
  void* fn = nullptr;
  cudaDriverEntryPointQueryResult st;
  cudaGetDriverEntryPoint("cuTensorMapEncodeTiled", &fn, cudaEnableDefault, &st);
  EncodeFn enc = (EncodeFn)fn;
  void* scp = nullptr;
  cudaGetSymbolAddress(&scp, g_scratch);
  Maps tm;
  { const cuuint64_t d[3] = {640, 1024, 2}, s[2] = {2560, 1280}; const cuuint32_t b[3] = {64, 128, 1}; make_map(enc, &tm.x, x, d, s, b, CU_TENSOR_MAP_SWIZZLE_128B); }
  { const cuuint64_t d[3] = {640, 640, 3}, s[2] = {3840, 1280}; const cuuint32_t b[3] = {64, 64, 1}; make_map(enc, &tm.w, wqkv, d, s, b, CU_TENSOR_MAP_SWIZZLE_128B); }
  { const cuuint64_t d[3] = {640, 640, 3}, s[2] = {3840, 1280}; const cuuint32_t b[3] = {16, 64, 3}; make_map(enc, &tm.wr, wqkv, d, s, b, CU_TENSOR_MAP_SWIZZLE_32B); }
  { const cuuint64_t d[3] = {32, 640, 20}, s[2] = {1280, 64}; const cuuint32_t b[3] = {32, 80, 2}; make_map(enc, &tm.wo, wo, d, s, b, CU_TENSOR_MAP_SWIZZLE_64B); }
  { const cuuint64_t d[3] = {640, 640, 1}, s[2] = {1280, 819200}; const cuuint32_t b[3] = {16, 80, 1}; make_map(enc, &tm.wor, wo, d, s, b, CU_TENSOR_MAP_SWIZZLE_64B); }
  { const cuuint64_t d[3] = {1536, 640, 1}, s[2] = {3072, 1966080}; const cuuint32_t b[3] = {32, 128, 1};
    make_map(enc, &tm.gate, d_in[5], d, s, b, CU_TENSOR_MAP_SWIZZLE_64B); make_map(enc, &tm.up, d_in[6], d, s, b, CU_TENSOR_MAP_SWIZZLE_64B); }
  { const cuuint64_t d[3] = {640, 1536, 1}, s[2] = {1280, 1966080}; const cuuint32_t b[3] = {8, 128, 1}; make_map(enc, &tm.down, d_in[7], d, s, b, CU_TENSOR_MAP_SWIZZLE_NONE); }
  cudaFuncSetAttribute(fused_kernel, cudaFuncAttributeMaxDynamicSharedMemorySize, SMEM_BYTES);
  fused_kernel<<<128, 512, SMEM_BYTES, cudaStreamPerThread>>>(x, wqkv, wo, (const __nv_bfloat16*)d_in[4], (const __nv_bfloat16*)d_in[5],
                                                              (const __nv_bfloat16*)d_in[6], (const __nv_bfloat16*)d_in[7], (__nv_bfloat16*)d_out, (Scratch*)scp, tm);
}
```

```cpp
#include <cuda_runtime.h>
#include <cuda_bf16.h>
#include <cuda.h>
#include <stdint.h>

#define PFW_NS 50
#define ACT_NS 100
#define OUT_LATE 0
#define REG_P 72
#define REG_C 184
#define AUX_NS 50
#define LEAD 1
#define RST_IT 4
#define ORDX 1
#define THR 2
#define PF_FIRST 3
#define PF_T0 2000
#define PF_CLK 500
#define HK_IT 1
#define F_IT 9
#define F_PER 2
#define F_MAX 8
#define HOLD 2
#define F_LATE 12
#define HALO_NS 0
#define AK 3
#define KEY_NS 60
#define FW 5
#define ONE_RED 2
#define CNT_NS 0
#define NO_LATE 0
#define EARLY 1
#define PREW 9

namespace {

constexpr int SLOT    = 47104;
constexpr int OFF_O   = 122880;
constexpr int OFF_W2  = 4 * SLOT;
constexpr int OFF_CS  = OFF_W2 + 32768;
constexpr int OFF_RS  = OFF_CS + 3840;
constexpr int OFF_MN  = OFF_RS + 576;
constexpr int OFF_WR  = OFF_MN + 1024;
constexpr int OFF_RED = OFF_CS;
constexpr int OFF_HN  = OFF_CS + 2048;
constexpr int OFF_PT  = OFF_WR + 352;
constexpr int OFF_BAR = OFF_PT + 768;
constexpr int SMEM_BYTES = OFF_BAR + 392 + 384;
constexpr uint32_t D0 = 1024 >> 4;
constexpr uint32_t SENT = 0xFFFFFFFFu;
constexpr int SPIN_MAX = 1 << 20;

struct Glob {
  uint4 cand[128][8][24];
  uint32_t act[768];
  uint32_t pad[256];
};
constexpr int GLOB_PER_CTA = sizeof(Glob) / 16 / 128;
static_assert(GLOB_PER_CTA * 128 * 16 == sizeof(Glob), "glob size");
struct Own {
  uint4 halo[5][32];
  uint4 st1[32];
  uint2 cs[32];
  uint4 st2[16];
  uint4 cnt[8];
};
struct Scratch {
  Glob x;
  Own own[128];
  uint4 o[32][8][640];
  uint32_t epoch[128];
};
__device__ __align__(128) Scratch g_scratch;
#define g_x (sc->x)
#define g_own (sc->own)
#define g_o (sc->o)
#define g_epoch (sc->epoch)
#define TS(i)

__device__ __forceinline__ void mbar_init(uint32_t bar, uint32_t cnt) { asm volatile("mbarrier.init.shared::cta.b64 [%0], %1;" :: "r"(bar), "r"(cnt) : "memory"); }
__device__ __forceinline__ void mbar_expect_tx(uint32_t bar, uint32_t bytes) { asm volatile("mbarrier.arrive.expect_tx.shared::cta.b64 _, [%0], %1;" :: "r"(bar), "r"(bytes) : "memory"); }
__device__ __forceinline__ void mbar_arrive(uint32_t bar) { asm volatile("mbarrier.arrive.shared::cta.b64 _, [%0];" :: "r"(bar) : "memory"); }
__device__ __forceinline__ void mbar_arrive_cta(uint32_t bar, uint32_t cta) {
  asm volatile("{\n.reg .b32 ra;\nmapa.shared::cluster.u32 ra, %0, %1;\nmbarrier.arrive.shared::cluster.b64 _, [ra];\n}\n" :: "r"(bar), "r"(cta) : "memory");
}
__device__ __forceinline__ void mbar_wait(uint32_t bar, uint32_t parity) {
  asm volatile("{\n.reg .pred p;\n.reg .u32 n;\nmov.u32 n, 0;\nW:\nmbarrier.try_wait.parity.shared::cta.b64 p, [%0], %1;\n@p bra.uni D;\n"
               "add.u32 n, n, 1;\nsetp.lt.u32 p, n, %2;\n@p bra.uni W;\nD:\n}\n" :: "r"(bar), "r"(parity), "n"(SPIN_MAX) : "memory");
}
__device__ __forceinline__ void tma_3d(uint32_t dst, const void* tm, uint32_t bar, int c0, int c1, int c2) {
  asm volatile("cp.async.bulk.tensor.3d.shared::cluster.global.mbarrier::complete_tx::bytes [%0], [%1, {%3, %4, %5}], [%2];" :: "r"(dst), "l"(tm), "r"(bar), "r"(c0), "r"(c1), "r"(c2) : "memory");
}
__device__ __forceinline__ void tma_3d_mc(uint32_t dst, const void* tm, uint32_t bar, int c0, int c1, int c2) {
  asm volatile("cp.async.bulk.tensor.3d.shared::cluster.global.mbarrier::complete_tx::bytes.multicast::cluster [%0], [%1, {%3, %4, %5}], [%2], %6;" :: "r"(dst), "l"(tm), "r"(bar), "r"(c0), "r"(c1), "r"(c2), "h"((uint16_t)3) : "memory");
}
__device__ __forceinline__ void wgmma_fence() { asm volatile("wgmma.fence.sync.aligned;" ::: "memory"); }
__device__ __forceinline__ void wgmma_commit() { asm volatile("wgmma.commit_group.sync.aligned;" ::: "memory"); }
template <int N> __device__ __forceinline__ void wgmma_wait() { asm volatile("wgmma.wait_group.sync.aligned %0;" :: "n"(N) : "memory"); }
__device__ __forceinline__ uint64_t make_desc(uint32_t addr, uint32_t lbo, uint32_t sbo, uint32_t swz) {
  return (uint64_t)(((addr & 0x3FFFF) >> 4) | ((lbo >> 4) << 16)) | ((uint64_t)((sbo >> 4) | (swz << 30)) << 32);
}
__device__ __forceinline__ void bar_sync(int id, int n) { asm volatile("bar.sync %0, %1;" :: "r"(id), "r"(n) : "memory"); }
__device__ __forceinline__ void st_pkt(void* p, uint32_t a, uint32_t b, uint32_t c, uint32_t d) {
  asm volatile("st.relaxed.gpu.v4.u32 [%0], {%1, %2, %3, %4};" :: "l"(p), "r"(a), "r"(b), "r"(c), "r"(d) : "memory");
}
__device__ __forceinline__ uint4 ldg_pkt(const void* p) {
  uint4 v; asm volatile("ld.relaxed.gpu.global.v4.u32 {%0, %1, %2, %3}, [%4];" : "=r"(v.x), "=r"(v.y), "=r"(v.z), "=r"(v.w) : "l"(p) : "memory"); return v;
}
__device__ __forceinline__ void stg_pkt(void* p, uint32_t a, uint32_t b, uint32_t c, uint32_t d) {
  asm volatile("st.relaxed.gpu.global.v4.u32 [%0], {%1, %2, %3, %4};" :: "l"(p), "r"(a), "r"(b), "r"(c), "r"(d) : "memory");
}
__device__ __forceinline__ uint32_t ldg_rlx32(const void* p) { uint32_t v; asm volatile("ld.relaxed.gpu.global.u32 %0, [%1];" : "=r"(v) : "l"(p) : "memory"); return v; }
__device__ __forceinline__ uint2 ldg_rlx64(const void* p) { uint2 v; asm volatile("ld.relaxed.gpu.global.v2.u32 {%0, %1}, [%2];" : "=r"(v.x), "=r"(v.y) : "l"(p) : "memory"); return v; }
__device__ __forceinline__ void stg128(void* p, const uint4& v) { asm volatile("st.global.v4.u32 [%0], {%1, %2, %3, %4};" :: "l"(p), "r"(v.x), "r"(v.y), "r"(v.z), "r"(v.w) : "memory"); }
__device__ __forceinline__ uint32_t pin(uint32_t v) { asm volatile("" : "+r"(v)); return v; }
__device__ __forceinline__ uint64_t mk64(uint32_t lo, uint32_t hi) { return ((uint64_t)hi << 32) | lo; }
template <class T> __device__ __forceinline__ T* hold(T* p) { return (T*)__shfl_sync(0xffffffffu, (unsigned long long)p, threadIdx.x & 31); }
template <class T> __device__ __forceinline__ T* pin(T* p) { asm volatile("" : "+l"(p)); return p; }
__device__ __forceinline__ void stg_rlx32(void* p, uint32_t v) { asm volatile("st.relaxed.gpu.global.u32 [%0], %1;" :: "l"(p), "r"(v) : "memory"); }
__device__ __forceinline__ void stg_rlx64(void* p, uint32_t a, uint32_t b) { asm volatile("st.relaxed.gpu.global.v2.u32 [%0], {%1, %2};" :: "l"(p), "r"(a), "r"(b) : "memory"); }
__device__ __forceinline__ uint4 ldsm4(uint32_t a) { uint4 v; asm volatile("ldmatrix.sync.aligned.m8n8.x4.shared.b16 {%0, %1, %2, %3}, [%4];" : "=r"(v.x), "=r"(v.y), "=r"(v.z), "=r"(v.w) : "r"(a) : "memory"); return v; }
__device__ __forceinline__ void ldsm4_if(uint4& v, uint32_t a, int off, bool p) {
  asm volatile("{\n.reg .pred q;\nsetp.ne.u32 q, %5, 0;\n@q ldmatrix.sync.aligned.m8n8.x4.shared.b16 {%0, %1, %2, %3}, [%4];\n}\n"
               : "+r"(v.x), "+r"(v.y), "+r"(v.z), "+r"(v.w) : "r"(a + off), "r"((int)p) : "memory");
}
__device__ __forceinline__ uint4 ldsm4t(uint32_t a) { uint4 v; asm volatile("ldmatrix.sync.aligned.m8n8.x4.trans.shared.b16 {%0, %1, %2, %3}, [%4];" : "=r"(v.x), "=r"(v.y), "=r"(v.z), "=r"(v.w) : "r"(a) : "memory"); return v; }
__device__ __forceinline__ void stsm4(uint32_t a, uint32_t x, uint32_t y, uint32_t z, uint32_t w) { asm volatile("stmatrix.sync.aligned.m8n8.x4.shared.b16 [%0], {%1, %2, %3, %4};" :: "r"(a), "r"(x), "r"(y), "r"(z), "r"(w) : "memory"); }
__device__ __forceinline__ void mma_acc(float (&c)[4], const uint4& a, uint32_t b0, uint32_t b1) {
  asm("mma.sync.aligned.m16n8k16.row.col.f32.bf16.bf16.f32 {%0,%1,%2,%3}, {%4,%5,%6,%7}, {%8,%9}, {%0,%1,%2,%3};"
      : "+f"(c[0]), "+f"(c[1]), "+f"(c[2]), "+f"(c[3]) : "r"(a.x), "r"(a.y), "r"(a.z), "r"(a.w), "r"(b0), "r"(b1));
}
__device__ __forceinline__ uint4 lds128(uint32_t a) { uint4 v; asm volatile("ld.shared.v4.u32 {%0, %1, %2, %3}, [%4];" : "=r"(v.x), "=r"(v.y), "=r"(v.z), "=r"(v.w) : "r"(a) : "memory"); return v; }
__device__ __forceinline__ float2 lds64f(uint32_t a) { float2 v; asm volatile("ld.shared.v2.f32 {%0, %1}, [%2];" : "=f"(v.x), "=f"(v.y) : "r"(a)); return v; }
__device__ __forceinline__ float lds32f(uint32_t a) { float v; asm volatile("ld.shared.f32 %0, [%1];" : "=f"(v) : "r"(a)); return v; }
__device__ __forceinline__ void sts32f(uint32_t a, float v) { asm volatile("st.shared.f32 [%0], %1;" :: "r"(a), "f"(v) : "memory"); }
__device__ __forceinline__ uint32_t pack_bf16(float lo, float hi) { uint32_t r; asm("cvt.rn.bf16x2.f32 %0, %1, %2;" : "=r"(r) : "f"(hi), "f"(lo)); return r; }
__device__ __forceinline__ float bf_lo(uint32_t v) { return __uint_as_float(v << 16); }
__device__ __forceinline__ float bf_hi(uint32_t v) { return __uint_as_float(v & 0xffff0000u); }
__device__ __forceinline__ uint32_t movm(uint32_t a) { uint32_t d; asm("movmatrix.sync.aligned.m8n8.trans.b16 %0, %1;" : "=r"(d) : "r"(a)); return d; }
__device__ __forceinline__ float ex2(float x) { float y; asm("ex2.approx.ftz.f32 %0, %1;" : "=f"(y) : "f"(x)); return y; }
__device__ __forceinline__ float rsq(float x) { float y; asm("rsqrt.approx.ftz.f32 %0, %1;" : "=f"(y) : "f"(x)); return y; }
__device__ __forceinline__ float rcp(float x) { float y; asm("rcp.approx.ftz.f32 %0, %1;" : "=f"(y) : "f"(x)); return y; }
__device__ __forceinline__ bool elect() { uint32_t p; asm volatile("{\n.reg .pred q;\nelect.sync _|q, 0xffffffff;\nselp.u32 %0, 1, 0, q;\n}\n" : "=r"(p)); return p; }
__device__ __forceinline__ int clk() { int c; asm volatile("mov.u32 %0, %%clock;" : "=r"(c) :: "memory"); return c; }
__device__ __forceinline__ void pf_l2(const void* p) { asm volatile("prefetch.global.L2 [%0];" :: "l"(p)); }
__device__ __forceinline__ bool anyw(bool p) { return __any_sync(0xffffffffu, p); }
__device__ __forceinline__ float shx(float v, int m) { return __shfl_xor_sync(0xffffffffu, v, m); }
__device__ __forceinline__ void mma_k24(float (&c)[4], uint32_t a0, uint32_t a1, uint32_t a2, uint32_t a3, uint32_t b0, uint32_t b1,
                                        uint32_t e0, uint32_t e1, uint32_t f0) {
  asm("mma.sync.aligned.m16n8k16.row.col.f32.bf16.bf16.f32 {%0,%1,%2,%3}, {%4,%5,%6,%7}, {%8,%9}, {%10,%10,%10,%10};"
      : "=f"(c[0]), "=f"(c[1]), "=f"(c[2]), "=f"(c[3]) : "r"(a0), "r"(a1), "r"(a2), "r"(a3), "r"(b0), "r"(b1), "f"(0.f));
  asm("mma.sync.aligned.m16n8k8.row.col.f32.bf16.bf16.f32 {%0,%1,%2,%3}, {%4,%5}, {%6}, {%0,%1,%2,%3};"
      : "+f"(c[0]), "+f"(c[1]), "+f"(c[2]), "+f"(c[3]) : "r"(e0), "r"(e1), "r"(f0));
}
__device__ __forceinline__ uint32_t ord_key(float r) { uint32_t u = __float_as_uint(r); return u ^ ((uint32_t)((int32_t)u >> 31) | 0x80000000u); }

__device__ __forceinline__ void wgmma_n48hi_ss(float (&d)[120], uint64_t da, uint64_t db, int scale_d) {
  asm volatile("{\n.reg .pred p;\nsetp.ne.b32 p, %26, 0;\n"
    "wgmma.mma_async.sync.aligned.m64n48k16.f32.bf16.bf16 "
    "{%0, %1, %2, %3, %4, %5, %6, %7, %8, %9, %10, %11, %12, %13, %14, %15, "
    "%16, %17, %18, %19, %20, %21, %22, %23}, "
    "%24, %25, p, 1, 1, 0, 1;\n}\n"
    : "+f"(d[96]), "+f"(d[97]), "+f"(d[98]), "+f"(d[99]), "+f"(d[100]), "+f"(d[101]), "+f"(d[102]), "+f"(d[103]),
      "+f"(d[104]), "+f"(d[105]), "+f"(d[106]), "+f"(d[107]), "+f"(d[108]), "+f"(d[109]), "+f"(d[110]), "+f"(d[111]),
      "+f"(d[112]), "+f"(d[113]), "+f"(d[114]), "+f"(d[115]), "+f"(d[116]), "+f"(d[117]), "+f"(d[118]), "+f"(d[119])
    : "l"(da), "l"(db), "r"(scale_d));
}
__device__ __forceinline__ void wgmma_n192lo_ss(float (&d)[120], uint64_t da, uint64_t db, int scale_d) {
  asm volatile("{\n.reg .pred p;\nsetp.ne.b32 p, %98, 0;\n"
    "wgmma.mma_async.sync.aligned.m64n192k16.f32.bf16.bf16 "
    "{%0, %1, %2, %3, %4, %5, %6, %7, %8, %9, %10, %11, %12, %13, %14, %15, "
    "%16, %17, %18, %19, %20, %21, %22, %23, %24, %25, %26, %27, %28, %29, %30, %31, "
    "%32, %33, %34, %35, %36, %37, %38, %39, %40, %41, %42, %43, %44, %45, %46, %47, "
    "%48, %49, %50, %51, %52, %53, %54, %55, %56, %57, %58, %59, %60, %61, %62, %63, "
    "%64, %65, %66, %67, %68, %69, %70, %71, %72, %73, %74, %75, %76, %77, %78, %79, "
    "%80, %81, %82, %83, %84, %85, %86, %87, %88, %89, %90, %91, %92, %93, %94, %95}, "
    "%96, %97, p, 1, 1, 0, 1;\n}\n"
    : "+f"(d[0]), "+f"(d[1]), "+f"(d[2]), "+f"(d[3]), "+f"(d[4]), "+f"(d[5]), "+f"(d[6]), "+f"(d[7]),
      "+f"(d[8]), "+f"(d[9]), "+f"(d[10]), "+f"(d[11]), "+f"(d[12]), "+f"(d[13]), "+f"(d[14]), "+f"(d[15]),
      "+f"(d[16]), "+f"(d[17]), "+f"(d[18]), "+f"(d[19]), "+f"(d[20]), "+f"(d[21]), "+f"(d[22]), "+f"(d[23]),
      "+f"(d[24]), "+f"(d[25]), "+f"(d[26]), "+f"(d[27]), "+f"(d[28]), "+f"(d[29]), "+f"(d[30]), "+f"(d[31]),
      "+f"(d[32]), "+f"(d[33]), "+f"(d[34]), "+f"(d[35]), "+f"(d[36]), "+f"(d[37]), "+f"(d[38]), "+f"(d[39]),
      "+f"(d[40]), "+f"(d[41]), "+f"(d[42]), "+f"(d[43]), "+f"(d[44]), "+f"(d[45]), "+f"(d[46]), "+f"(d[47]),
      "+f"(d[48]), "+f"(d[49]), "+f"(d[50]), "+f"(d[51]), "+f"(d[52]), "+f"(d[53]), "+f"(d[54]), "+f"(d[55]),
      "+f"(d[56]), "+f"(d[57]), "+f"(d[58]), "+f"(d[59]), "+f"(d[60]), "+f"(d[61]), "+f"(d[62]), "+f"(d[63]),
      "+f"(d[64]), "+f"(d[65]), "+f"(d[66]), "+f"(d[67]), "+f"(d[68]), "+f"(d[69]), "+f"(d[70]), "+f"(d[71]),
      "+f"(d[72]), "+f"(d[73]), "+f"(d[74]), "+f"(d[75]), "+f"(d[76]), "+f"(d[77]), "+f"(d[78]), "+f"(d[79]),
      "+f"(d[80]), "+f"(d[81]), "+f"(d[82]), "+f"(d[83]), "+f"(d[84]), "+f"(d[85]), "+f"(d[86]), "+f"(d[87]),
      "+f"(d[88]), "+f"(d[89]), "+f"(d[90]), "+f"(d[91]), "+f"(d[92]), "+f"(d[93]), "+f"(d[94]), "+f"(d[95])
    : "l"(da), "l"(db), "r"(scale_d));
}
__device__ __forceinline__ void wgmma_n48hi_rk(float (&d)[120], uint32_t a0, uint32_t a1, uint32_t a2, uint32_t a3, uint64_t db, int scale_d) {
  asm volatile("{\n.reg .pred p;\nsetp.ne.b32 p, %29, 0;\n"
    "wgmma.mma_async.sync.aligned.m64n48k16.f32.bf16.bf16 "
    "{%0, %1, %2, %3, %4, %5, %6, %7, %8, %9, %10, %11, %12, %13, %14, %15, "
    "%16, %17, %18, %19, %20, %21, %22, %23}, "
    "{%24, %25, %26, %27}, %28, p, 1, 1, 0;\n}\n"
    : "+f"(d[96]), "+f"(d[97]), "+f"(d[98]), "+f"(d[99]), "+f"(d[100]), "+f"(d[101]), "+f"(d[102]), "+f"(d[103]),
      "+f"(d[104]), "+f"(d[105]), "+f"(d[106]), "+f"(d[107]), "+f"(d[108]), "+f"(d[109]), "+f"(d[110]), "+f"(d[111]),
      "+f"(d[112]), "+f"(d[113]), "+f"(d[114]), "+f"(d[115]), "+f"(d[116]), "+f"(d[117]), "+f"(d[118]), "+f"(d[119])
    : "r"(a0), "r"(a1), "r"(a2), "r"(a3), "l"(db), "r"(scale_d));
}
__device__ __forceinline__ void wgmma_n192lo_rk(float (&d)[120], uint32_t a0, uint32_t a1, uint32_t a2, uint32_t a3, uint64_t db, int scale_d) {
  asm volatile("{\n.reg .pred p;\nsetp.ne.b32 p, %101, 0;\n"
    "wgmma.mma_async.sync.aligned.m64n192k16.f32.bf16.bf16 "
    "{%0, %1, %2, %3, %4, %5, %6, %7, %8, %9, %10, %11, %12, %13, %14, %15, "
    "%16, %17, %18, %19, %20, %21, %22, %23, %24, %25, %26, %27, %28, %29, %30, %31, "
    "%32, %33, %34, %35, %36, %37, %38, %39, %40, %41, %42, %43, %44, %45, %46, %47, "
    "%48, %49, %50, %51, %52, %53, %54, %55, %56, %57, %58, %59, %60, %61, %62, %63, "
    "%64, %65, %66, %67, %68, %69, %70, %71, %72, %73, %74, %75, %76, %77, %78, %79, "
    "%80, %81, %82, %83, %84, %85, %86, %87, %88, %89, %90, %91, %92, %93, %94, %95}, "
    "{%96, %97, %98, %99}, %100, p, 1, 1, 0;\n}\n"
    : "+f"(d[0]), "+f"(d[1]), "+f"(d[2]), "+f"(d[3]), "+f"(d[4]), "+f"(d[5]), "+f"(d[6]), "+f"(d[7]),
      "+f"(d[8]), "+f"(d[9]), "+f"(d[10]), "+f"(d[11]), "+f"(d[12]), "+f"(d[13]), "+f"(d[14]), "+f"(d[15]),
      "+f"(d[16]), "+f"(d[17]), "+f"(d[18]), "+f"(d[19]), "+f"(d[20]), "+f"(d[21]), "+f"(d[22]), "+f"(d[23]),
      "+f"(d[24]), "+f"(d[25]), "+f"(d[26]), "+f"(d[27]), "+f"(d[28]), "+f"(d[29]), "+f"(d[30]), "+f"(d[31]),
      "+f"(d[32]), "+f"(d[33]), "+f"(d[34]), "+f"(d[35]), "+f"(d[36]), "+f"(d[37]), "+f"(d[38]), "+f"(d[39]),
      "+f"(d[40]), "+f"(d[41]), "+f"(d[42]), "+f"(d[43]), "+f"(d[44]), "+f"(d[45]), "+f"(d[46]), "+f"(d[47]),
      "+f"(d[48]), "+f"(d[49]), "+f"(d[50]), "+f"(d[51]), "+f"(d[52]), "+f"(d[53]), "+f"(d[54]), "+f"(d[55]),
      "+f"(d[56]), "+f"(d[57]), "+f"(d[58]), "+f"(d[59]), "+f"(d[60]), "+f"(d[61]), "+f"(d[62]), "+f"(d[63]),
      "+f"(d[64]), "+f"(d[65]), "+f"(d[66]), "+f"(d[67]), "+f"(d[68]), "+f"(d[69]), "+f"(d[70]), "+f"(d[71]),
      "+f"(d[72]), "+f"(d[73]), "+f"(d[74]), "+f"(d[75]), "+f"(d[76]), "+f"(d[77]), "+f"(d[78]), "+f"(d[79]),
      "+f"(d[80]), "+f"(d[81]), "+f"(d[82]), "+f"(d[83]), "+f"(d[84]), "+f"(d[85]), "+f"(d[86]), "+f"(d[87]),
      "+f"(d[88]), "+f"(d[89]), "+f"(d[90]), "+f"(d[91]), "+f"(d[92]), "+f"(d[93]), "+f"(d[94]), "+f"(d[95])
    : "r"(a0), "r"(a1), "r"(a2), "r"(a3), "l"(db), "r"(scale_d));
}
__device__ __forceinline__ void wgmma_n80_rs(float (&d)[40], uint32_t a0, uint32_t a1, uint32_t a2, uint32_t a3, uint64_t db, int scale_d) {
  asm volatile("{\n.reg .pred p;\nsetp.ne.b32 p, %45, 0;\n"
    "wgmma.mma_async.sync.aligned.m64n80k16.f32.bf16.bf16 "
    "{%0, %1, %2, %3, %4, %5, %6, %7, %8, %9, %10, %11, %12, %13, %14, %15, "
    "%16, %17, %18, %19, %20, %21, %22, %23, %24, %25, %26, %27, %28, %29, %30, %31, "
    "%32, %33, %34, %35, %36, %37, %38, %39}, "
    "{%40, %41, %42, %43}, %44, p, 1, 1, 1;\n}\n"
    : "+f"(d[0]), "+f"(d[1]), "+f"(d[2]), "+f"(d[3]), "+f"(d[4]), "+f"(d[5]), "+f"(d[6]), "+f"(d[7]),
      "+f"(d[8]), "+f"(d[9]), "+f"(d[10]), "+f"(d[11]), "+f"(d[12]), "+f"(d[13]), "+f"(d[14]), "+f"(d[15]),
      "+f"(d[16]), "+f"(d[17]), "+f"(d[18]), "+f"(d[19]), "+f"(d[20]), "+f"(d[21]), "+f"(d[22]), "+f"(d[23]),
      "+f"(d[24]), "+f"(d[25]), "+f"(d[26]), "+f"(d[27]), "+f"(d[28]), "+f"(d[29]), "+f"(d[30]), "+f"(d[31]),
      "+f"(d[32]), "+f"(d[33]), "+f"(d[34]), "+f"(d[35]), "+f"(d[36]), "+f"(d[37]), "+f"(d[38]), "+f"(d[39])
    : "r"(a0), "r"(a1), "r"(a2), "r"(a3), "l"(db), "r"(scale_d));
}
__device__ __forceinline__ void wgmma_n80_ss(float (&d)[40], uint64_t da, uint64_t db, int scale_d) {
  asm volatile("{\n.reg .pred p;\nsetp.ne.b32 p, %42, 0;\n"
    "wgmma.mma_async.sync.aligned.m64n80k16.f32.bf16.bf16 "
    "{%0, %1, %2, %3, %4, %5, %6, %7, %8, %9, %10, %11, %12, %13, %14, %15, "
    "%16, %17, %18, %19, %20, %21, %22, %23, %24, %25, %26, %27, %28, %29, %30, %31, "
    "%32, %33, %34, %35, %36, %37, %38, %39}, "
    "%40, %41, p, 1, 1, 0, 1;\n}\n"
    : "+f"(d[0]), "+f"(d[1]), "+f"(d[2]), "+f"(d[3]), "+f"(d[4]), "+f"(d[5]), "+f"(d[6]), "+f"(d[7]),
      "+f"(d[8]), "+f"(d[9]), "+f"(d[10]), "+f"(d[11]), "+f"(d[12]), "+f"(d[13]), "+f"(d[14]), "+f"(d[15]),
      "+f"(d[16]), "+f"(d[17]), "+f"(d[18]), "+f"(d[19]), "+f"(d[20]), "+f"(d[21]), "+f"(d[22]), "+f"(d[23]),
      "+f"(d[24]), "+f"(d[25]), "+f"(d[26]), "+f"(d[27]), "+f"(d[28]), "+f"(d[29]), "+f"(d[30]), "+f"(d[31]),
      "+f"(d[32]), "+f"(d[33]), "+f"(d[34]), "+f"(d[35]), "+f"(d[36]), "+f"(d[37]), "+f"(d[38]), "+f"(d[39])
    : "l"(da), "l"(db), "r"(scale_d));
}

__device__ __forceinline__ constexpr int QT(int t) { return t < 8 ? t : 16 + t; }
__device__ __forceinline__ constexpr int KT(int t) { return t < 8 ? 8 + t : 18 + t; }
__device__ __forceinline__ constexpr int VT(int t) { return t < 8 ? 16 + t : 20 + t; }

struct Maps { CUtensorMap x, w, wr, wo, wor, gate, up, down; };

__global__ void __cluster_dims__(2, 1, 1) __launch_bounds__(512, 1)
fused_kernel(const __nv_bfloat16* __restrict__ x, const __nv_bfloat16* __restrict__ wqkv,
             const __nv_bfloat16* __restrict__ wo, const __nv_bfloat16* __restrict__ w_r, const __nv_bfloat16* __restrict__ w_gate,
             const __nv_bfloat16* __restrict__ w_up, const __nv_bfloat16* __restrict__ w_down, __nv_bfloat16* __restrict__ out,
             Scratch* __restrict__ sc, const __grid_constant__ Maps tm) {
  extern __shared__ __align__(1024) uint8_t smem[];
  const int tid = threadIdx.x, bid = blockIdx.x;
  if ((unsigned)(tid - 128) < 16u) pf_l2((const char*)x + (bid * 16 + tid - 128) * 1280);
  if ((unsigned)(tid - 160) < 15u) pf_l2((const char*)wqkv + (bid * 15 + tid - 160) * 128);
  const int warp = __shfl_sync(0xffffffffu, tid >> 5, 0), lane = tid & 31;
  const uint32_t sb = (uint32_t)__cvta_generic_to_shared(smem);
  const uint32_t bar_full = sb + OFF_BAR, bar_empty = bar_full + 32, bar_aux = bar_full + 64, bar_ffn = bar_full + 72, bar_win = bar_full + 80, bar_rst = bar_full + 88,
                 bar_o = bar_full + 96, bar_oc = bar_o + 112, bar_st = bar_o + 224, bar_go = bar_o + 248, bar_kv = bar_o + 272, bar_tag = bar_o + 288;
  if (warp < 4 && elect()) {
    mbar_init(bar_full + 8 * (warp ^ 2), 1);
    mbar_init(bar_empty + 8 * warp, 24);
    mbar_init(bar_aux + 8 * warp, warp == 0 ? 64 : warp == 2 ? 32 : 1);
    asm volatile("fence.mbarrier_init.release.cluster;" ::: "memory");
  }
  if (warp == 6 && elect()) mbar_init(bar_tag, 2);
  asm volatile("barrier.cluster.arrive.relaxed.aligned;" ::: "memory");
  if (warp >= 8 && warp < 11 && elect()) asm volatile("prefetch.tensormap [%0];" :: "l"(&tm.x + (warp - 8)) : "memory");
  auto pf_slice = [&](int ks) {
    pf_l2(lane < 16 ? (const char*)x + ((bid * 16 + lane) * 1280 + ks * 128) : (const char*)wqkv + ((bid * 15 + min(lane, 30) - 16) * 128 + ks * 245760));
  };
  if (!EARLY && warp == 4) pf_slice(0);
  const int rank = bid & 1, cl = bid >> 1;
  const int q7 = ((cl - 36) * 37) >> 8;
  const int P = cl < 4 ? 0 : cl < 36 ? (cl - 4) & 7 : cl - 35 - 7 * q7;
  const int g = cl < 4 ? 4 + cl : cl < 36 ? (cl - 4) >> 3 : 4 + q7;
  const int mt = 2 * P + rank, cid = mt * 8 + g;
  const bool ffn1 = g >= 5;
  const int fj = ffn1 ? mt * 3 + g - 5 : (P * 5 + g) * 2 + rank;
  const int ord = ((g >> 2) ^ P) & 1;
  auto ks_of = [&](int it) { return !ORDX || ord == 0 || it == 0 ? it : it <= 5 ? it + 4 : it - 5; };
  auto load_w = [&](int it, uint32_t a, uint32_t full) {
    tma_3d_mc(a + 16384 + rank * 16384, &tm.w, full, g * 80, it * 64, rank * 2);
    tma_3d_mc(a + (rank ? 40960 : 24576), rank ? &tm.wr : &tm.w, full, g * 80 + rank * 64, it * 64, 1 - rank);
  };
  if (warp == 0 && elect()) {
    mbar_expect_tx(bar_full + 16, SLOT);
    tma_3d(sb + 2 * SLOT, &tm.x, bar_full + 16, 0, P * 128, rank);
  }
  asm volatile("barrier.cluster.wait.aligned;" ::: "memory");
  if (warp == 0) {
    if (elect()) load_w(0, sb + 2 * SLOT, bar_full + 16);
    asm volatile("bar.arrive 4, 64;" ::: "memory");
  }

  if (warp >= 8) {
    asm volatile("setmaxnreg.dec.sync.aligned.u32 %0;" :: "n"(REG_P));
#define TS_T 0
    if (warp == 8) {
      TS(8);
      bar_sync(4, 64);
      if (elect()) {
        TS(10);
        int fjn = 0;
#pragma unroll 1
        for (int it = 1; it < 17; it++) {
          const int s = (it + 2) & 3;
          const uint32_t full = bar_full + 8 * s, a = sb + s * SLOT;
          if (it >= 13) { mbar_wait(bar_oc + 8 * (it - 13), 0); mbar_wait(bar_oc + 56 + 8 * (it - 13), 0); }
          else if (it >= 4) mbar_wait(bar_empty + 8 * s, ((it >> 2) - 1) & 1);
          else if (it >= THR) mbar_wait(bar_full + 8 * ((it - THR + 2) & 3), 0);
          if (it < 10) {
            const int ks = ks_of(it);
            mbar_expect_tx(full, SLOT);
            tma_3d(a, &tm.x, full, ks * 64, P * 128, rank);
            load_w(ks, a, full);
            TS(12 + it);
            if ((unsigned)(it - RST_IT) < 2u) {
              mbar_wait(bar_rst, 0);
              asm volatile("cp.async.bulk.global.shared::cta.bulk_group [%0], [%1], %2;\ncp.async.bulk.commit_group;"
                           :: "l"(it == RST_IT ? (uint4*)(g_own + cid) : (uint4*)&g_x + cid * GLOB_PER_CTA), "r"(sb + OFF_CS),
                              "r"(it == RST_IT ? (int)sizeof(Own) : GLOB_PER_CTA * 16) : "memory");
            }
            if (it == RST_IT + 2) { asm volatile("cp.async.bulk.wait_group 0;" ::: "memory"); mbar_arrive(bar_tag); }
          } else if (it < 13) {
            const int g0 = 3 * (it - 10), g1 = min(g0 + 3, 8);
            mbar_expect_tx(full, (g1 - g0) * 12800);
#pragma unroll 1
            for (int gp = g0 + ((g0 ^ rank) & 1); gp < g1; gp += 2) {
              tma_3d_mc(sb + gp * 15360, &tm.wo, full, 0, gp * 80, g * 2);
              tma_3d_mc(sb + gp * 15360 + 10240, &tm.wor, full, 512 + g * 16, gp * 80, 0);
            }
          }
          if (it == 4) mbar_expect_tx(bar_ffn, NO_LATE == 2 ? 0 : NO_LATE ? (ffn1 ? 32768 : F_MAX * 2048) : ffn1 ? 81920 : 24576);
          if ((NO_LATE && it >= 13) || NO_LATE == 2) continue;
          const int j1 = ffn1 ? (it >= 13 ? min(2 * it - 21, 10) : min(max(it - F_IT + 1, 0), 4)) : (it >= 13 ? (it == 16 ? 12 : min(F_MAX + (it - 12) * F_LATE, 12)) : min(max((it - F_IT + 1) * F_PER, 0), F_MAX));
#pragma unroll 1
          for (; fjn < j1; fjn++) {
            const int j = fjn < 4 ? fjn + 6 : fjn - 4;
            if (ffn1) tma_3d(sb + (j < 6 ? 0 : OFF_W2 - 49152) + j * 8192, j < 5 ? &tm.gate : &tm.up, bar_ffn, fj * 32, (j < 5 ? j : j - 5) * 128, 0);
            else tma_3d(sb + OFF_W2 + fjn * 2048, &tm.down, bar_ffn, fj * 8, fjn * 128, 0);
          }
        }
        TS(11);
      }
#undef TS_T
#define TS_T 64
    } else if (warp >= 12) {
      const int l7 = lane & 7, j = warp - 12, ch = min((P >> 1) * 4 + rank * 2 + (j >> 1), 14);
      const uint32_t sxo = ((g & 3) * 32 + j * 8 + l7) * 128 + (((lane >> 3) ^ l7) * 16);
      const uint32_t swo = ch < 12 ? 16384 + (ch >> 2) * 8192 + lane * 128 + ((((ch & 3) * 2 + (j & 1)) ^ l7) * 16)
                                   : 40960 + (ch - 12) * 2048 + lane * 32 + (((j & 1) ^ (l7 >> 2)) * 16);
      float ps = 0.f, pq = 0.f, pq1 = 0.f, pc = 0.f;
      uint32_t tag = 0;
      char* const pp = hold((lane & 1) ? (char*)&g_own[cid].cs[j * 8 + (lane >> 2)] : (char*)&g_own[cid].st1[j * 8 + (lane >> 2)]);
#pragma unroll 1
      for (int it = ord; it < ord + 5; it++) {
        const int sl = (it + 2) & 3;
        if (it == ord + 4) { mbar_wait(bar_tag, 0); tag = __float_as_uint(lds32f(sb + OFF_WR + 324)); }
        mbar_wait(bar_full + 8 * sl, (it >> 2) & 1);
        TS(it);
        const uint32_t a = sb + sl * SLOT;
        const uint4 v0 = ldsm4(a + sxo), v1 = ldsm4((a + sxo) ^ 64), w0 = ldsm4t(a + swo), w1 = ldsm4t(a + swo + (ch < 12 ? 4096 : 1024));
        if (lane + (int)((v0.x & v1.x & w0.x & w1.x) == 0x7fc17fc1u && (v0.x | v1.x) == 0u) < 2) mbar_arrive_cta(bar_empty + 8 * sl, lane);
        const uint32_t vv[8] = {v0.x, v0.y, v0.z, v0.w, v1.x, v1.y, v1.z, v1.w}, ww[8] = {w0.x, w0.y, w0.z, w0.w, w1.x, w1.y, w1.z, w1.w};
#pragma unroll
        for (int i = 0; i < 8; i++) {
          const float d = bf_lo(vv[i]), e = bf_hi(vv[i]);
          ps += d + e; pq = fmaf(d, d, pq); pq1 = fmaf(e, e, pq1); pc += bf_lo(ww[i]) + bf_hi(ww[i]);
        }
      }
      pq += pq1;
      ps += shx(ps, 1); pq += shx(pq, 1); pc += shx(pc, 1);
      ps += shx(ps, 2); pq += shx(pq, 2); pc += shx(pc, 2);
      if ((lane & 3) == 0) stg_pkt(pp, __float_as_uint(ps), __float_as_uint(pq), tag, 0u);
      if ((lane & 3) == 1) stg_rlx64(pp, __float_as_uint(pc), tag);
      asm volatile("bar.arrive 2, 192;" ::: "memory");
      if (warp == 12) {
        const uint4* const hp = hold(&g_own[max(cid - 16, 0)].halo[0][lane]);
        mbar_wait(bar_aux, 0);
        mbar_wait(bar_go, 0);
        uint4 v[5] = {};
        int guard = SPIN_MAX;
        if (P > 0) {
          do {
#pragma unroll
            for (int i = 0; i < 5; i++) v[i] = ldg_pkt(hp + 32 * i);
          } while (anyw(v[0].x == SENT || v[1].x == SENT || v[2].x == SENT || v[3].x == SENT || v[4].x == SENT) && --guard > 0);
        }
#pragma unroll
        for (int i = 0; i < 5; i++) *(uint4*)(smem + OFF_O + 10240 + i * 512 + lane * 16) = v[i];
        mbar_arrive(bar_kv);
      }
#undef TS_T
#define TS_T 32
    } else if (warp < 11) {
      const int l7 = lane & 7, hk = lane >> 4;
      if (warp == 10 && elect()) {
#pragma unroll 1
        for (int i = 0; i < 36; i++) mbar_init(bar_o + 8 * i, i < 14 || i == 30 ? 1 : i < 34 ? 4 : 128);
      }
      {
        const int t0 = clk();
#pragma unroll 1
        for (int i = PF_FIRST; i < 6; i++) {
          while (clk() - t0 < PF_T0 + (i - PF_FIRST) * PF_CLK) __nanosleep(20);
          pf_slice(warp == 9 ? min(i, 4) : i + 4);
        }
      }
      mbar_wait(bar_tag, 0);
      const uint32_t tag = __float_as_uint(lds32f(sb + OFF_WR + 324));
      bar_sync(2, 192);
      TS(0);
      int guard = SPIN_MAX;
      if (warp == 9) {
        const uint4* sp = &g_own[mt * 8].st1[lane];
        const uint4* hp = &g_own[max(mt - 2, 0) * 8 + 3].st1[24 + l7];
        uint4 a[5], b[5];
        bool bad;
        do {
          __nanosleep(AUX_NS);
          bad = false;
#pragma unroll
          for (int i = 0; i < 5; i++) {
            const uint4* q = i < 4 ? sp + i * (sizeof(Own) / 16) : hp;
            a[i] = ldg_pkt(q); b[i] = ldg_pkt(q + 4 * sizeof(Own) / 16);
          }
#pragma unroll
          for (int i = 0; i < 5; i++) bad |= a[i].z != tag || b[i].z != tag;
        } while (anyw(bad) && --guard);
        TS(1);
#pragma unroll
        for (int i = 0; i < 5; i++) {
          const float m = (__uint_as_float(a[i].x) + __uint_as_float(b[i].x)) * (1.f / 640.f);
          const float rs = rsq(fmaxf(fmaf(-m, m, (__uint_as_float(a[i].y) + __uint_as_float(b[i].y)) * (1.f / 640.f)), 0.f) + 1e-5f);
          ((float*)(smem + OFF_RS))[i < 4 ? 8 + lane + 32 * i : l7] = rs;
          const uint32_t mh = pack_bf16(-m, -m);
          const float ml = -m - bf_lo(mh);
          if (i < 4) ((uint2*)(smem + OFF_MN))[lane + 32 * i] = make_uint2(mh, pack_bf16(ml, ml));
        }
      } else {
        const uint4* cp = (const uint4*)g_own[hk * 8 + g].cs + (lane & 15);
        uint4 a[4], b[4];
        bool bad;
        do {
          __nanosleep(AUX_NS);
          bad = false;
#pragma unroll
          for (int i = 0; i < 4; i++) { a[i] = ldg_pkt(cp + i * 32 * sizeof(Own) / 16); b[i] = ldg_pkt(cp + (i * 32 + 16) * sizeof(Own) / 16); }
#pragma unroll
          for (int i = 0; i < 4; i++) bad |= a[i].y != tag || a[i].w != tag || b[i].y != tag || b[i].w != tag;
        } while (anyw(bad) && --guard);
#pragma unroll
        for (int i = 0; i < 4; i++)
          if (i < 3 || lane < 24) {
            const float c0 = __uint_as_float(a[i].x) + __uint_as_float(b[i].x), c1 = __uint_as_float(a[i].z) + __uint_as_float(b[i].z);
            const uint32_t hi = pack_bf16(c0, c1), w0 = pack_bf16(c0, c0 - bf_lo(hi)), w1 = pack_bf16(c1, c1 - bf_hi(hi));
            uint4* const d = (uint4*)(smem + OFF_CS) + 2 * (lane + 32 * i);
            d[0] = make_uint4(w0, w0, 0, 0); d[1] = make_uint4(w1, w1, 0, 0);
          }
        asm volatile("fence.proxy.async.shared::cta;" ::: "memory");
      }
      mbar_arrive(bar_aux);
      TS(2);
      const int fo = warp - 9, wq = fo ? 1 - LEAD : LEAD;
      const uint4* const fp = hold(g_own[mt * 8 + wq * 4].cnt);
      const char* src = hold((const char*)g_o[mt * 2 + wq]);
      if (elect()) {
        const uint32_t bo = bar_o + fo * 56;
#pragma unroll
        for (int i = 0; i < 7; i++) mbar_expect_tx(bo + 8 * i, 10240);
        mbar_wait(bar_st + 8 * fo, 0);
        if (ONE_RED == 1) {
          asm volatile("red.relaxed.gpu.global.add.u32 [%0], 4;" :: "l"(fp) : "memory");
          if (CNT_NS) __nanosleep(CNT_NS);
        }
        uint32_t cv = 0;
        if (ONE_RED == 2) { asm volatile("atom.relaxed.gpu.global.add.u32 %0, [%1], 4;" : "=r"(cv) : "l"(fp) : "memory"); cv += 4; }
        while (cv != 32u && --guard > 0) cv = ldg_rlx32(fp);
        asm volatile("fence.proxy.async.global;" ::: "memory");
        TS(6);
#pragma unroll
        for (int i = 0; i < 7; i++) {
          if (fo || i == 6) mbar_wait(bo + 64 + 8 * i, 0);
          else if (i == FW) mbar_arrive(bar_go - 8);
          if (!fo && i == 4) mbar_wait(bar_st + 8, 0);
          if (i == g) src += 10240;
          asm volatile("cp.async.bulk.shared::cluster.global.mbarrier::complete_tx::bytes [%0], [%1], 10240, [%2];"
                       :: "r"(sb + OFF_O + ((i + 2) % 6) * 10240 + fo * (i == 3 ? -51200 : 10240)), "l"(src + i * 10240), "r"(bo + 8 * i) : "memory");
        }
      }
#undef TS_T
#define TS_T 96
    } else {
      if ((sb & 0x3FFFF) != D0 * 16) __trap();
#pragma unroll 1
      for (int i = lane; i < 232; i += 32) { const uint32_t f = i < 208 ? SENT : 0u; ((uint4*)(smem + OFF_CS))[i] = make_uint4(f, f, f, f); }
      asm volatile("fence.proxy.async.shared::cta;" ::: "memory");
      if (elect()) mbar_arrive(bar_rst);
      mbar_wait(bar_full + 8 * ((HK_IT + 2) & 3), 0);
      TS(4);
      const uint32_t epoch = ldg_rlx32(g_epoch + cid) + 1;
      uint32_t wv[10];
#pragma unroll
      for (int i = 0; i < 10; i++) wv[i] = __ldg((const uint32_t*)w_r + lane + 32 * i);
      float s = 0.f;
#pragma unroll
      for (int i = 0; i < 10; i++) {
        s += bf_lo(wv[i]) + bf_hi(wv[i]);
        const unsigned u = i < 8 ? lane + 32 * (i - g) : lane + 32 * (i - 7) - g * 8;
        if (i < 8 ? u < 32u : u - 32u < 8u) *(float2*)(smem + OFF_WR + ((u & 3) * 10 + (u >> 2)) * 8) = make_float2(bf_lo(wv[i]), bf_hi(wv[i]));
      }
#pragma unroll
      for (int m = 1; m < 32; m <<= 1) s += shx(s, m);
      *(float2*)(smem + OFF_WR + 320) = make_float2(s, __uint_as_float(epoch * 0x9E3779B8u));
      g_epoch[cid] = epoch;
      TS(3);
      TS(5);
      if (elect()) mbar_arrive(bar_tag);
#pragma unroll 1
      for (int i = 0; i < 14; i++) {
        const int m = (i + 2) >> 2, n = m == 0 ? 50 : 120, t = (m == 0 ? i : (i + 2) & 3) * 32 + lane;
        const char* b = (const char*)(m == 0 ? wo : m == 1 ? w_up : m == 2 ? w_down : w_gate);
        if (t < n) pf_l2(b + (bid * n + t) * 128);
        __nanosleep(PFW_NS);
      }
      const uint4* const kp = hold(g_own[1].cnt);
      const uint4* const cb = hold(&g_x.cand[0][lane >> 2][lane & 3]);
      bar_sync(3, 64);
      uint4 k;
      uint32_t have = SENT;
      int guard = SPIN_MAX;
      while (true) {
        k = ldg_pkt(kp);
        if (ffn1) {
          while (k.x != have && --guard > 0) {
            const uint32_t tk = 2047u - (k.x & 2047u), want = k.x;
            const uint4* q = cb + ((tk >> 8) * 16 + (tk & 1) * 8 + ((tk >> 5) & 7)) * 192;
            const uint4 c0 = ldg_pkt(q), c1 = ldg_pkt(q + 4); const uint2 c2 = ldg_rlx64(q + 8);
            k = ldg_pkt(kp);
            *(uint4*)(smem + OFF_HN + lane * 16) = c0; *(uint4*)(smem + OFF_HN + 512 + lane * 16) = c1; *(uint2*)(smem + OFF_HN + 1024 + lane * 16) = c2;
            have = anyw(c0.x == SENT || c1.x == SENT || c2.x == SENT) ? SENT : want;
          }
        } else if (KEY_NS && k.z != 128u) __nanosleep(KEY_NS);
        if (k.z == 128u || --guard <= 0) break;
      }
      *(uint2*)(smem + OFF_WR + 336) = make_uint2(k.x, k.y);
      mbar_arrive(bar_win);
      TS(7);
    }
#undef TS_T
  } else {
#define TS_T 0
    asm volatile("setmaxnreg.inc.sync.aligned.u32 %0;" :: "n"(REG_C));
    const int wg = warp >> 2, w4 = warp & 3, r = lane >> 2, c = lane & 3;
    float acc[120];
    uint4 xr[5] = {};
    const uint32_t xa = pin(sb + (warp * 16 + (lane & 15)) * 128 + ((lane >> 4) ^ (lane & 7)) * 16);
    const int fol = wg != LEAD;
    const bool first = (P == 0) && (warp == 0);
    const uint32_t kvs = sb + OFF_O + fol * 10240 + w4 * 2560 + lane * 16;
    uint4* const kvd = hold(warp == 7 ? &g_own[cid].halo[0][lane] : (uint4*)(smem + (warp == 3 ? OFF_O + lane * 16 : kvs - sb + 2560)));
    uint4* const odst = hold(&g_o[mt * 2 + wg][g][w4 * 160]);
    uint4* const ocnt = hold(g_own[mt * 8 + wg * 4].cnt);
    uint32_t m0 = 0, m1 = 0;
    const uint32_t mna = pin(sb + OFF_MN + (warp * 16 + r) * 8 + c * 4);
    const int itx = ord == 0 || g == 0 ? g : g < 5 ? g + 5 : g - 4, ity = (ord ? 4 : 8) + (g >> 2);
    uint32_t rel;
    asm volatile("mapa.shared::cluster.u32 %0, %1, %2;" : "=r"(rel) : "r"(bar_empty), "r"(tid & 1));
    const uint32_t xa1 = pin(xa ^ 32), xa2 = pin(xa ^ 64), xa3 = pin(xa ^ 96), xb = pin(xa ^ ((g & 3) * 32));
    const uint32_t da0 = wg * 512;
    const bool rel2 = lane < 2, rel6 = lane < 2 + 2 * (warp & 1);
    const uint32_t zero = (uint32_t)(uintptr_t)x & 8u;
    mbar_wait(bar_full + 16, 0);
    TS(13);
    wgmma_fence();
#pragma unroll
    for (int it = 0; it < 10; it++) {
      const int s = (it + 2) & 3;
      if (it == 9 && fol) bar_sync(10, 256);
#pragma unroll
      for (int kk = 0; kk < 4; kk++) {
        if (kk == 2 && it > 0) {
          wgmma_commit();
          wgmma_wait<1>();
          const uint32_t ra = ((xr[0].x ^ xr[1].x ^ xr[2].x ^ xr[3].x ^ xr[4].x) & zero) | rel;
          if (it == 1 ? (ord ? rel6 : rel2) : it == 6 ? (ord ? rel2 : rel6) : it < 6 ? rel2 : rel6)
            asm volatile("mbarrier.arrive.shared::cluster.b64 _, [%0];" :: "r"(ra + 8 * ((it + 1) & 3)) : "memory");
        }
        if (kk == 2) {
          ldsm4_if(xr[0], xa, s * SLOT, it == itx); ldsm4_if(xr[1], xa1, s * SLOT, it == itx);
          ldsm4_if(xr[2], xa2, s * SLOT, it == itx); ldsm4_if(xr[3], xa3, s * SLOT, it == itx);
          if ((it & 6) == 4 || it >= 8) ldsm4_if(xr[4], xb, s * SLOT, it == ity);
        }
        if (kk == AK && it == 9) {
          mbar_wait(bar_aux, 0);
          TS(3);
          if (c < 2) { m0 = __float_as_uint(lds32f(mna)); m1 = __float_as_uint(lds32f(mna + 64)); }
          if (!fol) bar_sync(11, 256);
        }
        if (kk == 3 && it < 9 && it >= PREW) {
          mbar_wait(bar_full + 8 * ((it + 3) & 3), ((it + 1) >> 2) & 1);
          if (it < 8) TS(14 + it);
        }
        const uint64_t da = mk64(da0 + (D0 + s * (SLOT >> 4) + kk * 2 + (1 << 16)), 0x40000040u);
        wgmma_n48hi_ss(acc, da, mk64(D0 + s * (SLOT >> 4) + 2560 + kk * 32 + (128 << 16), 0xC0000010u), (it | kk) != 0);
        wgmma_n192lo_ss(acc, da, mk64(D0 + s * (SLOT >> 4) + 1024 + kk * 128 + (512 << 16), 0x40000040u), (it | kk) != 0);
      }
      wgmma_commit();
      if (it == 8 && fol) asm volatile("bar.arrive 11, 256;" ::: "memory");
      if (it < 9 && it < PREW) {
        mbar_wait(bar_full + 8 * ((it + 3) & 3), ((it + 1) >> 2) & 1);
        if (it < 8) TS(14 + it);
      }
    }
    {
      const uint64_t dc = make_desc(D0 * 16 + OFF_CS, 0, 128, 0);
      wgmma_fence();
      wgmma_n48hi_rk(acc, m0, m1, 0u, 0u, dc + 192, 1);
      wgmma_n192lo_rk(acc, m0, m1, 0u, 0u, dc, 1);
      wgmma_commit();
      if (!fol) asm volatile("bar.arrive 10, 256;" ::: "memory");
    }
    const uint32_t stb = sb + OFF_RS + warp * 64;
    const float rlo = lds32f(stb + (8 + r) * 4), rhi = lds32f(stb + (16 + r) * 4);
    wgmma_wait<0>();
#pragma unroll
    for (int i = 0; i < 120; i++) asm volatile("" : "+f"(acc[i]) :: "memory");
    if (fol && lane == 0) mbar_arrive(bar_go);
    TS(2);
    uint32_t Qlo[10], Qhi[10], Klo[10], Khi[10], Vlo[10], Vhi[10];
#pragma unroll
    for (int t = 0; t < 10; t++) {
      const int k = KT(t), v = VT(t);
      Khi[t] = pack_bf16(acc[4 * k + 2], acc[4 * k + 3]);
      Vhi[t] = pack_bf16(acc[4 * v + 2] * rhi, acc[4 * v + 3] * rhi);
    }
    st_pkt(kvd, Khi[0], Khi[1], Khi[3], Khi[4]);
    st_pkt(kvd + 32, Khi[5], Khi[6], Khi[8], Khi[9]);
    st_pkt(kvd + 64, Khi[2], Khi[7], Vhi[0], Vhi[1]);
    st_pkt(kvd + 96, Vhi[2], Vhi[3], Vhi[4], Vhi[5]);
    st_pkt(kvd + 128, Vhi[6], Vhi[7], Vhi[8], Vhi[9]);
    if (warp < 7) mbar_arrive(bar_kv + ((warp + 1) >> 2) * 8);
    mbar_wait(bar_aux, 0);
#pragma unroll
    for (int t = 0; t < 10; t++) {
      const int q = QT(t), k = KT(t), v = VT(t);
      Vhi[t] = movm(Vhi[t]);
      Klo[t] = pack_bf16(acc[4 * k], acc[4 * k + 1]);
      Vlo[t] = movm(pack_bf16(acc[4 * v] * rlo, acc[4 * v + 1] * rlo));
      Qlo[t] = pack_bf16(acc[4 * q], acc[4 * q + 1]);
      Qhi[t] = pack_bf16(acc[4 * q + 2], acc[4 * q + 3]);
    }
    const bool in0 = 2 * c <= r, in1 = 2 * c + 1 <= r;
    const uint32_t mL = (in0 ? 0xffffu : 0u) | (in1 ? 0xffff0000u : 0u);
    const float qs = 0.22360679774997896f * 1.4426950408889634f;
    const uint32_t kb0 = stb + (2 * c + (in0 ? 8 : 0)) * 4, kb1 = stb + (2 * c + 1 + (in1 ? 8 : 0)) * 4;
    const float scl0 = lds32f(kb0) * rlo * qs, scl1 = lds32f(kb1) * rlo * qs;
    const float sch0 = lds32f(kb0 + 32) * rhi * qs, sch1 = lds32f(kb1 + 32) * rhi * qs;
    const float bias0 = (first && !in0) ? -INFINITY : 0.f, bias1 = (first && !in1) ? -INFINITY : 0.f;
    const int slot = mt * 8 + warp;
    int guard = SPIN_MAX;
    uint4 pv[5];
    const bool cA = c < 2, nA = r < 4;
    TS(0);
    mbar_wait(bar_go + fol * 8, 0);
    TS(23);
    uint32_t qe[4][2];
    float sl0[4], sl1[4], th0[4], th1[4];
#pragma unroll
    for (int hd = 0; hd < 4; hd++) {
      const int ta = 5 * (hd >> 1) + 3 * (hd & 1), ts = 5 * (hd >> 1) + 2;
      const bool mine = (hd & 1) ? !cA : cA;
      qe[hd][0] = mine ? Qlo[ts] : 0u; qe[hd][1] = mine ? Qhi[ts] : 0u;
      float sl[4], sh[4];
      mma_k24(sl, Qlo[ta], Qhi[ta], Qlo[ta + 1], Qhi[ta + 1], Klo[ta], Klo[ta + 1], qe[hd][0], qe[hd][1], Klo[ts]);
      mma_k24(sh, Qlo[ta], Qhi[ta], Qlo[ta + 1], Qhi[ta + 1], Khi[ta], Khi[ta + 1], qe[hd][0], qe[hd][1], Khi[ts]);
      th0[hd] = (in0 ? sh[2] : sl[2]) * sch0; th1[hd] = (in1 ? sh[3] : sl[3]) * sch1;
      float mh = fmaxf(th0[hd], th1[hd]);
      mh = fmaxf(mh, shx(mh, 1)); mh = fmaxf(mh, shx(mh, 2));
      th0[hd] -= mh; th1[hd] -= mh;
      sl0[hd] = sl[0]; sl1[hd] = sl[1];
    }
    mbar_wait(bar_kv + wg * 8, 0);
    TS(4);
#pragma unroll
    for (int j = 0; j < 5; j++) pv[j] = lds128(kvs + 512 * j);
    const uint32_t Kp[10] = {pv[0].x, pv[0].y, pv[2].x, pv[0].z, pv[0].w, pv[1].x, pv[1].y, pv[2].y, pv[1].z, pv[1].w};
    const uint32_t Vp[10] = {movm(pv[2].z), movm(pv[2].w), movm(pv[3].x), movm(pv[3].y), movm(pv[3].z), movm(pv[3].w), movm(pv[4].x), movm(pv[4].y), movm(pv[4].z), movm(pv[4].w)};
    const uint32_t ONES = 0x3f803f80u;
    uint32_t of[20];
#pragma unroll
    for (int hp = 0; hp < 2; hp++) {
      float o[6][4];
#pragma unroll
      for (int hh = 0; hh < 2; hh++) {
        const int hd = 2 * hp + hh, ta = 5 * hp + 3 * hh, ts = 5 * hp + 2;
        float sp[4];
        mma_k24(sp, Qlo[ta], Qhi[ta], Qlo[ta + 1], Qhi[ta + 1], Kp[ta], Kp[ta + 1], qe[hd][0], qe[hd][1], Kp[ts]);
        const float tl0 = fmaf(in0 ? sl0[hd] : sp[0], scl0, bias0), tl1 = fmaf(in1 ? sl1[hd] : sp[1], scl1, bias1);
        float ml = fmaxf(tl0, tl1);
        ml = fmaxf(ml, shx(ml, 1)); ml = fmaxf(ml, shx(ml, 2));
        if (HOLD == 1 && hd == 3 && !fol && lane == 0) mbar_arrive(bar_go + 8);
        const uint32_t Pl = pack_bf16(ex2(tl0 - ml), ex2(tl1 - ml)), Ph = pack_bf16(ex2(th0[hd]), ex2(th1[hd]));
        const uint32_t a0 = Pl & mL, a1 = Ph & ~mL, a3 = Ph & mL, ap = Pl & ~mL;
        const bool vm = hh == 0 ? nA : !nA;
        mma_k24(o[3 * hh], a0, a1, 0u, a3, Vlo[ta], Vhi[ta], ap, 0u, Vp[ta]);
        mma_k24(o[3 * hh + 1], a0, a1, 0u, a3, Vlo[ta + 1], Vhi[ta + 1], ap, 0u, Vp[ta + 1]);
        mma_k24(o[3 * hh + 2], a0, a1, 0u, a3, vm ? Vlo[ts] : ONES, vm ? Vhi[ts] : ONES, ap, 0u, vm ? Vp[ts] : ONES);
      }
      const float il = rcp(cA ? o[5][0] : o[2][0]), ih = rcp(cA ? o[5][2] : o[2][2]);
      const float jl = shx(il, 2), jh = shx(ih, 2);
      const float al = cA ? jl : il, ah = cA ? jh : ih, bl = cA ? il : jl, bh = cA ? ih : jh;
      const int t0 = 5 * hp;
      of[2 * t0]     = pack_bf16(o[0][0] * al, o[0][1] * al); of[2 * t0 + 1] = pack_bf16(o[0][2] * ah, o[0][3] * ah);
      of[2 * t0 + 2] = pack_bf16(o[1][0] * al, o[1][1] * al); of[2 * t0 + 3] = pack_bf16(o[1][2] * ah, o[1][3] * ah);
      of[2 * t0 + 4] = pack_bf16((cA ? o[2][0] : o[5][0]) * jl, (cA ? o[2][1] : o[5][1]) * jl);
      of[2 * t0 + 5] = pack_bf16((cA ? o[2][2] : o[5][2]) * jh, (cA ? o[2][3] : o[5][3]) * jh);
      of[2 * t0 + 6] = pack_bf16(o[3][0] * bl, o[3][1] * bl); of[2 * t0 + 7] = pack_bf16(o[3][2] * bh, o[3][3] * bh);
      of[2 * t0 + 8] = pack_bf16(o[4][0] * bl, o[4][1] * bl); of[2 * t0 + 9] = pack_bf16(o[4][2] * bh, o[4][3] * bh);
    }
    {
      const uint32_t os = sb + OFF_O + (fol ? 0 : 20480) + w4 * 2560, oa = os + ((lane >> 3) & 1) * 1280 + (lane >> 4) * 128 + (lane & 7) * 16;
#pragma unroll
      for (int s = 0; s < 5; s++) {
        stsm4(oa + s * 256, of[4 * s], of[4 * s + 1], of[4 * s + 2], of[4 * s + 3]);
        if (s == 0 && (fol || HOLD == 2) && lane == 0) mbar_arrive(bar_go + 8 + 8 * fol);
      }
      asm volatile("fence.proxy.async.shared::cta;" ::: "memory");
      __syncwarp();
      if (FW < 5 && fol) mbar_wait(bar_go - 8, 0);
      if (elect()) {
        asm volatile("cp.async.bulk.global.shared::cta.bulk_group [%0], [%1], 2560;\ncp.async.bulk.commit_group;" :: "l"(odst), "r"(os) : "memory");
      }
    }
    TS(5);
    float h[40];
#pragma unroll
    for (int s = 0; s < 5; s++) {
      const uint4 v = xr[s];
      h[8 * s] = bf_lo(v.x); h[8 * s + 1] = bf_hi(v.x); h[8 * s + 2] = bf_lo(v.y); h[8 * s + 3] = bf_hi(v.y);
      h[8 * s + 4] = bf_lo(v.z); h[8 * s + 5] = bf_hi(v.z); h[8 * s + 6] = bf_lo(v.w); h[8 * s + 7] = bf_hi(v.w);
    }
    if (elect()) {
      asm volatile("cp.async.bulk.wait_group 0;" ::: "memory");
      if (!ONE_RED) asm volatile("red.relaxed.gpu.global.add.u32 [%0], 1;" :: "l"(ocnt) : "memory");
      mbar_arrive(bar_st + 8 * fol);
    }
    __syncwarp();
    TS(22);
    mbar_wait(bar_full, 0); mbar_wait(bar_full + 8, 0); mbar_wait(bar_full + 16, 1);
    mbar_wait(bar_go + 16, 0);
    const uint64_t dwo = make_desc(D0 * 16, 5120, 512, 2);
    wgmma_fence();
#pragma unroll
    for (int s = 0; s < 5; s++) wgmma_n80_rs(h, of[4 * s], of[4 * s + 1], of[4 * s + 2], of[4 * s + 3], dwo + g * 960 + s * 64, 1);
    wgmma_commit();
    TS(6);
    const uint32_t bo = bar_o + fol * 56;
#pragma unroll
    for (int i = 0; i < 7; i++) {
      mbar_wait(bo + 8 * i, 0);
      if (i == 0) TS(1);
      const uint32_t da = D0 + OFF_O / 16 + (8 << 16) + ((i + 2) % 6) * 640 + fol * (i == 3 ? -3200 : 640), db = D0 + (320 << 16) + (i >= g ? i + 1 : i) * 960;
      wgmma_fence();
#pragma unroll
      for (int s = 0; s < 5; s++) wgmma_n80_ss(h, mk64(da + s * 16, 80u), mk64(db + s * 64, 0x80000020u), 1);
      wgmma_commit();
      wgmma_wait<1>();
      if (lane == 0 && i > 0) mbar_arrive(bo + 104 + 8 * i);
    }
    const bool odd = c & 1;
    float wr[20];
#pragma unroll
    for (int j = 0; j < 5; j++) {
      const uint4 v = lds128(sb + OFF_WR + c * 80 + j * 16);
      wr[4 * j] = __uint_as_float(v.x); wr[4 * j + 1] = __uint_as_float(v.y); wr[4 * j + 2] = __uint_as_float(v.z); wr[4 * j + 3] = __uint_as_float(v.w);
    }
    const float wsum = lds32f(sb + OFF_WR + 320);
    uint4* const sp = hold(&g_own[slot].st2[r + (odd ? 8 : 0)]);
    uint4* const cdp = hold(&g_x.cand[slot][g][0]);
    const int tok0 = P * 256 + 32 * warp + rank;
    wgmma_wait<0>();
#pragma unroll
    for (int i = 0; i < 40; i++) asm volatile("" : "+f"(h[i]) :: "memory");
    if (lane == 0) mbar_arrive(bo + 160);
    TS(7);
    float mean, rstd, rr;
    {
      float l1 = 0.f, l2 = 0.f, l3 = 0.f, h1 = 0.f, h2 = 0.f, h3 = 0.f;
#pragma unroll
      for (int j = 0; j < 10; j++) {
        l1 += h[4 * j] + h[4 * j + 1]; h1 += h[4 * j + 2] + h[4 * j + 3];
        l2 = fmaf(h[4 * j], h[4 * j], l2); l2 = fmaf(h[4 * j + 1], h[4 * j + 1], l2);
        h2 = fmaf(h[4 * j + 2], h[4 * j + 2], h2); h2 = fmaf(h[4 * j + 3], h[4 * j + 3], h2);
        l3 = fmaf(h[4 * j], wr[2 * j], l3); l3 = fmaf(h[4 * j + 1], wr[2 * j + 1], l3);
        h3 = fmaf(h[4 * j + 2], wr[2 * j], h3); h3 = fmaf(h[4 * j + 3], wr[2 * j + 1], h3);
      }
      float s1 = (odd ? h1 : l1) + shx(odd ? l1 : h1, 1), s2 = (odd ? h2 : l2) + shx(odd ? l2 : h2, 1), s3 = (odd ? h3 : l3) + shx(odd ? l3 : h3, 1);
      s1 += shx(s1, 2); s2 += shx(s2, 2); s3 += shx(s3, 2);
      if (cA) asm volatile("red.relaxed.gpu.global.add.v4.f32 [%0], {%1, %2, %3, %4};" :: "l"(sp), "f"(s1), "f"(s2), "f"(s3), "f"(1.f) : "memory");
      uint4 p0;
      do { p0 = ldg_pkt(sp); } while (anyw(p0.w != 0x41000000u) && --guard > 0);
      mean = __uint_as_float(p0.x) * (1.f / 640.f);
      rstd = rsq(fmaxf(fmaf(-mean, mean, __uint_as_float(p0.y) * (1.f / 640.f)), 0.f) + 1e-5f);
      rr = fmaf(-mean, wsum, __uint_as_float(p0.z)) * rstd;
    }
    TS(8);
    const uint32_t kk = ord_key(rr), kmax = __reduce_max_sync(0xffffffffu, kk);
    const int L = __ffs(__ballot_sync(0xffffffffu, kk == kmax)) - 1;
    const int crow = (L >> 2) + 8 * (L & 1);
    if (warp == g) {
      if (elect()) {
        asm volatile("red.relaxed.gpu.global.max.u64 [%0], %1;" :: "l"(g_own[1].cnt), "l"(((uint64_t)kmax << 32) | (uint32_t)(2047 - tok0 - 2 * crow)) : "memory");
        asm volatile("red.relaxed.gpu.global.add.u32 [%0], 1;" :: "l"(&g_own[1].cnt[0].z) : "memory");
      }
      asm volatile("bar.arrive 3, 64;" ::: "memory");
    }
    const uint32_t stg = sb + (fol ? OFF_O : g * 15360) + w4 * 2560;
    uint4 held;
    {
      const float om = shx(mean, 1), os = shx(rstd, 1);
      const float rl = odd ? os : rstd, rh = odd ? rstd : os;
      const float bl = -(odd ? om : mean) * rl, bh = -(odd ? mean : om) * rh, al = 1.f + rl, ah = 1.f + rh;
      if ((L >> 2) == r) {
        const bool chi = L & 1;
        const float rc = chi ? rh : rl, bc = chi ? bh : bl;
        uint32_t n[10];
#pragma unroll
        for (int j = 0; j < 10; j++) n[j] = pack_bf16(fmaf(chi ? h[4 * j + 2] : h[4 * j], rc, bc), fmaf(chi ? h[4 * j + 3] : h[4 * j + 1], rc, bc));
        uint4* d = cdp + c;
        stg_pkt(d, n[0], n[1], n[2], n[3]); stg_pkt(d + 4, n[4], n[5], n[6], n[7]); stg_rlx64(d + 8, n[8], n[9]);
      }
      mbar_wait(bar_oc + 56, 0);
      const uint32_t fa = stg + (lane & 15) * 160 + (lane >> 4) * 16;
#pragma unroll
      for (int s = 0; s < 5; s++)
        stsm4(fa + s * 32, pack_bf16(fmaf(h[8 * s], al, bl), fmaf(h[8 * s + 1], al, bl)), pack_bf16(fmaf(h[8 * s + 2], ah, bh), fmaf(h[8 * s + 3], ah, bh)),
              pack_bf16(fmaf(h[8 * s + 4], al, bl), fmaf(h[8 * s + 5], al, bl)), pack_bf16(fmaf(h[8 * s + 6], ah, bh), fmaf(h[8 * s + 7], ah, bh)));
      __syncwarp();
      held = lds128(stg + crow * 160 + min(lane, 9) * 16);
      if (lane < 10) stg_pkt(cdp + 12 + lane, held.x, held.y, held.z, held.w);
    }
    TS(9);
    mbar_wait(bar_ffn, 0);
    const uint32_t red = sb + OFF_RED;
    if (ffn1) {
      uint4 w1[4][5];
      {
        const int k = (lane & 7) + (lane >> 4) * 8;
        const uint32_t a1 = sb + k * 64, sw = ((lane >> 3) & 1) ^ ((lane >> 1) & 3);
#pragma unroll
        for (int s = 0; s < 5; s++)
#pragma unroll
          for (int u = 0; u < 4; u++)
            w1[u][s] = ldsm4t(a1 + (s < 4 ? warp * 4096 + s * 1024 : 32768 + warp * 1024) + (u >> 1) * (40960 + (s == 4 || warp >= 2 ? OFF_W2 - 49152 : 0)) + ((sw ^ (2 * (u & 1))) * 16));
      }
      uint32_t* const ap = hold(g_x.act + fj * 16 + (lane >> 1));
      mbar_wait(bar_win, 0);
      const uint32_t hp = sb + OFF_HN + (warp * 4 + c) * 16;
      const uint4 c0 = lds128(hp), c1 = lds128(hp + 512), c2 = lds128(hp + 1024);
      TS(10);
      float a[4][4];
#pragma unroll
      for (int u = 0; u < 4; u++) {
        a[u][0] = a[u][1] = a[u][2] = a[u][3] = 0.f;
        mma_acc(a[u], w1[u][0], c0.x, c0.y); mma_acc(a[u], w1[u][1], c0.z, c0.w); mma_acc(a[u], w1[u][2], c1.x, c1.y);
        mma_acc(a[u], w1[u][3], c1.z, c1.w); mma_acc(a[u], w1[u][4], c2.x, c2.y);
      }
      asm volatile("st.shared.v2.f32 [%0], {%1, %2};" :: "r"(red + (warp * 32 + c * 8 + r) * 8),
                   "f"(cA ? (odd ? a[0][2] : a[0][0]) : (odd ? a[1][2] : a[1][0])), "f"(cA ? (odd ? a[2][2] : a[2][0]) : (odd ? a[3][2] : a[3][0])) : "memory");
      bar_sync(1, 256);
      if (warp == 0) {
        float2 t[8];
#pragma unroll
        for (int i = 0; i < 8; i++) t[i] = lds64f(red + (i * 32 + lane) * 8);
        const float s = ((t[0].x + t[1].x) + (t[2].x + t[3].x)) + ((t[4].x + t[5].x) + (t[6].x + t[7].x));
        const float u = ((t[0].y + t[1].y) + (t[2].y + t[3].y)) + ((t[4].y + t[5].y) + (t[6].y + t[7].y));
        const float av = s * u * rcp(1.f + ex2(-1.4426950408889634f * s));
        const float an = shx(av, 1);
        if (!odd) stg_rlx32(ap, pack_bf16(av, an));
      }
      bar_sync(1, 256);
      TS(11);
    }
    if (OUT_LATE) mbar_wait(bar_win, 0);
    char* const ob2 = (char*)(out + tok0 * 640 + g * 64);
    const int remo = 896 - 96 * g;
#pragma unroll
    for (int s = 0; s < 5; s++) {
      const int row = s < 4 ? 4 * s + (lane >> 3) : lane >> 1, pc = s < 4 ? lane & 7 : 8 + (lane & 1);
      const uint4 v = lds128(stg + row * 160 + pc * 16);
      if (row != crow) stg128(ob2 + row * 2560 + pc * 16 + (s < 4 ? 0 : remo), v);
    }
    mbar_wait(bar_win, 0);
    uint4 win = lds128(sb + OFF_WR + 336);
    win.z = win.y; win.y = 2047u - (win.x & 2047u); win.x = (win.y >> 8) * 16 + (win.y & 1) * 8 + ((win.y >> 5) & 7);
    if (win.x != slot && lane < 10) stg128(ob2 + crow * 2560 + lane * 16 + (lane < 8 ? 0 : remo), held);
    if (!ffn1) {
      TS(10);
      uint4 w2[6];
      const uint32_t a2 = sb + OFF_W2 + (warp * 192 + 8 * (((lane >> 3) & 1) * 4 + ((lane & 7) >> 1)) + 2 * (lane >> 4) + (lane & 1)) * 16;
#pragma unroll
      for (int s = 0; s < 6; s++) w2[s] = ldsm4t(a2 + (s >> 1) * 1024 + (s & 1) * 64);
      const uint4* p = (const uint4*)(g_x.act + warp * 96) + (r & 1) * 4 + c;
      const uint32_t* pb = (const uint32_t*)&g_x.cand[win.x][fj < 64 ? fj >> 3 : (fj - 64) >> 1][fj < 64 ? 12 + (fj & 7) : 20 + (fj & 1)] + c;
      uint32_t* const op = hold((uint32_t*)(out + win.y * 640 + fj * 8) + c);
      const float sg = rcp(1.f + ex2(-1.4426950408889634f * __uint_as_float(win.z ^ ((uint32_t)((int32_t)~win.z >> 31) | 0x80000000u))));
      uint4 c0, c1, c2; uint32_t bw;
      if (ACT_NS) __nanosleep(ACT_NS);
      do {
        c0 = ldg_pkt(p); c1 = ldg_pkt(p + 8); c2 = ldg_pkt(p + 16); bw = ldg_rlx32(pb);
      } while (anyw(max(max(max(max(c0.x, c0.y), max(c0.z, c0.w)), max(max(c1.x, c1.y), max(c1.z, c1.w))), max(max(max(c2.x, c2.y), max(c2.z, c2.w)), bw)) == SENT) && --guard > 0);
      TS(11);
      float a[4] = {0.f, 0.f, 0.f, 0.f}, b[4] = {0.f, 0.f, 0.f, 0.f}, d[4] = {0.f, 0.f, 0.f, 0.f};
      mma_acc(a, w2[0], c0.x, c0.y); mma_acc(b, w2[2], c1.x, c1.y); mma_acc(d, w2[4], c2.x, c2.y);
      mma_acc(a, w2[1], c0.z, c0.w); mma_acc(b, w2[3], c1.z, c1.w); mma_acc(d, w2[5], c2.z, c2.w);
      if (c == 0) sts32f(red + (warp * 8 + r) * 4, ((a[0] + a[3]) + (b[0] + b[3])) + (d[0] + d[3]));
      bar_sync(1, 256);
      if (tid < 4) {
        float2 t[8];
#pragma unroll
        for (int i = 0; i < 8; i++) t[i] = lds64f(red + (i * 4 + tid) * 8);
        const float y0 = ((t[0].x + t[1].x) + (t[2].x + t[3].x)) + ((t[4].x + t[5].x) + (t[6].x + t[7].x));
        const float y1 = ((t[0].y + t[1].y) + (t[2].y + t[3].y)) + ((t[4].y + t[5].y) + (t[6].y + t[7].y));
        *op = pack_bf16(fmaf(y0, sg, bf_lo(bw)), fmaf(y1, sg, bf_hi(bw)));
      }
    }
    TS(12);
#undef TS_T
  }
}

typedef CUresult (*EncodeFn)(CUtensorMap*, CUtensorMapDataType, cuuint32_t, void*, const cuuint64_t*, const cuuint64_t*, const cuuint32_t*,
                             const cuuint32_t*, CUtensorMapInterleave, CUtensorMapSwizzle, CUtensorMapL2promotion, CUtensorMapFloatOOBfill);

void make_map(EncodeFn enc, CUtensorMap* m, const void* base, const cuuint64_t* dims, const cuuint64_t* strides, const cuuint32_t* box,
              CUtensorMapSwizzle swz) {
  const cuuint32_t es[3] = {1, 1, 1};
  enc(m, CU_TENSOR_MAP_DATA_TYPE_BFLOAT16, 3, (void*)base, dims, strides, box, es, CU_TENSOR_MAP_INTERLEAVE_NONE, swz,
      CU_TENSOR_MAP_L2_PROMOTION_L2_128B, CU_TENSOR_MAP_FLOAT_OOB_FILL_NONE);
}

}

extern "C" void kernel_launch(void* const* d_in, const int* in_sizes, int n_in, void* d_out, int out_size) {
  const __nv_bfloat16* x = (const __nv_bfloat16*)d_in[0];
  const __nv_bfloat16* wqkv = (const __nv_bfloat16*)d_in[1];
  const __nv_bfloat16* wo = (const __nv_bfloat16*)d_in[2];
  void* fn = nullptr;
  cudaDriverEntryPointQueryResult st;
  cudaGetDriverEntryPoint("cuTensorMapEncodeTiled", &fn, cudaEnableDefault, &st);
  EncodeFn enc = (EncodeFn)fn;
  void* scp = nullptr;
  cudaGetSymbolAddress(&scp, g_scratch);
  Maps tm;
  { const cuuint64_t d[3] = {640, 1024, 2}, s[2] = {2560, 1280}; const cuuint32_t b[3] = {64, 128, 1}; make_map(enc, &tm.x, x, d, s, b, CU_TENSOR_MAP_SWIZZLE_128B); }
  { const cuuint64_t d[3] = {640, 640, 3}, s[2] = {3840, 1280}; const cuuint32_t b[3] = {64, 64, 1}; make_map(enc, &tm.w, wqkv, d, s, b, CU_TENSOR_MAP_SWIZZLE_128B); }
  { const cuuint64_t d[3] = {640, 640, 3}, s[2] = {3840, 1280}; const cuuint32_t b[3] = {16, 64, 3}; make_map(enc, &tm.wr, wqkv, d, s, b, CU_TENSOR_MAP_SWIZZLE_32B); }
  { const cuuint64_t d[3] = {32, 640, 20}, s[2] = {1280, 64}; const cuuint32_t b[3] = {32, 80, 2}; make_map(enc, &tm.wo, wo, d, s, b, CU_TENSOR_MAP_SWIZZLE_64B); }
  { const cuuint64_t d[3] = {640, 640, 1}, s[2] = {1280, 819200}; const cuuint32_t b[3] = {16, 80, 1}; make_map(enc, &tm.wor, wo, d, s, b, CU_TENSOR_MAP_SWIZZLE_64B); }
  { const cuuint64_t d[3] = {1536, 640, 1}, s[2] = {3072, 1966080}; const cuuint32_t b[3] = {32, 128, 1};
    make_map(enc, &tm.gate, d_in[5], d, s, b, CU_TENSOR_MAP_SWIZZLE_64B); make_map(enc, &tm.up, d_in[6], d, s, b, CU_TENSOR_MAP_SWIZZLE_64B); }
  { const cuuint64_t d[3] = {640, 1536, 1}, s[2] = {1280, 1966080}; const cuuint32_t b[3] = {8, 128, 1}; make_map(enc, &tm.down, d_in[7], d, s, b, CU_TENSOR_MAP_SWIZZLE_NONE); }
  cudaFuncSetAttribute(fused_kernel, cudaFuncAttributeMaxDynamicSharedMemorySize, SMEM_BYTES);
  fused_kernel<<<128, 512, SMEM_BYTES, cudaStreamPerThread>>>(x, wqkv, wo, (const __nv_bfloat16*)d_in[4], (const __nv_bfloat16*)d_in[5],
                                                              (const __nv_bfloat16*)d_in[6], (const __nv_bfloat16*)d_in[7], (__nv_bfloat16*)d_out, (Scratch*)scp, tm);
}
```

```cpp
#include <cuda_runtime.h>
#include <cuda_bf16.h>
#include <cuda.h>
#include <stdint.h>

#define PFW_NS 50
#define ACT_NS 100
#define OUT_LATE 0
#define REG_P 72
#define REG_C 184
#define AUX_NS 50
#define LEAD 1
#define RST_IT 4
#define ORDX 1
#define THR 2
#define PF_FIRST 2
#define PF_T0 1200
#define PF_CLK 500
#define HK_IT 1
#define F_IT 9
#define F_PER 2
#define F_MAX 8
#define HOLD 2
#define F_LATE 12
#define HALO_NS 0
#define AK 3
#define KEY_NS 60
#define FW 5
#define ONE_RED 2
#define CNT_NS 0
#define NO_LATE 0
#define EARLY 1
#define PREW 9
#define NSPLIT 3
#define E1_CLK 400

namespace {

constexpr int SLOT    = 47104;
constexpr int OFF_O   = 122880;
constexpr int OFF_W2  = 4 * SLOT;
constexpr int OFF_CS  = OFF_W2 + 32768;
constexpr int OFF_RS  = OFF_CS + 3840;
constexpr int OFF_MN  = OFF_RS + 576;
constexpr int OFF_WR  = OFF_MN + 1024;
constexpr int OFF_RED = OFF_CS;
constexpr int OFF_HN  = OFF_CS + 2048;
constexpr int OFF_PT  = OFF_WR + 352;
constexpr int OFF_BAR = OFF_PT + 768;
constexpr int SMEM_BYTES = OFF_BAR + 424 + 384;
constexpr uint32_t D0 = 1024 >> 4;
constexpr uint32_t SENT = 0xFFFFFFFFu;
constexpr int SPIN_MAX = 1 << 20;

struct Glob {
  uint4 cand[128][8][24];
  uint32_t act[768];
  uint32_t pad[256];
};
constexpr int GLOB_PER_CTA = sizeof(Glob) / 16 / 128;
static_assert(GLOB_PER_CTA * 128 * 16 == sizeof(Glob), "glob size");
struct Own {
  uint4 halo[5][32];
  uint4 st1[32];
  uint2 cs[32];
  uint4 st2[16];
  uint4 cnt[8];
};
struct Scratch {
  Glob x;
  Own own[128];
  uint4 o[32][8][640];
  uint32_t epoch[128];
};
__device__ __align__(128) Scratch g_scratch;
#define g_x (sc->x)
#define g_own (sc->own)
#define g_o (sc->o)
#define g_epoch (sc->epoch)
#define TS(i)

__device__ __forceinline__ void mbar_init(uint32_t bar, uint32_t cnt) { asm volatile("mbarrier.init.shared::cta.b64 [%0], %1;" :: "r"(bar), "r"(cnt) : "memory"); }
__device__ __forceinline__ void mbar_expect_tx(uint32_t bar, uint32_t bytes) { asm volatile("mbarrier.arrive.expect_tx.shared::cta.b64 _, [%0], %1;" :: "r"(bar), "r"(bytes) : "memory"); }
__device__ __forceinline__ void mbar_arrive(uint32_t bar) { asm volatile("mbarrier.arrive.shared::cta.b64 _, [%0];" :: "r"(bar) : "memory"); }
__device__ __forceinline__ void mbar_arrive_cta(uint32_t bar, uint32_t cta) {
  asm volatile("{\n.reg .b32 ra;\nmapa.shared::cluster.u32 ra, %0, %1;\nmbarrier.arrive.shared::cluster.b64 _, [ra];\n}\n" :: "r"(bar), "r"(cta) : "memory");
}
__device__ __forceinline__ void mbar_wait(uint32_t bar, uint32_t parity) {
  asm volatile("{\n.reg .pred p;\n.reg .u32 n;\nmov.u32 n, 0;\nW:\nmbarrier.try_wait.parity.shared::cta.b64 p, [%0], %1;\n@p bra.uni D;\n"
               "add.u32 n, n, 1;\nsetp.lt.u32 p, n, %2;\n@p bra.uni W;\nD:\n}\n" :: "r"(bar), "r"(parity), "n"(SPIN_MAX) : "memory");
}
__device__ __forceinline__ void tma_3d(uint32_t dst, const void* tm, uint32_t bar, int c0, int c1, int c2) {
  asm volatile("cp.async.bulk.tensor.3d.shared::cluster.global.mbarrier::complete_tx::bytes [%0], [%1, {%3, %4, %5}], [%2];" :: "r"(dst), "l"(tm), "r"(bar), "r"(c0), "r"(c1), "r"(c2) : "memory");
}
__device__ __forceinline__ void tma_3d_mc(uint32_t dst, const void* tm, uint32_t bar, int c0, int c1, int c2) {
  asm volatile("cp.async.bulk.tensor.3d.shared::cluster.global.mbarrier::complete_tx::bytes.multicast::cluster [%0], [%1, {%3, %4, %5}], [%2], %6;" :: "r"(dst), "l"(tm), "r"(bar), "r"(c0), "r"(c1), "r"(c2), "h"((uint16_t)3) : "memory");
}
__device__ __forceinline__ void wgmma_fence() { asm volatile("wgmma.fence.sync.aligned;" ::: "memory"); }
__device__ __forceinline__ void wgmma_commit() { asm volatile("wgmma.commit_group.sync.aligned;" ::: "memory"); }
template <int N> __device__ __forceinline__ void wgmma_wait() { asm volatile("wgmma.wait_group.sync.aligned %0;" :: "n"(N) : "memory"); }
__device__ __forceinline__ uint64_t make_desc(uint32_t addr, uint32_t lbo, uint32_t sbo, uint32_t swz) {
  return (uint64_t)(((addr & 0x3FFFF) >> 4) | ((lbo >> 4) << 16)) | ((uint64_t)((sbo >> 4) | (swz << 30)) << 32);
}
__device__ __forceinline__ void bar_sync(int id, int n) { asm volatile("bar.sync %0, %1;" :: "r"(id), "r"(n) : "memory"); }
__device__ __forceinline__ void st_pkt(void* p, uint32_t a, uint32_t b, uint32_t c, uint32_t d) {
  asm volatile("st.relaxed.gpu.v4.u32 [%0], {%1, %2, %3, %4};" :: "l"(p), "r"(a), "r"(b), "r"(c), "r"(d) : "memory");
}
__device__ __forceinline__ uint4 ldg_pkt(const void* p) {
  uint4 v; asm volatile("ld.relaxed.gpu.global.v4.u32 {%0, %1, %2, %3}, [%4];" : "=r"(v.x), "=r"(v.y), "=r"(v.z), "=r"(v.w) : "l"(p) : "memory"); return v;
}
__device__ __forceinline__ void stg_pkt(void* p, uint32_t a, uint32_t b, uint32_t c, uint32_t d) {
  asm volatile("st.relaxed.gpu.global.v4.u32 [%0], {%1, %2, %3, %4};" :: "l"(p), "r"(a), "r"(b), "r"(c), "r"(d) : "memory");
}
__device__ __forceinline__ uint32_t ldg_rlx32(const void* p) { uint32_t v; asm volatile("ld.relaxed.gpu.global.u32 %0, [%1];" : "=r"(v) : "l"(p) : "memory"); return v; }
__device__ __forceinline__ uint2 ldg_rlx64(const void* p) { uint2 v; asm volatile("ld.relaxed.gpu.global.v2.u32 {%0, %1}, [%2];" : "=r"(v.x), "=r"(v.y) : "l"(p) : "memory"); return v; }
__device__ __forceinline__ void stg128(void* p, const uint4& v) { asm volatile("st.global.v4.u32 [%0], {%1, %2, %3, %4};" :: "l"(p), "r"(v.x), "r"(v.y), "r"(v.z), "r"(v.w) : "memory"); }
__device__ __forceinline__ uint32_t pin(uint32_t v) { asm volatile("" : "+r"(v)); return v; }
__device__ __forceinline__ uint64_t mk64(uint32_t lo, uint32_t hi) { return ((uint64_t)hi << 32) | lo; }
template <class T> __device__ __forceinline__ T* hold(T* p) { return (T*)__shfl_sync(0xffffffffu, (unsigned long long)p, threadIdx.x & 31); }
template <class T> __device__ __forceinline__ T* pin(T* p) { asm volatile("" : "+l"(p)); return p; }
__device__ __forceinline__ void stg_rlx32(void* p, uint32_t v) { asm volatile("st.relaxed.gpu.global.u32 [%0], %1;" :: "l"(p), "r"(v) : "memory"); }
__device__ __forceinline__ void stg_rlx64(void* p, uint32_t a, uint32_t b) { asm volatile("st.relaxed.gpu.global.v2.u32 [%0], {%1, %2};" :: "l"(p), "r"(a), "r"(b) : "memory"); }
__device__ __forceinline__ uint4 ldsm4(uint32_t a) { uint4 v; asm volatile("ldmatrix.sync.aligned.m8n8.x4.shared.b16 {%0, %1, %2, %3}, [%4];" : "=r"(v.x), "=r"(v.y), "=r"(v.z), "=r"(v.w) : "r"(a) : "memory"); return v; }
__device__ __forceinline__ void ldsm4_if(uint4& v, uint32_t a, int off, bool p) {
  asm volatile("{\n.reg .pred q;\nsetp.ne.u32 q, %5, 0;\n@q ldmatrix.sync.aligned.m8n8.x4.shared.b16 {%0, %1, %2, %3}, [%4];\n}\n"
               : "+r"(v.x), "+r"(v.y), "+r"(v.z), "+r"(v.w) : "r"(a + off), "r"((int)p) : "memory");
}
__device__ __forceinline__ uint4 ldsm4t(uint32_t a) { uint4 v; asm volatile("ldmatrix.sync.aligned.m8n8.x4.trans.shared.b16 {%0, %1, %2, %3}, [%4];" : "=r"(v.x), "=r"(v.y), "=r"(v.z), "=r"(v.w) : "r"(a) : "memory"); return v; }
__device__ __forceinline__ void stsm4(uint32_t a, uint32_t x, uint32_t y, uint32_t z, uint32_t w) { asm volatile("stmatrix.sync.aligned.m8n8.x4.shared.b16 [%0], {%1, %2, %3, %4};" :: "r"(a), "r"(x), "r"(y), "r"(z), "r"(w) : "memory"); }
__device__ __forceinline__ void mma_acc(float (&c)[4], const uint4& a, uint32_t b0, uint32_t b1) {
  asm("mma.sync.aligned.m16n8k16.row.col.f32.bf16.bf16.f32 {%0,%1,%2,%3}, {%4,%5,%6,%7}, {%8,%9}, {%0,%1,%2,%3};"
      : "+f"(c[0]), "+f"(c[1]), "+f"(c[2]), "+f"(c[3]) : "r"(a.x), "r"(a.y), "r"(a.z), "r"(a.w), "r"(b0), "r"(b1));
}
__device__ __forceinline__ uint4 lds128(uint32_t a) { uint4 v; asm volatile("ld.shared.v4.u32 {%0, %1, %2, %3}, [%4];" : "=r"(v.x), "=r"(v.y), "=r"(v.z), "=r"(v.w) : "r"(a) : "memory"); return v; }
__device__ __forceinline__ float2 lds64f(uint32_t a) { float2 v; asm volatile("ld.shared.v2.f32 {%0, %1}, [%2];" : "=f"(v.x), "=f"(v.y) : "r"(a)); return v; }
__device__ __forceinline__ float lds32f(uint32_t a) { float v; asm volatile("ld.shared.f32 %0, [%1];" : "=f"(v) : "r"(a)); return v; }
__device__ __forceinline__ void sts32f(uint32_t a, float v) { asm volatile("st.shared.f32 [%0], %1;" :: "r"(a), "f"(v) : "memory"); }
__device__ __forceinline__ uint32_t pack_bf16(float lo, float hi) { uint32_t r; asm("cvt.rn.bf16x2.f32 %0, %1, %2;" : "=r"(r) : "f"(hi), "f"(lo)); return r; }
__device__ __forceinline__ float bf_lo(uint32_t v) { return __uint_as_float(v << 16); }
__device__ __forceinline__ float bf_hi(uint32_t v) { return __uint_as_float(v & 0xffff0000u); }
__device__ __forceinline__ uint32_t movm(uint32_t a) { uint32_t d; asm("movmatrix.sync.aligned.m8n8.trans.b16 %0, %1;" : "=r"(d) : "r"(a)); return d; }
__device__ __forceinline__ float ex2(float x) { float y; asm("ex2.approx.ftz.f32 %0, %1;" : "=f"(y) : "f"(x)); return y; }
__device__ __forceinline__ float rsq(float x) { float y; asm("rsqrt.approx.ftz.f32 %0, %1;" : "=f"(y) : "f"(x)); return y; }
__device__ __forceinline__ float rcp(float x) { float y; asm("rcp.approx.ftz.f32 %0, %1;" : "=f"(y) : "f"(x)); return y; }
__device__ __forceinline__ bool elect() { uint32_t p; asm volatile("{\n.reg .pred q;\nelect.sync _|q, 0xffffffff;\nselp.u32 %0, 1, 0, q;\n}\n" : "=r"(p)); return p; }
__device__ __forceinline__ int clk() { int c; asm volatile("mov.u32 %0, %%clock;" : "=r"(c) :: "memory"); return c; }
__device__ __forceinline__ void pf_l2(const void* p) { asm volatile("prefetch.global.L2 [%0];" :: "l"(p)); }
__device__ __forceinline__ bool anyw(bool p) { return __any_sync(0xffffffffu, p); }
__device__ __forceinline__ float shx(float v, int m) { return __shfl_xor_sync(0xffffffffu, v, m); }
__device__ __forceinline__ void mma_k24(float (&c)[4], uint32_t a0, uint32_t a1, uint32_t a2, uint32_t a3, uint32_t b0, uint32_t b1,
                                        uint32_t e0, uint32_t e1, uint32_t f0) {
  asm("mma.sync.aligned.m16n8k16.row.col.f32.bf16.bf16.f32 {%0,%1,%2,%3}, {%4,%5,%6,%7}, {%8,%9}, {%10,%10,%10,%10};"
      : "=f"(c[0]), "=f"(c[1]), "=f"(c[2]), "=f"(c[3]) : "r"(a0), "r"(a1), "r"(a2), "r"(a3), "r"(b0), "r"(b1), "f"(0.f));
  asm("mma.sync.aligned.m16n8k8.row.col.f32.bf16.bf16.f32 {%0,%1,%2,%3}, {%4,%5}, {%6}, {%0,%1,%2,%3};"
      : "+f"(c[0]), "+f"(c[1]), "+f"(c[2]), "+f"(c[3]) : "r"(e0), "r"(e1), "r"(f0));
}
__device__ __forceinline__ uint32_t ord_key(float r) { uint32_t u = __float_as_uint(r); return u ^ ((uint32_t)((int32_t)u >> 31) | 0x80000000u); }

__device__ __forceinline__ void wgmma_n48hi_ss(float (&d)[120], uint64_t da, uint64_t db, int scale_d) {
  asm volatile("{\n.reg .pred p;\nsetp.ne.b32 p, %26, 0;\n"
    "wgmma.mma_async.sync.aligned.m64n48k16.f32.bf16.bf16 "
    "{%0, %1, %2, %3, %4, %5, %6, %7, %8, %9, %10, %11, %12, %13, %14, %15, "
    "%16, %17, %18, %19, %20, %21, %22, %23}, "
    "%24, %25, p, 1, 1, 0, 1;\n}\n"
    : "+f"(d[96]), "+f"(d[97]), "+f"(d[98]), "+f"(d[99]), "+f"(d[100]), "+f"(d[101]), "+f"(d[102]), "+f"(d[103]),
      "+f"(d[104]), "+f"(d[105]), "+f"(d[106]), "+f"(d[107]), "+f"(d[108]), "+f"(d[109]), "+f"(d[110]), "+f"(d[111]),
      "+f"(d[112]), "+f"(d[113]), "+f"(d[114]), "+f"(d[115]), "+f"(d[116]), "+f"(d[117]), "+f"(d[118]), "+f"(d[119])
    : "l"(da), "l"(db), "r"(scale_d));
}
__device__ __forceinline__ void wgmma_n192lo_ss(float (&d)[120], uint64_t da, uint64_t db, int scale_d) {
  asm volatile("{\n.reg .pred p;\nsetp.ne.b32 p, %98, 0;\n"
    "wgmma.mma_async.sync.aligned.m64n192k16.f32.bf16.bf16 "
    "{%0, %1, %2, %3, %4, %5, %6, %7, %8, %9, %10, %11, %12, %13, %14, %15, "
    "%16, %17, %18, %19, %20, %21, %22, %23, %24, %25, %26, %27, %28, %29, %30, %31, "
    "%32, %33, %34, %35, %36, %37, %38, %39, %40, %41, %42, %43, %44, %45, %46, %47, "
    "%48, %49, %50, %51, %52, %53, %54, %55, %56, %57, %58, %59, %60, %61, %62, %63, "
    "%64, %65, %66, %67, %68, %69, %70, %71, %72, %73, %74, %75, %76, %77, %78, %79, "
    "%80, %81, %82, %83, %84, %85, %86, %87, %88, %89, %90, %91, %92, %93, %94, %95}, "
    "%96, %97, p, 1, 1, 0, 1;\n}\n"
    : "+f"(d[0]), "+f"(d[1]), "+f"(d[2]), "+f"(d[3]), "+f"(d[4]), "+f"(d[5]), "+f"(d[6]), "+f"(d[7]),
      "+f"(d[8]), "+f"(d[9]), "+f"(d[10]), "+f"(d[11]), "+f"(d[12]), "+f"(d[13]), "+f"(d[14]), "+f"(d[15]),
      "+f"(d[16]), "+f"(d[17]), "+f"(d[18]), "+f"(d[19]), "+f"(d[20]), "+f"(d[21]), "+f"(d[22]), "+f"(d[23]),
      "+f"(d[24]), "+f"(d[25]), "+f"(d[26]), "+f"(d[27]), "+f"(d[28]), "+f"(d[29]), "+f"(d[30]), "+f"(d[31]),
      "+f"(d[32]), "+f"(d[33]), "+f"(d[34]), "+f"(d[35]), "+f"(d[36]), "+f"(d[37]), "+f"(d[38]), "+f"(d[39]),
      "+f"(d[40]), "+f"(d[41]), "+f"(d[42]), "+f"(d[43]), "+f"(d[44]), "+f"(d[45]), "+f"(d[46]), "+f"(d[47]),
      "+f"(d[48]), "+f"(d[49]), "+f"(d[50]), "+f"(d[51]), "+f"(d[52]), "+f"(d[53]), "+f"(d[54]), "+f"(d[55]),
      "+f"(d[56]), "+f"(d[57]), "+f"(d[58]), "+f"(d[59]), "+f"(d[60]), "+f"(d[61]), "+f"(d[62]), "+f"(d[63]),
      "+f"(d[64]), "+f"(d[65]), "+f"(d[66]), "+f"(d[67]), "+f"(d[68]), "+f"(d[69]), "+f"(d[70]), "+f"(d[71]),
      "+f"(d[72]), "+f"(d[73]), "+f"(d[74]), "+f"(d[75]), "+f"(d[76]), "+f"(d[77]), "+f"(d[78]), "+f"(d[79]),
      "+f"(d[80]), "+f"(d[81]), "+f"(d[82]), "+f"(d[83]), "+f"(d[84]), "+f"(d[85]), "+f"(d[86]), "+f"(d[87]),
      "+f"(d[88]), "+f"(d[89]), "+f"(d[90]), "+f"(d[91]), "+f"(d[92]), "+f"(d[93]), "+f"(d[94]), "+f"(d[95])
    : "l"(da), "l"(db), "r"(scale_d));
}
__device__ __forceinline__ void wgmma_n48hi_rk(float (&d)[120], uint32_t a0, uint32_t a1, uint32_t a2, uint32_t a3, uint64_t db, int scale_d) {
  asm volatile("{\n.reg .pred p;\nsetp.ne.b32 p, %29, 0;\n"
    "wgmma.mma_async.sync.aligned.m64n48k16.f32.bf16.bf16 "
    "{%0, %1, %2, %3, %4, %5, %6, %7, %8, %9, %10, %11, %12, %13, %14, %15, "
    "%16, %17, %18, %19, %20, %21, %22, %23}, "
    "{%24, %25, %26, %27}, %28, p, 1, 1, 0;\n}\n"
    : "+f"(d[96]), "+f"(d[97]), "+f"(d[98]), "+f"(d[99]), "+f"(d[100]), "+f"(d[101]), "+f"(d[102]), "+f"(d[103]),
      "+f"(d[104]), "+f"(d[105]), "+f"(d[106]), "+f"(d[107]), "+f"(d[108]), "+f"(d[109]), "+f"(d[110]), "+f"(d[111]),
      "+f"(d[112]), "+f"(d[113]), "+f"(d[114]), "+f"(d[115]), "+f"(d[116]), "+f"(d[117]), "+f"(d[118]), "+f"(d[119])
    : "r"(a0), "r"(a1), "r"(a2), "r"(a3), "l"(db), "r"(scale_d));
}
__device__ __forceinline__ void wgmma_n192lo_rk(float (&d)[120], uint32_t a0, uint32_t a1, uint32_t a2, uint32_t a3, uint64_t db, int scale_d) {
  asm volatile("{\n.reg .pred p;\nsetp.ne.b32 p, %101, 0;\n"
    "wgmma.mma_async.sync.aligned.m64n192k16.f32.bf16.bf16 "
    "{%0, %1, %2, %3, %4, %5, %6, %7, %8, %9, %10, %11, %12, %13, %14, %15, "
    "%16, %17, %18, %19, %20, %21, %22, %23, %24, %25, %26, %27, %28, %29, %30, %31, "
    "%32, %33, %34, %35, %36, %37, %38, %39, %40, %41, %42, %43, %44, %45, %46, %47, "
    "%48, %49, %50, %51, %52, %53, %54, %55, %56, %57, %58, %59, %60, %61, %62, %63, "
    "%64, %65, %66, %67, %68, %69, %70, %71, %72, %73, %74, %75, %76, %77, %78, %79, "
    "%80, %81, %82, %83, %84, %85, %86, %87, %88, %89, %90, %91, %92, %93, %94, %95}, "
    "{%96, %97, %98, %99}, %100, p, 1, 1, 0;\n}\n"
    : "+f"(d[0]), "+f"(d[1]), "+f"(d[2]), "+f"(d[3]), "+f"(d[4]), "+f"(d[5]), "+f"(d[6]), "+f"(d[7]),
      "+f"(d[8]), "+f"(d[9]), "+f"(d[10]), "+f"(d[11]), "+f"(d[12]), "+f"(d[13]), "+f"(d[14]), "+f"(d[15]),
      "+f"(d[16]), "+f"(d[17]), "+f"(d[18]), "+f"(d[19]), "+f"(d[20]), "+f"(d[21]), "+f"(d[22]), "+f"(d[23]),
      "+f"(d[24]), "+f"(d[25]), "+f"(d[26]), "+f"(d[27]), "+f"(d[28]), "+f"(d[29]), "+f"(d[30]), "+f"(d[31]),
      "+f"(d[32]), "+f"(d[33]), "+f"(d[34]), "+f"(d[35]), "+f"(d[36]), "+f"(d[37]), "+f"(d[38]), "+f"(d[39]),
      "+f"(d[40]), "+f"(d[41]), "+f"(d[42]), "+f"(d[43]), "+f"(d[44]), "+f"(d[45]), "+f"(d[46]), "+f"(d[47]),
      "+f"(d[48]), "+f"(d[49]), "+f"(d[50]), "+f"(d[51]), "+f"(d[52]), "+f"(d[53]), "+f"(d[54]), "+f"(d[55]),
      "+f"(d[56]), "+f"(d[57]), "+f"(d[58]), "+f"(d[59]), "+f"(d[60]), "+f"(d[61]), "+f"(d[62]), "+f"(d[63]),
      "+f"(d[64]), "+f"(d[65]), "+f"(d[66]), "+f"(d[67]), "+f"(d[68]), "+f"(d[69]), "+f"(d[70]), "+f"(d[71]),
      "+f"(d[72]), "+f"(d[73]), "+f"(d[74]), "+f"(d[75]), "+f"(d[76]), "+f"(d[77]), "+f"(d[78]), "+f"(d[79]),
      "+f"(d[80]), "+f"(d[81]), "+f"(d[82]), "+f"(d[83]), "+f"(d[84]), "+f"(d[85]), "+f"(d[86]), "+f"(d[87]),
      "+f"(d[88]), "+f"(d[89]), "+f"(d[90]), "+f"(d[91]), "+f"(d[92]), "+f"(d[93]), "+f"(d[94]), "+f"(d[95])
    : "r"(a0), "r"(a1), "r"(a2), "r"(a3), "l"(db), "r"(scale_d));
}
__device__ __forceinline__ void wgmma_n80_rs(float (&d)[40], uint32_t a0, uint32_t a1, uint32_t a2, uint32_t a3, uint64_t db, int scale_d) {
  asm volatile("{\n.reg .pred p;\nsetp.ne.b32 p, %45, 0;\n"
    "wgmma.mma_async.sync.aligned.m64n80k16.f32.bf16.bf16 "
    "{%0, %1, %2, %3, %4, %5, %6, %7, %8, %9, %10, %11, %12, %13, %14, %15, "
    "%16, %17, %18, %19, %20, %21, %22, %23, %24, %25, %26, %27, %28, %29, %30, %31, "
    "%32, %33, %34, %35, %36, %37, %38, %39}, "
    "{%40, %41, %42, %43}, %44, p, 1, 1, 1;\n}\n"
    : "+f"(d[0]), "+f"(d[1]), "+f"(d[2]), "+f"(d[3]), "+f"(d[4]), "+f"(d[5]), "+f"(d[6]), "+f"(d[7]),
      "+f"(d[8]), "+f"(d[9]), "+f"(d[10]), "+f"(d[11]), "+f"(d[12]), "+f"(d[13]), "+f"(d[14]), "+f"(d[15]),
      "+f"(d[16]), "+f"(d[17]), "+f"(d[18]), "+f"(d[19]), "+f"(d[20]), "+f"(d[21]), "+f"(d[22]), "+f"(d[23]),
      "+f"(d[24]), "+f"(d[25]), "+f"(d[26]), "+f"(d[27]), "+f"(d[28]), "+f"(d[29]), "+f"(d[30]), "+f"(d[31]),
      "+f"(d[32]), "+f"(d[33]), "+f"(d[34]), "+f"(d[35]), "+f"(d[36]), "+f"(d[37]), "+f"(d[38]), "+f"(d[39])
    : "r"(a0), "r"(a1), "r"(a2), "r"(a3), "l"(db), "r"(scale_d));
}
__device__ __forceinline__ void wgmma_n80_ss(float (&d)[40], uint64_t da, uint64_t db, int scale_d) {
  asm volatile("{\n.reg .pred p;\nsetp.ne.b32 p, %42, 0;\n"
    "wgmma.mma_async.sync.aligned.m64n80k16.f32.bf16.bf16 "
    "{%0, %1, %2, %3, %4, %5, %6, %7, %8, %9, %10, %11, %12, %13, %14, %15, "
    "%16, %17, %18, %19, %20, %21, %22, %23, %24, %25, %26, %27, %28, %29, %30, %31, "
    "%32, %33, %34, %35, %36, %37, %38, %39}, "
    "%40, %41, p, 1, 1, 0, 1;\n}\n"
    : "+f"(d[0]), "+f"(d[1]), "+f"(d[2]), "+f"(d[3]), "+f"(d[4]), "+f"(d[5]), "+f"(d[6]), "+f"(d[7]),
      "+f"(d[8]), "+f"(d[9]), "+f"(d[10]), "+f"(d[11]), "+f"(d[12]), "+f"(d[13]), "+f"(d[14]), "+f"(d[15]),
      "+f"(d[16]), "+f"(d[17]), "+f"(d[18]), "+f"(d[19]), "+f"(d[20]), "+f"(d[21]), "+f"(d[22]), "+f"(d[23]),
      "+f"(d[24]), "+f"(d[25]), "+f"(d[26]), "+f"(d[27]), "+f"(d[28]), "+f"(d[29]), "+f"(d[30]), "+f"(d[31]),
      "+f"(d[32]), "+f"(d[33]), "+f"(d[34]), "+f"(d[35]), "+f"(d[36]), "+f"(d[37]), "+f"(d[38]), "+f"(d[39])
    : "l"(da), "l"(db), "r"(scale_d));
}

__device__ __forceinline__ constexpr int QT(int t) { return t < 8 ? t : 16 + t; }
__device__ __forceinline__ constexpr int KT(int t) { return t < 8 ? 8 + t : 18 + t; }
__device__ __forceinline__ constexpr int VT(int t) { return t < 8 ? 16 + t : 20 + t; }

struct Maps { CUtensorMap x, w, wr, wo, wor, gate, up, down; };

__global__ void __cluster_dims__(2, 1, 1) __launch_bounds__(512, 1)
fused_kernel(const __nv_bfloat16* __restrict__ x, const __nv_bfloat16* __restrict__ wqkv,
             const __nv_bfloat16* __restrict__ wo, const __nv_bfloat16* __restrict__ w_r, const __nv_bfloat16* __restrict__ w_gate,
             const __nv_bfloat16* __restrict__ w_up, const __nv_bfloat16* __restrict__ w_down, __nv_bfloat16* __restrict__ out,
             Scratch* __restrict__ sc, const __grid_constant__ Maps tm) {
  extern __shared__ __align__(1024) uint8_t smem[];
  const int tid = threadIdx.x, bid = blockIdx.x;
  if ((unsigned)(tid - 128) < 16u) pf_l2((const char*)x + (bid * 16 + tid - 128) * 1280);
  if ((unsigned)(tid - 160) < 15u) pf_l2((const char*)wqkv + (bid * 15 + tid - 160) * 128);
  const int warp = __shfl_sync(0xffffffffu, tid >> 5, 0), lane = tid & 31;
  const uint32_t sb = (uint32_t)__cvta_generic_to_shared(smem);
  const uint32_t bar_full = sb + OFF_BAR, bar_empty = bar_full + 32, bar_aux = bar_full + 64, bar_ffn = bar_full + 72, bar_win = bar_full + 80, bar_rst = bar_full + 88,
                 bar_o = bar_full + 96, bar_oc = bar_o + 112, bar_st = bar_o + 224, bar_go = bar_o + 248, bar_kv = bar_o + 272, bar_tag = bar_o + 288, bar_half = bar_o + 296;
  if (warp < 4 && elect()) {
    mbar_init(bar_half + 8 * warp, 1);
    mbar_init(bar_full + 8 * (warp ^ 2), 1);
    mbar_init(bar_empty + 8 * warp, 24);
    mbar_init(bar_aux + 8 * warp, warp == 0 ? 64 : warp == 2 ? 32 : 1);
    asm volatile("fence.mbarrier_init.release.cluster;" ::: "memory");
  }
  if (warp == 6 && elect()) mbar_init(bar_tag, 2);
  asm volatile("barrier.cluster.arrive.relaxed.aligned;" ::: "memory");
  if (warp >= 8 && warp < 11 && elect()) asm volatile("prefetch.tensormap [%0];" :: "l"(&tm.x + (warp - 8)) : "memory");
  auto pf_slice = [&](int ks) {
    pf_l2(lane < 16 ? (const char*)x + ((bid * 16 + lane) * 1280 + ks * 128) : (const char*)wqkv + ((bid * 15 + min(lane, 30) - 16) * 128 + ks * 245760));
  };
  if (E1_CLK && (warp == 6 || warp == 7)) { const int t0 = clk(); while (clk() - t0 < E1_CLK) {} pf_slice(warp == 6 ? 1 : 5); }
  const int rank = bid & 1, cl = bid >> 1;
  const int q7 = ((cl - 36) * 37) >> 8;
  const int P = cl < 4 ? 0 : cl < 36 ? (cl - 4) & 7 : cl - 35 - 7 * q7;
  const int g = cl < 4 ? 4 + cl : cl < 36 ? (cl - 4) >> 3 : 4 + q7;
  const int mt = 2 * P + rank, cid = mt * 8 + g;
  const bool ffn1 = g >= 5;
  const int fj = ffn1 ? mt * 3 + g - 5 : (P * 5 + g) * 2 + rank;
  const int ord = ((g >> 2) ^ P) & 1;
  auto ks_of = [&](int it) { return !ORDX || ord == 0 || it == 0 ? it : it <= 5 ? it + 4 : it - 5; };
  auto load_w = [&](int ks, uint32_t a, uint32_t bar, int kk) {
    tma_3d_mc(a + 16384 + kk * 6144, &tm.w, bar, g * 80, ks * 64 + kk * 16, 0);
    tma_3d_mc(a + 40960 + kk * 1536, &tm.wr, bar, g * 80 + 64, ks * 64 + kk * 16, 0);
  };
  if (warp == 0 && elect()) {
    mbar_expect_tx(bar_half, SLOT - 15360);
    tma_3d(sb + 2 * SLOT, &tm.x, bar_half, 0, P * 128, rank);
    mbar_expect_tx(bar_full + 16, 15360);
  }
  asm volatile("barrier.cluster.wait.aligned;" ::: "memory");
  if (warp == 0) {
    if (elect()) { load_w(0, sb + 2 * SLOT, bar_half, rank); load_w(0, sb + 2 * SLOT, bar_full + 16, rank + 2); }
    asm volatile("bar.arrive 4, 64;" ::: "memory");
  }

  if (warp >= 8) {
    asm volatile("setmaxnreg.dec.sync.aligned.u32 %0;" :: "n"(REG_P));
#define TS_T 0
    if (warp == 8) {
      TS(8);
      bar_sync(4, 64);
      if (elect()) {
        TS(10);
        int fjn = 0;
#pragma unroll 1
        for (int it = 1; it < 17; it++) {
          const int s = (it + 2) & 3;
          const uint32_t full = bar_full + 8 * s, a = sb + s * SLOT;
          if (it >= 13) { mbar_wait(bar_oc + 8 * (it - 13), 0); mbar_wait(bar_oc + 56 + 8 * (it - 13), 0); }
          else if (it >= 4) mbar_wait(bar_empty + 8 * s, ((it >> 2) - 1) & 1);
          else if (it >= THR) mbar_wait(bar_full + 8 * ((it - THR + 2) & 3), 0);
          if (it < 10) {
            const int ks = ks_of(it);
            const uint32_t half = it < NSPLIT ? bar_half + 8 * it : full;
            if (it < NSPLIT) mbar_expect_tx(half, SLOT - 15360);
            mbar_expect_tx(full, it < NSPLIT ? 15360 : SLOT);
            tma_3d(a, &tm.x, half, ks * 64, P * 128, rank);
            load_w(ks, a, half, rank);
            load_w(ks, a, full, rank + 2);
            TS(12 + it);
            if ((unsigned)(it - RST_IT) < 2u) {
              mbar_wait(bar_rst, 0);
              asm volatile("cp.async.bulk.global.shared::cta.bulk_group [%0], [%1], %2;\ncp.async.bulk.commit_group;"
                           :: "l"(it == RST_IT ? (uint4*)(g_own + cid) : (uint4*)&g_x + cid * GLOB_PER_CTA), "r"(sb + OFF_CS),
                              "r"(it == RST_IT ? (int)sizeof(Own) : GLOB_PER_CTA * 16) : "memory");
            }
            if (it == RST_IT + 2) { asm volatile("cp.async.bulk.wait_group 0;" ::: "memory"); mbar_arrive(bar_tag); }
          } else if (it < 13) {
            const int g0 = 3 * (it - 10), g1 = min(g0 + 3, 8);
            mbar_expect_tx(full, (g1 - g0) * 12800);
#pragma unroll 1
            for (int gp = g0 + ((g0 ^ rank) & 1); gp < g1; gp += 2) {
              tma_3d_mc(sb + gp * 15360, &tm.wo, full, 0, gp * 80, g * 2);
              tma_3d_mc(sb + gp * 15360 + 10240, &tm.wor, full, 512 + g * 16, gp * 80, 0);
            }
          }
          if (it == 4) mbar_expect_tx(bar_ffn, NO_LATE == 2 ? 0 : NO_LATE ? (ffn1 ? 32768 : F_MAX * 2048) : ffn1 ? 81920 : 24576);
          if ((NO_LATE && it >= 13) || NO_LATE == 2) continue;
          const int j1 = ffn1 ? (it >= 13 ? min(2 * it - 21, 10) : min(max(it - F_IT + 1, 0), 4)) : (it >= 13 ? (it == 16 ? 12 : min(F_MAX + (it - 12) * F_LATE, 12)) : min(max((it - F_IT + 1) * F_PER, 0), F_MAX));
#pragma unroll 1
          for (; fjn < j1; fjn++) {
            const int j = fjn < 4 ? fjn + 6 : fjn - 4;
            if (ffn1) tma_3d(sb + (j < 6 ? 0 : OFF_W2 - 49152) + j * 8192, j < 5 ? &tm.gate : &tm.up, bar_ffn, fj * 32, (j < 5 ? j : j - 5) * 128, 0);
            else tma_3d(sb + OFF_W2 + fjn * 2048, &tm.down, bar_ffn, fj * 8, fjn * 128, 0);
          }
        }
        TS(11);
      }
#undef TS_T
#define TS_T 64
    } else if (warp >= 12) {
      const int l7 = lane & 7, j = warp - 12, ch = min((P >> 1) * 4 + rank * 2 + (j >> 1), 14);
      const uint32_t sxo = ((g & 3) * 32 + j * 8 + l7) * 128 + (((lane >> 3) ^ l7) * 16);
      const uint32_t swo = ch < 12 ? 16384 + (lane >> 4) * 6144 + (ch >> 2) * 2048 + (lane & 15) * 128 + ((((ch & 3) * 2 + (j & 1)) ^ l7) * 16)
                                   : 40960 + (lane >> 4) * 1536 + (ch - 12) * 512 + (lane & 15) * 32 + (((j & 1) ^ (l7 >> 2)) * 16);
      float ps = 0.f, pq = 0.f, pq1 = 0.f, pc = 0.f;
      uint32_t tag = 0;
      char* const pp = hold((lane & 1) ? (char*)&g_own[cid].cs[j * 8 + (lane >> 2)] : (char*)&g_own[cid].st1[j * 8 + (lane >> 2)]);
#pragma unroll 1
      for (int it = ord; it < ord + 5; it++) {
        const int sl = (it + 2) & 3;
        if (it == ord + 4) { mbar_wait(bar_tag, 0); tag = __float_as_uint(lds32f(sb + OFF_WR + 324)); }
        if (it < NSPLIT) mbar_wait(bar_half + 8 * it, 0);
        mbar_wait(bar_full + 8 * sl, (it >> 2) & 1);
        TS(it);
        const uint32_t a = sb + sl * SLOT;
        const uint4 v0 = ldsm4(a + sxo), v1 = ldsm4((a + sxo) ^ 64), w0 = ldsm4t(a + swo), w1 = ldsm4t(a + swo + (ch < 12 ? 12288 : 3072));
        if (lane + (int)((v0.x & v1.x & w0.x & w1.x) == 0x7fc17fc1u && (v0.x | v1.x) == 0u) < 2) mbar_arrive_cta(bar_empty + 8 * sl, lane);
        const uint32_t vv[8] = {v0.x, v0.y, v0.z, v0.w, v1.x, v1.y, v1.z, v1.w}, ww[8] = {w0.x, w0.y, w0.z, w0.w, w1.x, w1.y, w1.z, w1.w};
#pragma unroll
        for (int i = 0; i < 8; i++) {
          const float d = bf_lo(vv[i]), e = bf_hi(vv[i]);
          ps += d + e; pq = fmaf(d, d, pq); pq1 = fmaf(e, e, pq1); pc += bf_lo(ww[i]) + bf_hi(ww[i]);
        }
      }
      pq += pq1;
      ps += shx(ps, 1); pq += shx(pq, 1); pc += shx(pc, 1);
      ps += shx(ps, 2); pq += shx(pq, 2); pc += shx(pc, 2);
      if ((lane & 3) == 0) stg_pkt(pp, __float_as_uint(ps), __float_as_uint(pq), tag, 0u);
      if ((lane & 3) == 1) stg_rlx64(pp, __float_as_uint(pc), tag);
      asm volatile("bar.arrive 2, 192;" ::: "memory");
      if (warp == 12) {
        const uint4* const hp = hold(&g_own[max(cid - 16, 0)].halo[0][lane]);
        mbar_wait(bar_aux, 0);
        mbar_wait(bar_go, 0);
        uint4 v[5] = {};
        int guard = SPIN_MAX;
        if (P > 0) {
          do {
#pragma unroll
            for (int i = 0; i < 5; i++) v[i] = ldg_pkt(hp + 32 * i);
          } while (anyw(v[0].x == SENT || v[1].x == SENT || v[2].x == SENT || v[3].x == SENT || v[4].x == SENT) && --guard > 0);
        }
#pragma unroll
        for (int i = 0; i < 5; i++) *(uint4*)(smem + OFF_O + 10240 + i * 512 + lane * 16) = v[i];
        mbar_arrive(bar_kv);
      }
#undef TS_T
#define TS_T 32
    } else if (warp < 11) {
      const int l7 = lane & 7, hk = lane >> 4;
      if (warp == 10 && elect()) {
#pragma unroll 1
        for (int i = 0; i < 36; i++) mbar_init(bar_o + 8 * i, i < 14 || i == 30 ? 1 : i < 34 ? 4 : 128);
      }
      {
        const int t0 = clk();
#pragma unroll 1
        for (int i = PF_FIRST; i < 6; i++) {
          while (clk() - t0 < PF_T0 + (i - PF_FIRST) * PF_CLK) __nanosleep(20);
          pf_slice(warp == 9 ? min(i, 4) : i + 4);
        }
      }
      mbar_wait(bar_tag, 0);
      const uint32_t tag = __float_as_uint(lds32f(sb + OFF_WR + 324));
      bar_sync(2, 192);
      TS(0);
      int guard = SPIN_MAX;
      if (warp == 9) {
        const uint4* sp = &g_own[mt * 8].st1[lane];
        const uint4* hp = &g_own[max(mt - 2, 0) * 8 + 3].st1[24 + l7];
        uint4 a[5], b[5];
        bool bad;
        do {
          __nanosleep(AUX_NS);
          bad = false;
#pragma unroll
          for (int i = 0; i < 5; i++) {
            const uint4* q = i < 4 ? sp + i * (sizeof(Own) / 16) : hp;
            a[i] = ldg_pkt(q); b[i] = ldg_pkt(q + 4 * sizeof(Own) / 16);
          }
#pragma unroll
          for (int i = 0; i < 5; i++) bad |= a[i].z != tag || b[i].z != tag;
        } while (anyw(bad) && --guard);
        TS(1);
#pragma unroll
        for (int i = 0; i < 5; i++) {
          const float m = (__uint_as_float(a[i].x) + __uint_as_float(b[i].x)) * (1.f / 640.f);
          const float rs = rsq(fmaxf(fmaf(-m, m, (__uint_as_float(a[i].y) + __uint_as_float(b[i].y)) * (1.f / 640.f)), 0.f) + 1e-5f);
          ((float*)(smem + OFF_RS))[i < 4 ? 8 + lane + 32 * i : l7] = rs;
          const uint32_t mh = pack_bf16(-m, -m);
          const float ml = -m - bf_lo(mh);
          if (i < 4) ((uint2*)(smem + OFF_MN))[lane + 32 * i] = make_uint2(mh, pack_bf16(ml, ml));
        }
      } else {
        const uint4* cp = (const uint4*)g_own[hk * 8 + g].cs + (lane & 15);
        uint4 a[4], b[4];
        bool bad;
        do {
          __nanosleep(AUX_NS);
          bad = false;
#pragma unroll
          for (int i = 0; i < 4; i++) { a[i] = ldg_pkt(cp + i * 32 * sizeof(Own) / 16); b[i] = ldg_pkt(cp + (i * 32 + 16) * sizeof(Own) / 16); }
#pragma unroll
          for (int i = 0; i < 4; i++) bad |= a[i].y != tag || a[i].w != tag || b[i].y != tag || b[i].w != tag;
        } while (anyw(bad) && --guard);
#pragma unroll
        for (int i = 0; i < 4; i++)
          if (i < 3 || lane < 24) {
            const float c0 = __uint_as_float(a[i].x) + __uint_as_float(b[i].x), c1 = __uint_as_float(a[i].z) + __uint_as_float(b[i].z);
            const uint32_t hi = pack_bf16(c0, c1), w0 = pack_bf16(c0, c0 - bf_lo(hi)), w1 = pack_bf16(c1, c1 - bf_hi(hi));
            uint4* const d = (uint4*)(smem + OFF_CS) + 2 * (lane + 32 * i);
            d[0] = make_uint4(w0, w0, 0, 0); d[1] = make_uint4(w1, w1, 0, 0);
          }
        asm volatile("fence.proxy.async.shared::cta;" ::: "memory");
      }
      mbar_arrive(bar_aux);
      TS(2);
      const int fo = warp - 9, wq = fo ? 1 - LEAD : LEAD;
      const uint4* const fp = hold(g_own[mt * 8 + wq * 4].cnt);
      const char* src = hold((const char*)g_o[mt * 2 + wq]);
      if (elect()) {
        const uint32_t bo = bar_o + fo * 56;
#pragma unroll
        for (int i = 0; i < 7; i++) mbar_expect_tx(bo + 8 * i, 10240);
        mbar_wait(bar_st + 8 * fo, 0);
        if (ONE_RED == 1) {
          asm volatile("red.relaxed.gpu.global.add.u32 [%0], 4;" :: "l"(fp) : "memory");
          if (CNT_NS) __nanosleep(CNT_NS);
        }
        uint32_t cv = 0;
        if (ONE_RED == 2) { asm volatile("atom.relaxed.gpu.global.add.u32 %0, [%1], 4;" : "=r"(cv) : "l"(fp) : "memory"); cv += 4; }
        while (cv != 32u && --guard > 0) cv = ldg_rlx32(fp);
        asm volatile("fence.proxy.async.global;" ::: "memory");
        TS(6);
#pragma unroll
        for (int i = 0; i < 7; i++) {
          if (fo || i == 6) mbar_wait(bo + 64 + 8 * i, 0);
          else if (i == FW) mbar_arrive(bar_go - 8);
          if (!fo && i == 4) mbar_wait(bar_st + 8, 0);
          if (i == g) src += 10240;
          asm volatile("cp.async.bulk.shared::cluster.global.mbarrier::complete_tx::bytes [%0], [%1], 10240, [%2];"
                       :: "r"(sb + OFF_O + ((i + 2) % 6) * 10240 + fo * (i == 3 ? -51200 : 10240)), "l"(src + i * 10240), "r"(bo + 8 * i) : "memory");
        }
      }
#undef TS_T
#define TS_T 96
    } else {
      if ((sb & 0x3FFFF) != D0 * 16) __trap();
#pragma unroll 1
      for (int i = lane; i < 232; i += 32) { const uint32_t f = i < 208 ? SENT : 0u; ((uint4*)(smem + OFF_CS))[i] = make_uint4(f, f, f, f); }
      asm volatile("fence.proxy.async.shared::cta;" ::: "memory");
      if (elect()) mbar_arrive(bar_rst);
      mbar_wait(bar_full + 8 * ((HK_IT + 2) & 3), 0);
      TS(4);
      const uint32_t epoch = ldg_rlx32(g_epoch + cid) + 1;
      uint32_t wv[10];
#pragma unroll
      for (int i = 0; i < 10; i++) wv[i] = __ldg((const uint32_t*)w_r + lane + 32 * i);
      float s = 0.f;
#pragma unroll
      for (int i = 0; i < 10; i++) {
        s += bf_lo(wv[i]) + bf_hi(wv[i]);
        const unsigned u = i < 8 ? lane + 32 * (i - g) : lane + 32 * (i - 7) - g * 8;
        if (i < 8 ? u < 32u : u - 32u < 8u) *(float2*)(smem + OFF_WR + ((u & 3) * 10 + (u >> 2)) * 8) = make_float2(bf_lo(wv[i]), bf_hi(wv[i]));
      }
#pragma unroll
      for (int m = 1; m < 32; m <<= 1) s += shx(s, m);
      *(float2*)(smem + OFF_WR + 320) = make_float2(s, __uint_as_float(epoch * 0x9E3779B8u));
      g_epoch[cid] = epoch;
      TS(3);
      TS(5);
      if (elect()) mbar_arrive(bar_tag);
#pragma unroll 1
      for (int i = 0; i < 14; i++) {
        const int m = (i + 2) >> 2, n = m == 0 ? 50 : 120, t = (m == 0 ? i : (i + 2) & 3) * 32 + lane;
        const char* b = (const char*)(m == 0 ? wo : m == 1 ? w_up : m == 2 ? w_down : w_gate);
        if (t < n) pf_l2(b + (bid * n + t) * 128);
        __nanosleep(PFW_NS);
      }
      const uint4* const kp = hold(g_own[1].cnt);
      const uint4* const cb = hold(&g_x.cand[0][lane >> 2][lane & 3]);
      bar_sync(3, 64);
      uint4 k;
      uint32_t have = SENT;
      int guard = SPIN_MAX;
      while (true) {
        k = ldg_pkt(kp);
        if (ffn1) {
          while (k.x != have && --guard > 0) {
            const uint32_t tk = 2047u - (k.x & 2047u), want = k.x;
            const uint4* q = cb + ((tk >> 8) * 16 + (tk & 1) * 8 + ((tk >> 5) & 7)) * 192;
            const uint4 c0 = ldg_pkt(q), c1 = ldg_pkt(q + 4); const uint2 c2 = ldg_rlx64(q + 8);
            k = ldg_pkt(kp);
            *(uint4*)(smem + OFF_HN + lane * 16) = c0; *(uint4*)(smem + OFF_HN + 512 + lane * 16) = c1; *(uint2*)(smem + OFF_HN + 1024 + lane * 16) = c2;
            have = anyw(c0.x == SENT || c1.x == SENT || c2.x == SENT) ? SENT : want;
          }
        } else if (KEY_NS && k.z != 128u) __nanosleep(KEY_NS);
        if (k.z == 128u || --guard <= 0) break;
      }
      *(uint2*)(smem + OFF_WR + 336) = make_uint2(k.x, k.y);
      mbar_arrive(bar_win);
      TS(7);
    }
#undef TS_T
  } else {
#define TS_T 0
    asm volatile("setmaxnreg.inc.sync.aligned.u32 %0;" :: "n"(REG_C));
    const int wg = warp >> 2, w4 = warp & 3, r = lane >> 2, c = lane & 3;
    float acc[120];
    uint4 xr[5] = {};
    const uint32_t xa = pin(sb + (warp * 16 + (lane & 15)) * 128 + ((lane >> 4) ^ (lane & 7)) * 16);
    const int fol = wg != LEAD;
    const bool first = (P == 0) && (warp == 0);
    const uint32_t kvs = sb + OFF_O + fol * 10240 + w4 * 2560 + lane * 16;
    uint4* const kvd = hold(warp == 7 ? &g_own[cid].halo[0][lane] : (uint4*)(smem + (warp == 3 ? OFF_O + lane * 16 : kvs - sb + 2560)));
    uint4* const odst = hold(&g_o[mt * 2 + wg][g][w4 * 160]);
    uint4* const ocnt = hold(g_own[mt * 8 + wg * 4].cnt);
    uint32_t m0 = 0, m1 = 0;
    const uint32_t mna = pin(sb + OFF_MN + (warp * 16 + r) * 8 + c * 4);
    const int itx = ord == 0 || g == 0 ? g : g < 5 ? g + 5 : g - 4, ity = (ord ? 4 : 8) + (g >> 2);
    uint32_t rel;
    asm volatile("mapa.shared::cluster.u32 %0, %1, %2;" : "=r"(rel) : "r"(bar_empty), "r"(tid & 1));
    const uint32_t xa1 = pin(xa ^ 32), xa2 = pin(xa ^ 64), xa3 = pin(xa ^ 96), xb = pin(xa ^ ((g & 3) * 32));
    const uint32_t da0 = wg * 512;
    const bool rel2 = lane < 2, rel6 = lane < 2 + 2 * (warp & 1);
    const uint32_t zero = (uint32_t)(uintptr_t)x & 8u;
    mbar_wait(bar_half, 0);
    TS(13);
    wgmma_fence();
#pragma unroll
    for (int it = 0; it < 10; it++) {
      const int s = (it + 2) & 3;
      if (it == 9 && fol) bar_sync(10, 256);
#pragma unroll
      for (int kk = 0; kk < 4; kk++) {
        if (kk == 2 && it > 0) {
          wgmma_commit();
          wgmma_wait<1>();
          const uint32_t ra = ((xr[0].x ^ xr[1].x ^ xr[2].x ^ xr[3].x ^ xr[4].x) & zero) | rel;
          if (it == 1 ? (ord ? rel6 : rel2) : it == 6 ? (ord ? rel2 : rel6) : it < 6 ? rel2 : rel6)
            asm volatile("mbarrier.arrive.shared::cluster.b64 _, [%0];" :: "r"(ra + 8 * ((it + 1) & 3)) : "memory");
        }
        if (kk == 2) {
          ldsm4_if(xr[0], xa, s * SLOT, it == itx); ldsm4_if(xr[1], xa1, s * SLOT, it == itx);
          ldsm4_if(xr[2], xa2, s * SLOT, it == itx); ldsm4_if(xr[3], xa3, s * SLOT, it == itx);
          if ((it & 6) == 4 || it >= 8) ldsm4_if(xr[4], xb, s * SLOT, it == ity);
        }
        if (kk == AK && it == 9) {
          mbar_wait(bar_aux, 0);
          TS(3);
          if (c < 2) { m0 = __float_as_uint(lds32f(mna)); m1 = __float_as_uint(lds32f(mna + 64)); }
          if (!fol) bar_sync(11, 256);
        }
        if (kk == 2 && it < NSPLIT) mbar_wait(bar_full + 8 * s, 0);
        const uint64_t da = mk64(da0 + (D0 + s * (SLOT >> 4) + kk * 2 + (1 << 16)), 0x40000040u);
        wgmma_n48hi_ss(acc, da, mk64(D0 + s * (SLOT >> 4) + 2560 + kk * 96 + (32 << 16), 0xC0000010u), (it | kk) != 0);
        wgmma_n192lo_ss(acc, da, mk64(D0 + s * (SLOT >> 4) + 1024 + kk * 384 + (128 << 16), 0x40000040u), (it | kk) != 0);
      }
      wgmma_commit();
      if (it == 8 && fol) asm volatile("bar.arrive 11, 256;" ::: "memory");
      if (it < 9) {
        if (it + 1 < NSPLIT) mbar_wait(bar_half + 8 * (it + 1), 0);
        else mbar_wait(bar_full + 8 * ((it + 3) & 3), ((it + 1) >> 2) & 1);
        if (it < 8) TS(14 + it);
      }
    }
    {
      const uint64_t dc = make_desc(D0 * 16 + OFF_CS, 0, 128, 0);
      wgmma_fence();
      wgmma_n48hi_rk(acc, m0, m1, 0u, 0u, dc + 192, 1);
      wgmma_n192lo_rk(acc, m0, m1, 0u, 0u, dc, 1);
      wgmma_commit();
      if (!fol) asm volatile("bar.arrive 10, 256;" ::: "memory");
    }
    const uint32_t stb = sb + OFF_RS + warp * 64;
    const float rlo = lds32f(stb + (8 + r) * 4), rhi = lds32f(stb + (16 + r) * 4);
    wgmma_wait<0>();
#pragma unroll
    for (int i = 0; i < 120; i++) asm volatile("" : "+f"(acc[i]) :: "memory");
    if (fol && lane == 0) mbar_arrive(bar_go);
    TS(2);
    uint32_t Qlo[10], Qhi[10], Klo[10], Khi[10], Vlo[10], Vhi[10];
#pragma unroll
    for (int t = 0; t < 10; t++) {
      const int k = KT(t), v = VT(t);
      Khi[t] = pack_bf16(acc[4 * k + 2], acc[4 * k + 3]);
      Vhi[t] = pack_bf16(acc[4 * v + 2] * rhi, acc[4 * v + 3] * rhi);
    }
    st_pkt(kvd, Khi[0], Khi[1], Khi[3], Khi[4]);
    st_pkt(kvd + 32, Khi[5], Khi[6], Khi[8], Khi[9]);
    st_pkt(kvd + 64, Khi[2], Khi[7], Vhi[0], Vhi[1]);
    st_pkt(kvd + 96, Vhi[2], Vhi[3], Vhi[4], Vhi[5]);
    st_pkt(kvd + 128, Vhi[6], Vhi[7], Vhi[8], Vhi[9]);
    if (warp < 7) mbar_arrive(bar_kv + ((warp + 1) >> 2) * 8);
    mbar_wait(bar_aux, 0);
#pragma unroll
    for (int t = 0; t < 10; t++) {
      const int q = QT(t), k = KT(t), v = VT(t);
      Vhi[t] = movm(Vhi[t]);
      Klo[t] = pack_bf16(acc[4 * k], acc[4 * k + 1]);
      Vlo[t] = movm(pack_bf16(acc[4 * v] * rlo, acc[4 * v + 1] * rlo));
      Qlo[t] = pack_bf16(acc[4 * q], acc[4 * q + 1]);
      Qhi[t] = pack_bf16(acc[4 * q + 2], acc[4 * q + 3]);
    }
    const bool in0 = 2 * c <= r, in1 = 2 * c + 1 <= r;
    const uint32_t mL = (in0 ? 0xffffu : 0u) | (in1 ? 0xffff0000u : 0u);
    const float qs = 0.22360679774997896f * 1.4426950408889634f;
    const uint32_t kb0 = stb + (2 * c + (in0 ? 8 : 0)) * 4, kb1 = stb + (2 * c + 1 + (in1 ? 8 : 0)) * 4;
    const float scl0 = lds32f(kb0) * rlo * qs, scl1 = lds32f(kb1) * rlo * qs;
    const float sch0 = lds32f(kb0 + 32) * rhi * qs, sch1 = lds32f(kb1 + 32) * rhi * qs;
    const float bias0 = (first && !in0) ? -INFINITY : 0.f, bias1 = (first && !in1) ? -INFINITY : 0.f;
    const int slot = mt * 8 + warp;
    int guard = SPIN_MAX;
    uint4 pv[5];
    const bool cA = c < 2, nA = r < 4;
    TS(0);
    mbar_wait(bar_go + fol * 8, 0);
    TS(23);
    uint32_t qe[4][2];
    float sl0[4], sl1[4], th0[4], th1[4];
#pragma unroll
    for (int hd = 0; hd < 4; hd++) {
      const int ta = 5 * (hd >> 1) + 3 * (hd & 1), ts = 5 * (hd >> 1) + 2;
      const bool mine = (hd & 1) ? !cA : cA;
      qe[hd][0] = mine ? Qlo[ts] : 0u; qe[hd][1] = mine ? Qhi[ts] : 0u;
      float sl[4], sh[4];
      mma_k24(sl, Qlo[ta], Qhi[ta], Qlo[ta + 1], Qhi[ta + 1], Klo[ta], Klo[ta + 1], qe[hd][0], qe[hd][1], Klo[ts]);
      mma_k24(sh, Qlo[ta], Qhi[ta], Qlo[ta + 1], Qhi[ta + 1], Khi[ta], Khi[ta + 1], qe[hd][0], qe[hd][1], Khi[ts]);
      th0[hd] = (in0 ? sh[2] : sl[2]) * sch0; th1[hd] = (in1 ? sh[3] : sl[3]) * sch1;
      float mh = fmaxf(th0[hd], th1[hd]);
      mh = fmaxf(mh, shx(mh, 1)); mh = fmaxf(mh, shx(mh, 2));
      th0[hd] -= mh; th1[hd] -= mh;
      sl0[hd] = sl[0]; sl1[hd] = sl[1];
    }
    mbar_wait(bar_kv + wg * 8, 0);
    TS(4);
#pragma unroll
    for (int j = 0; j < 5; j++) pv[j] = lds128(kvs + 512 * j);
    const uint32_t Kp[10] = {pv[0].x, pv[0].y, pv[2].x, pv[0].z, pv[0].w, pv[1].x, pv[1].y, pv[2].y, pv[1].z, pv[1].w};
    const uint32_t Vp[10] = {movm(pv[2].z), movm(pv[2].w), movm(pv[3].x), movm(pv[3].y), movm(pv[3].z), movm(pv[3].w), movm(pv[4].x), movm(pv[4].y), movm(pv[4].z), movm(pv[4].w)};
    const uint32_t ONES = 0x3f803f80u;
    uint32_t of[20];
#pragma unroll
    for (int hp = 0; hp < 2; hp++) {
      float o[6][4];
#pragma unroll
      for (int hh = 0; hh < 2; hh++) {
        const int hd = 2 * hp + hh, ta = 5 * hp + 3 * hh, ts = 5 * hp + 2;
        float sp[4];
        mma_k24(sp, Qlo[ta], Qhi[ta], Qlo[ta + 1], Qhi[ta + 1], Kp[ta], Kp[ta + 1], qe[hd][0], qe[hd][1], Kp[ts]);
        const float tl0 = fmaf(in0 ? sl0[hd] : sp[0], scl0, bias0), tl1 = fmaf(in1 ? sl1[hd] : sp[1], scl1, bias1);
        float ml = fmaxf(tl0, tl1);
        ml = fmaxf(ml, shx(ml, 1)); ml = fmaxf(ml, shx(ml, 2));
        if (HOLD == 1 && hd == 3 && !fol && lane == 0) mbar_arrive(bar_go + 8);
        const uint32_t Pl = pack_bf16(ex2(tl0 - ml), ex2(tl1 - ml)), Ph = pack_bf16(ex2(th0[hd]), ex2(th1[hd]));
        const uint32_t a0 = Pl & mL, a1 = Ph & ~mL, a3 = Ph & mL, ap = Pl & ~mL;
        const bool vm = hh == 0 ? nA : !nA;
        mma_k24(o[3 * hh], a0, a1, 0u, a3, Vlo[ta], Vhi[ta], ap, 0u, Vp[ta]);
        mma_k24(o[3 * hh + 1], a0, a1, 0u, a3, Vlo[ta + 1], Vhi[ta + 1], ap, 0u, Vp[ta + 1]);
        mma_k24(o[3 * hh + 2], a0, a1, 0u, a3, vm ? Vlo[ts] : ONES, vm ? Vhi[ts] : ONES, ap, 0u, vm ? Vp[ts] : ONES);
      }
      const float il = rcp(cA ? o[5][0] : o[2][0]), ih = rcp(cA ? o[5][2] : o[2][2]);
      const float jl = shx(il, 2), jh = shx(ih, 2);
      const float al = cA ? jl : il, ah = cA ? jh : ih, bl = cA ? il : jl, bh = cA ? ih : jh;
      const int t0 = 5 * hp;
      of[2 * t0]     = pack_bf16(o[0][0] * al, o[0][1] * al); of[2 * t0 + 1] = pack_bf16(o[0][2] * ah, o[0][3] * ah);
      of[2 * t0 + 2] = pack_bf16(o[1][0] * al, o[1][1] * al); of[2 * t0 + 3] = pack_bf16(o[1][2] * ah, o[1][3] * ah);
      of[2 * t0 + 4] = pack_bf16((cA ? o[2][0] : o[5][0]) * jl, (cA ? o[2][1] : o[5][1]) * jl);
      of[2 * t0 + 5] = pack_bf16((cA ? o[2][2] : o[5][2]) * jh, (cA ? o[2][3] : o[5][3]) * jh);
      of[2 * t0 + 6] = pack_bf16(o[3][0] * bl, o[3][1] * bl); of[2 * t0 + 7] = pack_bf16(o[3][2] * bh, o[3][3] * bh);
      of[2 * t0 + 8] = pack_bf16(o[4][0] * bl, o[4][1] * bl); of[2 * t0 + 9] = pack_bf16(o[4][2] * bh, o[4][3] * bh);
    }
    {
      const uint32_t os = sb + OFF_O + (fol ? 0 : 20480) + w4 * 2560, oa = os + ((lane >> 3) & 1) * 1280 + (lane >> 4) * 128 + (lane & 7) * 16;
#pragma unroll
      for (int s = 0; s < 5; s++) {
        stsm4(oa + s * 256, of[4 * s], of[4 * s + 1], of[4 * s + 2], of[4 * s + 3]);
        if (s == 0 && (fol || HOLD == 2) && lane == 0) mbar_arrive(bar_go + 8 + 8 * fol);
      }
      asm volatile("fence.proxy.async.shared::cta;" ::: "memory");
      __syncwarp();
      if (FW < 5 && fol) mbar_wait(bar_go - 8, 0);
      if (elect()) {
        asm volatile("cp.async.bulk.global.shared::cta.bulk_group [%0], [%1], 2560;\ncp.async.bulk.commit_group;" :: "l"(odst), "r"(os) : "memory");
      }
    }
    TS(5);
    float h[40];
#pragma unroll
    for (int s = 0; s < 5; s++) {
      const uint4 v = xr[s];
      h[8 * s] = bf_lo(v.x); h[8 * s + 1] = bf_hi(v.x); h[8 * s + 2] = bf_lo(v.y); h[8 * s + 3] = bf_hi(v.y);
      h[8 * s + 4] = bf_lo(v.z); h[8 * s + 5] = bf_hi(v.z); h[8 * s + 6] = bf_lo(v.w); h[8 * s + 7] = bf_hi(v.w);
    }
    if (elect()) {
      asm volatile("cp.async.bulk.wait_group 0;" ::: "memory");
      if (!ONE_RED) asm volatile("red.relaxed.gpu.global.add.u32 [%0], 1;" :: "l"(ocnt) : "memory");
      mbar_arrive(bar_st + 8 * fol);
    }
    __syncwarp();
    TS(22);
    mbar_wait(bar_full, 0); mbar_wait(bar_full + 8, 0); mbar_wait(bar_full + 16, 1);
    mbar_wait(bar_go + 16, 0);
    const uint64_t dwo = make_desc(D0 * 16, 5120, 512, 2);
    wgmma_fence();
#pragma unroll
    for (int s = 0; s < 5; s++) wgmma_n80_rs(h, of[4 * s], of[4 * s + 1], of[4 * s + 2], of[4 * s + 3], dwo + g * 960 + s * 64, 1);
    wgmma_commit();
    TS(6);
    const uint32_t bo = bar_o + fol * 56;
#pragma unroll
    for (int i = 0; i < 7; i++) {
      mbar_wait(bo + 8 * i, 0);
      if (i == 0) TS(1);
      const uint32_t da = D0 + OFF_O / 16 + (8 << 16) + ((i + 2) % 6) * 640 + fol * (i == 3 ? -3200 : 640), db = D0 + (320 << 16) + (i >= g ? i + 1 : i) * 960;
      wgmma_fence();
#pragma unroll
      for (int s = 0; s < 5; s++) wgmma_n80_ss(h, mk64(da + s * 16, 80u), mk64(db + s * 64, 0x80000020u), 1);
      wgmma_commit();
      wgmma_wait<1>();
      if (lane == 0 && i > 0) mbar_arrive(bo + 104 + 8 * i);
    }
    const bool odd = c & 1;
    float wr[20];
#pragma unroll
    for (int j = 0; j < 5; j++) {
      const uint4 v = lds128(sb + OFF_WR + c * 80 + j * 16);
      wr[4 * j] = __uint_as_float(v.x); wr[4 * j + 1] = __uint_as_float(v.y); wr[4 * j + 2] = __uint_as_float(v.z); wr[4 * j + 3] = __uint_as_float(v.w);
    }
    const float wsum = lds32f(sb + OFF_WR + 320);
    uint4* const sp = hold(&g_own[slot].st2[r + (odd ? 8 : 0)]);
    uint4* const cdp = hold(&g_x.cand[slot][g][0]);
    const int tok0 = P * 256 + 32 * warp + rank;
    wgmma_wait<0>();
#pragma unroll
    for (int i = 0; i < 40; i++) asm volatile("" : "+f"(h[i]) :: "memory");
    if (lane == 0) mbar_arrive(bo + 160);
    TS(7);
    float mean, rstd, rr;
    {
      float l1 = 0.f, l2 = 0.f, l3 = 0.f, h1 = 0.f, h2 = 0.f, h3 = 0.f;
#pragma unroll
      for (int j = 0; j < 10; j++) {
        l1 += h[4 * j] + h[4 * j + 1]; h1 += h[4 * j + 2] + h[4 * j + 3];
        l2 = fmaf(h[4 * j], h[4 * j], l2); l2 = fmaf(h[4 * j + 1], h[4 * j + 1], l2);
        h2 = fmaf(h[4 * j + 2], h[4 * j + 2], h2); h2 = fmaf(h[4 * j + 3], h[4 * j + 3], h2);
        l3 = fmaf(h[4 * j], wr[2 * j], l3); l3 = fmaf(h[4 * j + 1], wr[2 * j + 1], l3);
        h3 = fmaf(h[4 * j + 2], wr[2 * j], h3); h3 = fmaf(h[4 * j + 3], wr[2 * j + 1], h3);
      }
      float s1 = (odd ? h1 : l1) + shx(odd ? l1 : h1, 1), s2 = (odd ? h2 : l2) + shx(odd ? l2 : h2, 1), s3 = (odd ? h3 : l3) + shx(odd ? l3 : h3, 1);
      s1 += shx(s1, 2); s2 += shx(s2, 2); s3 += shx(s3, 2);
      if (cA) asm volatile("red.relaxed.gpu.global.add.v4.f32 [%0], {%1, %2, %3, %4};" :: "l"(sp), "f"(s1), "f"(s2), "f"(s3), "f"(1.f) : "memory");
      uint4 p0;
      do { p0 = ldg_pkt(sp); } while (anyw(p0.w != 0x41000000u) && --guard > 0);
      mean = __uint_as_float(p0.x) * (1.f / 640.f);
      rstd = rsq(fmaxf(fmaf(-mean, mean, __uint_as_float(p0.y) * (1.f / 640.f)), 0.f) + 1e-5f);
      rr = fmaf(-mean, wsum, __uint_as_float(p0.z)) * rstd;
    }
    TS(8);
    const uint32_t kk = ord_key(rr), kmax = __reduce_max_sync(0xffffffffu, kk);
    const int L = __ffs(__ballot_sync(0xffffffffu, kk == kmax)) - 1;
    const int crow = (L >> 2) + 8 * (L & 1);
    if (warp == g) {
      if (elect()) {
        asm volatile("red.relaxed.gpu.global.max.u64 [%0], %1;" :: "l"(g_own[1].cnt), "l"(((uint64_t)kmax << 32) | (uint32_t)(2047 - tok0 - 2 * crow)) : "memory");
        asm volatile("red.relaxed.gpu.global.add.u32 [%0], 1;" :: "l"(&g_own[1].cnt[0].z) : "memory");
      }
      asm volatile("bar.arrive 3, 64;" ::: "memory");
    }
    const uint32_t stg = sb + (fol ? OFF_O : g * 15360) + w4 * 2560;
    uint4 held;
    {
      const float om = shx(mean, 1), os = shx(rstd, 1);
      const float rl = odd ? os : rstd, rh = odd ? rstd : os;
      const float bl = -(odd ? om : mean) * rl, bh = -(odd ? mean : om) * rh, al = 1.f + rl, ah = 1.f + rh;
      if ((L >> 2) == r) {
        const bool chi = L & 1;
        const float rc = chi ? rh : rl, bc = chi ? bh : bl;
        uint32_t n[10];
#pragma unroll
        for (int j = 0; j < 10; j++) n[j] = pack_bf16(fmaf(chi ? h[4 * j + 2] : h[4 * j], rc, bc), fmaf(chi ? h[4 * j + 3] : h[4 * j + 1], rc, bc));
        uint4* d = cdp + c;
        stg_pkt(d, n[0], n[1], n[2], n[3]); stg_pkt(d + 4, n[4], n[5], n[6], n[7]); stg_rlx64(d + 8, n[8], n[9]);
      }
      mbar_wait(bar_oc + 56, 0);
      const uint32_t fa = stg + (lane & 15) * 160 + (lane >> 4) * 16;
#pragma unroll
      for (int s = 0; s < 5; s++)
        stsm4(fa + s * 32, pack_bf16(fmaf(h[8 * s], al, bl), fmaf(h[8 * s + 1], al, bl)), pack_bf16(fmaf(h[8 * s + 2], ah, bh), fmaf(h[8 * s + 3], ah, bh)),
              pack_bf16(fmaf(h[8 * s + 4], al, bl), fmaf(h[8 * s + 5], al, bl)), pack_bf16(fmaf(h[8 * s + 6], ah, bh), fmaf(h[8 * s + 7], ah, bh)));
      __syncwarp();
      held = lds128(stg + crow * 160 + min(lane, 9) * 16);
      if (lane < 10) stg_pkt(cdp + 12 + lane, held.x, held.y, held.z, held.w);
    }
    TS(9);
    mbar_wait(bar_ffn, 0);
    const uint32_t red = sb + OFF_RED;
    if (ffn1) {
      uint4 w1[4][5];
      {
        const int k = (lane & 7) + (lane >> 4) * 8;
        const uint32_t a1 = sb + k * 64, sw = ((lane >> 3) & 1) ^ ((lane >> 1) & 3);
#pragma unroll
        for (int s = 0; s < 5; s++)
#pragma unroll
          for (int u = 0; u < 4; u++)
            w1[u][s] = ldsm4t(a1 + (s < 4 ? warp * 4096 + s * 1024 : 32768 + warp * 1024) + (u >> 1) * (40960 + (s == 4 || warp >= 2 ? OFF_W2 - 49152 : 0)) + ((sw ^ (2 * (u & 1))) * 16));
      }
      uint32_t* const ap = hold(g_x.act + fj * 16 + (lane >> 1));
      mbar_wait(bar_win, 0);
      const uint32_t hp = sb + OFF_HN + (warp * 4 + c) * 16;
      const uint4 c0 = lds128(hp), c1 = lds128(hp + 512), c2 = lds128(hp + 1024);
      TS(10);
      float a[4][4];
#pragma unroll
      for (int u = 0; u < 4; u++) {
        a[u][0] = a[u][1] = a[u][2] = a[u][3] = 0.f;
        mma_acc(a[u], w1[u][0], c0.x, c0.y); mma_acc(a[u], w1[u][1], c0.z, c0.w); mma_acc(a[u], w1[u][2], c1.x, c1.y);
        mma_acc(a[u], w1[u][3], c1.z, c1.w); mma_acc(a[u], w1[u][4], c2.x, c2.y);
      }
      asm volatile("st.shared.v2.f32 [%0], {%1, %2};" :: "r"(red + (warp * 32 + c * 8 + r) * 8),
                   "f"(cA ? (odd ? a[0][2] : a[0][0]) : (odd ? a[1][2] : a[1][0])), "f"(cA ? (odd ? a[2][2] : a[2][0]) : (odd ? a[3][2] : a[3][0])) : "memory");
      bar_sync(1, 256);
      if (warp == 0) {
        float2 t[8];
#pragma unroll
        for (int i = 0; i < 8; i++) t[i] = lds64f(red + (i * 32 + lane) * 8);
        const float s = ((t[0].x + t[1].x) + (t[2].x + t[3].x)) + ((t[4].x + t[5].x) + (t[6].x + t[7].x));
        const float u = ((t[0].y + t[1].y) + (t[2].y + t[3].y)) + ((t[4].y + t[5].y) + (t[6].y + t[7].y));
        const float av = s * u * rcp(1.f + ex2(-1.4426950408889634f * s));
        const float an = shx(av, 1);
        if (!odd) stg_rlx32(ap, pack_bf16(av, an));
      }
      bar_sync(1, 256);
      TS(11);
    }
    if (OUT_LATE) mbar_wait(bar_win, 0);
    char* const ob2 = (char*)(out + tok0 * 640 + g * 64);
    const int remo = 896 - 96 * g;
#pragma unroll
    for (int s = 0; s < 5; s++) {
      const int row = s < 4 ? 4 * s + (lane >> 3) : lane >> 1, pc = s < 4 ? lane & 7 : 8 + (lane & 1);
      const uint4 v = lds128(stg + row * 160 + pc * 16);
      if (row != crow) stg128(ob2 + row * 2560 + pc * 16 + (s < 4 ? 0 : remo), v);
    }
    mbar_wait(bar_win, 0);
    uint4 win = lds128(sb + OFF_WR + 336);
    win.z = win.y; win.y = 2047u - (win.x & 2047u); win.x = (win.y >> 8) * 16 + (win.y & 1) * 8 + ((win.y >> 5) & 7);
    if (win.x != slot && lane < 10) stg128(ob2 + crow * 2560 + lane * 16 + (lane < 8 ? 0 : remo), held);
    if (!ffn1) {
      TS(10);
      uint4 w2[6];
      const uint32_t a2 = sb + OFF_W2 + (warp * 192 + 8 * (((lane >> 3) & 1) * 4 + ((lane & 7) >> 1)) + 2 * (lane >> 4) + (lane & 1)) * 16;
#pragma unroll
      for (int s = 0; s < 6; s++) w2[s] = ldsm4t(a2 + (s >> 1) * 1024 + (s & 1) * 64);
      const uint4* p = (const uint4*)(g_x.act + warp * 96) + (r & 1) * 4 + c;
      const uint32_t* pb = (const uint32_t*)&g_x.cand[win.x][fj < 64 ? fj >> 3 : (fj - 64) >> 1][fj < 64 ? 12 + (fj & 7) : 20 + (fj & 1)] + c;
      uint32_t* const op = hold((uint32_t*)(out + win.y * 640 + fj * 8) + c);
      const float sg = rcp(1.f + ex2(-1.4426950408889634f * __uint_as_float(win.z ^ ((uint32_t)((int32_t)~win.z >> 31) | 0x80000000u))));
      uint4 c0, c1, c2; uint32_t bw;
      if (ACT_NS) __nanosleep(ACT_NS);
      do {
        c0 = ldg_pkt(p); c1 = ldg_pkt(p + 8); c2 = ldg_pkt(p + 16); bw = ldg_rlx32(pb);
      } while (anyw(max(max(max(max(c0.x, c0.y), max(c0.z, c0.w)), max(max(c1.x, c1.y), max(c1.z, c1.w))), max(max(max(c2.x, c2.y), max(c2.z, c2.w)), bw)) == SENT) && --guard > 0);
      TS(11);
      float a[4] = {0.f, 0.f, 0.f, 0.f}, b[4] = {0.f, 0.f, 0.f, 0.f}, d[4] = {0.f, 0.f, 0.f, 0.f};
      mma_acc(a, w2[0], c0.x, c0.y); mma_acc(b, w2[2], c1.x, c1.y); mma_acc(d, w2[4], c2.x, c2.y);
      mma_acc(a, w2[1], c0.z, c0.w); mma_acc(b, w2[3], c1.z, c1.w); mma_acc(d, w2[5], c2.z, c2.w);
      if (c == 0) sts32f(red + (warp * 8 + r) * 4, ((a[0] + a[3]) + (b[0] + b[3])) + (d[0] + d[3]));
      bar_sync(1, 256);
      if (tid < 4) {
        float2 t[8];
#pragma unroll
        for (int i = 0; i < 8; i++) t[i] = lds64f(red + (i * 4 + tid) * 8);
        const float y0 = ((t[0].x + t[1].x) + (t[2].x + t[3].x)) + ((t[4].x + t[5].x) + (t[6].x + t[7].x));
        const float y1 = ((t[0].y + t[1].y) + (t[2].y + t[3].y)) + ((t[4].y + t[5].y) + (t[6].y + t[7].y));
        *op = pack_bf16(fmaf(y0, sg, bf_lo(bw)), fmaf(y1, sg, bf_hi(bw)));
      }
    }
    TS(12);
#undef TS_T
  }
}

typedef CUresult (*EncodeFn)(CUtensorMap*, CUtensorMapDataType, cuuint32_t, void*, const cuuint64_t*, const cuuint64_t*, const cuuint32_t*,
                             const cuuint32_t*, CUtensorMapInterleave, CUtensorMapSwizzle, CUtensorMapL2promotion, CUtensorMapFloatOOBfill);

void make_map(EncodeFn enc, CUtensorMap* m, const void* base, const cuuint64_t* dims, const cuuint64_t* strides, const cuuint32_t* box,
              CUtensorMapSwizzle swz) {
  const cuuint32_t es[3] = {1, 1, 1};
  enc(m, CU_TENSOR_MAP_DATA_TYPE_BFLOAT16, 3, (void*)base, dims, strides, box, es, CU_TENSOR_MAP_INTERLEAVE_NONE, swz,
      CU_TENSOR_MAP_L2_PROMOTION_L2_128B, CU_TENSOR_MAP_FLOAT_OOB_FILL_NONE);
}

}

extern "C" void kernel_launch(void* const* d_in, const int* in_sizes, int n_in, void* d_out, int out_size) {
  const __nv_bfloat16* x = (const __nv_bfloat16*)d_in[0];
  const __nv_bfloat16* wqkv = (const __nv_bfloat16*)d_in[1];
  const __nv_bfloat16* wo = (const __nv_bfloat16*)d_in[2];
  void* fn = nullptr;
  cudaDriverEntryPointQueryResult st;
  cudaGetDriverEntryPoint("cuTensorMapEncodeTiled", &fn, cudaEnableDefault, &st);
  EncodeFn enc = (EncodeFn)fn;
  void* scp = nullptr;
  cudaGetSymbolAddress(&scp, g_scratch);
  Maps tm;
  { const cuuint64_t d[3] = {640, 1024, 2}, s[2] = {2560, 1280}; const cuuint32_t b[3] = {64, 128, 1}; make_map(enc, &tm.x, x, d, s, b, CU_TENSOR_MAP_SWIZZLE_128B); }
  { const cuuint64_t d[3] = {640, 640, 3}, s[2] = {3840, 1280}; const cuuint32_t b[3] = {64, 16, 3}; make_map(enc, &tm.w, wqkv, d, s, b, CU_TENSOR_MAP_SWIZZLE_128B); }
  { const cuuint64_t d[3] = {640, 640, 3}, s[2] = {3840, 1280}; const cuuint32_t b[3] = {16, 16, 3}; make_map(enc, &tm.wr, wqkv, d, s, b, CU_TENSOR_MAP_SWIZZLE_32B); }
  { const cuuint64_t d[3] = {32, 640, 20}, s[2] = {1280, 64}; const cuuint32_t b[3] = {32, 80, 2}; make_map(enc, &tm.wo, wo, d, s, b, CU_TENSOR_MAP_SWIZZLE_64B); }
  { const cuuint64_t d[3] = {640, 640, 1}, s[2] = {1280, 819200}; const cuuint32_t b[3] = {16, 80, 1}; make_map(enc, &tm.wor, wo, d, s, b, CU_TENSOR_MAP_SWIZZLE_64B); }
  { const cuuint64_t d[3] = {1536, 640, 1}, s[2] = {3072, 1966080}; const cuuint32_t b[3] = {32, 128, 1};
    make_map(enc, &tm.gate, d_in[5], d, s, b, CU_TENSOR_MAP_SWIZZLE_64B); make_map(enc, &tm.up, d_in[6], d, s, b, CU_TENSOR_MAP_SWIZZLE_64B); }
  { const cuuint64_t d[3] = {640, 1536, 1}, s[2] = {1280, 1966080}; const cuuint32_t b[3] = {8, 128, 1}; make_map(enc, &tm.down, d_in[7], d, s, b, CU_TENSOR_MAP_SWIZZLE_NONE); }
  cudaFuncSetAttribute(fused_kernel, cudaFuncAttributeMaxDynamicSharedMemorySize, SMEM_BYTES);
  fused_kernel<<<128, 512, SMEM_BYTES, cudaStreamPerThread>>>(x, wqkv, wo, (const __nv_bfloat16*)d_in[4], (const __nv_bfloat16*)d_in[5],
                                                              (const __nv_bfloat16*)d_in[6], (const __nv_bfloat16*)d_in[7], (__nv_bfloat16*)d_out, (Scratch*)scp, tm);
}
```

```cpp
#include <cuda_runtime.h>
#include <cuda_bf16.h>
#include <cuda.h>
#include <stdint.h>

#define PFW_NS 50
#define ACT_NS 100
#define OUT_LATE 0
#define REG_P 72
#define REG_C 184
#define AUX_NS 50
#define LEAD 1
#define RST_IT 4
#define ORDX 1
#define THR 2
#define PF_FIRST 3
#define PF_T0 1500
#define PF_CLK 500
#define HK_IT 1
#define F_IT 9
#define F_PER 2
#define F_MAX 8
#define HOLD 2
#define F_LATE 12
#define HALO_NS 0
#define AK 3
#define KEY_NS 60
#define FW 5
#define ONE_RED 2
#define CNT_NS 0
#define NO_LATE 0
#define EARLY 1
#define PREW 9
#define NSPLIT 3
#define E1_CLK 0
#define THR_END 4
#define S1_CLK 0
#define GX 0
#define ODDS 1
#define BOUNDED 0
#define TLIGHT 0

namespace {

constexpr int SLOT    = 49152;
constexpr int OFF_O   = 122880;
constexpr int OFF_W2  = 4 * SLOT;
constexpr int OFF_CS  = OFF_W2 + 24576;
constexpr int OFF_RS  = OFF_CS + 3840;
constexpr int OFF_MN  = OFF_RS + 576;
constexpr int OFF_WR  = OFF_MN + 1024;
constexpr int OFF_RED = OFF_CS;
constexpr int OFF_HN  = OFF_CS + 2048;
constexpr int OFF_PT  = OFF_WR + 352;
constexpr int OFF_BAR = OFF_PT + 768;
constexpr int SMEM_BYTES = OFF_BAR + 424 + 384;
constexpr uint32_t D0 = 1024 >> 4;
constexpr uint32_t SENT = 0xFFFFFFFFu;
constexpr int SPIN_MAX = 1 << 20;

struct Glob {
  uint4 cand[128][8][24];
  uint32_t act[768];
  uint32_t pad[256];
};
constexpr int GLOB_PER_CTA = sizeof(Glob) / 16 / 128;
static_assert(GLOB_PER_CTA * 128 * 16 == sizeof(Glob), "glob size");
struct Own {
  uint4 halo[5][32];
  uint4 st1[32];
  uint2 cs[32];
  uint4 st2[16];
  uint4 cnt[8];
};
struct Scratch {
  Glob x;
  Own own[128];
  uint4 o[32][8][640];
  uint32_t epoch[128];
};
__device__ __align__(128) Scratch g_scratch;
#define g_x (sc->x)
#define g_own (sc->own)
#define g_o (sc->o)
#define g_epoch (sc->epoch)
#define TS(i)

__device__ __forceinline__ void mbar_init(uint32_t bar, uint32_t cnt) { asm volatile("mbarrier.init.shared::cta.b64 [%0], %1;" :: "r"(bar), "r"(cnt) : "memory"); }
__device__ __forceinline__ void mbar_expect_tx(uint32_t bar, uint32_t bytes) { asm volatile("mbarrier.arrive.expect_tx.shared::cta.b64 _, [%0], %1;" :: "r"(bar), "r"(bytes) : "memory"); }
__device__ __forceinline__ void mbar_arrive(uint32_t bar) { asm volatile("mbarrier.arrive.shared::cta.b64 _, [%0];" :: "r"(bar) : "memory"); }
__device__ __forceinline__ void mbar_arrive_cta(uint32_t bar, uint32_t cta) {
  asm volatile("{\n.reg .b32 ra;\nmapa.shared::cluster.u32 ra, %0, %1;\nmbarrier.arrive.shared::cluster.b64 _, [ra];\n}\n" :: "r"(bar), "r"(cta) : "memory");
}
__device__ __forceinline__ void mbar_wait(uint32_t bar, uint32_t parity) {
  asm volatile("{\n.reg .pred p;\nW:\nmbarrier.try_wait.parity.shared::cta.b64 p, [%0], %1;\n@!p bra.uni W;\n}\n" :: "r"(bar), "r"(parity) : "memory");
}
__device__ __forceinline__ void tma_3d(uint32_t dst, const void* tm, uint32_t bar, int c0, int c1, int c2) {
  asm volatile("cp.async.bulk.tensor.3d.shared::cluster.global.mbarrier::complete_tx::bytes [%0], [%1, {%3, %4, %5}], [%2];" :: "r"(dst), "l"(tm), "r"(bar), "r"(c0), "r"(c1), "r"(c2) : "memory");
}
__device__ __forceinline__ void tma_3d_mc(uint32_t dst, const void* tm, uint32_t bar, int c0, int c1, int c2) {
  asm volatile("cp.async.bulk.tensor.3d.shared::cluster.global.mbarrier::complete_tx::bytes.multicast::cluster [%0], [%1, {%3, %4, %5}], [%2], %6;" :: "r"(dst), "l"(tm), "r"(bar), "r"(c0), "r"(c1), "r"(c2), "h"((uint16_t)3) : "memory");
}
__device__ __forceinline__ void wgmma_fence() { asm volatile("wgmma.fence.sync.aligned;" ::: "memory"); }
__device__ __forceinline__ void wgmma_commit() { asm volatile("wgmma.commit_group.sync.aligned;" ::: "memory"); }
template <int N> __device__ __forceinline__ void wgmma_wait() { asm volatile("wgmma.wait_group.sync.aligned %0;" :: "n"(N) : "memory"); }
__device__ __forceinline__ uint64_t make_desc(uint32_t addr, uint32_t lbo, uint32_t sbo, uint32_t swz) {
  return (uint64_t)(((addr & 0x3FFFF) >> 4) | ((lbo >> 4) << 16)) | ((uint64_t)((sbo >> 4) | (swz << 30)) << 32);
}
__device__ __forceinline__ void bar_sync(int id, int n) { asm volatile("bar.sync %0, %1;" :: "r"(id), "r"(n) : "memory"); }
__device__ __forceinline__ void st_pkt(void* p, uint32_t a, uint32_t b, uint32_t c, uint32_t d) {
  asm volatile("st.relaxed.gpu.v4.u32 [%0], {%1, %2, %3, %4};" :: "l"(p), "r"(a), "r"(b), "r"(c), "r"(d) : "memory");
}
__device__ __forceinline__ uint4 ldg_pkt(const void* p) {
  uint4 v; asm volatile("ld.relaxed.gpu.global.v4.u32 {%0, %1, %2, %3}, [%4];" : "=r"(v.x), "=r"(v.y), "=r"(v.z), "=r"(v.w) : "l"(p) : "memory"); return v;
}
__device__ __forceinline__ void stg_pkt(void* p, uint32_t a, uint32_t b, uint32_t c, uint32_t d) {
  asm volatile("st.relaxed.gpu.global.v4.u32 [%0], {%1, %2, %3, %4};" :: "l"(p), "r"(a), "r"(b), "r"(c), "r"(d) : "memory");
}
__device__ __forceinline__ uint32_t ldg_rlx32(const void* p) { uint32_t v; asm volatile("ld.relaxed.gpu.global.u32 %0, [%1];" : "=r"(v) : "l"(p) : "memory"); return v; }
__device__ __forceinline__ uint2 ldg_rlx64(const void* p) { uint2 v; asm volatile("ld.relaxed.gpu.global.v2.u32 {%0, %1}, [%2];" : "=r"(v.x), "=r"(v.y) : "l"(p) : "memory"); return v; }
__device__ __forceinline__ void stg128(void* p, const uint4& v) { asm volatile("st.global.v4.u32 [%0], {%1, %2, %3, %4};" :: "l"(p), "r"(v.x), "r"(v.y), "r"(v.z), "r"(v.w) : "memory"); }
__device__ __forceinline__ uint32_t pin(uint32_t v) { asm volatile("" : "+r"(v)); return v; }
__device__ __forceinline__ uint64_t mk64(uint32_t lo, uint32_t hi) { return ((uint64_t)hi << 32) | lo; }
template <class T> __device__ __forceinline__ T* hold(T* p) { return (T*)__shfl_sync(0xffffffffu, (unsigned long long)p, threadIdx.x & 31); }
template <class T> __device__ __forceinline__ T* pin(T* p) { asm volatile("" : "+l"(p)); return p; }
__device__ __forceinline__ void stg_rlx32(void* p, uint32_t v) { asm volatile("st.relaxed.gpu.global.u32 [%0], %1;" :: "l"(p), "r"(v) : "memory"); }
__device__ __forceinline__ void stg_rlx64(void* p, uint32_t a, uint32_t b) { asm volatile("st.relaxed.gpu.global.v2.u32 [%0], {%1, %2};" :: "l"(p), "r"(a), "r"(b) : "memory"); }
__device__ __forceinline__ uint4 ldsm4(uint32_t a) { uint4 v; asm volatile("ldmatrix.sync.aligned.m8n8.x4.shared.b16 {%0, %1, %2, %3}, [%4];" : "=r"(v.x), "=r"(v.y), "=r"(v.z), "=r"(v.w) : "r"(a) : "memory"); return v; }
__device__ __forceinline__ void ldsm4_if(uint4& v, uint32_t a, int off, bool p) {
  asm volatile("{\n.reg .pred q;\nsetp.ne.u32 q, %5, 0;\n@q ldmatrix.sync.aligned.m8n8.x4.shared.b16 {%0, %1, %2, %3}, [%4];\n}\n"
               : "+r"(v.x), "+r"(v.y), "+r"(v.z), "+r"(v.w) : "r"(a + off), "r"((int)p) : "memory");
}
__device__ __forceinline__ uint4 ldsm4t(uint32_t a) { uint4 v; asm volatile("ldmatrix.sync.aligned.m8n8.x4.trans.shared.b16 {%0, %1, %2, %3}, [%4];" : "=r"(v.x), "=r"(v.y), "=r"(v.z), "=r"(v.w) : "r"(a) : "memory"); return v; }
__device__ __forceinline__ void stsm4(uint32_t a, uint32_t x, uint32_t y, uint32_t z, uint32_t w) { asm volatile("stmatrix.sync.aligned.m8n8.x4.shared.b16 [%0], {%1, %2, %3, %4};" :: "r"(a), "r"(x), "r"(y), "r"(z), "r"(w) : "memory"); }
__device__ __forceinline__ void mma_acc(float (&c)[4], const uint4& a, uint32_t b0, uint32_t b1) {
  asm("mma.sync.aligned.m16n8k16.row.col.f32.bf16.bf16.f32 {%0,%1,%2,%3}, {%4,%5,%6,%7}, {%8,%9}, {%0,%1,%2,%3};"
      : "+f"(c[0]), "+f"(c[1]), "+f"(c[2]), "+f"(c[3]) : "r"(a.x), "r"(a.y), "r"(a.z), "r"(a.w), "r"(b0), "r"(b1));
}
__device__ __forceinline__ uint4 lds128(uint32_t a) { uint4 v; asm volatile("ld.shared.v4.u32 {%0, %1, %2, %3}, [%4];" : "=r"(v.x), "=r"(v.y), "=r"(v.z), "=r"(v.w) : "r"(a) : "memory"); return v; }
__device__ __forceinline__ float2 lds64f(uint32_t a) { float2 v; asm volatile("ld.shared.v2.f32 {%0, %1}, [%2];" : "=f"(v.x), "=f"(v.y) : "r"(a)); return v; }
__device__ __forceinline__ float lds32f(uint32_t a) { float v; asm volatile("ld.shared.f32 %0, [%1];" : "=f"(v) : "r"(a)); return v; }
__device__ __forceinline__ void sts32f(uint32_t a, float v) { asm volatile("st.shared.f32 [%0], %1;" :: "r"(a), "f"(v) : "memory"); }
__device__ __forceinline__ uint32_t pack_bf16(float lo, float hi) { uint32_t r; asm("cvt.rn.bf16x2.f32 %0, %1, %2;" : "=r"(r) : "f"(hi), "f"(lo)); return r; }
__device__ __forceinline__ float bf_lo(uint32_t v) { return __uint_as_float(v << 16); }
__device__ __forceinline__ float bf_hi(uint32_t v) { return __uint_as_float(v & 0xffff0000u); }
__device__ __forceinline__ uint32_t movm(uint32_t a) { uint32_t d; asm("movmatrix.sync.aligned.m8n8.trans.b16 %0, %1;" : "=r"(d) : "r"(a)); return d; }
__device__ __forceinline__ float ex2(float x) { float y; asm("ex2.approx.ftz.f32 %0, %1;" : "=f"(y) : "f"(x)); return y; }
__device__ __forceinline__ float rsq(float x) { float y; asm("rsqrt.approx.ftz.f32 %0, %1;" : "=f"(y) : "f"(x)); return y; }
__device__ __forceinline__ float rcp(float x) { float y; asm("rcp.approx.ftz.f32 %0, %1;" : "=f"(y) : "f"(x)); return y; }
__device__ __forceinline__ bool elect() { uint32_t p; asm volatile("{\n.reg .pred q;\nelect.sync _|q, 0xffffffff;\nselp.u32 %0, 1, 0, q;\n}\n" : "=r"(p)); return p; }
__device__ __forceinline__ int clk() { int c; asm volatile("mov.u32 %0, %%clock;" : "=r"(c) :: "memory"); return c; }
__device__ __forceinline__ void pf_l2(const void* p) { asm volatile("prefetch.global.L2 [%0];" :: "l"(p)); }
__device__ __forceinline__ bool anyw(bool p) { return __any_sync(0xffffffffu, p); }
__device__ __forceinline__ float shx(float v, int m) { return __shfl_xor_sync(0xffffffffu, v, m); }
__device__ __forceinline__ void mma_k24(float (&c)[4], uint32_t a0, uint32_t a1, uint32_t a2, uint32_t a3, uint32_t b0, uint32_t b1,
                                        uint32_t e0, uint32_t e1, uint32_t f0) {
  asm("mma.sync.aligned.m16n8k16.row.col.f32.bf16.bf16.f32 {%0,%1,%2,%3}, {%4,%5,%6,%7}, {%8,%9}, {%10,%10,%10,%10};"
      : "=f"(c[0]), "=f"(c[1]), "=f"(c[2]), "=f"(c[3]) : "r"(a0), "r"(a1), "r"(a2), "r"(a3), "r"(b0), "r"(b1), "f"(0.f));
  asm("mma.sync.aligned.m16n8k8.row.col.f32.bf16.bf16.f32 {%0,%1,%2,%3}, {%4,%5}, {%6}, {%0,%1,%2,%3};"
      : "+f"(c[0]), "+f"(c[1]), "+f"(c[2]), "+f"(c[3]) : "r"(e0), "r"(e1), "r"(f0));
}
__device__ __forceinline__ uint32_t ord_key(float r) { uint32_t u = __float_as_uint(r); return u ^ ((uint32_t)((int32_t)u >> 31) | 0x80000000u); }

__device__ __forceinline__ void wgmma_n64hi_ss(float (&d)[120], uint64_t da, uint64_t db, int scale_d) {
  asm volatile("{\n.reg .pred p;\nsetp.ne.b32 p, %34, 0;\n"
    "wgmma.mma_async.sync.aligned.m64n64k16.f32.bf16.bf16 "
    "{%0, %1, %2, %3, %4, %5, %6, %7, %8, %9, %10, %11, %12, %13, %14, %15, "
    "%16, %17, %18, %19, %20, %21, %22, %23, %24, %25, %26, %27, %28, %29, %30, %31}, "
    "%32, %33, p, 1, 1, 0, 1;\n}\n"
    : "+f"(d[88]), "+f"(d[89]), "+f"(d[90]), "+f"(d[91]), "+f"(d[92]), "+f"(d[93]), "+f"(d[94]), "+f"(d[95]),
      "+f"(d[96]), "+f"(d[97]), "+f"(d[98]), "+f"(d[99]), "+f"(d[100]), "+f"(d[101]), "+f"(d[102]), "+f"(d[103]),
      "+f"(d[104]), "+f"(d[105]), "+f"(d[106]), "+f"(d[107]), "+f"(d[108]), "+f"(d[109]), "+f"(d[110]), "+f"(d[111]),
      "+f"(d[112]), "+f"(d[113]), "+f"(d[114]), "+f"(d[115]), "+f"(d[116]), "+f"(d[117]), "+f"(d[118]), "+f"(d[119])
    : "l"(da), "l"(db), "r"(scale_d));
}
__device__ __forceinline__ void wgmma_n176lo_ss(float (&d)[120], uint64_t da, uint64_t db, int scale_d) {
  asm volatile("{\n.reg .pred p;\nsetp.ne.b32 p, %90, 0;\n"
    "wgmma.mma_async.sync.aligned.m64n176k16.f32.bf16.bf16 "
    "{%0, %1, %2, %3, %4, %5, %6, %7, %8, %9, %10, %11, %12, %13, %14, %15, "
    "%16, %17, %18, %19, %20, %21, %22, %23, %24, %25, %26, %27, %28, %29, %30, %31, "
    "%32, %33, %34, %35, %36, %37, %38, %39, %40, %41, %42, %43, %44, %45, %46, %47, "
    "%48, %49, %50, %51, %52, %53, %54, %55, %56, %57, %58, %59, %60, %61, %62, %63, "
    "%64, %65, %66, %67, %68, %69, %70, %71, %72, %73, %74, %75, %76, %77, %78, %79, "
    "%80, %81, %82, %83, %84, %85, %86, %87}, "
    "%88, %89, p, 1, 1, 0, 1;\n}\n"
    : "+f"(d[0]), "+f"(d[1]), "+f"(d[2]), "+f"(d[3]), "+f"(d[4]), "+f"(d[5]), "+f"(d[6]), "+f"(d[7]),
      "+f"(d[8]), "+f"(d[9]), "+f"(d[10]), "+f"(d[11]), "+f"(d[12]), "+f"(d[13]), "+f"(d[14]), "+f"(d[15]),
      "+f"(d[16]), "+f"(d[17]), "+f"(d[18]), "+f"(d[19]), "+f"(d[20]), "+f"(d[21]), "+f"(d[22]), "+f"(d[23]),
      "+f"(d[24]), "+f"(d[25]), "+f"(d[26]), "+f"(d[27]), "+f"(d[28]), "+f"(d[29]), "+f"(d[30]), "+f"(d[31]),
      "+f"(d[32]), "+f"(d[33]), "+f"(d[34]), "+f"(d[35]), "+f"(d[36]), "+f"(d[37]), "+f"(d[38]), "+f"(d[39]),
      "+f"(d[40]), "+f"(d[41]), "+f"(d[42]), "+f"(d[43]), "+f"(d[44]), "+f"(d[45]), "+f"(d[46]), "+f"(d[47]),
      "+f"(d[48]), "+f"(d[49]), "+f"(d[50]), "+f"(d[51]), "+f"(d[52]), "+f"(d[53]), "+f"(d[54]), "+f"(d[55]),
      "+f"(d[56]), "+f"(d[57]), "+f"(d[58]), "+f"(d[59]), "+f"(d[60]), "+f"(d[61]), "+f"(d[62]), "+f"(d[63]),
      "+f"(d[64]), "+f"(d[65]), "+f"(d[66]), "+f"(d[67]), "+f"(d[68]), "+f"(d[69]), "+f"(d[70]), "+f"(d[71]),
      "+f"(d[72]), "+f"(d[73]), "+f"(d[74]), "+f"(d[75]), "+f"(d[76]), "+f"(d[77]), "+f"(d[78]), "+f"(d[79]),
      "+f"(d[80]), "+f"(d[81]), "+f"(d[82]), "+f"(d[83]), "+f"(d[84]), "+f"(d[85]), "+f"(d[86]), "+f"(d[87])
    : "l"(da), "l"(db), "r"(scale_d));
}
__device__ __forceinline__ void wgmma_n64hi_rk(float (&d)[120], uint32_t a0, uint32_t a1, uint32_t a2, uint32_t a3, uint64_t db, int scale_d) {
  asm volatile("{\n.reg .pred p;\nsetp.ne.b32 p, %37, 0;\n"
    "wgmma.mma_async.sync.aligned.m64n64k16.f32.bf16.bf16 "
    "{%0, %1, %2, %3, %4, %5, %6, %7, %8, %9, %10, %11, %12, %13, %14, %15, "
    "%16, %17, %18, %19, %20, %21, %22, %23, %24, %25, %26, %27, %28, %29, %30, %31}, "
    "{%32, %33, %34, %35}, %36, p, 1, 1, 0;\n}\n"
    : "+f"(d[88]), "+f"(d[89]), "+f"(d[90]), "+f"(d[91]), "+f"(d[92]), "+f"(d[93]), "+f"(d[94]), "+f"(d[95]),
      "+f"(d[96]), "+f"(d[97]), "+f"(d[98]), "+f"(d[99]), "+f"(d[100]), "+f"(d[101]), "+f"(d[102]), "+f"(d[103]),
      "+f"(d[104]), "+f"(d[105]), "+f"(d[106]), "+f"(d[107]), "+f"(d[108]), "+f"(d[109]), "+f"(d[110]), "+f"(d[111]),
      "+f"(d[112]), "+f"(d[113]), "+f"(d[114]), "+f"(d[115]), "+f"(d[116]), "+f"(d[117]), "+f"(d[118]), "+f"(d[119])
    : "r"(a0), "r"(a1), "r"(a2), "r"(a3), "l"(db), "r"(scale_d));
}
__device__ __forceinline__ void wgmma_n176lo_rk(float (&d)[120], uint32_t a0, uint32_t a1, uint32_t a2, uint32_t a3, uint64_t db, int scale_d) {
  asm volatile("{\n.reg .pred p;\nsetp.ne.b32 p, %93, 0;\n"
    "wgmma.mma_async.sync.aligned.m64n176k16.f32.bf16.bf16 "
    "{%0, %1, %2, %3, %4, %5, %6, %7, %8, %9, %10, %11, %12, %13, %14, %15, "
    "%16, %17, %18, %19, %20, %21, %22, %23, %24, %25, %26, %27, %28, %29, %30, %31, "
    "%32, %33, %34, %35, %36, %37, %38, %39, %40, %41, %42, %43, %44, %45, %46, %47, "
    "%48, %49, %50, %51, %52, %53, %54, %55, %56, %57, %58, %59, %60, %61, %62, %63, "
    "%64, %65, %66, %67, %68, %69, %70, %71, %72, %73, %74, %75, %76, %77, %78, %79, "
    "%80, %81, %82, %83, %84, %85, %86, %87}, "
    "{%88, %89, %90, %91}, %92, p, 1, 1, 0;\n}\n"
    : "+f"(d[0]), "+f"(d[1]), "+f"(d[2]), "+f"(d[3]), "+f"(d[4]), "+f"(d[5]), "+f"(d[6]), "+f"(d[7]),
      "+f"(d[8]), "+f"(d[9]), "+f"(d[10]), "+f"(d[11]), "+f"(d[12]), "+f"(d[13]), "+f"(d[14]), "+f"(d[15]),
      "+f"(d[16]), "+f"(d[17]), "+f"(d[18]), "+f"(d[19]), "+f"(d[20]), "+f"(d[21]), "+f"(d[22]), "+f"(d[23]),
      "+f"(d[24]), "+f"(d[25]), "+f"(d[26]), "+f"(d[27]), "+f"(d[28]), "+f"(d[29]), "+f"(d[30]), "+f"(d[31]),
      "+f"(d[32]), "+f"(d[33]), "+f"(d[34]), "+f"(d[35]), "+f"(d[36]), "+f"(d[37]), "+f"(d[38]), "+f"(d[39]),
      "+f"(d[40]), "+f"(d[41]), "+f"(d[42]), "+f"(d[43]), "+f"(d[44]), "+f"(d[45]), "+f"(d[46]), "+f"(d[47]),
      "+f"(d[48]), "+f"(d[49]), "+f"(d[50]), "+f"(d[51]), "+f"(d[52]), "+f"(d[53]), "+f"(d[54]), "+f"(d[55]),
      "+f"(d[56]), "+f"(d[57]), "+f"(d[58]), "+f"(d[59]), "+f"(d[60]), "+f"(d[61]), "+f"(d[62]), "+f"(d[63]),
      "+f"(d[64]), "+f"(d[65]), "+f"(d[66]), "+f"(d[67]), "+f"(d[68]), "+f"(d[69]), "+f"(d[70]), "+f"(d[71]),
      "+f"(d[72]), "+f"(d[73]), "+f"(d[74]), "+f"(d[75]), "+f"(d[76]), "+f"(d[77]), "+f"(d[78]), "+f"(d[79]),
      "+f"(d[80]), "+f"(d[81]), "+f"(d[82]), "+f"(d[83]), "+f"(d[84]), "+f"(d[85]), "+f"(d[86]), "+f"(d[87])
    : "r"(a0), "r"(a1), "r"(a2), "r"(a3), "l"(db), "r"(scale_d));
}
__device__ __forceinline__ void wgmma_n80_rs(float (&d)[40], uint32_t a0, uint32_t a1, uint32_t a2, uint32_t a3, uint64_t db, int scale_d) {
  asm volatile("{\n.reg .pred p;\nsetp.ne.b32 p, %45, 0;\n"
    "wgmma.mma_async.sync.aligned.m64n80k16.f32.bf16.bf16 "
    "{%0, %1, %2, %3, %4, %5, %6, %7, %8, %9, %10, %11, %12, %13, %14, %15, "
    "%16, %17, %18, %19, %20, %21, %22, %23, %24, %25, %26, %27, %28, %29, %30, %31, "
    "%32, %33, %34, %35, %36, %37, %38, %39}, "
    "{%40, %41, %42, %43}, %44, p, 1, 1, 1;\n}\n"
    : "+f"(d[0]), "+f"(d[1]), "+f"(d[2]), "+f"(d[3]), "+f"(d[4]), "+f"(d[5]), "+f"(d[6]), "+f"(d[7]),
      "+f"(d[8]), "+f"(d[9]), "+f"(d[10]), "+f"(d[11]), "+f"(d[12]), "+f"(d[13]), "+f"(d[14]), "+f"(d[15]),
      "+f"(d[16]), "+f"(d[17]), "+f"(d[18]), "+f"(d[19]), "+f"(d[20]), "+f"(d[21]), "+f"(d[22]), "+f"(d[23]),
      "+f"(d[24]), "+f"(d[25]), "+f"(d[26]), "+f"(d[27]), "+f"(d[28]), "+f"(d[29]), "+f"(d[30]), "+f"(d[31]),
      "+f"(d[32]), "+f"(d[33]), "+f"(d[34]), "+f"(d[35]), "+f"(d[36]), "+f"(d[37]), "+f"(d[38]), "+f"(d[39])
    : "r"(a0), "r"(a1), "r"(a2), "r"(a3), "l"(db), "r"(scale_d));
}
__device__ __forceinline__ void wgmma_n80_ss(float (&d)[40], uint64_t da, uint64_t db, int scale_d) {
  asm volatile("{\n.reg .pred p;\nsetp.ne.b32 p, %42, 0;\n"
    "wgmma.mma_async.sync.aligned.m64n80k16.f32.bf16.bf16 "
    "{%0, %1, %2, %3, %4, %5, %6, %7, %8, %9, %10, %11, %12, %13, %14, %15, "
    "%16, %17, %18, %19, %20, %21, %22, %23, %24, %25, %26, %27, %28, %29, %30, %31, "
    "%32, %33, %34, %35, %36, %37, %38, %39}, "
    "%40, %41, p, 1, 1, 0, 1;\n}\n"
    : "+f"(d[0]), "+f"(d[1]), "+f"(d[2]), "+f"(d[3]), "+f"(d[4]), "+f"(d[5]), "+f"(d[6]), "+f"(d[7]),
      "+f"(d[8]), "+f"(d[9]), "+f"(d[10]), "+f"(d[11]), "+f"(d[12]), "+f"(d[13]), "+f"(d[14]), "+f"(d[15]),
      "+f"(d[16]), "+f"(d[17]), "+f"(d[18]), "+f"(d[19]), "+f"(d[20]), "+f"(d[21]), "+f"(d[22]), "+f"(d[23]),
      "+f"(d[24]), "+f"(d[25]), "+f"(d[26]), "+f"(d[27]), "+f"(d[28]), "+f"(d[29]), "+f"(d[30]), "+f"(d[31]),
      "+f"(d[32]), "+f"(d[33]), "+f"(d[34]), "+f"(d[35]), "+f"(d[36]), "+f"(d[37]), "+f"(d[38]), "+f"(d[39])
    : "l"(da), "l"(db), "r"(scale_d));
}

__device__ __forceinline__ constexpr int QT(int t) { return t < 8 ? t : 16 + t; }
__device__ __forceinline__ constexpr int KT(int t) { return t < 8 ? 8 + t : 18 + t; }
__device__ __forceinline__ constexpr int VT(int t) { return t < 8 ? 16 + t : 20 + t; }

struct Maps { CUtensorMap x, w, wr, wv, wo, wor, gate, up, down; };

__global__ void __cluster_dims__(2, 1, 1) __launch_bounds__(512, 1)
fused_kernel(const __nv_bfloat16* __restrict__ x, const __nv_bfloat16* __restrict__ wqkv,
             const __nv_bfloat16* __restrict__ wo, const __nv_bfloat16* __restrict__ w_r, const __nv_bfloat16* __restrict__ w_gate,
             const __nv_bfloat16* __restrict__ w_up, const __nv_bfloat16* __restrict__ w_down, __nv_bfloat16* __restrict__ out,
             Scratch* __restrict__ sc, const __grid_constant__ Maps tm) {
  extern __shared__ __align__(1024) uint8_t smem[];
  const int tid = threadIdx.x, bid = blockIdx.x;
  if ((unsigned)(tid - 128) < 16u) pf_l2((const char*)x + (bid * 16 + tid - 128) * 1280);
  if ((unsigned)(tid - 160) < 15u) pf_l2((const char*)wqkv + (bid * 15 + tid - 160) * 128);
  const int warp = __shfl_sync(0xffffffffu, tid >> 5, 0), lane = tid & 31;
  const uint32_t sb = (uint32_t)__cvta_generic_to_shared(smem);
  const uint32_t bar_full = sb + OFF_BAR, bar_empty = bar_full + 32, bar_aux = bar_full + 64, bar_ffn = bar_full + 72, bar_win = bar_full + 80, bar_tag = bar_full + 88, bar_rst = bar_full + 96 + 296 + 24,
                 bar_o = bar_full + 96, bar_oc = bar_o + 112, bar_st = bar_o + 224, bar_go = bar_o + 248, bar_kv = bar_o + 272, bar_half = bar_o + 296;
  if (warp < 4 && elect()) {
    mbar_init(bar_half + 8 * warp, 1);
    mbar_init(bar_full + 8 * (warp ^ 2), 1);
    mbar_init(bar_empty + 8 * warp, 24);
    mbar_init(bar_aux + 8 * warp, warp == 0 ? 64 : warp == 2 ? 32 : warp == 3 ? 2 : 1);
    asm volatile("fence.mbarrier_init.release.cluster;" ::: "memory");
  }
  asm volatile("barrier.cluster.arrive.relaxed.aligned;" ::: "memory");
  if (warp >= 8 && warp < 12 && elect()) asm volatile("prefetch.tensormap [%0];" :: "l"(&tm.x + (warp - 8)) : "memory");
  auto pf_slice = [&](int ks) {
    pf_l2(lane < 16 ? (const char*)x + ((bid * 16 + lane) * 1280 + ks * 128) : (const char*)wqkv + ((bid * 15 + min(lane, 30) - 16) * 128 + ks * 245760));
  };
  if (E1_CLK && (warp == 6 || warp == 7)) { const int t0 = clk(); while (clk() - t0 < E1_CLK) {} pf_slice(warp == 6 ? 1 : 5); }
  const int rank = bid & 1, cl = bid >> 1;
  const int q7 = ((cl - 36) * 37) >> 8;
  const int P = cl < 4 ? 0 : cl < 36 ? (cl - 4) & 7 : cl - 35 - 7 * q7;
  const int g = (cl < 4 ? 4 + cl : cl < 36 ? (cl - 4) >> 3 : 4 + q7) ^ GX;
  const int mt = 2 * P + rank, cid = mt * 8 + g;
  const bool ffn1 = g >= 5;
  const int fj = ffn1 ? mt * 3 + g - 5 : (P * 5 + g) * 2 + rank;
  const int ord = ((g >> 2) ^ P) & 1;
  auto ks_of = [&](int it) { return !ORDX || ord == 0 || it == 0 ? it : it <= 5 ? it + 4 : it - 5; };
  const int godd = g & ODDS, cm = g * 80 + godd * 16, cr = g * 80 + 64 - godd * 64;
  auto load_w = [&](int ks, uint32_t a, uint32_t bar, int kk) {
    tma_3d_mc(a + 16384 + kk * 6144, &tm.w, bar, cm, ks * 64 + kk * 16, 0);
    tma_3d_mc(a + 41472 + kk * 2048, &tm.wr, bar, cr, ks * 64 + kk * 16, 0);
    tma_3d_mc(a + 40960 + kk * 2048, &tm.wv, bar, cm + 48, ks * 64 + kk * 16, 2);
  };
  if (warp == 0 && elect()) {
    mbar_expect_tx(bar_half, 32768);
    tma_3d(sb + 2 * SLOT, &tm.x, bar_half, 0, P * 128, rank);
    mbar_expect_tx(bar_full + 16, 16384);
  }
  asm volatile("barrier.cluster.wait.aligned;" ::: "memory");
  if (warp == 0) {
    if (elect()) {
      uint32_t bar = bar_half;
#pragma unroll 1
      for (int kk = rank; kk < 4; kk += 2) { load_w(0, sb + 2 * SLOT, bar, kk); bar = bar_full + 16; }
    }
    asm volatile("bar.arrive 4, 64;" ::: "memory");
  }

  if (warp >= 8) {
    asm volatile("setmaxnreg.dec.sync.aligned.u32 %0;" :: "n"(REG_P));
#define TS_T 0
    if (warp == 8) {
      TS(8);
      bar_sync(4, 64);
      if (elect()) {
        TS(10);
#pragma unroll 1
        for (int it = 1; it < 10; it++) {
          const int s = (it + 2) & 3, ks = ks_of(it);
          const uint32_t full = bar_full + 8 * s, a = sb + s * SLOT;
          uint32_t bar = it < NSPLIT ? bar_half + 8 * it : full;
          if (it >= 4) mbar_wait(full + 32, ((it >> 2) - 1) & 1);
          if (it == 1 && S1_CLK) { const int t0 = clk(); while (clk() - t0 < S1_CLK) {} }
          if (it >= 2 && it < THR_END) mbar_wait(bar_full + 8 * (it & 3), 0);
          if (it < NSPLIT) mbar_expect_tx(bar, 32768);
          mbar_expect_tx(full, it < NSPLIT ? 16384 : SLOT);
          tma_3d(a, &tm.x, bar, ks * 64, P * 128, rank);
#pragma unroll 1
          for (int kk = rank; kk < 4; kk += 2) { load_w(ks, a, bar, kk); bar = full; }
          TS(12 + it);
          if ((it >> 1) == 2) {
            mbar_wait(bar_rst, 0);
            asm volatile("cp.async.bulk.global.shared::cta.bulk_group [%0], [%1], %2;\ncp.async.bulk.commit_group;"
                         :: "l"(it == 4 ? (uint4*)(g_own + cid) : (uint4*)&g_x + cid * GLOB_PER_CTA), "r"(sb + OFF_CS), "r"(it == 4 ? (int)sizeof(Own) : GLOB_PER_CTA * 16) : "memory");
          }
          if (it == 6) { asm volatile("cp.async.bulk.wait_group 0;" ::: "memory"); mbar_arrive(bar_tag); }
        }
        mbar_expect_tx(bar_ffn, ffn1 ? 81920 : 24576);
        int fjn = 0;
#pragma unroll 1
        for (int it = 9; it < 17; it++) {
          if (it >= 13) { mbar_wait(bar_oc + 8 * (it - 13), 0); mbar_wait(bar_oc + 56 + 8 * (it - 13), 0); }
          else if (it >= 10) {
            const uint32_t full = bar_full + 8 * (it - 10);
            const int g0 = 3 * (it - 10), g1 = min(g0 + 3, 8);
            mbar_wait(full + 32, it < 12);
            mbar_expect_tx(full, (g1 - g0) * 12800);
#pragma unroll 1
            for (int gp = g0 + ((g0 ^ rank) & 1); gp < g1; gp += 2) {
              tma_3d_mc(sb + gp * 15360, &tm.wo, full, 0, gp * 80, g * 2);
              tma_3d_mc(sb + gp * 15360 + 10240, &tm.wor, full, 512 + g * 16, gp * 80, 0);
            }
          }
          const int j1 = ffn1 ? (it >= 13 ? 2 * it - 22 : min(it - 8, 3)) : (it >= 13 ? 12 : min((it - 8) * F_PER, F_MAX));
#pragma unroll 1
          for (; fjn < j1; fjn++) {
            const int j = fjn < 3 ? fjn + 7 : fjn - 3;
            if (ffn1) tma_3d(sb + (j < 7 ? 0 : OFF_W2 - 57344) + j * 8192, j < 5 ? &tm.gate : &tm.up, bar_ffn, fj * 32, (j < 5 ? j : j - 5) * 128, 0);
            else tma_3d(sb + OFF_W2 + fjn * 2048, &tm.down, bar_ffn, fj * 8, fjn * 128, 0);
          }
        }
        TS(11);
      }
#undef TS_T
#define TS_T 64
    } else if (warp >= 12) {
      const int l7 = lane & 7, j = warp - 12, ch = min((P >> 1) * 4 + rank * 2 + (j >> 1), 14);
      const uint32_t sxo = ((g & 3) * 32 + j * 8 + l7) * 128 + (((lane >> 3) ^ l7) * 16);
      const uint32_t swo = ch < 12 ? 16384 + (lane >> 4) * 6144 + (ch >> 2) * 2048 + (lane & 15) * 128 + ((((ch & 3) * 2 + (j & 1)) ^ l7) * 16)
                                   : 41472 + (lane >> 4) * 2048 + (ch - 12) * 512 + (lane & 15) * 32 + (((j & 1) ^ (l7 >> 2)) * 16);
      float ps = 0.f, pq = 0.f, pq1 = 0.f, pc = 0.f;
      uint32_t tag = 0;
      char* const pp = hold((lane & 1) ? (char*)&g_own[cid].cs[j * 8 + (lane >> 2)] : (char*)&g_own[cid].st1[j * 8 + (lane >> 2)]);
#pragma unroll 1
      for (int it = ord; it < ord + 5; it++) {
        const int sl = (it + 2) & 3;
        if (it == ord + 4) { mbar_wait(bar_tag, 0); tag = __float_as_uint(lds32f(sb + OFF_WR + 324)); }
        if (it < NSPLIT) mbar_wait(bar_half + 8 * it, 0);
        mbar_wait(bar_full + 8 * sl, (it >> 2) & 1);
        TS(it);
        const uint32_t a = sb + sl * SLOT;
        const uint4 v0 = ldsm4(a + sxo), v1 = ldsm4((a + sxo) ^ 64), w0 = ldsm4t(a + swo), w1 = ldsm4t(a + swo + (ch < 12 ? 12288 : 4096));
        if (lane + (int)((v0.x & v1.x & w0.x & w1.x) == 0x7fc17fc1u && (v0.x | v1.x) == 0u) < 2) mbar_arrive_cta(bar_empty + 8 * sl, lane);
        const uint32_t vv[8] = {v0.x, v0.y, v0.z, v0.w, v1.x, v1.y, v1.z, v1.w}, ww[8] = {w0.x, w0.y, w0.z, w0.w, w1.x, w1.y, w1.z, w1.w};
#pragma unroll
        for (int i = 0; i < 8; i++) {
          const float d = bf_lo(vv[i]), e = bf_hi(vv[i]);
          ps += d + e; pq = fmaf(d, d, pq); pq1 = fmaf(e, e, pq1); pc += bf_lo(ww[i]) + bf_hi(ww[i]);
        }
      }
      pq += pq1;
      ps += shx(ps, 1); pq += shx(pq, 1); pc += shx(pc, 1);
      ps += shx(ps, 2); pq += shx(pq, 2); pc += shx(pc, 2);
      if ((lane & 3) == 0) stg_pkt(pp, __float_as_uint(ps), __float_as_uint(pq), tag, 0u);
      if ((lane & 3) == 1) stg_rlx64(pp, __float_as_uint(pc), tag);
      asm volatile("bar.arrive 2, 192;" ::: "memory");
      if (warp == 12) {
        const uint4* const hp = hold(&g_own[max(cid - 16, 0)].halo[0][lane]);
        mbar_wait(bar_aux, 0);
        mbar_wait(bar_go, 0);
        uint4 v[5] = {};
        int guard = SPIN_MAX;
        if (P > 0) {
          do {
#pragma unroll
            for (int i = 0; i < 5; i++) v[i] = ldg_pkt(hp + 32 * i);
          } while (anyw(v[0].x == SENT || v[1].x == SENT || v[2].x == SENT || v[3].x == SENT || v[4].x == SENT) && --guard > 0);
        }
#pragma unroll
        for (int i = 0; i < 5; i++) *(uint4*)(smem + OFF_O + 10240 + i * 512 + lane * 16) = v[i];
        mbar_arrive(bar_kv);
      }
#undef TS_T
#define TS_T 32
    } else if (warp < 11) {
      const int l7 = lane & 7, hk = lane >> 4;
      if (warp == 10 && elect()) {
#pragma unroll 1
        for (int i = 0; i < 36; i++) mbar_init(bar_o + 8 * i, i < 14 || i == 30 ? 1 : i < 34 ? 4 : 128);
      }
      {
        const int t0 = clk();
#pragma unroll 1
        for (int i = PF_FIRST; i < 6; i++) {
          while (clk() - t0 < PF_T0 + (i - PF_FIRST) * PF_CLK) __nanosleep(20);
          pf_slice(warp == 9 ? min(i, 4) : i + 4);
        }
      }
      mbar_wait(bar_tag, 0);
      const uint32_t tag = __float_as_uint(lds32f(sb + OFF_WR + 324));
      bar_sync(2, 192);
      TS(0);
      int guard = SPIN_MAX;
      if (warp == 9) {
        const uint4* sp = &g_own[mt * 8].st1[lane];
        const uint4* hp = &g_own[max(mt - 2, 0) * 8 + 3].st1[24 + l7];
        uint4 a[5], b[5];
        bool bad;
        do {
          __nanosleep(AUX_NS);
          bad = false;
#pragma unroll
          for (int i = 0; i < 5; i++) {
            const uint4* q = i < 4 ? sp + i * (sizeof(Own) / 16) : hp;
            a[i] = ldg_pkt(q); b[i] = ldg_pkt(q + 4 * sizeof(Own) / 16);
          }
#pragma unroll
          for (int i = 0; i < 5; i++) bad |= a[i].z != tag || b[i].z != tag;
        } while (anyw(bad) && --guard);
        TS(1);
#pragma unroll
        for (int i = 0; i < 5; i++) {
          const float m = (__uint_as_float(a[i].x) + __uint_as_float(b[i].x)) * (1.f / 640.f);
          const float rs = rsq(fmaxf(fmaf(-m, m, (__uint_as_float(a[i].y) + __uint_as_float(b[i].y)) * (1.f / 640.f)), 0.f) + 1e-5f);
          ((float*)(smem + OFF_RS))[i < 4 ? 8 + lane + 32 * i : l7] = rs;
          const uint32_t mh = pack_bf16(-m, -m);
          const float ml = -m - bf_lo(mh);
          if (i < 4) ((uint2*)(smem + OFF_MN))[lane + 32 * i] = make_uint2(mh, pack_bf16(ml, ml));
        }
      } else {
        const uint4* cp = (const uint4*)g_own[hk * 8 + g].cs + (lane & 15);
        uint4 a[4], b[4];
        bool bad;
        do {
          __nanosleep(AUX_NS);
          bad = false;
#pragma unroll
          for (int i = 0; i < 4; i++) { a[i] = ldg_pkt(cp + i * 32 * sizeof(Own) / 16); b[i] = ldg_pkt(cp + (i * 32 + 16) * sizeof(Own) / 16); }
#pragma unroll
          for (int i = 0; i < 4; i++) bad |= a[i].y != tag || a[i].w != tag || b[i].y != tag || b[i].w != tag;
        } while (anyw(bad) && --guard);
#pragma unroll
        for (int i = 0; i < 4; i++)
          if (i < 3 || lane < 24) {
            const float c0 = __uint_as_float(a[i].x) + __uint_as_float(b[i].x), c1 = __uint_as_float(a[i].z) + __uint_as_float(b[i].z);
            const uint32_t hi = pack_bf16(c0, c1), w0 = pack_bf16(c0, c0 - bf_lo(hi)), w1 = pack_bf16(c1, c1 - bf_hi(hi));
            uint4* const d = (uint4*)(smem + OFF_CS) + 2 * (lane + 32 * i);
            d[0] = make_uint4(w0, w0, 0, 0); d[1] = make_uint4(w1, w1, 0, 0);
          }
        asm volatile("fence.proxy.async.shared::cta;" ::: "memory");
      }
      mbar_arrive(bar_aux);
      TS(2);
      const int fo = warp - 9, wq = fo ? 1 - LEAD : LEAD;
      const uint4* const fp = hold(g_own[mt * 8 + wq * 4].cnt);
      const char* src = hold((const char*)g_o[mt * 2 + wq]);
      if (elect()) {
        const uint32_t bo = bar_o + fo * 56;
#pragma unroll
        for (int i = 0; i < 7; i++) mbar_expect_tx(bo + 8 * i, 10240);
        mbar_wait(bar_st + 8 * fo, 0);
        uint32_t cv;
        asm volatile("atom.relaxed.gpu.global.add.u32 %0, [%1], 1;" : "=r"(cv) : "l"(fp) : "memory");
        cv++;
        while (cv != 8u && --guard > 0) cv = ldg_rlx32(fp);
        asm volatile("fence.proxy.async.global;" ::: "memory");
        TS(6);
        uint32_t dst = sb + OFF_O + (2 + fo) * 10240;
#pragma unroll 1
        for (int i = 0; i < 7; i++) {
          if (fo || i >= 4) mbar_wait(fo || i == 6 ? bo + 64 + 8 * i : bar_st + 8, 0);
          if (i == g) src += 10240;
          asm volatile("cp.async.bulk.shared::cluster.global.mbarrier::complete_tx::bytes [%0], [%1], 10240, [%2];" :: "r"(dst), "l"(src), "r"(bo + 8 * i) : "memory");
          src += 10240;
          dst += i + fo == 3 ? -51200 : 10240;
        }
      }
#undef TS_T
#define TS_T 96
    } else {
      if ((sb & 0x3FFFF) != D0 * 16) __trap();
#pragma unroll 1
      for (int i = lane; i < 232; i += 32) { const uint32_t f = i < 208 ? SENT : 0u; ((uint4*)(smem + OFF_CS))[i] = make_uint4(f, f, f, f); }
      asm volatile("fence.proxy.async.shared::cta;" ::: "memory");
      if (elect()) mbar_arrive(bar_rst);
      mbar_wait(bar_full + 8 * ((HK_IT + 2) & 3), 0);
      TS(4);
      const uint32_t epoch = ldg_rlx32(g_epoch + cid) + 1;
      uint32_t wv[10];
#pragma unroll
      for (int i = 0; i < 10; i++) wv[i] = __ldg((const uint32_t*)w_r + lane + 32 * i);
      float s = 0.f;
#pragma unroll
      for (int i = 0; i < 10; i++) {
        s += bf_lo(wv[i]) + bf_hi(wv[i]);
        const unsigned u = i < 8 ? lane + 32 * (i - g) : lane + 32 * (i - 7) - g * 8;
        if (i < 8 ? u < 32u : u - 32u < 8u) *(float2*)(smem + OFF_WR + ((u & 3) * 10 + (u >> 2)) * 8) = make_float2(bf_lo(wv[i]), bf_hi(wv[i]));
      }
#pragma unroll
      for (int m = 1; m < 32; m <<= 1) s += shx(s, m);
      *(float2*)(smem + OFF_WR + 320) = make_float2(s, __uint_as_float(epoch * 0x9E3779B8u));
      g_epoch[cid] = epoch;
      TS(3);
      if (elect()) mbar_arrive(bar_tag);
      TS(5);
#pragma unroll 1
      for (int i = 0; i < 14; i++) {
        const int m = (i + 2) >> 2, n = m == 0 ? 50 : 120, t = (m == 0 ? i : (i + 2) & 3) * 32 + lane;
        const char* b = (const char*)(m == 0 ? wo : m == 1 ? w_up : m == 2 ? w_down : w_gate);
        if (t < n) pf_l2(b + (bid * n + t) * 128);
        __nanosleep(PFW_NS);
      }
      const uint4* const kp = hold(g_own[1].cnt);
      const uint4* const cb = hold(&g_x.cand[0][lane >> 2][lane & 3]);
      bar_sync(3, 64);
      uint4 k;
      uint32_t have = SENT;
      int guard = SPIN_MAX;
      while (true) {
        k = ldg_pkt(kp);
        if (ffn1) {
          while (k.x != have && --guard > 0) {
            const uint32_t tk = 2047u - (k.x & 2047u), want = k.x;
            const uint4* q = cb + ((tk >> 8) * 16 + (tk & 1) * 8 + ((tk >> 5) & 7)) * 192;
            const uint4 c0 = ldg_pkt(q), c1 = ldg_pkt(q + 4); const uint2 c2 = ldg_rlx64(q + 8);
            k = ldg_pkt(kp);
            *(uint4*)(smem + OFF_HN + lane * 16) = c0; *(uint4*)(smem + OFF_HN + 512 + lane * 16) = c1; *(uint2*)(smem + OFF_HN + 1024 + lane * 16) = c2;
            have = anyw(c0.x == SENT || c1.x == SENT || c2.x == SENT) ? SENT : want;
          }
        } else if (KEY_NS && k.z != 128u) __nanosleep(KEY_NS);
        if (k.z == 128u || --guard <= 0) break;
      }
      *(uint2*)(smem + OFF_WR + 336) = make_uint2(k.x, k.y);
      mbar_arrive(bar_win);
      TS(7);
    }
#undef TS_T
  } else {
#define TS_T 0
    asm volatile("setmaxnreg.inc.sync.aligned.u32 %0;" :: "n"(REG_C));
    const int wg = warp >> 2, w4 = warp & 3, r = lane >> 2, c = lane & 3;
    float acc[120];
    uint4 xr[5] = {};
    const uint32_t xa = pin(sb + (warp * 16 + (lane & 15)) * 128 + ((lane >> 4) ^ (lane & 7)) * 16);
    const int fol = wg != LEAD;
    const bool first = (P == 0) && (warp == 0);
    const uint32_t kvs = sb + OFF_O + fol * 10240 + w4 * 2560 + lane * 16;
    uint4* const kvd = hold(warp == 7 ? &g_own[cid].halo[0][lane] : (uint4*)(smem + (warp == 3 ? OFF_O + lane * 16 : kvs - sb + 2560)));
    uint4* const odst = hold(&g_o[mt * 2 + wg][g][w4 * 160]);
    uint32_t m0 = 0, m1 = 0;
    const uint32_t mna = pin(sb + OFF_MN + (warp * 16 + r) * 8 + c * 4);
    const int itx = ord == 0 || g == 0 ? g : g < 5 ? g + 5 : g - 4, ity = (ord ? 4 : 8) + (g >> 2);
    uint32_t rel;
    asm volatile("mapa.shared::cluster.u32 %0, %1, %2;" : "=r"(rel) : "r"(bar_empty), "r"(tid & 1));
    const uint32_t xa1 = pin(xa ^ 32), xa2 = pin(xa ^ 64), xa3 = pin(xa ^ 96), xb = pin(xa ^ ((g & 3) * 32));
    const uint32_t da0 = wg * 512;
    const bool rel2 = lane < 2, rel6 = lane < 2 + 2 * (warp & 1);
    const uint32_t zero = __shfl_sync(0xffffffffu, (uint32_t)(uintptr_t)x & 8u, 0);
    mbar_wait(bar_half, 0);
    TS(13);
    wgmma_fence();
#pragma unroll
    for (int it = 0; it < 10; it++) {
      const int s = (it + 2) & 3;
      if (it == 9 && fol) bar_sync(10, 256);
#pragma unroll
      for (int kk = 0; kk < 4; kk++) {
        if (kk == 2 && it > 0) {
          wgmma_commit();
          wgmma_wait<1>();
          const uint32_t ra = ((xr[0].x ^ xr[1].x ^ xr[2].x ^ xr[3].x ^ xr[4].x) & zero) | rel;
          if (it == 1 ? (ord ? rel6 : rel2) : it == 6 ? (ord ? rel2 : rel6) : it < 6 ? rel2 : rel6)
            asm volatile("mbarrier.arrive.shared::cluster.b64 _, [%0];" :: "r"(ra + 8 * ((it + 1) & 3)) : "memory");
        }
        if (kk == 2) {
          ldsm4_if(xr[0], xa, s * SLOT, it == itx); ldsm4_if(xr[1], xa1, s * SLOT, it == itx);
          ldsm4_if(xr[2], xa2, s * SLOT, it == itx); ldsm4_if(xr[3], xa3, s * SLOT, it == itx);
          if ((it & 6) == 4 || it >= 8) ldsm4_if(xr[4], xb, s * SLOT, it == ity);
        }
        if (kk == AK && it == 9) {
          mbar_wait(bar_aux, 0);
          TS(3);
          if (c < 2) { m0 = __float_as_uint(lds32f(mna)); m1 = __float_as_uint(lds32f(mna + 64)); }
          if (!fol) bar_sync(11, 256);
        }
        if (kk == 2 && it < NSPLIT) mbar_wait(bar_full + 8 * s, 0);
        const uint64_t da = mk64(da0 + (D0 + s * (SLOT >> 4) + kk * 2 + (1 << 16)), 0x40000040u);
        wgmma_n64hi_ss(acc, da, mk64(D0 + s * (SLOT >> 4) + 2560 + kk * 128 + (32 << 16), 0xC0000010u), (it | kk) != 0);
        wgmma_n176lo_ss(acc, da, mk64(D0 + s * (SLOT >> 4) + 1024 + kk * 384 + (128 << 16), 0x40000040u), (it | kk) != 0);
      }
      wgmma_commit();
      if (it == 8 && fol) asm volatile("bar.arrive 11, 256;" ::: "memory");
      if (it < 9) {
        if (it + 1 < NSPLIT) mbar_wait(bar_half + 8 * (it + 1), 0);
        else mbar_wait(bar_full + 8 * ((it + 3) & 3), ((it + 1) >> 2) & 1);
        if (it < 8) TS(14 + it);
      }
    }
    {
      const uint64_t dc = make_desc(D0 * 16 + OFF_CS, 0, 128, 0);
      wgmma_fence();
      wgmma_n64hi_rk(acc, m0, m1, 0u, 0u, dc + 176, 1);
      wgmma_n176lo_rk(acc, m0, m1, 0u, 0u, dc, 1);
      wgmma_commit();
      if (!fol) asm volatile("bar.arrive 10, 256;" ::: "memory");
    }
    const uint32_t stb = sb + OFF_RS + warp * 64;
    const float rlo = lds32f(stb + (8 + r) * 4), rhi = lds32f(stb + (16 + r) * 4);
    wgmma_wait<0>();
#pragma unroll
    for (int i = 0; i < 120; i++) asm volatile("" : "+f"(acc[i]) :: "memory");
    if (fol && lane == 0) mbar_arrive(bar_go);
    TS(2);
    uint32_t Qlo[10], Qhi[10], Klo[10], Khi[10], Vlo[10], Vhi[10];
#define CONV_HI(ROT) _Pragma("unroll") for (int t = 0; t < 10; t++) { \
      const int k = KT((t + ROT) % 10), v = VT((t + ROT) % 10); \
      Khi[t] = pack_bf16(acc[4 * k + 2], acc[4 * k + 3]); \
      Vhi[t] = pack_bf16(acc[4 * v + 2] * rhi, acc[4 * v + 3] * rhi); }
    if (godd) { CONV_HI(8) } else { CONV_HI(0) }
    st_pkt(kvd, Khi[0], Khi[1], Khi[3], Khi[4]);
    st_pkt(kvd + 32, Khi[5], Khi[6], Khi[8], Khi[9]);
    st_pkt(kvd + 64, Khi[2], Khi[7], Vhi[0], Vhi[1]);
    st_pkt(kvd + 96, Vhi[2], Vhi[3], Vhi[4], Vhi[5]);
    st_pkt(kvd + 128, Vhi[6], Vhi[7], Vhi[8], Vhi[9]);
    if (warp < 7) mbar_arrive(bar_kv + ((warp + 1) >> 2) * 8);
    if (!ODDS) mbar_wait(bar_aux, 0);
#define CONV_LO(ROT) _Pragma("unroll") for (int t = 0; t < 10; t++) { \
      const int q = QT((t + ROT) % 10), k = KT((t + ROT) % 10), v = VT((t + ROT) % 10); \
      Vhi[t] = movm(Vhi[t]); \
      Klo[t] = pack_bf16(acc[4 * k], acc[4 * k + 1]); \
      Vlo[t] = movm(pack_bf16(acc[4 * v] * rlo, acc[4 * v + 1] * rlo)); \
      Qlo[t] = pack_bf16(acc[4 * q], acc[4 * q + 1]); \
      Qhi[t] = pack_bf16(acc[4 * q + 2], acc[4 * q + 3]); }
    if (godd) { CONV_LO(8) } else { CONV_LO(0) }
    const bool in0 = 2 * c <= r, in1 = 2 * c + 1 <= r;
    const uint32_t mL = (in0 ? 0xffffu : 0u) | (in1 ? 0xffff0000u : 0u);
    const float qs = 0.22360679774997896f * 1.4426950408889634f;
    const uint32_t kb0 = stb + (2 * c + (in0 ? 8 : 0)) * 4, kb1 = stb + (2 * c + 1 + (in1 ? 8 : 0)) * 4;
    const float scl0 = lds32f(kb0) * rlo * qs, scl1 = lds32f(kb1) * rlo * qs;
    const float sch0 = lds32f(kb0 + 32) * rhi * qs, sch1 = lds32f(kb1 + 32) * rhi * qs;
    const float bias0 = (first && !in0) ? -INFINITY : 0.f, bias1 = (first && !in1) ? -INFINITY : 0.f;
    const int slot = mt * 8 + warp;
    int guard = SPIN_MAX;
    uint4 pv[5];
    const bool cA = c < 2, nA = r < 4;
    TS(0);
    mbar_wait(bar_go + fol * 8, 0);
    TS(23);
    uint32_t qe[4][2];
    float sl0[4], sl1[4], th0[4], th1[4];
#pragma unroll
    for (int hd = 0; hd < 4; hd++) {
      const int ta = 5 * (hd >> 1) + 3 * (hd & 1), ts = 5 * (hd >> 1) + 2;
      const bool mine = (hd & 1) ? !cA : cA;
      qe[hd][0] = mine ? Qlo[ts] : 0u; qe[hd][1] = mine ? Qhi[ts] : 0u;
      float sl[4], sh[4];
      mma_k24(sl, Qlo[ta], Qhi[ta], Qlo[ta + 1], Qhi[ta + 1], Klo[ta], Klo[ta + 1], qe[hd][0], qe[hd][1], Klo[ts]);
      mma_k24(sh, Qlo[ta], Qhi[ta], Qlo[ta + 1], Qhi[ta + 1], Khi[ta], Khi[ta + 1], qe[hd][0], qe[hd][1], Khi[ts]);
      th0[hd] = (in0 ? sh[2] : sl[2]) * sch0; th1[hd] = (in1 ? sh[3] : sl[3]) * sch1;
      float mh = fmaxf(th0[hd], th1[hd]);
      mh = fmaxf(mh, shx(mh, 1)); mh = fmaxf(mh, shx(mh, 2));
      th0[hd] -= mh; th1[hd] -= mh;
      sl0[hd] = sl[0]; sl1[hd] = sl[1];
    }
    mbar_wait(bar_kv + wg * 8, 0);
    TS(4);
#pragma unroll
    for (int j = 0; j < 5; j++) pv[j] = lds128(kvs + 512 * j);
    const uint32_t Kp[10] = {pv[0].x, pv[0].y, pv[2].x, pv[0].z, pv[0].w, pv[1].x, pv[1].y, pv[2].y, pv[1].z, pv[1].w};
    const uint32_t Vp[10] = {movm(pv[2].z), movm(pv[2].w), movm(pv[3].x), movm(pv[3].y), movm(pv[3].z), movm(pv[3].w), movm(pv[4].x), movm(pv[4].y), movm(pv[4].z), movm(pv[4].w)};
    const uint32_t ONES = 0x3f803f80u;
    uint32_t of[20];
#pragma unroll
    for (int hp = 0; hp < 2; hp++) {
      float o[6][4];
#pragma unroll
      for (int hh = 0; hh < 2; hh++) {
        const int hd = 2 * hp + hh, ta = 5 * hp + 3 * hh, ts = 5 * hp + 2;
        float sp[4];
        mma_k24(sp, Qlo[ta], Qhi[ta], Qlo[ta + 1], Qhi[ta + 1], Kp[ta], Kp[ta + 1], qe[hd][0], qe[hd][1], Kp[ts]);
        const float tl0 = fmaf(in0 ? sl0[hd] : sp[0], scl0, bias0), tl1 = fmaf(in1 ? sl1[hd] : sp[1], scl1, bias1);
        float ml = fmaxf(tl0, tl1);
        ml = fmaxf(ml, shx(ml, 1)); ml = fmaxf(ml, shx(ml, 2));
        if (HOLD == 1 && hd == 3 && !fol && lane == 0) mbar_arrive(bar_go + 8);
        const uint32_t Pl = pack_bf16(ex2(tl0 - ml), ex2(tl1 - ml)), Ph = pack_bf16(ex2(th0[hd]), ex2(th1[hd]));
        const uint32_t a0 = Pl & mL, a1 = Ph & ~mL, a3 = Ph & mL, ap = Pl & ~mL;
        const bool vm = hh == 0 ? nA : !nA;
        mma_k24(o[3 * hh], a0, a1, 0u, a3, Vlo[ta], Vhi[ta], ap, 0u, Vp[ta]);
        mma_k24(o[3 * hh + 1], a0, a1, 0u, a3, Vlo[ta + 1], Vhi[ta + 1], ap, 0u, Vp[ta + 1]);
        mma_k24(o[3 * hh + 2], a0, a1, 0u, a3, vm ? Vlo[ts] : ONES, vm ? Vhi[ts] : ONES, ap, 0u, vm ? Vp[ts] : ONES);
      }
      const float il = rcp(cA ? o[5][0] : o[2][0]), ih = rcp(cA ? o[5][2] : o[2][2]);
      const float jl = shx(il, 2), jh = shx(ih, 2);
      const float al = cA ? jl : il, ah = cA ? jh : ih, bl = cA ? il : jl, bh = cA ? ih : jh;
      const int t0 = 5 * hp;
      of[2 * t0]     = pack_bf16(o[0][0] * al, o[0][1] * al); of[2 * t0 + 1] = pack_bf16(o[0][2] * ah, o[0][3] * ah);
      of[2 * t0 + 2] = pack_bf16(o[1][0] * al, o[1][1] * al); of[2 * t0 + 3] = pack_bf16(o[1][2] * ah, o[1][3] * ah);
      of[2 * t0 + 4] = pack_bf16((cA ? o[2][0] : o[5][0]) * jl, (cA ? o[2][1] : o[5][1]) * jl);
      of[2 * t0 + 5] = pack_bf16((cA ? o[2][2] : o[5][2]) * jh, (cA ? o[2][3] : o[5][3]) * jh);
      of[2 * t0 + 6] = pack_bf16(o[3][0] * bl, o[3][1] * bl); of[2 * t0 + 7] = pack_bf16(o[3][2] * bh, o[3][3] * bh);
      of[2 * t0 + 8] = pack_bf16(o[4][0] * bl, o[4][1] * bl); of[2 * t0 + 9] = pack_bf16(o[4][2] * bh, o[4][3] * bh);
    }
    {
      const uint32_t os = sb + OFF_O + (fol ? 0 : 20480) + w4 * 2560, oa = os + ((lane >> 3) & 1) * 1280 + (lane >> 4) * 128 + (lane & 7) * 16;
#pragma unroll
      for (int s = 0; s < 5; s++) {
        stsm4(oa + s * 256, of[4 * s], of[4 * s + 1], of[4 * s + 2], of[4 * s + 3]);
        if (s == 0 && (fol || HOLD == 2) && lane == 0) mbar_arrive(bar_go + 8 + 8 * fol);
      }
      asm volatile("fence.proxy.async.shared::cta;" ::: "memory");
      __syncwarp();
      if (elect()) {
        asm volatile("cp.async.bulk.global.shared::cta.bulk_group [%0], [%1], 2560;\ncp.async.bulk.commit_group;" :: "l"(odst), "r"(os) : "memory");
      }
    }
    TS(5);
    float h[40];
#pragma unroll
    for (int s = 0; s < 5; s++) {
      const uint4 v = xr[s];
      h[8 * s] = bf_lo(v.x); h[8 * s + 1] = bf_hi(v.x); h[8 * s + 2] = bf_lo(v.y); h[8 * s + 3] = bf_hi(v.y);
      h[8 * s + 4] = bf_lo(v.z); h[8 * s + 5] = bf_hi(v.z); h[8 * s + 6] = bf_lo(v.w); h[8 * s + 7] = bf_hi(v.w);
    }
    if (elect()) {
      asm volatile("cp.async.bulk.wait_group 0;" ::: "memory");
      mbar_arrive(bar_st + 8 * fol);
    }
    __syncwarp();
    TS(22);
    mbar_wait(bar_full, 0); mbar_wait(bar_full + 8, 0); mbar_wait(bar_full + 16, 1);
    mbar_wait(bar_go + 16, 0);
    const uint64_t dwo = make_desc(D0 * 16, 5120, 512, 2);
    wgmma_fence();
#pragma unroll
    for (int s = 0; s < 5; s++) wgmma_n80_rs(h, of[4 * s], of[4 * s + 1], of[4 * s + 2], of[4 * s + 3], dwo + g * 960 + s * 64, 1);
    wgmma_commit();
    TS(6);
    const uint32_t bo = bar_o + fol * 56;
#pragma unroll
    for (int i = 0; i < 7; i++) {
      mbar_wait(bo + 8 * i, 0);
      if (i == 0) TS(1);
      const uint32_t da = D0 + OFF_O / 16 + (8 << 16) + ((i + 2) % 6) * 640 + fol * (i == 3 ? -3200 : 640), db = D0 + (320 << 16) + (i >= g ? i + 1 : i) * 960;
      wgmma_fence();
#pragma unroll
      for (int s = 0; s < 5; s++) wgmma_n80_ss(h, mk64(da + s * 16, 80u), mk64(db + s * 64, 0x80000020u), 1);
      wgmma_commit();
      wgmma_wait<1>();
      if (lane == 0 && i > 0) mbar_arrive(bo + 104 + 8 * i);
    }
    const bool odd = c & 1;
    float wr[20];
#pragma unroll
    for (int j = 0; j < 5; j++) {
      const uint4 v = lds128(sb + OFF_WR + c * 80 + j * 16);
      wr[4 * j] = __uint_as_float(v.x); wr[4 * j + 1] = __uint_as_float(v.y); wr[4 * j + 2] = __uint_as_float(v.z); wr[4 * j + 3] = __uint_as_float(v.w);
    }
    const float wsum = lds32f(sb + OFF_WR + 320);
    uint4* const sp = hold(&g_own[slot].st2[r + (odd ? 8 : 0)]);
    uint4* const cdp = hold(&g_x.cand[slot][g][0]);
    const int tok0 = P * 256 + 32 * warp + rank;
    wgmma_wait<0>();
#pragma unroll
    for (int i = 0; i < 40; i++) asm volatile("" : "+f"(h[i]) :: "memory");
    if (lane == 0) mbar_arrive(bo + 160);
    TS(7);
    float mean, rstd, rr;
    {
      float l1 = 0.f, l2 = 0.f, l3 = 0.f, h1 = 0.f, h2 = 0.f, h3 = 0.f;
#pragma unroll
      for (int j = 0; j < 10; j++) {
        l1 += h[4 * j] + h[4 * j + 1]; h1 += h[4 * j + 2] + h[4 * j + 3];
        l2 = fmaf(h[4 * j], h[4 * j], l2); l2 = fmaf(h[4 * j + 1], h[4 * j + 1], l2);
        h2 = fmaf(h[4 * j + 2], h[4 * j + 2], h2); h2 = fmaf(h[4 * j + 3], h[4 * j + 3], h2);
        l3 = fmaf(h[4 * j], wr[2 * j], l3); l3 = fmaf(h[4 * j + 1], wr[2 * j + 1], l3);
        h3 = fmaf(h[4 * j + 2], wr[2 * j], h3); h3 = fmaf(h[4 * j + 3], wr[2 * j + 1], h3);
      }
      float s1 = (odd ? h1 : l1) + shx(odd ? l1 : h1, 1), s2 = (odd ? h2 : l2) + shx(odd ? l2 : h2, 1), s3 = (odd ? h3 : l3) + shx(odd ? l3 : h3, 1);
      s1 += shx(s1, 2); s2 += shx(s2, 2); s3 += shx(s3, 2);
      if (cA) asm volatile("red.relaxed.gpu.global.add.v4.f32 [%0], {%1, %2, %3, %4};" :: "l"(sp), "f"(s1), "f"(s2), "f"(s3), "f"(1.f) : "memory");
      uint4 p0;
      do { p0 = ldg_pkt(sp); } while (anyw(p0.w != 0x41000000u) && --guard > 0);
      mean = __uint_as_float(p0.x) * (1.f / 640.f);
      rstd = rsq(fmaxf(fmaf(-mean, mean, __uint_as_float(p0.y) * (1.f / 640.f)), 0.f) + 1e-5f);
      rr = fmaf(-mean, wsum, __uint_as_float(p0.z)) * rstd;
    }
    TS(8);
    const uint32_t kk = ord_key(rr), kmax = __reduce_max_sync(0xffffffffu, kk);
    const int L = __ffs(__ballot_sync(0xffffffffu, kk == kmax)) - 1;
    const int crow = (L >> 2) + 8 * (L & 1);
    if (warp == g) {
      if (elect()) {
        asm volatile("red.relaxed.gpu.global.max.u64 [%0], %1;" :: "l"(g_own[1].cnt), "l"(((uint64_t)kmax << 32) | (uint32_t)(2047 - tok0 - 2 * crow)) : "memory");
        asm volatile("red.relaxed.gpu.global.add.u32 [%0], 1;" :: "l"(&g_own[1].cnt[0].z) : "memory");
      }
      asm volatile("bar.arrive 3, 64;" ::: "memory");
    }
    const uint32_t stg = sb + (fol ? OFF_O : g * 15360) + w4 * 2560;
    uint4 held;
    {
      const float om = shx(mean, 1), os = shx(rstd, 1);
      const float rl = odd ? os : rstd, rh = odd ? rstd : os;
      const float bl = -(odd ? om : mean) * rl, bh = -(odd ? mean : om) * rh, al = 1.f + rl, ah = 1.f + rh;
      if ((L >> 2) == r) {
        const bool chi = L & 1;
        const float rc = chi ? rh : rl, bc = chi ? bh : bl;
        uint32_t n[10];
#pragma unroll
        for (int j = 0; j < 10; j++) n[j] = pack_bf16(fmaf(chi ? h[4 * j + 2] : h[4 * j], rc, bc), fmaf(chi ? h[4 * j + 3] : h[4 * j + 1], rc, bc));
        uint4* d = cdp + c;
        stg_pkt(d, n[0], n[1], n[2], n[3]); stg_pkt(d + 4, n[4], n[5], n[6], n[7]); stg_rlx64(d + 8, n[8], n[9]);
      }
      mbar_wait(bar_oc + 56, 0);
      const uint32_t fa = stg + (lane & 15) * 160 + (lane >> 4) * 16;
#pragma unroll
      for (int s = 0; s < 5; s++)
        stsm4(fa + s * 32, pack_bf16(fmaf(h[8 * s], al, bl), fmaf(h[8 * s + 1], al, bl)), pack_bf16(fmaf(h[8 * s + 2], ah, bh), fmaf(h[8 * s + 3], ah, bh)),
              pack_bf16(fmaf(h[8 * s + 4], al, bl), fmaf(h[8 * s + 5], al, bl)), pack_bf16(fmaf(h[8 * s + 6], ah, bh), fmaf(h[8 * s + 7], ah, bh)));
      __syncwarp();
      held = lds128(stg + crow * 160 + min(lane, 9) * 16);
      if (lane < 10) stg_pkt(cdp + 12 + lane, held.x, held.y, held.z, held.w);
    }
    TS(9);
    mbar_wait(bar_ffn, 0);
    const uint32_t red = sb + OFF_RED;
    if (ffn1) {
      uint4 w1[4][5];
      {
        const int k = (lane & 7) + (lane >> 4) * 8;
        const uint32_t a1 = sb + k * 64, sw = ((lane >> 3) & 1) ^ ((lane >> 1) & 3);
#pragma unroll
        for (int s = 0; s < 5; s++)
#pragma unroll
          for (int u = 0; u < 4; u++)
            w1[u][s] = ldsm4t(a1 + (s < 4 ? warp * 4096 + s * 1024 : 32768 + warp * 1024) + (u >> 1) * (40960 + (s == 4 || warp >= 4 ? OFF_W2 - 57344 : 0)) + ((sw ^ (2 * (u & 1))) * 16));
      }
      uint32_t* const ap = hold(g_x.act + fj * 16 + (lane >> 1));
      mbar_wait(bar_win, 0);
      const uint32_t hp = sb + OFF_HN + (warp * 4 + c) * 16;
      const uint4 c0 = lds128(hp), c1 = lds128(hp + 512), c2 = lds128(hp + 1024);
      TS(10);
      float a[4][4];
#pragma unroll
      for (int u = 0; u < 4; u++) {
        a[u][0] = a[u][1] = a[u][2] = a[u][3] = 0.f;
        mma_acc(a[u], w1[u][0], c0.x, c0.y); mma_acc(a[u], w1[u][1], c0.z, c0.w); mma_acc(a[u], w1[u][2], c1.x, c1.y);
        mma_acc(a[u], w1[u][3], c1.z, c1.w); mma_acc(a[u], w1[u][4], c2.x, c2.y);
      }
      asm volatile("st.shared.v2.f32 [%0], {%1, %2};" :: "r"(red + (warp * 32 + c * 8 + r) * 8),
                   "f"(cA ? (odd ? a[0][2] : a[0][0]) : (odd ? a[1][2] : a[1][0])), "f"(cA ? (odd ? a[2][2] : a[2][0]) : (odd ? a[3][2] : a[3][0])) : "memory");
      bar_sync(1, 256);
      if (warp == 0) {
        float2 t[8];
#pragma unroll
        for (int i = 0; i < 8; i++) t[i] = lds64f(red + (i * 32 + lane) * 8);
        const float s = ((t[0].x + t[1].x) + (t[2].x + t[3].x)) + ((t[4].x + t[5].x) + (t[6].x + t[7].x));
        const float u = ((t[0].y + t[1].y) + (t[2].y + t[3].y)) + ((t[4].y + t[5].y) + (t[6].y + t[7].y));
        const float av = s * u * rcp(1.f + ex2(-1.4426950408889634f * s));
        const float an = shx(av, 1);
        if (!odd) stg_rlx32(ap, pack_bf16(av, an));
      }
      bar_sync(1, 256);
      TS(11);
    }
    if (OUT_LATE) mbar_wait(bar_win, 0);
    char* const ob2 = (char*)(out + tok0 * 640 + g * 64);
    const int remo = 896 - 96 * g;
#pragma unroll
    for (int s = 0; s < 5; s++) {
      const int row = s < 4 ? 4 * s + (lane >> 3) : lane >> 1, pc = s < 4 ? lane & 7 : 8 + (lane & 1);
      const uint4 v = lds128(stg + row * 160 + pc * 16);
      if (row != crow) stg128(ob2 + row * 2560 + pc * 16 + (s < 4 ? 0 : remo), v);
    }
    mbar_wait(bar_win, 0);
    uint4 win = lds128(sb + OFF_WR + 336);
    win.z = win.y; win.y = 2047u - (win.x & 2047u); win.x = (win.y >> 8) * 16 + (win.y & 1) * 8 + ((win.y >> 5) & 7);
    if (win.x != slot && lane < 10) stg128(ob2 + crow * 2560 + lane * 16 + (lane < 8 ? 0 : remo), held);
    if (!ffn1) {
      TS(10);
      uint4 w2[6];
      const uint32_t a2 = sb + OFF_W2 + (warp * 192 + 8 * (((lane >> 3) & 1) * 4 + ((lane & 7) >> 1)) + 2 * (lane >> 4) + (lane & 1)) * 16;
#pragma unroll
      for (int s = 0; s < 6; s++) w2[s] = ldsm4t(a2 + (s >> 1) * 1024 + (s & 1) * 64);
      const uint4* p = (const uint4*)(g_x.act + warp * 96) + (r & 1) * 4 + c;
      const uint32_t* pb = (const uint32_t*)&g_x.cand[win.x][fj < 64 ? fj >> 3 : (fj - 64) >> 1][fj < 64 ? 12 + (fj & 7) : 20 + (fj & 1)] + c;
      uint32_t* const op = hold((uint32_t*)(out + win.y * 640 + fj * 8) + c);
      const float sg = rcp(1.f + ex2(-1.4426950408889634f * __uint_as_float(win.z ^ ((uint32_t)((int32_t)~win.z >> 31) | 0x80000000u))));
      uint4 c0, c1, c2; uint32_t bw;
      if (ACT_NS) __nanosleep(ACT_NS);
      do {
        c0 = ldg_pkt(p); c1 = ldg_pkt(p + 8); c2 = ldg_pkt(p + 16); bw = ldg_rlx32(pb);
      } while (anyw(max(max(max(max(c0.x, c0.y), max(c0.z, c0.w)), max(max(c1.x, c1.y), max(c1.z, c1.w))), max(max(max(c2.x, c2.y), max(c2.z, c2.w)), bw)) == SENT) && --guard > 0);
      TS(11);
      float a[4] = {0.f, 0.f, 0.f, 0.f}, b[4] = {0.f, 0.f, 0.f, 0.f}, d[4] = {0.f, 0.f, 0.f, 0.f};
      mma_acc(a, w2[0], c0.x, c0.y); mma_acc(b, w2[2], c1.x, c1.y); mma_acc(d, w2[4], c2.x, c2.y);
      mma_acc(a, w2[1], c0.z, c0.w); mma_acc(b, w2[3], c1.z, c1.w); mma_acc(d, w2[5], c2.z, c2.w);
      if (c == 0) sts32f(red + (warp * 8 + r) * 4, ((a[0] + a[3]) + (b[0] + b[3])) + (d[0] + d[3]));
      bar_sync(1, 256);
      if (tid < 4) {
        float2 t[8];
#pragma unroll
        for (int i = 0; i < 8; i++) t[i] = lds64f(red + (i * 4 + tid) * 8);
        const float y0 = ((t[0].x + t[1].x) + (t[2].x + t[3].x)) + ((t[4].x + t[5].x) + (t[6].x + t[7].x));
        const float y1 = ((t[0].y + t[1].y) + (t[2].y + t[3].y)) + ((t[4].y + t[5].y) + (t[6].y + t[7].y));
        *op = pack_bf16(fmaf(y0, sg, bf_lo(bw)), fmaf(y1, sg, bf_hi(bw)));
      }
    }
    TS(12);
#undef TS_T
  }
}

typedef CUresult (*EncodeFn)(CUtensorMap*, CUtensorMapDataType, cuuint32_t, void*, const cuuint64_t*, const cuuint64_t*, const cuuint32_t*,
                             const cuuint32_t*, CUtensorMapInterleave, CUtensorMapSwizzle, CUtensorMapL2promotion, CUtensorMapFloatOOBfill);

void make_map(EncodeFn enc, CUtensorMap* m, const void* base, const cuuint64_t* dims, const cuuint64_t* strides, const cuuint32_t* box,
              CUtensorMapSwizzle swz) {
  const cuuint32_t es[3] = {1, 1, 1};
  enc(m, CU_TENSOR_MAP_DATA_TYPE_BFLOAT16, 3, (void*)base, dims, strides, box, es, CU_TENSOR_MAP_INTERLEAVE_NONE, swz,
      CU_TENSOR_MAP_L2_PROMOTION_L2_128B, CU_TENSOR_MAP_FLOAT_OOB_FILL_NONE);
}

}

extern "C" void kernel_launch(void* const* d_in, const int* in_sizes, int n_in, void* d_out, int out_size) {
  const __nv_bfloat16* x = (const __nv_bfloat16*)d_in[0];
  const __nv_bfloat16* wqkv = (const __nv_bfloat16*)d_in[1];
  const __nv_bfloat16* wo = (const __nv_bfloat16*)d_in[2];
  void* fn = nullptr;
  cudaDriverEntryPointQueryResult st;
  cudaGetDriverEntryPoint("cuTensorMapEncodeTiled", &fn, cudaEnableDefault, &st);
  EncodeFn enc = (EncodeFn)fn;
  void* scp = nullptr;
  cudaGetSymbolAddress(&scp, g_scratch);
  Maps tm;
  { const cuuint64_t d[3] = {640, 1024, 2}, s[2] = {2560, 1280}; const cuuint32_t b[3] = {64, 128, 1}; make_map(enc, &tm.x, x, d, s, b, CU_TENSOR_MAP_SWIZZLE_128B); }
  { const cuuint64_t d[3] = {640, 640, 3}, s[2] = {3840, 1280}; const cuuint32_t b[3] = {64, 16, 3}; make_map(enc, &tm.w, wqkv, d, s, b, CU_TENSOR_MAP_SWIZZLE_128B); }
  { const cuuint64_t d[3] = {640, 640, 3}, s[2] = {3840, 1280}; const cuuint32_t b[3] = {16, 16, 3}; make_map(enc, &tm.wr, wqkv, d, s, b, CU_TENSOR_MAP_SWIZZLE_32B); }
  { const cuuint64_t d[3] = {640, 640, 3}, s[2] = {3840, 1280}; const cuuint32_t b[3] = {16, 16, 1}; make_map(enc, &tm.wv, wqkv, d, s, b, CU_TENSOR_MAP_SWIZZLE_32B); }
  { const cuuint64_t d[3] = {32, 640, 20}, s[2] = {1280, 64}; const cuuint32_t b[3] = {32, 80, 2}; make_map(enc, &tm.wo, wo, d, s, b, CU_TENSOR_MAP_SWIZZLE_64B); }
  { const cuuint64_t d[3] = {640, 640, 1}, s[2] = {1280, 819200}; const cuuint32_t b[3] = {16, 80, 1}; make_map(enc, &tm.wor, wo, d, s, b, CU_TENSOR_MAP_SWIZZLE_64B); }
  { const cuuint64_t d[3] = {1536, 640, 1}, s[2] = {3072, 1966080}; const cuuint32_t b[3] = {32, 128, 1};
    make_map(enc, &tm.gate, d_in[5], d, s, b, CU_TENSOR_MAP_SWIZZLE_64B); make_map(enc, &tm.up, d_in[6], d, s, b, CU_TENSOR_MAP_SWIZZLE_64B); }
  { const cuuint64_t d[3] = {640, 1536, 1}, s[2] = {1280, 1966080}; const cuuint32_t b[3] = {8, 128, 1}; make_map(enc, &tm.down, d_in[7], d, s, b, CU_TENSOR_MAP_SWIZZLE_NONE); }
  cudaFuncSetAttribute(fused_kernel, cudaFuncAttributeMaxDynamicSharedMemorySize, SMEM_BYTES);
  fused_kernel<<<128, 512, SMEM_BYTES, cudaStreamPerThread>>>(x, wqkv, wo, (const __nv_bfloat16*)d_in[4], (const __nv_bfloat16*)d_in[5],
                                                              (const __nv_bfloat16*)d_in[6], (const __nv_bfloat16*)d_in[7], (__nv_bfloat16*)d_out, (Scratch*)scp, tm);
}
```

```cpp
#include <cuda_runtime.h>
#include <cuda_bf16.h>
#include <cuda.h>
#include <stdint.h>

#define PFW_NS 50
#define ACT_NS 100
#define OUT_LATE 0
#define REG_P 72
#define REG_C 184
#define AUX_NS 50
#define LEAD 1
#define RST_IT 4
#define ORDX 1
#define THR 2
#define PF_FIRST 3
#define PF_T0 1500
#define PF_CLK 500
#define HK_IT 1
#define F_IT 9
#define F_PER 2
#define F_MAX 8
#define HOLD 2
#define F_LATE 12
#define HALO_NS 0
#define AK 3
#define KEY_NS 0
#define FW 5
#define ONE_RED 2
#define CNT_NS 0
#define NO_LATE 0
#define EARLY 1
#define PREW 9
#define NSPLIT 3
#define E1_CLK 0
#define THR_END 4
#define S1_CLK 0
#define GX 0
#define ODDS 1
#define BOUNDED 0
#define TLIGHT 0
#define ATOM2 1

namespace {

constexpr int SLOT    = 49152;
constexpr int OFF_O   = 122880;
constexpr int OFF_W2  = 4 * SLOT;
constexpr int OFF_CS  = OFF_W2 + 24576;
constexpr int OFF_RS  = OFF_CS + 3840;
constexpr int OFF_MN  = OFF_RS + 576;
constexpr int OFF_WR  = OFF_MN + 1024;
constexpr int OFF_RED = OFF_CS;
constexpr int OFF_HN  = OFF_CS + 2048;
constexpr int OFF_PT  = OFF_WR + 352;
constexpr int OFF_BAR = OFF_PT + 768;
constexpr int SMEM_BYTES = OFF_BAR + 424 + 384;
constexpr uint32_t D0 = 1024 >> 4;
constexpr uint32_t SENT = 0xFFFFFFFFu;
constexpr int SPIN_MAX = 1 << 20;

struct Glob {
  uint4 cand[128][8][24];
  uint32_t act[768];
  uint32_t pad[256];
};
constexpr int GLOB_PER_CTA = sizeof(Glob) / 16 / 128;
static_assert(GLOB_PER_CTA * 128 * 16 == sizeof(Glob), "glob size");
struct Own {
  uint4 halo[5][32];
  uint4 st1[32];
  uint2 cs[32];
  uint4 st2[16];
  uint4 cnt[8];
};
struct Scratch {
  Glob x;
  Own own[128];
  uint4 o[32][8][640];
  uint32_t epoch[128];
};
__device__ __align__(128) Scratch g_scratch;
#define g_x (sc->x)
#define g_own (sc->own)
#define g_o (sc->o)
#define g_epoch (sc->epoch)
#define TS(i)

__device__ __forceinline__ void mbar_init(uint32_t bar, uint32_t cnt) { asm volatile("mbarrier.init.shared::cta.b64 [%0], %1;" :: "r"(bar), "r"(cnt) : "memory"); }
__device__ __forceinline__ void mbar_expect_tx(uint32_t bar, uint32_t bytes) { asm volatile("mbarrier.arrive.expect_tx.shared::cta.b64 _, [%0], %1;" :: "r"(bar), "r"(bytes) : "memory"); }
__device__ __forceinline__ void mbar_arrive(uint32_t bar) { asm volatile("mbarrier.arrive.shared::cta.b64 _, [%0];" :: "r"(bar) : "memory"); }
__device__ __forceinline__ void mbar_arrive_cta(uint32_t bar, uint32_t cta) {
  asm volatile("{\n.reg .b32 ra;\nmapa.shared::cluster.u32 ra, %0, %1;\nmbarrier.arrive.shared::cluster.b64 _, [ra];\n}\n" :: "r"(bar), "r"(cta) : "memory");
}
__device__ __forceinline__ void mbar_wait(uint32_t bar, uint32_t parity) {
  asm volatile("{\n.reg .pred p;\nW:\nmbarrier.try_wait.parity.shared::cta.b64 p, [%0], %1;\n@!p bra.uni W;\n}\n" :: "r"(bar), "r"(parity) : "memory");
}
__device__ __forceinline__ void tma_3d(uint32_t dst, const void* tm, uint32_t bar, int c0, int c1, int c2) {
  asm volatile("cp.async.bulk.tensor.3d.shared::cluster.global.mbarrier::complete_tx::bytes [%0], [%1, {%3, %4, %5}], [%2];" :: "r"(dst), "l"(tm), "r"(bar), "r"(c0), "r"(c1), "r"(c2) : "memory");
}
__device__ __forceinline__ void tma_3d_mc(uint32_t dst, const void* tm, uint32_t bar, int c0, int c1, int c2) {
  asm volatile("cp.async.bulk.tensor.3d.shared::cluster.global.mbarrier::complete_tx::bytes.multicast::cluster [%0], [%1, {%3, %4, %5}], [%2], %6;" :: "r"(dst), "l"(tm), "r"(bar), "r"(c0), "r"(c1), "r"(c2), "h"((uint16_t)3) : "memory");
}
__device__ __forceinline__ void wgmma_fence() { asm volatile("wgmma.fence.sync.aligned;" ::: "memory"); }
__device__ __forceinline__ void wgmma_commit() { asm volatile("wgmma.commit_group.sync.aligned;" ::: "memory"); }
template <int N> __device__ __forceinline__ void wgmma_wait() { asm volatile("wgmma.wait_group.sync.aligned %0;" :: "n"(N) : "memory"); }
__device__ __forceinline__ uint64_t make_desc(uint32_t addr, uint32_t lbo, uint32_t sbo, uint32_t swz) {
  return (uint64_t)(((addr & 0x3FFFF) >> 4) | ((lbo >> 4) << 16)) | ((uint64_t)((sbo >> 4) | (swz << 30)) << 32);
}
__device__ __forceinline__ void bar_sync(int id, int n) { asm volatile("bar.sync %0, %1;" :: "r"(id), "r"(n) : "memory"); }
__device__ __forceinline__ void st_pkt(void* p, uint32_t a, uint32_t b, uint32_t c, uint32_t d) {
  asm volatile("st.relaxed.gpu.v4.u32 [%0], {%1, %2, %3, %4};" :: "l"(p), "r"(a), "r"(b), "r"(c), "r"(d) : "memory");
}
__device__ __forceinline__ uint4 ldg_pkt(const void* p) {
  uint4 v; asm volatile("ld.relaxed.gpu.global.v4.u32 {%0, %1, %2, %3}, [%4];" : "=r"(v.x), "=r"(v.y), "=r"(v.z), "=r"(v.w) : "l"(p) : "memory"); return v;
}
__device__ __forceinline__ void stg_pkt(void* p, uint32_t a, uint32_t b, uint32_t c, uint32_t d) {
  asm volatile("st.relaxed.gpu.global.v4.u32 [%0], {%1, %2, %3, %4};" :: "l"(p), "r"(a), "r"(b), "r"(c), "r"(d) : "memory");
}
__device__ __forceinline__ uint32_t ldg_rlx32(const void* p) { uint32_t v; asm volatile("ld.relaxed.gpu.global.u32 %0, [%1];" : "=r"(v) : "l"(p) : "memory"); return v; }
__device__ __forceinline__ uint2 ldg_rlx64(const void* p) { uint2 v; asm volatile("ld.relaxed.gpu.global.v2.u32 {%0, %1}, [%2];" : "=r"(v.x), "=r"(v.y) : "l"(p) : "memory"); return v; }
__device__ __forceinline__ uint32_t pin(uint32_t v) { asm volatile("" : "+r"(v)); return v; }
__device__ __forceinline__ uint64_t mk64(uint32_t lo, uint32_t hi) { return ((uint64_t)hi << 32) | lo; }
template <class T> __device__ __forceinline__ T* hold(T* p) { return (T*)__shfl_sync(0xffffffffu, (unsigned long long)p, threadIdx.x & 31); }
__device__ __forceinline__ void stg128_if(bool q, void* p, const uint4& v) {
  asm volatile("{\n.reg .pred q;\nsetp.ne.u32 q, %5, 0;\n@q st.global.v4.u32 [%0], {%1, %2, %3, %4};\n}\n" :: "l"(p), "r"(v.x), "r"(v.y), "r"(v.z), "r"(v.w), "r"((int)q) : "memory");
}
template <class T> __device__ __forceinline__ T* pin(T* p) { asm volatile("" : "+l"(p)); return p; }
__device__ __forceinline__ void stg_rlx32(void* p, uint32_t v) { asm volatile("st.relaxed.gpu.global.u32 [%0], %1;" :: "l"(p), "r"(v) : "memory"); }
__device__ __forceinline__ void stg_rlx64(void* p, uint32_t a, uint32_t b) { asm volatile("st.relaxed.gpu.global.v2.u32 [%0], {%1, %2};" :: "l"(p), "r"(a), "r"(b) : "memory"); }
__device__ __forceinline__ uint4 ldsm4(uint32_t a) { uint4 v; asm volatile("ldmatrix.sync.aligned.m8n8.x4.shared.b16 {%0, %1, %2, %3}, [%4];" : "=r"(v.x), "=r"(v.y), "=r"(v.z), "=r"(v.w) : "r"(a) : "memory"); return v; }
__device__ __forceinline__ void ldsm4_if(uint4& v, uint32_t a, int off, bool p) {
  asm volatile("{\n.reg .pred q;\nsetp.ne.u32 q, %5, 0;\n@q ldmatrix.sync.aligned.m8n8.x4.shared.b16 {%0, %1, %2, %3}, [%4];\n}\n"
               : "+r"(v.x), "+r"(v.y), "+r"(v.z), "+r"(v.w) : "r"(a + off), "r"((int)p) : "memory");
}
__device__ __forceinline__ uint4 ldsm4t(uint32_t a) { uint4 v; asm volatile("ldmatrix.sync.aligned.m8n8.x4.trans.shared.b16 {%0, %1, %2, %3}, [%4];" : "=r"(v.x), "=r"(v.y), "=r"(v.z), "=r"(v.w) : "r"(a) : "memory"); return v; }
__device__ __forceinline__ void stsm4(uint32_t a, uint32_t x, uint32_t y, uint32_t z, uint32_t w) { asm volatile("stmatrix.sync.aligned.m8n8.x4.shared.b16 [%0], {%1, %2, %3, %4};" :: "r"(a), "r"(x), "r"(y), "r"(z), "r"(w) : "memory"); }
__device__ __forceinline__ void mma_acc(float (&c)[4], const uint4& a, uint32_t b0, uint32_t b1) {
  asm("mma.sync.aligned.m16n8k16.row.col.f32.bf16.bf16.f32 {%0,%1,%2,%3}, {%4,%5,%6,%7}, {%8,%9}, {%0,%1,%2,%3};"
      : "+f"(c[0]), "+f"(c[1]), "+f"(c[2]), "+f"(c[3]) : "r"(a.x), "r"(a.y), "r"(a.z), "r"(a.w), "r"(b0), "r"(b1));
}
__device__ __forceinline__ uint4 lds128(uint32_t a) { uint4 v; asm volatile("ld.shared.v4.u32 {%0, %1, %2, %3}, [%4];" : "=r"(v.x), "=r"(v.y), "=r"(v.z), "=r"(v.w) : "r"(a) : "memory"); return v; }
__device__ __forceinline__ float2 lds64f(uint32_t a) { float2 v; asm volatile("ld.shared.v2.f32 {%0, %1}, [%2];" : "=f"(v.x), "=f"(v.y) : "r"(a)); return v; }
__device__ __forceinline__ float lds32f(uint32_t a) { float v; asm volatile("ld.shared.f32 %0, [%1];" : "=f"(v) : "r"(a)); return v; }
__device__ __forceinline__ void sts32f(uint32_t a, float v) { asm volatile("st.shared.f32 [%0], %1;" :: "r"(a), "f"(v) : "memory"); }
__device__ __forceinline__ uint32_t pack_bf16(float lo, float hi) { uint32_t r; asm("cvt.rn.bf16x2.f32 %0, %1, %2;" : "=r"(r) : "f"(hi), "f"(lo)); return r; }
__device__ __forceinline__ float bf_lo(uint32_t v) { return __uint_as_float(v << 16); }
__device__ __forceinline__ float bf_hi(uint32_t v) { return __uint_as_float(v & 0xffff0000u); }
__device__ __forceinline__ uint32_t movm(uint32_t a) { uint32_t d; asm("movmatrix.sync.aligned.m8n8.trans.b16 %0, %1;" : "=r"(d) : "r"(a)); return d; }
__device__ __forceinline__ float ex2(float x) { float y; asm("ex2.approx.ftz.f32 %0, %1;" : "=f"(y) : "f"(x)); return y; }
__device__ __forceinline__ float rsq(float x) { float y; asm("rsqrt.approx.ftz.f32 %0, %1;" : "=f"(y) : "f"(x)); return y; }
__device__ __forceinline__ float rcp(float x) { float y; asm("rcp.approx.ftz.f32 %0, %1;" : "=f"(y) : "f"(x)); return y; }
__device__ __forceinline__ bool elect() { uint32_t p; asm volatile("{\n.reg .pred q;\nelect.sync _|q, 0xffffffff;\nselp.u32 %0, 1, 0, q;\n}\n" : "=r"(p)); return p; }
__device__ __forceinline__ int clk() { int c; asm volatile("mov.u32 %0, %%clock;" : "=r"(c) :: "memory"); return c; }
__device__ __forceinline__ void pf_l2(const void* p) { asm volatile("prefetch.global.L2 [%0];" :: "l"(p)); }
__device__ __forceinline__ bool anyw(bool p) { return __any_sync(0xffffffffu, p); }
__device__ __forceinline__ float shx(float v, int m) { return __shfl_xor_sync(0xffffffffu, v, m); }
__device__ __forceinline__ void mma_k24(float (&c)[4], uint32_t a0, uint32_t a1, uint32_t a2, uint32_t a3, uint32_t b0, uint32_t b1,
                                        uint32_t e0, uint32_t e1, uint32_t f0) {
  asm("mma.sync.aligned.m16n8k16.row.col.f32.bf16.bf16.f32 {%0,%1,%2,%3}, {%4,%5,%6,%7}, {%8,%9}, {%10,%10,%10,%10};"
      : "=f"(c[0]), "=f"(c[1]), "=f"(c[2]), "=f"(c[3]) : "r"(a0), "r"(a1), "r"(a2), "r"(a3), "r"(b0), "r"(b1), "f"(0.f));
  asm("mma.sync.aligned.m16n8k8.row.col.f32.bf16.bf16.f32 {%0,%1,%2,%3}, {%4,%5}, {%6}, {%0,%1,%2,%3};"
      : "+f"(c[0]), "+f"(c[1]), "+f"(c[2]), "+f"(c[3]) : "r"(e0), "r"(e1), "r"(f0));
}
__device__ __forceinline__ uint32_t ord_key(float r) { uint32_t u = __float_as_uint(r); return u ^ ((uint32_t)((int32_t)u >> 31) | 0x80000000u); }

__device__ __forceinline__ void wgmma_n64hi_ss(float (&d)[120], uint64_t da, uint64_t db, int scale_d) {
  asm volatile("{\n.reg .pred p;\nsetp.ne.b32 p, %34, 0;\n"
    "wgmma.mma_async.sync.aligned.m64n64k16.f32.bf16.bf16 "
    "{%0, %1, %2, %3, %4, %5, %6, %7, %8, %9, %10, %11, %12, %13, %14, %15, "
    "%16, %17, %18, %19, %20, %21, %22, %23, %24, %25, %26, %27, %28, %29, %30, %31}, "
    "%32, %33, p, 1, 1, 0, 1;\n}\n"
    : "+f"(d[88]), "+f"(d[89]), "+f"(d[90]), "+f"(d[91]), "+f"(d[92]), "+f"(d[93]), "+f"(d[94]), "+f"(d[95]),
      "+f"(d[96]), "+f"(d[97]), "+f"(d[98]), "+f"(d[99]), "+f"(d[100]), "+f"(d[101]), "+f"(d[102]), "+f"(d[103]),
      "+f"(d[104]), "+f"(d[105]), "+f"(d[106]), "+f"(d[107]), "+f"(d[108]), "+f"(d[109]), "+f"(d[110]), "+f"(d[111]),
      "+f"(d[112]), "+f"(d[113]), "+f"(d[114]), "+f"(d[115]), "+f"(d[116]), "+f"(d[117]), "+f"(d[118]), "+f"(d[119])
    : "l"(da), "l"(db), "r"(scale_d));
}
__device__ __forceinline__ void wgmma_n176lo_ss(float (&d)[120], uint64_t da, uint64_t db, int scale_d) {
  asm volatile("{\n.reg .pred p;\nsetp.ne.b32 p, %90, 0;\n"
    "wgmma.mma_async.sync.aligned.m64n176k16.f32.bf16.bf16 "
    "{%0, %1, %2, %3, %4, %5, %6, %7, %8, %9, %10, %11, %12, %13, %14, %15, "
    "%16, %17, %18, %19, %20, %21, %22, %23, %24, %25, %26, %27, %28, %29, %30, %31, "
    "%32, %33, %34, %35, %36, %37, %38, %39, %40, %41, %42, %43, %44, %45, %46, %47, "
    "%48, %49, %50, %51, %52, %53, %54, %55, %56, %57, %58, %59, %60, %61, %62, %63, "
    "%64, %65, %66, %67, %68, %69, %70, %71, %72, %73, %74, %75, %76, %77, %78, %79, "
    "%80, %81, %82, %83, %84, %85, %86, %87}, "
    "%88, %89, p, 1, 1, 0, 1;\n}\n"
    : "+f"(d[0]), "+f"(d[1]), "+f"(d[2]), "+f"(d[3]), "+f"(d[4]), "+f"(d[5]), "+f"(d[6]), "+f"(d[7]),
      "+f"(d[8]), "+f"(d[9]), "+f"(d[10]), "+f"(d[11]), "+f"(d[12]), "+f"(d[13]), "+f"(d[14]), "+f"(d[15]),
      "+f"(d[16]), "+f"(d[17]), "+f"(d[18]), "+f"(d[19]), "+f"(d[20]), "+f"(d[21]), "+f"(d[22]), "+f"(d[23]),
      "+f"(d[24]), "+f"(d[25]), "+f"(d[26]), "+f"(d[27]), "+f"(d[28]), "+f"(d[29]), "+f"(d[30]), "+f"(d[31]),
      "+f"(d[32]), "+f"(d[33]), "+f"(d[34]), "+f"(d[35]), "+f"(d[36]), "+f"(d[37]), "+f"(d[38]), "+f"(d[39]),
      "+f"(d[40]), "+f"(d[41]), "+f"(d[42]), "+f"(d[43]), "+f"(d[44]), "+f"(d[45]), "+f"(d[46]), "+f"(d[47]),
      "+f"(d[48]), "+f"(d[49]), "+f"(d[50]), "+f"(d[51]), "+f"(d[52]), "+f"(d[53]), "+f"(d[54]), "+f"(d[55]),
      "+f"(d[56]), "+f"(d[57]), "+f"(d[58]), "+f"(d[59]), "+f"(d[60]), "+f"(d[61]), "+f"(d[62]), "+f"(d[63]),
      "+f"(d[64]), "+f"(d[65]), "+f"(d[66]), "+f"(d[67]), "+f"(d[68]), "+f"(d[69]), "+f"(d[70]), "+f"(d[71]),
      "+f"(d[72]), "+f"(d[73]), "+f"(d[74]), "+f"(d[75]), "+f"(d[76]), "+f"(d[77]), "+f"(d[78]), "+f"(d[79]),
      "+f"(d[80]), "+f"(d[81]), "+f"(d[82]), "+f"(d[83]), "+f"(d[84]), "+f"(d[85]), "+f"(d[86]), "+f"(d[87])
    : "l"(da), "l"(db), "r"(scale_d));
}
__device__ __forceinline__ void wgmma_n64hi_rk(float (&d)[120], uint32_t a0, uint32_t a1, uint32_t a2, uint32_t a3, uint64_t db, int scale_d) {
  asm volatile("{\n.reg .pred p;\nsetp.ne.b32 p, %37, 0;\n"
    "wgmma.mma_async.sync.aligned.m64n64k16.f32.bf16.bf16 "
    "{%0, %1, %2, %3, %4, %5, %6, %7, %8, %9, %10, %11, %12, %13, %14, %15, "
    "%16, %17, %18, %19, %20, %21, %22, %23, %24, %25, %26, %27, %28, %29, %30, %31}, "
    "{%32, %33, %34, %35}, %36, p, 1, 1, 0;\n}\n"
    : "+f"(d[88]), "+f"(d[89]), "+f"(d[90]), "+f"(d[91]), "+f"(d[92]), "+f"(d[93]), "+f"(d[94]), "+f"(d[95]),
      "+f"(d[96]), "+f"(d[97]), "+f"(d[98]), "+f"(d[99]), "+f"(d[100]), "+f"(d[101]), "+f"(d[102]), "+f"(d[103]),
      "+f"(d[104]), "+f"(d[105]), "+f"(d[106]), "+f"(d[107]), "+f"(d[108]), "+f"(d[109]), "+f"(d[110]), "+f"(d[111]),
      "+f"(d[112]), "+f"(d[113]), "+f"(d[114]), "+f"(d[115]), "+f"(d[116]), "+f"(d[117]), "+f"(d[118]), "+f"(d[119])
    : "r"(a0), "r"(a1), "r"(a2), "r"(a3), "l"(db), "r"(scale_d));
}
__device__ __forceinline__ void wgmma_n176lo_rk(float (&d)[120], uint32_t a0, uint32_t a1, uint32_t a2, uint32_t a3, uint64_t db, int scale_d) {
  asm volatile("{\n.reg .pred p;\nsetp.ne.b32 p, %93, 0;\n"
    "wgmma.mma_async.sync.aligned.m64n176k16.f32.bf16.bf16 "
    "{%0, %1, %2, %3, %4, %5, %6, %7, %8, %9, %10, %11, %12, %13, %14, %15, "
    "%16, %17, %18, %19, %20, %21, %22, %23, %24, %25, %26, %27, %28, %29, %30, %31, "
    "%32, %33, %34, %35, %36, %37, %38, %39, %40, %41, %42, %43, %44, %45, %46, %47, "
    "%48, %49, %50, %51, %52, %53, %54, %55, %56, %57, %58, %59, %60, %61, %62, %63, "
    "%64, %65, %66, %67, %68, %69, %70, %71, %72, %73, %74, %75, %76, %77, %78, %79, "
    "%80, %81, %82, %83, %84, %85, %86, %87}, "
    "{%88, %89, %90, %91}, %92, p, 1, 1, 0;\n}\n"
    : "+f"(d[0]), "+f"(d[1]), "+f"(d[2]), "+f"(d[3]), "+f"(d[4]), "+f"(d[5]), "+f"(d[6]), "+f"(d[7]),
      "+f"(d[8]), "+f"(d[9]), "+f"(d[10]), "+f"(d[11]), "+f"(d[12]), "+f"(d[13]), "+f"(d[14]), "+f"(d[15]),
      "+f"(d[16]), "+f"(d[17]), "+f"(d[18]), "+f"(d[19]), "+f"(d[20]), "+f"(d[21]), "+f"(d[22]), "+f"(d[23]),
      "+f"(d[24]), "+f"(d[25]), "+f"(d[26]), "+f"(d[27]), "+f"(d[28]), "+f"(d[29]), "+f"(d[30]), "+f"(d[31]),
      "+f"(d[32]), "+f"(d[33]), "+f"(d[34]), "+f"(d[35]), "+f"(d[36]), "+f"(d[37]), "+f"(d[38]), "+f"(d[39]),
      "+f"(d[40]), "+f"(d[41]), "+f"(d[42]), "+f"(d[43]), "+f"(d[44]), "+f"(d[45]), "+f"(d[46]), "+f"(d[47]),
      "+f"(d[48]), "+f"(d[49]), "+f"(d[50]), "+f"(d[51]), "+f"(d[52]), "+f"(d[53]), "+f"(d[54]), "+f"(d[55]),
      "+f"(d[56]), "+f"(d[57]), "+f"(d[58]), "+f"(d[59]), "+f"(d[60]), "+f"(d[61]), "+f"(d[62]), "+f"(d[63]),
      "+f"(d[64]), "+f"(d[65]), "+f"(d[66]), "+f"(d[67]), "+f"(d[68]), "+f"(d[69]), "+f"(d[70]), "+f"(d[71]),
      "+f"(d[72]), "+f"(d[73]), "+f"(d[74]), "+f"(d[75]), "+f"(d[76]), "+f"(d[77]), "+f"(d[78]), "+f"(d[79]),
      "+f"(d[80]), "+f"(d[81]), "+f"(d[82]), "+f"(d[83]), "+f"(d[84]), "+f"(d[85]), "+f"(d[86]), "+f"(d[87])
    : "r"(a0), "r"(a1), "r"(a2), "r"(a3), "l"(db), "r"(scale_d));
}
__device__ __forceinline__ void wgmma_n80_rs(float (&d)[40], uint32_t a0, uint32_t a1, uint32_t a2, uint32_t a3, uint64_t db, int scale_d) {
  asm volatile("{\n.reg .pred p;\nsetp.ne.b32 p, %45, 0;\n"
    "wgmma.mma_async.sync.aligned.m64n80k16.f32.bf16.bf16 "
    "{%0, %1, %2, %3, %4, %5, %6, %7, %8, %9, %10, %11, %12, %13, %14, %15, "
    "%16, %17, %18, %19, %20, %21, %22, %23, %24, %25, %26, %27, %28, %29, %30, %31, "
    "%32, %33, %34, %35, %36, %37, %38, %39}, "
    "{%40, %41, %42, %43}, %44, p, 1, 1, 1;\n}\n"
    : "+f"(d[0]), "+f"(d[1]), "+f"(d[2]), "+f"(d[3]), "+f"(d[4]), "+f"(d[5]), "+f"(d[6]), "+f"(d[7]),
      "+f"(d[8]), "+f"(d[9]), "+f"(d[10]), "+f"(d[11]), "+f"(d[12]), "+f"(d[13]), "+f"(d[14]), "+f"(d[15]),
      "+f"(d[16]), "+f"(d[17]), "+f"(d[18]), "+f"(d[19]), "+f"(d[20]), "+f"(d[21]), "+f"(d[22]), "+f"(d[23]),
      "+f"(d[24]), "+f"(d[25]), "+f"(d[26]), "+f"(d[27]), "+f"(d[28]), "+f"(d[29]), "+f"(d[30]), "+f"(d[31]),
      "+f"(d[32]), "+f"(d[33]), "+f"(d[34]), "+f"(d[35]), "+f"(d[36]), "+f"(d[37]), "+f"(d[38]), "+f"(d[39])
    : "r"(a0), "r"(a1), "r"(a2), "r"(a3), "l"(db), "r"(scale_d));
}
__device__ __forceinline__ void wgmma_n80_ss(float (&d)[40], uint64_t da, uint64_t db, int scale_d) {
  asm volatile("{\n.reg .pred p;\nsetp.ne.b32 p, %42, 0;\n"
    "wgmma.mma_async.sync.aligned.m64n80k16.f32.bf16.bf16 "
    "{%0, %1, %2, %3, %4, %5, %6, %7, %8, %9, %10, %11, %12, %13, %14, %15, "
    "%16, %17, %18, %19, %20, %21, %22, %23, %24, %25, %26, %27, %28, %29, %30, %31, "
    "%32, %33, %34, %35, %36, %37, %38, %39}, "
    "%40, %41, p, 1, 1, 0, 1;\n}\n"
    : "+f"(d[0]), "+f"(d[1]), "+f"(d[2]), "+f"(d[3]), "+f"(d[4]), "+f"(d[5]), "+f"(d[6]), "+f"(d[7]),
      "+f"(d[8]), "+f"(d[9]), "+f"(d[10]), "+f"(d[11]), "+f"(d[12]), "+f"(d[13]), "+f"(d[14]), "+f"(d[15]),
      "+f"(d[16]), "+f"(d[17]), "+f"(d[18]), "+f"(d[19]), "+f"(d[20]), "+f"(d[21]), "+f"(d[22]), "+f"(d[23]),
      "+f"(d[24]), "+f"(d[25]), "+f"(d[26]), "+f"(d[27]), "+f"(d[28]), "+f"(d[29]), "+f"(d[30]), "+f"(d[31]),
      "+f"(d[32]), "+f"(d[33]), "+f"(d[34]), "+f"(d[35]), "+f"(d[36]), "+f"(d[37]), "+f"(d[38]), "+f"(d[39])
    : "l"(da), "l"(db), "r"(scale_d));
}

__device__ __forceinline__ constexpr int QT(int t) { return t < 8 ? t : 16 + t; }
__device__ __forceinline__ constexpr int KT(int t) { return t < 8 ? 8 + t : 18 + t; }
__device__ __forceinline__ constexpr int VT(int t) { return t < 8 ? 16 + t : 20 + t; }

struct Maps { CUtensorMap x, w, wr, wv, wo, wor, gate, up, down; };

__global__ void __cluster_dims__(2, 1, 1) __launch_bounds__(512, 1)
fused_kernel(const __nv_bfloat16* __restrict__ x, const __nv_bfloat16* __restrict__ wqkv,
             const __nv_bfloat16* __restrict__ wo, const __nv_bfloat16* __restrict__ w_r, const __nv_bfloat16* __restrict__ w_gate,
             const __nv_bfloat16* __restrict__ w_up, const __nv_bfloat16* __restrict__ w_down, __nv_bfloat16* __restrict__ out,
             Scratch* __restrict__ sc, const __grid_constant__ Maps tm) {
  extern __shared__ __align__(1024) uint8_t smem[];
  const int tid = threadIdx.x, bid = blockIdx.x;
  if ((unsigned)(tid - 128) < 16u) pf_l2((const char*)x + (bid * 16 + tid - 128) * 1280);
  if ((unsigned)(tid - 160) < 15u) pf_l2((const char*)wqkv + (bid * 15 + tid - 160) * 128);
  const int warp = __shfl_sync(0xffffffffu, tid >> 5, 0), lane = tid & 31;
  const uint32_t sb = (uint32_t)__cvta_generic_to_shared(smem);
  const uint32_t bar_full = sb + OFF_BAR, bar_empty = bar_full + 32, bar_aux = bar_full + 64, bar_ffn = bar_full + 72, bar_win = bar_full + 80, bar_tag = bar_full + 88, bar_rst = bar_full + 96 + 296 + 24,
                 bar_o = bar_full + 96, bar_oc = bar_o + 112, bar_st = bar_o + 224, bar_go = bar_o + 248, bar_kv = bar_o + 272, bar_half = bar_o + 296;
  if (warp < 4 && elect()) {
    mbar_init(bar_half + 8 * warp, 1);
    mbar_init(bar_full + 8 * (warp ^ 2), 1);
    mbar_init(bar_empty + 8 * warp, 24);
    mbar_init(bar_aux + 8 * warp, warp == 0 ? 64 : warp == 2 ? 32 : warp == 3 ? 2 : 1);
    asm volatile("fence.mbarrier_init.release.cluster;" ::: "memory");
  }
  asm volatile("barrier.cluster.arrive.relaxed.aligned;" ::: "memory");
  if (warp >= 8 && warp < 12 && elect()) asm volatile("prefetch.tensormap [%0];" :: "l"(&tm.x + (warp - 8)) : "memory");
  auto pf_slice = [&](int ks) {
    pf_l2(lane < 16 ? (const char*)x + ((bid * 16 + lane) * 1280 + ks * 128) : (const char*)wqkv + ((bid * 15 + min(lane, 30) - 16) * 128 + ks * 245760));
  };
  if (E1_CLK && (warp == 6 || warp == 7)) { const int t0 = clk(); while (clk() - t0 < E1_CLK) {} pf_slice(warp == 6 ? 1 : 5); }
  const int rank = bid & 1, cl = bid >> 1;
  const int q7 = ((cl - 36) * 37) >> 8;
  const int P = cl < 4 ? 0 : cl < 36 ? (cl - 4) & 7 : cl - 35 - 7 * q7;
  const int g = (cl < 4 ? 4 + cl : cl < 36 ? (cl - 4) >> 3 : 4 + q7) ^ GX;
  const int mt = 2 * P + rank, cid = mt * 8 + g;
  const bool ffn1 = g >= 5;
  const int fj = ffn1 ? mt * 3 + g - 5 : (P * 5 + g) * 2 + rank;
  const int ord = ((g >> 2) ^ P) & 1;
  auto ks_of = [&](int it) { return !ORDX || ord == 0 || it == 0 ? it : it <= 5 ? it + 4 : it - 5; };
  const int godd = g & ODDS, cm = g * 80 + godd * 16, cr = g * 80 + 64 - godd * 64;
  auto load_w = [&](int ks, uint32_t a, uint32_t bar, int kk) {
    tma_3d_mc(a + 16384 + kk * 6144, &tm.w, bar, cm, ks * 64 + kk * 16, 0);
    tma_3d_mc(a + 41472 + kk * 2048, &tm.wr, bar, cr, ks * 64 + kk * 16, 0);
    tma_3d_mc(a + 40960 + kk * 2048, &tm.wv, bar, cm + 48, ks * 64 + kk * 16, 2);
  };
  if (warp == 0 && elect()) {
    mbar_expect_tx(bar_half, 32768);
    tma_3d(sb + 2 * SLOT, &tm.x, bar_half, 0, P * 128, rank);
    mbar_expect_tx(bar_full + 16, 16384);
  }
  asm volatile("barrier.cluster.wait.aligned;" ::: "memory");
  if (warp == 0) {
    if (elect()) {
      uint32_t bar = bar_half;
#pragma unroll 1
      for (int kk = rank; kk < 4; kk += 2) { load_w(0, sb + 2 * SLOT, bar, kk); bar = bar_full + 16; }
    }
    asm volatile("bar.arrive 4, 64;" ::: "memory");
  }

  if (warp >= 8) {
    asm volatile("setmaxnreg.dec.sync.aligned.u32 %0;" :: "n"(REG_P));
#define TS_T 0
    if (warp == 8) {
      TS(8);
      bar_sync(4, 64);
      if (elect()) {
        TS(10);
#pragma unroll 1
        for (int it = 1; it < 10; it++) {
          const int s = (it + 2) & 3, ks = ks_of(it);
          const uint32_t full = bar_full + 8 * s, a = sb + s * SLOT;
          uint32_t bar = it < NSPLIT ? bar_half + 8 * it : full;
          if (it >= 4) mbar_wait(full + 32, ((it >> 2) - 1) & 1);
          if (it == 1 && S1_CLK) { const int t0 = clk(); while (clk() - t0 < S1_CLK) {} }
          if (it >= 2 && it < THR_END) mbar_wait(bar_full + 8 * (it & 3), 0);
          if (it < NSPLIT) mbar_expect_tx(bar, 32768);
          mbar_expect_tx(full, it < NSPLIT ? 16384 : SLOT);
          tma_3d(a, &tm.x, bar, ks * 64, P * 128, rank);
#pragma unroll 1
          for (int kk = rank; kk < 4; kk += 2) { load_w(ks, a, bar, kk); bar = full; }
          TS(12 + it);
          if ((it >> 1) == 2) {
            mbar_wait(bar_rst, 0);
            asm volatile("cp.async.bulk.global.shared::cta.bulk_group [%0], [%1], %2;\ncp.async.bulk.commit_group;"
                         :: "l"(it == 4 ? (uint4*)(g_own + cid) : (uint4*)&g_x + cid * GLOB_PER_CTA), "r"(sb + OFF_CS), "r"(it == 4 ? (int)sizeof(Own) : GLOB_PER_CTA * 16) : "memory");
          }
          if (it == 6) { asm volatile("cp.async.bulk.wait_group 0;" ::: "memory"); mbar_arrive(bar_tag); }
        }
        mbar_expect_tx(bar_ffn, ffn1 ? 81920 : 24576);
        int fjn = 0;
#pragma unroll 1
        for (int it = 9; it < 17; it++) {
          if (it >= 13) { mbar_wait(bar_oc + 8 * (it - 13), 0); mbar_wait(bar_oc + 56 + 8 * (it - 13), 0); }
          else if (it >= 10) {
            const uint32_t full = bar_full + 8 * (it - 10);
            const int g0 = 3 * (it - 10), g1 = min(g0 + 3, 8);
            mbar_wait(full + 32, it < 12);
            mbar_expect_tx(full, (g1 - g0) * 12800);
#pragma unroll 1
            for (int gp = g0 + ((g0 ^ rank) & 1); gp < g1; gp += 2) {
              tma_3d_mc(sb + gp * 15360, &tm.wo, full, 0, gp * 80, g * 2);
              tma_3d_mc(sb + gp * 15360 + 10240, &tm.wor, full, 512 + g * 16, gp * 80, 0);
            }
          }
          const int j1 = ffn1 ? (it >= 13 ? 2 * it - 22 : min(it - 8, 3)) : (it >= 13 ? 12 : min((it - 8) * F_PER, F_MAX));
#pragma unroll 1
          for (; fjn < j1; fjn++) {
            const int j = fjn < 3 ? fjn + 7 : fjn - 3;
            if (ffn1) tma_3d(sb + (j < 7 ? 0 : OFF_W2 - 57344) + j * 8192, j < 5 ? &tm.gate : &tm.up, bar_ffn, fj * 32, (j < 5 ? j : j - 5) * 128, 0);
            else tma_3d(sb + OFF_W2 + fjn * 2048, &tm.down, bar_ffn, fj * 8, fjn * 128, 0);
          }
        }
        TS(11);
      }
#undef TS_T
#define TS_T 64
    } else if (warp >= 12) {
      const int l7 = lane & 7, j = warp - 12, ch = min((P >> 1) * 4 + rank * 2 + (j >> 1), 14);
      const uint32_t sxo = ((g & 3) * 32 + j * 8 + l7) * 128 + (((lane >> 3) ^ l7) * 16);
      const uint32_t swo = ch < 12 ? 16384 + (lane >> 4) * 6144 + (ch >> 2) * 2048 + (lane & 15) * 128 + ((((ch & 3) * 2 + (j & 1)) ^ l7) * 16)
                                   : 41472 + (lane >> 4) * 2048 + (ch - 12) * 512 + (lane & 15) * 32 + (((j & 1) ^ (l7 >> 2)) * 16);
      float ps = 0.f, pq = 0.f, pq1 = 0.f, pc = 0.f;
      uint32_t tag = 0;
      char* const pp = hold((lane & 1) ? (char*)&g_own[cid].cs[j * 8 + (lane >> 2)] : (char*)&g_own[cid].st1[j * 8 + (lane >> 2)]);
#pragma unroll 1
      for (int it = ord; it < ord + 5; it++) {
        const int sl = (it + 2) & 3;
        if (it == ord + 4) { mbar_wait(bar_tag, 0); tag = __float_as_uint(lds32f(sb + OFF_WR + 324)); }
        if (it < NSPLIT) mbar_wait(bar_half + 8 * it, 0);
        mbar_wait(bar_full + 8 * sl, (it >> 2) & 1);
        TS(it);
        const uint32_t a = sb + sl * SLOT;
        const uint4 v0 = ldsm4(a + sxo), v1 = ldsm4((a + sxo) ^ 64), w0 = ldsm4t(a + swo), w1 = ldsm4t(a + swo + (ch < 12 ? 12288 : 4096));
        if (lane + (int)((v0.x & v1.x & w0.x & w1.x) == 0x7fc17fc1u && (v0.x | v1.x) == 0u) < 2) mbar_arrive_cta(bar_empty + 8 * sl, lane);
        const uint32_t vv[8] = {v0.x, v0.y, v0.z, v0.w, v1.x, v1.y, v1.z, v1.w}, ww[8] = {w0.x, w0.y, w0.z, w0.w, w1.x, w1.y, w1.z, w1.w};
#pragma unroll
        for (int i = 0; i < 8; i++) {
          const float d = bf_lo(vv[i]), e = bf_hi(vv[i]);
          ps += d + e; pq = fmaf(d, d, pq); pq1 = fmaf(e, e, pq1); pc += bf_lo(ww[i]) + bf_hi(ww[i]);
        }
      }
      pq += pq1;
      ps += shx(ps, 1); pq += shx(pq, 1); pc += shx(pc, 1);
      ps += shx(ps, 2); pq += shx(pq, 2); pc += shx(pc, 2);
      if ((lane & 3) == 0) stg_pkt(pp, __float_as_uint(ps), __float_as_uint(pq), tag, 0u);
      if ((lane & 3) == 1) stg_rlx64(pp, __float_as_uint(pc), tag);
      asm volatile("bar.arrive 2, 192;" ::: "memory");
      if (warp == 12) {
        const uint4* const hp = hold(&g_own[max(cid - 16, 0)].halo[0][lane]);
        mbar_wait(bar_aux, 0);
        mbar_wait(bar_go, 0);
        uint4 v[5] = {};
        int guard = SPIN_MAX;
        if (P > 0) {
          do {
#pragma unroll
            for (int i = 0; i < 5; i++) v[i] = ldg_pkt(hp + 32 * i);
          } while (anyw(v[0].x == SENT || v[1].x == SENT || v[2].x == SENT || v[3].x == SENT || v[4].x == SENT) && --guard > 0);
        }
#pragma unroll
        for (int i = 0; i < 5; i++) *(uint4*)(smem + OFF_O + 10240 + i * 512 + lane * 16) = v[i];
        mbar_arrive(bar_kv);
      }
#undef TS_T
#define TS_T 32
    } else if (warp < 11) {
      const int l7 = lane & 7, hk = lane >> 4;
      if (warp == 10 && elect()) {
#pragma unroll 1
        for (int i = 0; i < 36; i++) mbar_init(bar_o + 8 * i, i < 14 || i == 30 ? 1 : i < 34 ? 4 : 128);
      }
      {
        const int t0 = clk();
#pragma unroll 1
        for (int i = PF_FIRST; i < 6; i++) {
          while (clk() - t0 < PF_T0 + (i - PF_FIRST) * PF_CLK) __nanosleep(20);
          pf_slice(warp == 9 ? min(i, 4) : i + 4);
        }
      }
      mbar_wait(bar_tag, 0);
      const uint32_t tag = __float_as_uint(lds32f(sb + OFF_WR + 324));
      bar_sync(2, 192);
      TS(0);
      int guard = SPIN_MAX;
      if (warp == 9) {
        const uint4* sp = &g_own[mt * 8].st1[lane];
        const uint4* hp = &g_own[max(mt - 2, 0) * 8 + 3].st1[24 + l7];
        uint4 a[5], b[5];
        bool bad;
        do {
          __nanosleep(AUX_NS);
          bad = false;
#pragma unroll
          for (int i = 0; i < 5; i++) {
            const uint4* q = i < 4 ? sp + i * (sizeof(Own) / 16) : hp;
            a[i] = ldg_pkt(q); b[i] = ldg_pkt(q + 4 * sizeof(Own) / 16);
          }
#pragma unroll
          for (int i = 0; i < 5; i++) bad |= a[i].z != tag || b[i].z != tag;
        } while (anyw(bad) && --guard);
        TS(1);
#pragma unroll
        for (int i = 0; i < 5; i++) {
          const float m = (__uint_as_float(a[i].x) + __uint_as_float(b[i].x)) * (1.f / 640.f);
          const float rs = rsq(fmaxf(fmaf(-m, m, (__uint_as_float(a[i].y) + __uint_as_float(b[i].y)) * (1.f / 640.f)), 0.f) + 1e-5f);
          ((float*)(smem + OFF_RS))[i < 4 ? 8 + lane + 32 * i : l7] = rs;
          const uint32_t mh = pack_bf16(-m, -m);
          const float ml = -m - bf_lo(mh);
          if (i < 4) ((uint2*)(smem + OFF_MN))[lane + 32 * i] = make_uint2(mh, pack_bf16(ml, ml));
        }
      } else {
        const uint4* cp = (const uint4*)g_own[hk * 8 + g].cs + (lane & 15);
        uint4 a[4], b[4];
        bool bad;
        do {
          __nanosleep(AUX_NS);
          bad = false;
#pragma unroll
          for (int i = 0; i < 4; i++) { a[i] = ldg_pkt(cp + i * 32 * sizeof(Own) / 16); b[i] = ldg_pkt(cp + (i * 32 + 16) * sizeof(Own) / 16); }
#pragma unroll
          for (int i = 0; i < 4; i++) bad |= a[i].y != tag || a[i].w != tag || b[i].y != tag || b[i].w != tag;
        } while (anyw(bad) && --guard);
#pragma unroll
        for (int i = 0; i < 4; i++)
          if (i < 3 || lane < 24) {
            const float c0 = __uint_as_float(a[i].x) + __uint_as_float(b[i].x), c1 = __uint_as_float(a[i].z) + __uint_as_float(b[i].z);
            const uint32_t hi = pack_bf16(c0, c1), w0 = pack_bf16(c0, c0 - bf_lo(hi)), w1 = pack_bf16(c1, c1 - bf_hi(hi));
            uint4* const d = (uint4*)(smem + OFF_CS) + 2 * (lane + 32 * i);
            d[0] = make_uint4(w0, w0, 0, 0); d[1] = make_uint4(w1, w1, 0, 0);
          }
        asm volatile("fence.proxy.async.shared::cta;" ::: "memory");
      }
      mbar_arrive(bar_aux);
      TS(2);
      const int fo = warp - 9, wq = fo ? 1 - LEAD : LEAD;
      const uint4* const fp = hold(g_own[mt * 8 + wq * 4].cnt);
      const char* src = hold((const char*)g_o[mt * 2 + wq]);
      if (elect()) {
        const uint32_t bo = bar_o + fo * 56;
#pragma unroll
        for (int i = 0; i < 7; i++) mbar_expect_tx(bo + 8 * i, 10240);
        mbar_wait(bar_st + 8 * fo, 0);
        uint32_t cv;
        asm volatile("atom.relaxed.gpu.global.add.u32 %0, [%1], 1;" : "=r"(cv) : "l"(fp) : "memory");
        cv++;
        while (cv != 8u && --guard > 0) cv = ldg_rlx32(fp);
        asm volatile("fence.proxy.async.global;" ::: "memory");
        TS(6);
        uint32_t dst = sb + OFF_O + 20480;
#pragma unroll 1
        for (int i = 0; i < 7; i++) {
          if (fo || i == 5) mbar_wait(fo ? bar_oc + 8 * i : bar_st + 8, 0);
          if (i == g) src += 10240;
          asm volatile("cp.async.bulk.shared::cluster.global.mbarrier::complete_tx::bytes [%0], [%1], 10240, [%2];" :: "r"(dst), "l"(src), "r"(bo + 8 * i) : "memory");
          src += 10240;
          dst += i == 4 ? -61440 : 10240;
        }
      }
#undef TS_T
#define TS_T 96
    } else {
      if ((sb & 0x3FFFF) != D0 * 16) __trap();
#pragma unroll 1
      for (int i = lane; i < 232; i += 32) { const uint32_t f = i < 208 ? SENT : 0u; ((uint4*)(smem + OFF_CS))[i] = make_uint4(f, f, f, f); }
      asm volatile("fence.proxy.async.shared::cta;" ::: "memory");
      if (elect()) mbar_arrive(bar_rst);
      mbar_wait(bar_full + 8 * ((HK_IT + 2) & 3), 0);
      TS(4);
      const uint32_t epoch = ldg_rlx32(g_epoch + cid) + 1;
      uint32_t wv[10];
#pragma unroll
      for (int i = 0; i < 10; i++) wv[i] = __ldg((const uint32_t*)w_r + lane + 32 * i);
      float s = 0.f;
#pragma unroll
      for (int i = 0; i < 10; i++) {
        s += bf_lo(wv[i]) + bf_hi(wv[i]);
        const unsigned u = i < 8 ? lane + 32 * (i - g) : lane + 32 * (i - 7) - g * 8;
        if (i < 8 ? u < 32u : u - 32u < 8u) *(float2*)(smem + OFF_WR + ((u & 3) * 10 + (u >> 2)) * 8) = make_float2(bf_lo(wv[i]), bf_hi(wv[i]));
      }
#pragma unroll
      for (int m = 1; m < 32; m <<= 1) s += shx(s, m);
      *(float2*)(smem + OFF_WR + 320) = make_float2(s, __uint_as_float(epoch * 0x9E3779B8u));
      g_epoch[cid] = epoch;
      TS(3);
      if (elect()) mbar_arrive(bar_tag);
      TS(5);
#pragma unroll 1
      for (int i = 0; i < 14; i++) {
        const int m = (i + 2) >> 2, n = m == 0 ? 50 : 120, t = (m == 0 ? i : (i + 2) & 3) * 32 + lane;
        const char* b = (const char*)(m == 0 ? wo : m == 1 ? w_up : m == 2 ? w_down : w_gate);
        if (t < n) pf_l2(b + (bid * n + t) * 128);
        __nanosleep(PFW_NS);
      }
      const uint4* const kp = hold(g_own[1].cnt);
      const uint4* const cb = hold(&g_x.cand[0][lane >> 2][lane & 3]);
      bar_sync(3, 64);
      uint4 k;
      uint32_t have = SENT;
      int guard = SPIN_MAX;
      while (true) {
        k = ldg_pkt(kp);
        if (ffn1) {
          while (k.x != have && --guard > 0) {
            const uint32_t tk = 2047u - (k.x & 2047u), want = k.x;
            const uint4* q = cb + ((tk >> 8) * 16 + (tk & 1) * 8 + ((tk >> 5) & 7)) * 192;
            const uint4 c0 = ldg_pkt(q), c1 = ldg_pkt(q + 4); const uint2 c2 = ldg_rlx64(q + 8);
            k = ldg_pkt(kp);
            *(uint4*)(smem + OFF_HN + lane * 16) = c0; *(uint4*)(smem + OFF_HN + 512 + lane * 16) = c1; *(uint2*)(smem + OFF_HN + 1024 + lane * 16) = c2;
            have = anyw(c0.x == SENT || c1.x == SENT || c2.x == SENT) ? SENT : want;
          }
        } else if (KEY_NS && k.z != 128u) __nanosleep(KEY_NS);
        if (k.z == 128u || --guard <= 0) break;
      }
      *(uint2*)(smem + OFF_WR + 336) = make_uint2(k.x, k.y);
      mbar_arrive(bar_win);
      TS(7);
    }
#undef TS_T
  } else {
#define TS_T 0
    asm volatile("setmaxnreg.inc.sync.aligned.u32 %0;" :: "n"(REG_C));
    const int wg = warp >> 2, w4 = warp & 3, r = lane >> 2, c = lane & 3;
    float acc[120];
    uint4 xr[5] = {};
    const uint32_t xa = pin(sb + (warp * 16 + (lane & 15)) * 128 + ((lane >> 4) ^ (lane & 7)) * 16);
    const int fol = wg != LEAD;
    const bool first = (P == 0) && (warp == 0);
    const uint32_t kvs = sb + OFF_O + fol * 10240 + w4 * 2560 + lane * 16;
    uint4* const kvd = hold(warp == 7 ? &g_own[cid].halo[0][lane] : (uint4*)(smem + (warp == 3 ? OFF_O + lane * 16 : kvs - sb + 2560)));
    uint4* const odst = hold(&g_o[mt * 2 + wg][g][w4 * 160]);
    uint32_t m0 = 0, m1 = 0;
    const uint32_t mna = pin(sb + OFF_MN + (warp * 16 + r) * 8 + c * 4);
    const int itx = ord == 0 || g == 0 ? g : g < 5 ? g + 5 : g - 4, ity = (ord ? 4 : 8) + (g >> 2);
    uint32_t rel;
    asm volatile("mapa.shared::cluster.u32 %0, %1, %2;" : "=r"(rel) : "r"(bar_empty), "r"(tid & 1));
    const uint32_t xa1 = pin(xa ^ 32), xa2 = pin(xa ^ 64), xa3 = pin(xa ^ 96), xb = pin(xa ^ ((g & 3) * 32));
    const uint32_t da0 = wg * 512;
    const bool rel2 = lane < 2, rel6 = lane < 2 + 2 * (warp & 1);
    const uint32_t zero = __shfl_sync(0xffffffffu, (uint32_t)(uintptr_t)x & 8u, 0);
    mbar_wait(bar_half, 0);
    TS(13);
    wgmma_fence();
#pragma unroll
    for (int it = 0; it < 10; it++) {
      const int s = (it + 2) & 3;
      if (it == 9 && fol) bar_sync(10, 256);
#pragma unroll
      for (int kk = 0; kk < 4; kk++) {
        if (kk == 2 && it > 0) {
          wgmma_commit();
          wgmma_wait<1>();
          const uint32_t ra = ((xr[0].x ^ xr[1].x ^ xr[2].x ^ xr[3].x ^ xr[4].x) & zero) | rel;
          if (it == 1 ? (ord ? rel6 : rel2) : it == 6 ? (ord ? rel2 : rel6) : it < 6 ? rel2 : rel6)
            asm volatile("mbarrier.arrive.shared::cluster.b64 _, [%0];" :: "r"(ra + 8 * ((it + 1) & 3)) : "memory");
        }
        if (kk == 2) {
          ldsm4_if(xr[0], xa, s * SLOT, it == itx); ldsm4_if(xr[1], xa1, s * SLOT, it == itx);
          ldsm4_if(xr[2], xa2, s * SLOT, it == itx); ldsm4_if(xr[3], xa3, s * SLOT, it == itx);
          if ((it & 6) == 4 || it >= 8) ldsm4_if(xr[4], xb, s * SLOT, it == ity);
        }
        if (kk == AK && it == 9) {
          mbar_wait(bar_aux, 0);
          TS(3);
          if (c < 2) { m0 = __float_as_uint(lds32f(mna)); m1 = __float_as_uint(lds32f(mna + 64)); }
          if (!fol) bar_sync(11, 256);
        }
        if (kk == 2 && it < NSPLIT) mbar_wait(bar_full + 8 * s, 0);
        const uint64_t da = mk64(da0 + (D0 + s * (SLOT >> 4) + kk * 2 + (1 << 16)), 0x40000040u);
        wgmma_n64hi_ss(acc, da, mk64(D0 + s * (SLOT >> 4) + 2560 + kk * 128 + (32 << 16), 0xC0000010u), (it | kk) != 0);
        wgmma_n176lo_ss(acc, da, mk64(D0 + s * (SLOT >> 4) + 1024 + kk * 384 + (128 << 16), 0x40000040u), (it | kk) != 0);
      }
      wgmma_commit();
      if (it == 8 && fol) asm volatile("bar.arrive 11, 256;" ::: "memory");
      if (it < 9) {
        if (it + 1 < NSPLIT) mbar_wait(bar_half + 8 * (it + 1), 0);
        else mbar_wait(bar_full + 8 * ((it + 3) & 3), ((it + 1) >> 2) & 1);
        if (it < 8) TS(14 + it);
      }
    }
    {
      const uint64_t dc = make_desc(D0 * 16 + OFF_CS, 0, 128, 0);
      wgmma_fence();
      wgmma_n64hi_rk(acc, m0, m1, 0u, 0u, dc + 176, 1);
      wgmma_n176lo_rk(acc, m0, m1, 0u, 0u, dc, 1);
      wgmma_commit();
      if (!fol) asm volatile("bar.arrive 10, 256;" ::: "memory");
    }
    const uint32_t stb = sb + OFF_RS + warp * 64;
    const float rlo = lds32f(stb + (8 + r) * 4), rhi = lds32f(stb + (16 + r) * 4);
    wgmma_wait<0>();
#pragma unroll
    for (int i = 0; i < 120; i++) asm volatile("" : "+f"(acc[i]) :: "memory");
    if (fol && lane == 0) mbar_arrive(bar_go);
    TS(2);
    uint32_t Qlo[10], Qhi[10], Klo[10], Khi[10], Vlo[10], Vhi[10];
#define CONV_HI(ROT) _Pragma("unroll") for (int t = 0; t < 10; t++) { \
      const int k = KT((t + ROT) % 10), v = VT((t + ROT) % 10); \
      Khi[t] = pack_bf16(acc[4 * k + 2], acc[4 * k + 3]); \
      Vhi[t] = pack_bf16(acc[4 * v + 2] * rhi, acc[4 * v + 3] * rhi); }
    if (godd) { CONV_HI(8) } else { CONV_HI(0) }
    st_pkt(kvd, Khi[0], Khi[1], Khi[3], Khi[4]);
    st_pkt(kvd + 32, Khi[5], Khi[6], Khi[8], Khi[9]);
    st_pkt(kvd + 64, Khi[2], Khi[7], Vhi[0], Vhi[1]);
    st_pkt(kvd + 96, Vhi[2], Vhi[3], Vhi[4], Vhi[5]);
    st_pkt(kvd + 128, Vhi[6], Vhi[7], Vhi[8], Vhi[9]);
    if (warp < 7) mbar_arrive(bar_kv + ((warp + 1) >> 2) * 8);
    if (!ODDS) mbar_wait(bar_aux, 0);
#define CONV_LO(ROT) _Pragma("unroll") for (int t = 0; t < 10; t++) { \
      const int q = QT((t + ROT) % 10), k = KT((t + ROT) % 10), v = VT((t + ROT) % 10); \
      Vhi[t] = movm(Vhi[t]); \
      Klo[t] = pack_bf16(acc[4 * k], acc[4 * k + 1]); \
      Vlo[t] = movm(pack_bf16(acc[4 * v] * rlo, acc[4 * v + 1] * rlo)); \
      Qlo[t] = pack_bf16(acc[4 * q], acc[4 * q + 1]); \
      Qhi[t] = pack_bf16(acc[4 * q + 2], acc[4 * q + 3]); }
    if (godd) { CONV_LO(8) } else { CONV_LO(0) }
    const bool in0 = 2 * c <= r, in1 = 2 * c + 1 <= r;
    const uint32_t mL = (in0 ? 0xffffu : 0u) | (in1 ? 0xffff0000u : 0u);
    const float qs = 0.22360679774997896f * 1.4426950408889634f;
    const uint32_t kb0 = stb + (2 * c + (in0 ? 8 : 0)) * 4, kb1 = stb + (2 * c + 1 + (in1 ? 8 : 0)) * 4;
    const float scl0 = lds32f(kb0) * rlo * qs, scl1 = lds32f(kb1) * rlo * qs;
    const float sch0 = lds32f(kb0 + 32) * rhi * qs, sch1 = lds32f(kb1 + 32) * rhi * qs;
    const float bias0 = (first && !in0) ? -INFINITY : 0.f, bias1 = (first && !in1) ? -INFINITY : 0.f;
    const int slot = mt * 8 + warp;
    int guard = SPIN_MAX;
    uint4 pv[5];
    const bool cA = c < 2, nA = r < 4;
    TS(0);
    mbar_wait(bar_go + fol * 8, 0);
    TS(23);
    uint32_t qe[4][2];
    float sl0[4], sl1[4], th0[4], th1[4];
#pragma unroll
    for (int hd = 0; hd < 4; hd++) {
      const int ta = 5 * (hd >> 1) + 3 * (hd & 1), ts = 5 * (hd >> 1) + 2;
      const bool mine = (hd & 1) ? !cA : cA;
      qe[hd][0] = mine ? Qlo[ts] : 0u; qe[hd][1] = mine ? Qhi[ts] : 0u;
      float sl[4], sh[4];
      mma_k24(sl, Qlo[ta], Qhi[ta], Qlo[ta + 1], Qhi[ta + 1], Klo[ta], Klo[ta + 1], qe[hd][0], qe[hd][1], Klo[ts]);
      mma_k24(sh, Qlo[ta], Qhi[ta], Qlo[ta + 1], Qhi[ta + 1], Khi[ta], Khi[ta + 1], qe[hd][0], qe[hd][1], Khi[ts]);
      th0[hd] = (in0 ? sh[2] : sl[2]) * sch0; th1[hd] = (in1 ? sh[3] : sl[3]) * sch1;
      float mh = fmaxf(th0[hd], th1[hd]);
      mh = fmaxf(mh, shx(mh, 1)); mh = fmaxf(mh, shx(mh, 2));
      th0[hd] -= mh; th1[hd] -= mh;
      sl0[hd] = sl[0]; sl1[hd] = sl[1];
    }
    mbar_wait(bar_kv + wg * 8, 0);
    TS(4);
#pragma unroll
    for (int j = 0; j < 5; j++) pv[j] = lds128(kvs + 512 * j);
    const uint32_t Kp[10] = {pv[0].x, pv[0].y, pv[2].x, pv[0].z, pv[0].w, pv[1].x, pv[1].y, pv[2].y, pv[1].z, pv[1].w};
    const uint32_t Vp[10] = {movm(pv[2].z), movm(pv[2].w), movm(pv[3].x), movm(pv[3].y), movm(pv[3].z), movm(pv[3].w), movm(pv[4].x), movm(pv[4].y), movm(pv[4].z), movm(pv[4].w)};
    const uint32_t ONES = 0x3f803f80u;
    uint32_t of[20];
#pragma unroll
    for (int hp = 0; hp < 2; hp++) {
      float o[6][4];
#pragma unroll
      for (int hh = 0; hh < 2; hh++) {
        const int hd = 2 * hp + hh, ta = 5 * hp + 3 * hh, ts = 5 * hp + 2;
        float sp[4];
        mma_k24(sp, Qlo[ta], Qhi[ta], Qlo[ta + 1], Qhi[ta + 1], Kp[ta], Kp[ta + 1], qe[hd][0], qe[hd][1], Kp[ts]);
        const float tl0 = fmaf(in0 ? sl0[hd] : sp[0], scl0, bias0), tl1 = fmaf(in1 ? sl1[hd] : sp[1], scl1, bias1);
        float ml = fmaxf(tl0, tl1);
        ml = fmaxf(ml, shx(ml, 1)); ml = fmaxf(ml, shx(ml, 2));
        if (HOLD == 1 && hd == 3 && !fol && lane == 0) mbar_arrive(bar_go + 8);
        const uint32_t Pl = pack_bf16(ex2(tl0 - ml), ex2(tl1 - ml)), Ph = pack_bf16(ex2(th0[hd]), ex2(th1[hd]));
        const uint32_t a0 = Pl & mL, a1 = Ph & ~mL, a3 = Ph & mL, ap = Pl & ~mL;
        const bool vm = hh == 0 ? nA : !nA;
        mma_k24(o[3 * hh], a0, a1, 0u, a3, Vlo[ta], Vhi[ta], ap, 0u, Vp[ta]);
        mma_k24(o[3 * hh + 1], a0, a1, 0u, a3, Vlo[ta + 1], Vhi[ta + 1], ap, 0u, Vp[ta + 1]);
        mma_k24(o[3 * hh + 2], a0, a1, 0u, a3, vm ? Vlo[ts] : ONES, vm ? Vhi[ts] : ONES, ap, 0u, vm ? Vp[ts] : ONES);
      }
      const float il = rcp(cA ? o[5][0] : o[2][0]), ih = rcp(cA ? o[5][2] : o[2][2]);
      const float jl = shx(il, 2), jh = shx(ih, 2);
      const float al = cA ? jl : il, ah = cA ? jh : ih, bl = cA ? il : jl, bh = cA ? ih : jh;
      const int t0 = 5 * hp;
      of[2 * t0]     = pack_bf16(o[0][0] * al, o[0][1] * al); of[2 * t0 + 1] = pack_bf16(o[0][2] * ah, o[0][3] * ah);
      of[2 * t0 + 2] = pack_bf16(o[1][0] * al, o[1][1] * al); of[2 * t0 + 3] = pack_bf16(o[1][2] * ah, o[1][3] * ah);
      of[2 * t0 + 4] = pack_bf16((cA ? o[2][0] : o[5][0]) * jl, (cA ? o[2][1] : o[5][1]) * jl);
      of[2 * t0 + 5] = pack_bf16((cA ? o[2][2] : o[5][2]) * jh, (cA ? o[2][3] : o[5][3]) * jh);
      of[2 * t0 + 6] = pack_bf16(o[3][0] * bl, o[3][1] * bl); of[2 * t0 + 7] = pack_bf16(o[3][2] * bh, o[3][3] * bh);
      of[2 * t0 + 8] = pack_bf16(o[4][0] * bl, o[4][1] * bl); of[2 * t0 + 9] = pack_bf16(o[4][2] * bh, o[4][3] * bh);
    }
    {
      const uint32_t os = sb + OFF_O + (fol ? 0 : 20480) + w4 * 2560, oa = os + ((lane >> 3) & 1) * 1280 + (lane >> 4) * 128 + (lane & 7) * 16;
#pragma unroll
      for (int s = 0; s < 5; s++) {
        stsm4(oa + s * 256, of[4 * s], of[4 * s + 1], of[4 * s + 2], of[4 * s + 3]);
        if (s == 0 && (fol || HOLD == 2) && lane == 0) mbar_arrive(bar_go + 8 + 8 * fol);
      }
      asm volatile("fence.proxy.async.shared::cta;" ::: "memory");
      __syncwarp();
      asm volatile("{\n.reg .pred q;\nelect.sync _|q, 0xffffffff;\n@q cp.async.bulk.global.shared::cta.bulk_group [%0], [%1], 2560;\ncp.async.bulk.commit_group;\n}\n" :: "l"(odst), "r"(os) : "memory");
    }
    TS(5);
    float h[40];
#pragma unroll
    for (int s = 0; s < 5; s++) {
      const uint4 v = xr[s];
      h[8 * s] = bf_lo(v.x); h[8 * s + 1] = bf_hi(v.x); h[8 * s + 2] = bf_lo(v.y); h[8 * s + 3] = bf_hi(v.y);
      h[8 * s + 4] = bf_lo(v.z); h[8 * s + 5] = bf_hi(v.z); h[8 * s + 6] = bf_lo(v.w); h[8 * s + 7] = bf_hi(v.w);
    }
    asm volatile("cp.async.bulk.wait_group 0;" ::: "memory");
    __syncwarp();
    if (lane == 0) mbar_arrive(bar_st + 8 * fol);
    TS(22);
    mbar_wait(bar_full, 0); mbar_wait(bar_full + 8, 0); mbar_wait(bar_full + 16, 1);
    mbar_wait(bar_go + 16, 0);
    const uint64_t dwo = make_desc(D0 * 16, 5120, 512, 2);
    wgmma_fence();
#pragma unroll
    for (int s = 0; s < 5; s++) wgmma_n80_rs(h, of[4 * s], of[4 * s + 1], of[4 * s + 2], of[4 * s + 3], dwo + g * 960 + s * 64, 1);
    wgmma_commit();
    TS(6);
    const bool odd = c & 1;
    uint4* const sp = hold(&g_own[slot].st2[r + (odd ? 8 : 0)]);
    uint4* const cdp = hold(&g_x.cand[slot][g][0]);
    uint4* const kcp = hold(g_own[1].cnt);
    float wr[20];
#pragma unroll
    for (int j = 0; j < 5; j++) {
      const uint4 v = lds128(sb + OFF_WR + c * 80 + j * 16);
      wr[4 * j] = __uint_as_float(v.x); wr[4 * j + 1] = __uint_as_float(v.y); wr[4 * j + 2] = __uint_as_float(v.z); wr[4 * j + 3] = __uint_as_float(v.w);
    }
    const float wsum = lds32f(sb + OFF_WR + 320);
    const uint32_t bo = bar_o + fol * 56;
#pragma unroll
    for (int i = 0; i < 7; i++) {
      mbar_wait(bo + 8 * i, 0);
      if (i == 0) TS(1);
      const uint32_t da = D0 + OFF_O / 16 + (8 << 16) + ((i + 2) % 7) * 640, db = D0 + (320 << 16) + (i >= g ? i + 1 : i) * 960;
      wgmma_fence();
#pragma unroll
      for (int s = 0; s < 5; s++) wgmma_n80_ss(h, mk64(da + s * 16, 80u), mk64(db + s * 64, 0x80000020u), 1);
      wgmma_commit();
      wgmma_wait<1>();
      if (lane == 0 && i > 0) mbar_arrive(bo + 104 + 8 * i);
    }
    const int tok0 = P * 256 + 32 * warp + rank;
    wgmma_wait<0>();
#pragma unroll
    for (int i = 0; i < 40; i++) asm volatile("" : "+f"(h[i]) :: "memory");
    if (lane == 0) mbar_arrive(bo + 160);
    TS(7);
    float mean, rstd, rr;
    bool pub;
    {
      float l1 = 0.f, l2 = 0.f, l3 = 0.f, h1 = 0.f, h2 = 0.f, h3 = 0.f;
#pragma unroll
      for (int j = 0; j < 10; j++) {
        l1 += h[4 * j] + h[4 * j + 1]; h1 += h[4 * j + 2] + h[4 * j + 3];
        l2 = fmaf(h[4 * j], h[4 * j], l2); l2 = fmaf(h[4 * j + 1], h[4 * j + 1], l2);
        h2 = fmaf(h[4 * j + 2], h[4 * j + 2], h2); h2 = fmaf(h[4 * j + 3], h[4 * j + 3], h2);
        l3 = fmaf(h[4 * j], wr[2 * j], l3); l3 = fmaf(h[4 * j + 1], wr[2 * j + 1], l3);
        h3 = fmaf(h[4 * j + 2], wr[2 * j], h3); h3 = fmaf(h[4 * j + 3], wr[2 * j + 1], h3);
      }
      float s1 = (odd ? h1 : l1) + shx(odd ? l1 : h1, 1), s2 = (odd ? h2 : l2) + shx(odd ? l2 : h2, 1), s3 = (odd ? h3 : l3) + shx(odd ? l3 : h3, 1);
      s1 += shx(s1, 2); s2 += shx(s2, 2); s3 += shx(s3, 2);
      uint4 p0;
      float o1 = 0.f, o2 = 0.f, o3 = 0.f, oc = 7.f;
      asm volatile("{\n.reg .pred q;\nsetp.lt.u32 q, %9, 2;\n@q atom.relaxed.gpu.global.add.v4.f32 {%0, %1, %2, %3}, [%4], {%5, %6, %7, %8};\n}\n"
                   : "+f"(o1), "+f"(o2), "+f"(o3), "+f"(oc) : "l"(sp), "f"(s1), "f"(s2), "f"(s3), "f"(1.f), "r"(c) : "memory");
      const uint32_t last = __ballot_sync(0xffffffffu, oc == 7.f);
      pub = last & 1;
      p0.x = __float_as_uint(__shfl_sync(0xffffffffu, o1 + s1, lane & 29)); p0.y = __float_as_uint(__shfl_sync(0xffffffffu, o2 + s2, lane & 29));
      p0.z = __float_as_uint(__shfl_sync(0xffffffffu, o3 + s3, lane & 29));
      if (last != 0xffffffffu)
      do { p0 = ldg_pkt(sp); } while (anyw(p0.w != 0x41000000u) && --guard > 0);
      mean = __uint_as_float(p0.x) * (1.f / 640.f);
      rstd = rsq(fmaxf(fmaf(-mean, mean, __uint_as_float(p0.y) * (1.f / 640.f)), 0.f) + 1e-5f);
      rr = fmaf(-mean, wsum, __uint_as_float(p0.z)) * rstd;
    }
    TS(8);
    const uint32_t kk = ord_key(rr), kmax = __reduce_max_sync(0xffffffffu, kk);
    const int L = __ffs(__ballot_sync(0xffffffffu, kk == kmax)) - 1;
    const int crow = (L >> 2) + 8 * (L & 1);
    asm volatile("{\n.reg .pred q;\nsetp.ne.u32 q, %2, 0;\n@q red.relaxed.gpu.global.max.u64 [%0], %1;\n@q red.relaxed.gpu.global.add.u32 [%0 + 8], 1;\n}\n"
                 :: "l"(kcp), "l"(mk64(2047 - tok0 - 2 * crow, kmax)), "r"((int)(pub && lane == 0)) : "memory");
    if (warp == g) asm volatile("bar.arrive 3, 64;" ::: "memory");
    const uint32_t stg = sb + (fol ? OFF_O : g * 15360) + w4 * 2560;
    uint4 held;
    {
      const float om = shx(mean, 1), os = shx(rstd, 1);
      const float rl = odd ? os : rstd, rh = odd ? rstd : os;
      const float bl = -(odd ? om : mean) * rl, bh = -(odd ? mean : om) * rh, al = 1.f + rl, ah = 1.f + rh;
      if ((L >> 2) == r) {
        const bool chi = L & 1;
        const float rc = chi ? rh : rl, bc = chi ? bh : bl;
        uint32_t n[10];
#pragma unroll
        for (int j = 0; j < 10; j++) n[j] = pack_bf16(fmaf(chi ? h[4 * j + 2] : h[4 * j], rc, bc), fmaf(chi ? h[4 * j + 3] : h[4 * j + 1], rc, bc));
        uint4* d = cdp + c;
        stg_pkt(d, n[0], n[1], n[2], n[3]); stg_pkt(d + 4, n[4], n[5], n[6], n[7]); stg_rlx64(d + 8, n[8], n[9]);
      }
      mbar_wait(bar_oc + 56, 0);
      const uint32_t fa = stg + (lane & 15) * 160 + (lane >> 4) * 16;
#pragma unroll
      for (int s = 0; s < 5; s++)
        stsm4(fa + s * 32, pack_bf16(fmaf(h[8 * s], al, bl), fmaf(h[8 * s + 1], al, bl)), pack_bf16(fmaf(h[8 * s + 2], ah, bh), fmaf(h[8 * s + 3], ah, bh)),
              pack_bf16(fmaf(h[8 * s + 4], al, bl), fmaf(h[8 * s + 5], al, bl)), pack_bf16(fmaf(h[8 * s + 6], ah, bh), fmaf(h[8 * s + 7], ah, bh)));
      __syncwarp();
      held = lds128(stg + crow * 160 + min(lane, 9) * 16);
      if (lane < 10) stg_pkt(cdp + 12 + lane, held.x, held.y, held.z, held.w);
    }
    TS(9);
    mbar_wait(bar_ffn, 0);
    const uint32_t red = sb + OFF_RED;
    if (ffn1) {
      uint4 w1[4][5];
      {
        const int k = (lane & 7) + (lane >> 4) * 8;
        const uint32_t a1 = sb + k * 64, sw = ((lane >> 3) & 1) ^ ((lane >> 1) & 3);
#pragma unroll
        for (int s = 0; s < 5; s++)
#pragma unroll
          for (int u = 0; u < 4; u++)
            w1[u][s] = ldsm4t(a1 + (s < 4 ? warp * 4096 + s * 1024 : 32768 + warp * 1024) + (u >> 1) * (40960 + (s == 4 || warp >= 4 ? OFF_W2 - 57344 : 0)) + ((sw ^ (2 * (u & 1))) * 16));
      }
      uint32_t* const ap = hold(g_x.act + fj * 16 + (lane >> 1));
      mbar_wait(bar_win, 0);
      const uint32_t hp = sb + OFF_HN + (warp * 4 + c) * 16;
      const uint4 c0 = lds128(hp), c1 = lds128(hp + 512), c2 = lds128(hp + 1024);
      TS(10);
      float a[4][4];
#pragma unroll
      for (int u = 0; u < 4; u++) {
        a[u][0] = a[u][1] = a[u][2] = a[u][3] = 0.f;
        mma_acc(a[u], w1[u][0], c0.x, c0.y); mma_acc(a[u], w1[u][1], c0.z, c0.w); mma_acc(a[u], w1[u][2], c1.x, c1.y);
        mma_acc(a[u], w1[u][3], c1.z, c1.w); mma_acc(a[u], w1[u][4], c2.x, c2.y);
      }
      asm volatile("st.shared.v2.f32 [%0], {%1, %2};" :: "r"(red + (warp * 32 + c * 8 + r) * 8),
                   "f"(cA ? (odd ? a[0][2] : a[0][0]) : (odd ? a[1][2] : a[1][0])), "f"(cA ? (odd ? a[2][2] : a[2][0]) : (odd ? a[3][2] : a[3][0])) : "memory");
      bar_sync(1, 256);
      if (warp == 0) {
        float2 t[8];
#pragma unroll
        for (int i = 0; i < 8; i++) t[i] = lds64f(red + (i * 32 + lane) * 8);
        const float s = ((t[0].x + t[1].x) + (t[2].x + t[3].x)) + ((t[4].x + t[5].x) + (t[6].x + t[7].x));
        const float u = ((t[0].y + t[1].y) + (t[2].y + t[3].y)) + ((t[4].y + t[5].y) + (t[6].y + t[7].y));
        const float av = s * u * rcp(1.f + ex2(-1.4426950408889634f * s));
        const float an = shx(av, 1);
        if (!odd) stg_rlx32(ap, pack_bf16(av, an));
      }
      bar_sync(1, 256);
      TS(11);
    }
    char* const ob2 = (char*)(out + tok0 * 640 + g * 64);
    const int remo = 896 - 96 * g;
    {
      char* const q0 = ob2 + (lane >> 3) * 2560 + (lane & 7) * 16;
      const uint32_t s0 = stg + (lane >> 3) * 160 + (lane & 7) * 16;
#pragma unroll
      for (int s = 0; s < 4; s++) stg128_if(4 * s + (lane >> 3) != crow, q0 + s * 10240, lds128(s0 + s * 640));
      stg128_if((lane >> 1) != crow, ob2 + (lane >> 1) * 2560 + (lane & 1) * 16 + 128 + remo, lds128(stg + (lane >> 1) * 160 + (lane & 1) * 16 + 128));
    }
    mbar_wait(bar_win, 0);
    uint4 win = lds128(sb + OFF_WR + 336);
    win.z = win.y; win.y = 2047u - (win.x & 2047u); win.x = (win.y >> 8) * 16 + (win.y & 1) * 8 + ((win.y >> 5) & 7);
    stg128_if(win.x != slot && lane < 10, ob2 + crow * 2560 + lane * 16 + (lane < 8 ? 0 : remo), held);
    if (!ffn1) {
      TS(10);
      uint4 w2[6];
      const uint32_t a2 = sb + OFF_W2 + (warp * 192 + 8 * (((lane >> 3) & 1) * 4 + ((lane & 7) >> 1)) + 2 * (lane >> 4) + (lane & 1)) * 16;
#pragma unroll
      for (int s = 0; s < 6; s++) w2[s] = ldsm4t(a2 + (s >> 1) * 1024 + (s & 1) * 64);
      const uint4* p = (const uint4*)(g_x.act + warp * 96) + (r & 1) * 4 + c;
      const uint32_t* pb = (const uint32_t*)&g_x.cand[win.x][fj < 64 ? fj >> 3 : (fj - 64) >> 1][fj < 64 ? 12 + (fj & 7) : 20 + (fj & 1)] + c;
      uint32_t* const op = hold((uint32_t*)(out + win.y * 640 + fj * 8) + c);
      const float sg = rcp(1.f + ex2(-1.4426950408889634f * __uint_as_float(win.z ^ ((uint32_t)((int32_t)~win.z >> 31) | 0x80000000u))));
      uint4 c0, c1, c2; uint32_t bw;
      if (ACT_NS) __nanosleep(ACT_NS);
      do {
        c0 = ldg_pkt(p); c1 = ldg_pkt(p + 8); c2 = ldg_pkt(p + 16); bw = ldg_rlx32(pb);
      } while (anyw(max(max(max(max(c0.x, c0.y), max(c0.z, c0.w)), max(max(c1.x, c1.y), max(c1.z, c1.w))), max(max(max(c2.x, c2.y), max(c2.z, c2.w)), bw)) == SENT) && --guard > 0);
      TS(11);
      float a[4] = {0.f, 0.f, 0.f, 0.f}, b[4] = {0.f, 0.f, 0.f, 0.f}, d[4] = {0.f, 0.f, 0.f, 0.f};
      mma_acc(a, w2[0], c0.x, c0.y); mma_acc(b, w2[2], c1.x, c1.y); mma_acc(d, w2[4], c2.x, c2.y);
      mma_acc(a, w2[1], c0.z, c0.w); mma_acc(b, w2[3], c1.z, c1.w); mma_acc(d, w2[5], c2.z, c2.w);
      if (c == 0) sts32f(red + (warp * 8 + r) * 4, ((a[0] + a[3]) + (b[0] + b[3])) + (d[0] + d[3]));
      bar_sync(1, 256);
      if (tid < 4) {
        float2 t[8];
#pragma unroll
        for (int i = 0; i < 8; i++) t[i] = lds64f(red + (i * 4 + tid) * 8);
        const float y0 = ((t[0].x + t[1].x) + (t[2].x + t[3].x)) + ((t[4].x + t[5].x) + (t[6].x + t[7].x));
        const float y1 = ((t[0].y + t[1].y) + (t[2].y + t[3].y)) + ((t[4].y + t[5].y) + (t[6].y + t[7].y));
        *op = pack_bf16(fmaf(y0, sg, bf_lo(bw)), fmaf(y1, sg, bf_hi(bw)));
      }
    }
    TS(12);
#undef TS_T
  }
}

typedef CUresult (*EncodeFn)(CUtensorMap*, CUtensorMapDataType, cuuint32_t, void*, const cuuint64_t*, const cuuint64_t*, const cuuint32_t*,
                             const cuuint32_t*, CUtensorMapInterleave, CUtensorMapSwizzle, CUtensorMapL2promotion, CUtensorMapFloatOOBfill);

void make_map(EncodeFn enc, CUtensorMap* m, const void* base, const cuuint64_t* dims, const cuuint64_t* strides, const cuuint32_t* box,
              CUtensorMapSwizzle swz) {
  const cuuint32_t es[3] = {1, 1, 1};
  enc(m, CU_TENSOR_MAP_DATA_TYPE_BFLOAT16, 3, (void*)base, dims, strides, box, es, CU_TENSOR_MAP_INTERLEAVE_NONE, swz,
      CU_TENSOR_MAP_L2_PROMOTION_L2_128B, CU_TENSOR_MAP_FLOAT_OOB_FILL_NONE);
}

}

extern "C" void kernel_launch(void* const* d_in, const int* in_sizes, int n_in, void* d_out, int out_size) {
  const __nv_bfloat16* x = (const __nv_bfloat16*)d_in[0];
  const __nv_bfloat16* wqkv = (const __nv_bfloat16*)d_in[1];
  const __nv_bfloat16* wo = (const __nv_bfloat16*)d_in[2];
  void* fn = nullptr;
  cudaDriverEntryPointQueryResult st;
  cudaGetDriverEntryPoint("cuTensorMapEncodeTiled", &fn, cudaEnableDefault, &st);
  EncodeFn enc = (EncodeFn)fn;
  void* scp = nullptr;
  cudaGetSymbolAddress(&scp, g_scratch);
  Maps tm;
  { const cuuint64_t d[3] = {640, 1024, 2}, s[2] = {2560, 1280}; const cuuint32_t b[3] = {64, 128, 1}; make_map(enc, &tm.x, x, d, s, b, CU_TENSOR_MAP_SWIZZLE_128B); }
  { const cuuint64_t d[3] = {640, 640, 3}, s[2] = {3840, 1280}; const cuuint32_t b[3] = {64, 16, 3}; make_map(enc, &tm.w, wqkv, d, s, b, CU_TENSOR_MAP_SWIZZLE_128B); }
  { const cuuint64_t d[3] = {640, 640, 3}, s[2] = {3840, 1280}; const cuuint32_t b[3] = {16, 16, 3}; make_map(enc, &tm.wr, wqkv, d, s, b, CU_TENSOR_MAP_SWIZZLE_32B); }
  { const cuuint64_t d[3] = {640, 640, 3}, s[2] = {3840, 1280}; const cuuint32_t b[3] = {16, 16, 1}; make_map(enc, &tm.wv, wqkv, d, s, b, CU_TENSOR_MAP_SWIZZLE_32B); }
  { const cuuint64_t d[3] = {32, 640, 20}, s[2] = {1280, 64}; const cuuint32_t b[3] = {32, 80, 2}; make_map(enc, &tm.wo, wo, d, s, b, CU_TENSOR_MAP_SWIZZLE_64B); }
  { const cuuint64_t d[3] = {640, 640, 1}, s[2] = {1280, 819200}; const cuuint32_t b[3] = {16, 80, 1}; make_map(enc, &tm.wor, wo, d, s, b, CU_TENSOR_MAP_SWIZZLE_64B); }
  { const cuuint64_t d[3] = {1536, 640, 1}, s[2] = {3072, 1966080}; const cuuint32_t b[3] = {32, 128, 1};
    make_map(enc, &tm.gate, d_in[5], d, s, b, CU_TENSOR_MAP_SWIZZLE_64B); make_map(enc, &tm.up, d_in[6], d, s, b, CU_TENSOR_MAP_SWIZZLE_64B); }
  { const cuuint64_t d[3] = {640, 1536, 1}, s[2] = {1280, 1966080}; const cuuint32_t b[3] = {8, 128, 1}; make_map(enc, &tm.down, d_in[7], d, s, b, CU_TENSOR_MAP_SWIZZLE_NONE); }
  cudaFuncSetAttribute(fused_kernel, cudaFuncAttributeMaxDynamicSharedMemorySize, SMEM_BYTES);
  fused_kernel<<<128, 512, SMEM_BYTES, cudaStreamPerThread>>>(x, wqkv, wo, (const __nv_bfloat16*)d_in[4], (const __nv_bfloat16*)d_in[5],
                                                              (const __nv_bfloat16*)d_in[6], (const __nv_bfloat16*)d_in[7], (__nv_bfloat16*)d_out, (Scratch*)scp, tm);
}
```

```cpp
#include <cuda_runtime.h>
#include <cuda_bf16.h>
#include <cuda.h>
#include <stdint.h>

#define PFW_NS 50
#define PFW_N 14
#define ACT_NS 100
#define KEY_NS 0
#define AUX_NS 50
#define REG_P 72
#define REG_C 184
#define LEAD 1
#define HK_IT 1
#define F_PER 2
#define F_MAX 8
#define HOLD 2
#define AK 3
#define NSPLIT 3
#define THR_END 4
#define BOUNDED 0
#define TLIGHT 0
#define ATOM2 1

namespace {

constexpr int SLOT    = 49152;
constexpr int OFF_O   = 122880;
constexpr int OFF_W2  = 4 * SLOT;
constexpr int OFF_CS  = OFF_W2 + 24576;
constexpr int OFF_RS  = OFF_CS + 3840;
constexpr int OFF_MN  = OFF_RS + 576;
constexpr int OFF_WR  = OFF_MN + 1024;
constexpr int OFF_RED = OFF_CS;
constexpr int OFF_HN  = OFF_CS + 2048;
constexpr int OFF_PT  = OFF_WR + 352;
constexpr int OFF_BAR = OFF_PT + 768;
constexpr int SMEM_BYTES = OFF_BAR + 424 + 384;
constexpr uint32_t D0 = 1024 >> 4;
constexpr uint32_t SENT = 0xFFFFFFFFu;
constexpr int SPIN_MAX = 1 << 20;

struct Glob {
  uint4 cand[128][8][24];
  uint32_t act[768];
  uint32_t pad[256];
};
constexpr int GLOB_PER_CTA = sizeof(Glob) / 16 / 128;
static_assert(GLOB_PER_CTA * 128 * 16 == sizeof(Glob), "glob size");
struct Own {
  uint4 halo[5][32];
  uint4 st1[32];
  uint2 cs[32];
  uint4 st2[16];
  uint4 cnt[8];
};
struct Scratch {
  Glob x;
  Own own[128];
  uint4 o[32][8][640];
  uint32_t epoch[128];
};
__device__ __align__(128) Scratch g_scratch;
#define g_x (sc->x)
#define g_own (sc->own)
#define g_o (sc->o)
#define g_epoch (sc->epoch)
#define TS(i)

__device__ __forceinline__ void mbar_init(uint32_t bar, uint32_t cnt) { asm volatile("mbarrier.init.shared::cta.b64 [%0], %1;" :: "r"(bar), "r"(cnt) : "memory"); }
__device__ __forceinline__ void mbar_expect_tx(uint32_t bar, uint32_t bytes) { asm volatile("mbarrier.arrive.expect_tx.shared::cta.b64 _, [%0], %1;" :: "r"(bar), "r"(bytes) : "memory"); }
__device__ __forceinline__ void mbar_arrive(uint32_t bar) { asm volatile("mbarrier.arrive.shared::cta.b64 _, [%0];" :: "r"(bar) : "memory"); }
__device__ __forceinline__ void mbar_arrive_cta(uint32_t bar, uint32_t cta) {
  asm volatile("{\n.reg .b32 ra;\nmapa.shared::cluster.u32 ra, %0, %1;\nmbarrier.arrive.shared::cluster.b64 _, [ra];\n}\n" :: "r"(bar), "r"(cta) : "memory");
}
__device__ __forceinline__ void mbar_wait(uint32_t bar, uint32_t parity) {
  asm volatile("{\n.reg .pred p;\nW:\nmbarrier.try_wait.parity.shared::cta.b64 p, [%0], %1;\n@!p bra.uni W;\n}\n" :: "r"(bar), "r"(parity) : "memory");
}
__device__ __forceinline__ void tma_3d(uint32_t dst, const void* tm, uint32_t bar, int c0, int c1, int c2) {
  asm volatile("cp.async.bulk.tensor.3d.shared::cluster.global.mbarrier::complete_tx::bytes [%0], [%1, {%3, %4, %5}], [%2];" :: "r"(dst), "l"(tm), "r"(bar), "r"(c0), "r"(c1), "r"(c2) : "memory");
}
__device__ __forceinline__ void tma_3d_mc(uint32_t dst, const void* tm, uint32_t bar, int c0, int c1, int c2) {
  asm volatile("cp.async.bulk.tensor.3d.shared::cluster.global.mbarrier::complete_tx::bytes.multicast::cluster [%0], [%1, {%3, %4, %5}], [%2], %6;" :: "r"(dst), "l"(tm), "r"(bar), "r"(c0), "r"(c1), "r"(c2), "h"((uint16_t)3) : "memory");
}
__device__ __forceinline__ void wgmma_fence() { asm volatile("wgmma.fence.sync.aligned;" ::: "memory"); }
__device__ __forceinline__ void wgmma_commit() { asm volatile("wgmma.commit_group.sync.aligned;" ::: "memory"); }
template <int N> __device__ __forceinline__ void wgmma_wait() { asm volatile("wgmma.wait_group.sync.aligned %0;" :: "n"(N) : "memory"); }
__device__ __forceinline__ uint64_t make_desc(uint32_t addr, uint32_t lbo, uint32_t sbo, uint32_t swz) {
  return (uint64_t)(((addr & 0x3FFFF) >> 4) | ((lbo >> 4) << 16)) | ((uint64_t)((sbo >> 4) | (swz << 30)) << 32);
}
__device__ __forceinline__ void bar_sync(int id, int n) { asm volatile("bar.sync %0, %1;" :: "r"(id), "r"(n) : "memory"); }
__device__ __forceinline__ void st_pkt(void* p, uint32_t a, uint32_t b, uint32_t c, uint32_t d) {
  asm volatile("st.relaxed.gpu.v4.u32 [%0], {%1, %2, %3, %4};" :: "l"(p), "r"(a), "r"(b), "r"(c), "r"(d) : "memory");
}
__device__ __forceinline__ uint4 ldg_pkt(const void* p) {
  uint4 v; asm volatile("ld.relaxed.gpu.global.v4.u32 {%0, %1, %2, %3}, [%4];" : "=r"(v.x), "=r"(v.y), "=r"(v.z), "=r"(v.w) : "l"(p) : "memory"); return v;
}
__device__ __forceinline__ void stg_pkt(void* p, uint32_t a, uint32_t b, uint32_t c, uint32_t d) {
  asm volatile("st.relaxed.gpu.global.v4.u32 [%0], {%1, %2, %3, %4};" :: "l"(p), "r"(a), "r"(b), "r"(c), "r"(d) : "memory");
}
__device__ __forceinline__ uint32_t ldg_rlx32(const void* p) { uint32_t v; asm volatile("ld.relaxed.gpu.global.u32 %0, [%1];" : "=r"(v) : "l"(p) : "memory"); return v; }
__device__ __forceinline__ uint2 ldg_rlx64(const void* p) { uint2 v; asm volatile("ld.relaxed.gpu.global.v2.u32 {%0, %1}, [%2];" : "=r"(v.x), "=r"(v.y) : "l"(p) : "memory"); return v; }
__device__ __forceinline__ uint32_t pin(uint32_t v) { asm volatile("" : "+r"(v)); return v; }
__device__ __forceinline__ uint64_t mk64(uint32_t lo, uint32_t hi) { return ((uint64_t)hi << 32) | lo; }
template <class T> __device__ __forceinline__ T* hold(T* p) { return (T*)__shfl_sync(0xffffffffu, (unsigned long long)p, threadIdx.x & 31); }
__device__ __forceinline__ void stg128_if(bool q, void* p, const uint4& v) {
  asm volatile("{\n.reg .pred q;\nsetp.ne.u32 q, %5, 0;\n@q st.global.v4.u32 [%0], {%1, %2, %3, %4};\n}\n" :: "l"(p), "r"(v.x), "r"(v.y), "r"(v.z), "r"(v.w), "r"((int)q) : "memory");
}
template <class T> __device__ __forceinline__ T* pin(T* p) { asm volatile("" : "+l"(p)); return p; }
__device__ __forceinline__ void stg_rlx32(void* p, uint32_t v) { asm volatile("st.relaxed.gpu.global.u32 [%0], %1;" :: "l"(p), "r"(v) : "memory"); }
__device__ __forceinline__ void stg_rlx64(void* p, uint32_t a, uint32_t b) { asm volatile("st.relaxed.gpu.global.v2.u32 [%0], {%1, %2};" :: "l"(p), "r"(a), "r"(b) : "memory"); }
__device__ __forceinline__ uint4 ldsm4(uint32_t a) { uint4 v; asm volatile("ldmatrix.sync.aligned.m8n8.x4.shared.b16 {%0, %1, %2, %3}, [%4];" : "=r"(v.x), "=r"(v.y), "=r"(v.z), "=r"(v.w) : "r"(a) : "memory"); return v; }
__device__ __forceinline__ void ldsm4_if(uint4& v, uint32_t a, int off, bool p) {
  asm volatile("{\n.reg .pred q;\nsetp.ne.u32 q, %5, 0;\n@q ldmatrix.sync.aligned.m8n8.x4.shared.b16 {%0, %1, %2, %3}, [%4];\n}\n"
               : "+r"(v.x), "+r"(v.y), "+r"(v.z), "+r"(v.w) : "r"(a + off), "r"((int)p) : "memory");
}
__device__ __forceinline__ uint4 ldsm4t(uint32_t a) { uint4 v; asm volatile("ldmatrix.sync.aligned.m8n8.x4.trans.shared.b16 {%0, %1, %2, %3}, [%4];" : "=r"(v.x), "=r"(v.y), "=r"(v.z), "=r"(v.w) : "r"(a) : "memory"); return v; }
__device__ __forceinline__ void stsm4(uint32_t a, uint32_t x, uint32_t y, uint32_t z, uint32_t w) { asm volatile("stmatrix.sync.aligned.m8n8.x4.shared.b16 [%0], {%1, %2, %3, %4};" :: "r"(a), "r"(x), "r"(y), "r"(z), "r"(w) : "memory"); }
__device__ __forceinline__ void mma_acc(float (&c)[4], const uint4& a, uint32_t b0, uint32_t b1) {
  asm("mma.sync.aligned.m16n8k16.row.col.f32.bf16.bf16.f32 {%0,%1,%2,%3}, {%4,%5,%6,%7}, {%8,%9}, {%0,%1,%2,%3};"
      : "+f"(c[0]), "+f"(c[1]), "+f"(c[2]), "+f"(c[3]) : "r"(a.x), "r"(a.y), "r"(a.z), "r"(a.w), "r"(b0), "r"(b1));
}
__device__ __forceinline__ uint4 lds128(uint32_t a) { uint4 v; asm volatile("ld.shared.v4.u32 {%0, %1, %2, %3}, [%4];" : "=r"(v.x), "=r"(v.y), "=r"(v.z), "=r"(v.w) : "r"(a) : "memory"); return v; }
__device__ __forceinline__ float2 lds64f(uint32_t a) { float2 v; asm volatile("ld.shared.v2.f32 {%0, %1}, [%2];" : "=f"(v.x), "=f"(v.y) : "r"(a)); return v; }
__device__ __forceinline__ float lds32f(uint32_t a) { float v; asm volatile("ld.shared.f32 %0, [%1];" : "=f"(v) : "r"(a)); return v; }
__device__ __forceinline__ void sts32f(uint32_t a, float v) { asm volatile("st.shared.f32 [%0], %1;" :: "r"(a), "f"(v) : "memory"); }
__device__ __forceinline__ uint32_t pack_bf16(float lo, float hi) { uint32_t r; asm("cvt.rn.bf16x2.f32 %0, %1, %2;" : "=r"(r) : "f"(hi), "f"(lo)); return r; }
__device__ __forceinline__ float bf_lo(uint32_t v) { return __uint_as_float(v << 16); }
__device__ __forceinline__ float bf_hi(uint32_t v) { return __uint_as_float(v & 0xffff0000u); }
__device__ __forceinline__ uint32_t movm(uint32_t a) { uint32_t d; asm("movmatrix.sync.aligned.m8n8.trans.b16 %0, %1;" : "=r"(d) : "r"(a)); return d; }
__device__ __forceinline__ float ex2(float x) { float y; asm("ex2.approx.ftz.f32 %0, %1;" : "=f"(y) : "f"(x)); return y; }
__device__ __forceinline__ float rsq(float x) { float y; asm("rsqrt.approx.ftz.f32 %0, %1;" : "=f"(y) : "f"(x)); return y; }
__device__ __forceinline__ float rcp(float x) { float y; asm("rcp.approx.ftz.f32 %0, %1;" : "=f"(y) : "f"(x)); return y; }
__device__ __forceinline__ bool elect() { uint32_t p; asm volatile("{\n.reg .pred q;\nelect.sync _|q, 0xffffffff;\nselp.u32 %0, 1, 0, q;\n}\n" : "=r"(p)); return p; }
__device__ __forceinline__ void pf_l2(const void* p) { asm volatile("prefetch.global.L2 [%0];" :: "l"(p)); }
__device__ __forceinline__ bool anyw(bool p) { return __any_sync(0xffffffffu, p); }
__device__ __forceinline__ float shx(float v, int m) { return __shfl_xor_sync(0xffffffffu, v, m); }
__device__ __forceinline__ void mma_k24(float (&c)[4], uint32_t a0, uint32_t a1, uint32_t a2, uint32_t a3, uint32_t b0, uint32_t b1,
                                        uint32_t e0, uint32_t e1, uint32_t f0) {
  asm("mma.sync.aligned.m16n8k16.row.col.f32.bf16.bf16.f32 {%0,%1,%2,%3}, {%4,%5,%6,%7}, {%8,%9}, {%10,%10,%10,%10};"
      : "=f"(c[0]), "=f"(c[1]), "=f"(c[2]), "=f"(c[3]) : "r"(a0), "r"(a1), "r"(a2), "r"(a3), "r"(b0), "r"(b1), "f"(0.f));
  asm("mma.sync.aligned.m16n8k8.row.col.f32.bf16.bf16.f32 {%0,%1,%2,%3}, {%4,%5}, {%6}, {%0,%1,%2,%3};"
      : "+f"(c[0]), "+f"(c[1]), "+f"(c[2]), "+f"(c[3]) : "r"(e0), "r"(e1), "r"(f0));
}
__device__ __forceinline__ uint32_t ord_key(float r) { uint32_t u = __float_as_uint(r); return u ^ ((uint32_t)((int32_t)u >> 31) | 0x80000000u); }

__device__ __forceinline__ void wgmma_n64hi_ss(float (&d)[120], uint64_t da, uint64_t db, int scale_d) {
  asm volatile("{\n.reg .pred p;\nsetp.ne.b32 p, %34, 0;\n"
    "wgmma.mma_async.sync.aligned.m64n64k16.f32.bf16.bf16 "
    "{%0, %1, %2, %3, %4, %5, %6, %7, %8, %9, %10, %11, %12, %13, %14, %15, "
    "%16, %17, %18, %19, %20, %21, %22, %23, %24, %25, %26, %27, %28, %29, %30, %31}, "
    "%32, %33, p, 1, 1, 0, 1;\n}\n"
    : "+f"(d[88]), "+f"(d[89]), "+f"(d[90]), "+f"(d[91]), "+f"(d[92]), "+f"(d[93]), "+f"(d[94]), "+f"(d[95]),
      "+f"(d[96]), "+f"(d[97]), "+f"(d[98]), "+f"(d[99]), "+f"(d[100]), "+f"(d[101]), "+f"(d[102]), "+f"(d[103]),
      "+f"(d[104]), "+f"(d[105]), "+f"(d[106]), "+f"(d[107]), "+f"(d[108]), "+f"(d[109]), "+f"(d[110]), "+f"(d[111]),
      "+f"(d[112]), "+f"(d[113]), "+f"(d[114]), "+f"(d[115]), "+f"(d[116]), "+f"(d[117]), "+f"(d[118]), "+f"(d[119])
    : "l"(da), "l"(db), "r"(scale_d));
}
__device__ __forceinline__ void wgmma_n176lo_ss(float (&d)[120], uint64_t da, uint64_t db, int scale_d) {
  asm volatile("{\n.reg .pred p;\nsetp.ne.b32 p, %90, 0;\n"
    "wgmma.mma_async.sync.aligned.m64n176k16.f32.bf16.bf16 "
    "{%0, %1, %2, %3, %4, %5, %6, %7, %8, %9, %10, %11, %12, %13, %14, %15, "
    "%16, %17, %18, %19, %20, %21, %22, %23, %24, %25, %26, %27, %28, %29, %30, %31, "
    "%32, %33, %34, %35, %36, %37, %38, %39, %40, %41, %42, %43, %44, %45, %46, %47, "
    "%48, %49, %50, %51, %52, %53, %54, %55, %56, %57, %58, %59, %60, %61, %62, %63, "
    "%64, %65, %66, %67, %68, %69, %70, %71, %72, %73, %74, %75, %76, %77, %78, %79, "
    "%80, %81, %82, %83, %84, %85, %86, %87}, "
    "%88, %89, p, 1, 1, 0, 1;\n}\n"
    : "+f"(d[0]), "+f"(d[1]), "+f"(d[2]), "+f"(d[3]), "+f"(d[4]), "+f"(d[5]), "+f"(d[6]), "+f"(d[7]),
      "+f"(d[8]), "+f"(d[9]), "+f"(d[10]), "+f"(d[11]), "+f"(d[12]), "+f"(d[13]), "+f"(d[14]), "+f"(d[15]),
      "+f"(d[16]), "+f"(d[17]), "+f"(d[18]), "+f"(d[19]), "+f"(d[20]), "+f"(d[21]), "+f"(d[22]), "+f"(d[23]),
      "+f"(d[24]), "+f"(d[25]), "+f"(d[26]), "+f"(d[27]), "+f"(d[28]), "+f"(d[29]), "+f"(d[30]), "+f"(d[31]),
      "+f"(d[32]), "+f"(d[33]), "+f"(d[34]), "+f"(d[35]), "+f"(d[36]), "+f"(d[37]), "+f"(d[38]), "+f"(d[39]),
      "+f"(d[40]), "+f"(d[41]), "+f"(d[42]), "+f"(d[43]), "+f"(d[44]), "+f"(d[45]), "+f"(d[46]), "+f"(d[47]),
      "+f"(d[48]), "+f"(d[49]), "+f"(d[50]), "+f"(d[51]), "+f"(d[52]), "+f"(d[53]), "+f"(d[54]), "+f"(d[55]),
      "+f"(d[56]), "+f"(d[57]), "+f"(d[58]), "+f"(d[59]), "+f"(d[60]), "+f"(d[61]), "+f"(d[62]), "+f"(d[63]),
      "+f"(d[64]), "+f"(d[65]), "+f"(d[66]), "+f"(d[67]), "+f"(d[68]), "+f"(d[69]), "+f"(d[70]), "+f"(d[71]),
      "+f"(d[72]), "+f"(d[73]), "+f"(d[74]), "+f"(d[75]), "+f"(d[76]), "+f"(d[77]), "+f"(d[78]), "+f"(d[79]),
      "+f"(d[80]), "+f"(d[81]), "+f"(d[82]), "+f"(d[83]), "+f"(d[84]), "+f"(d[85]), "+f"(d[86]), "+f"(d[87])
    : "l"(da), "l"(db), "r"(scale_d));
}
__device__ __forceinline__ void wgmma_n64hi_rk(float (&d)[120], uint32_t a0, uint32_t a1, uint32_t a2, uint32_t a3, uint64_t db, int scale_d) {
  asm volatile("{\n.reg .pred p;\nsetp.ne.b32 p, %37, 0;\n"
    "wgmma.mma_async.sync.aligned.m64n64k16.f32.bf16.bf16 "
    "{%0, %1, %2, %3, %4, %5, %6, %7, %8, %9, %10, %11, %12, %13, %14, %15, "
    "%16, %17, %18, %19, %20, %21, %22, %23, %24, %25, %26, %27, %28, %29, %30, %31}, "
    "{%32, %33, %34, %35}, %36, p, 1, 1, 0;\n}\n"
    : "+f"(d[88]), "+f"(d[89]), "+f"(d[90]), "+f"(d[91]), "+f"(d[92]), "+f"(d[93]), "+f"(d[94]), "+f"(d[95]),
      "+f"(d[96]), "+f"(d[97]), "+f"(d[98]), "+f"(d[99]), "+f"(d[100]), "+f"(d[101]), "+f"(d[102]), "+f"(d[103]),
      "+f"(d[104]), "+f"(d[105]), "+f"(d[106]), "+f"(d[107]), "+f"(d[108]), "+f"(d[109]), "+f"(d[110]), "+f"(d[111]),
      "+f"(d[112]), "+f"(d[113]), "+f"(d[114]), "+f"(d[115]), "+f"(d[116]), "+f"(d[117]), "+f"(d[118]), "+f"(d[119])
    : "r"(a0), "r"(a1), "r"(a2), "r"(a3), "l"(db), "r"(scale_d));
}
__device__ __forceinline__ void wgmma_n176lo_rk(float (&d)[120], uint32_t a0, uint32_t a1, uint32_t a2, uint32_t a3, uint64_t db, int scale_d) {
  asm volatile("{\n.reg .pred p;\nsetp.ne.b32 p, %93, 0;\n"
    "wgmma.mma_async.sync.aligned.m64n176k16.f32.bf16.bf16 "
    "{%0, %1, %2, %3, %4, %5, %6, %7, %8, %9, %10, %11, %12, %13, %14, %15, "
    "%16, %17, %18, %19, %20, %21, %22, %23, %24, %25, %26, %27, %28, %29, %30, %31, "
    "%32, %33, %34, %35, %36, %37, %38, %39, %40, %41, %42, %43, %44, %45, %46, %47, "
    "%48, %49, %50, %51, %52, %53, %54, %55, %56, %57, %58, %59, %60, %61, %62, %63, "
    "%64, %65, %66, %67, %68, %69, %70, %71, %72, %73, %74, %75, %76, %77, %78, %79, "
    "%80, %81, %82, %83, %84, %85, %86, %87}, "
    "{%88, %89, %90, %91}, %92, p, 1, 1, 0;\n}\n"
    : "+f"(d[0]), "+f"(d[1]), "+f"(d[2]), "+f"(d[3]), "+f"(d[4]), "+f"(d[5]), "+f"(d[6]), "+f"(d[7]),
      "+f"(d[8]), "+f"(d[9]), "+f"(d[10]), "+f"(d[11]), "+f"(d[12]), "+f"(d[13]), "+f"(d[14]), "+f"(d[15]),
      "+f"(d[16]), "+f"(d[17]), "+f"(d[18]), "+f"(d[19]), "+f"(d[20]), "+f"(d[21]), "+f"(d[22]), "+f"(d[23]),
      "+f"(d[24]), "+f"(d[25]), "+f"(d[26]), "+f"(d[27]), "+f"(d[28]), "+f"(d[29]), "+f"(d[30]), "+f"(d[31]),
      "+f"(d[32]), "+f"(d[33]), "+f"(d[34]), "+f"(d[35]), "+f"(d[36]), "+f"(d[37]), "+f"(d[38]), "+f"(d[39]),
      "+f"(d[40]), "+f"(d[41]), "+f"(d[42]), "+f"(d[43]), "+f"(d[44]), "+f"(d[45]), "+f"(d[46]), "+f"(d[47]),
      "+f"(d[48]), "+f"(d[49]), "+f"(d[50]), "+f"(d[51]), "+f"(d[52]), "+f"(d[53]), "+f"(d[54]), "+f"(d[55]),
      "+f"(d[56]), "+f"(d[57]), "+f"(d[58]), "+f"(d[59]), "+f"(d[60]), "+f"(d[61]), "+f"(d[62]), "+f"(d[63]),
      "+f"(d[64]), "+f"(d[65]), "+f"(d[66]), "+f"(d[67]), "+f"(d[68]), "+f"(d[69]), "+f"(d[70]), "+f"(d[71]),
      "+f"(d[72]), "+f"(d[73]), "+f"(d[74]), "+f"(d[75]), "+f"(d[76]), "+f"(d[77]), "+f"(d[78]), "+f"(d[79]),
      "+f"(d[80]), "+f"(d[81]), "+f"(d[82]), "+f"(d[83]), "+f"(d[84]), "+f"(d[85]), "+f"(d[86]), "+f"(d[87])
    : "r"(a0), "r"(a1), "r"(a2), "r"(a3), "l"(db), "r"(scale_d));
}
__device__ __forceinline__ void wgmma_n80_rs(float (&d)[40], uint32_t a0, uint32_t a1, uint32_t a2, uint32_t a3, uint64_t db, int scale_d) {
  asm volatile("{\n.reg .pred p;\nsetp.ne.b32 p, %45, 0;\n"
    "wgmma.mma_async.sync.aligned.m64n80k16.f32.bf16.bf16 "
    "{%0, %1, %2, %3, %4, %5, %6, %7, %8, %9, %10, %11, %12, %13, %14, %15, "
    "%16, %17, %18, %19, %20, %21, %22, %23, %24, %25, %26, %27, %28, %29, %30, %31, "
    "%32, %33, %34, %35, %36, %37, %38, %39}, "
    "{%40, %41, %42, %43}, %44, p, 1, 1, 1;\n}\n"
    : "+f"(d[0]), "+f"(d[1]), "+f"(d[2]), "+f"(d[3]), "+f"(d[4]), "+f"(d[5]), "+f"(d[6]), "+f"(d[7]),
      "+f"(d[8]), "+f"(d[9]), "+f"(d[10]), "+f"(d[11]), "+f"(d[12]), "+f"(d[13]), "+f"(d[14]), "+f"(d[15]),
      "+f"(d[16]), "+f"(d[17]), "+f"(d[18]), "+f"(d[19]), "+f"(d[20]), "+f"(d[21]), "+f"(d[22]), "+f"(d[23]),
      "+f"(d[24]), "+f"(d[25]), "+f"(d[26]), "+f"(d[27]), "+f"(d[28]), "+f"(d[29]), "+f"(d[30]), "+f"(d[31]),
      "+f"(d[32]), "+f"(d[33]), "+f"(d[34]), "+f"(d[35]), "+f"(d[36]), "+f"(d[37]), "+f"(d[38]), "+f"(d[39])
    : "r"(a0), "r"(a1), "r"(a2), "r"(a3), "l"(db), "r"(scale_d));
}
__device__ __forceinline__ void wgmma_n80_ss(float (&d)[40], uint64_t da, uint64_t db, int scale_d) {
  asm volatile("{\n.reg .pred p;\nsetp.ne.b32 p, %42, 0;\n"
    "wgmma.mma_async.sync.aligned.m64n80k16.f32.bf16.bf16 "
    "{%0, %1, %2, %3, %4, %5, %6, %7, %8, %9, %10, %11, %12, %13, %14, %15, "
    "%16, %17, %18, %19, %20, %21, %22, %23, %24, %25, %26, %27, %28, %29, %30, %31, "
    "%32, %33, %34, %35, %36, %37, %38, %39}, "
    "%40, %41, p, 1, 1, 0, 1;\n}\n"
    : "+f"(d[0]), "+f"(d[1]), "+f"(d[2]), "+f"(d[3]), "+f"(d[4]), "+f"(d[5]), "+f"(d[6]), "+f"(d[7]),
      "+f"(d[8]), "+f"(d[9]), "+f"(d[10]), "+f"(d[11]), "+f"(d[12]), "+f"(d[13]), "+f"(d[14]), "+f"(d[15]),
      "+f"(d[16]), "+f"(d[17]), "+f"(d[18]), "+f"(d[19]), "+f"(d[20]), "+f"(d[21]), "+f"(d[22]), "+f"(d[23]),
      "+f"(d[24]), "+f"(d[25]), "+f"(d[26]), "+f"(d[27]), "+f"(d[28]), "+f"(d[29]), "+f"(d[30]), "+f"(d[31]),
      "+f"(d[32]), "+f"(d[33]), "+f"(d[34]), "+f"(d[35]), "+f"(d[36]), "+f"(d[37]), "+f"(d[38]), "+f"(d[39])
    : "l"(da), "l"(db), "r"(scale_d));
}

__device__ __forceinline__ constexpr int QT(int t) { return t < 8 ? t : 16 + t; }
__device__ __forceinline__ constexpr int KT(int t) { return t < 8 ? 8 + t : 18 + t; }
__device__ __forceinline__ constexpr int VT(int t) { return t < 8 ? 16 + t : 20 + t; }

struct Maps { CUtensorMap x, w, wr, wv, wo, wor, gate, up, down; };

__global__ void __cluster_dims__(2, 1, 1) __launch_bounds__(512, 1)
fused_kernel(const __nv_bfloat16* __restrict__ x, const __nv_bfloat16* __restrict__ wqkv,
             const __nv_bfloat16* __restrict__ wo, const __nv_bfloat16* __restrict__ w_r, const __nv_bfloat16* __restrict__ w_gate,
             const __nv_bfloat16* __restrict__ w_up, const __nv_bfloat16* __restrict__ w_down, __nv_bfloat16* __restrict__ out,
             Scratch* __restrict__ sc, const __grid_constant__ Maps tm) {
  extern __shared__ __align__(1024) uint8_t smem[];
  const int tid = threadIdx.x, bid = blockIdx.x;
  if ((unsigned)(tid - 128) < 16u) pf_l2((const char*)x + (bid * 16 + tid - 128) * 1280);
  if ((unsigned)(tid - 160) < 15u) pf_l2((const char*)wqkv + (bid * 15 + tid - 160) * 128);
  const int warp = __shfl_sync(0xffffffffu, tid >> 5, 0), lane = tid & 31;
  const uint32_t sb = (uint32_t)__cvta_generic_to_shared(smem);
  const uint32_t bar_full = sb + OFF_BAR, bar_empty = bar_full + 32, bar_aux = bar_full + 64, bar_ffn = bar_full + 72, bar_win = bar_full + 80, bar_tag = bar_full + 88, bar_rst = bar_full + 96 + 296 + 24,
                 bar_o = bar_full + 96, bar_oc = bar_o + 112, bar_st = bar_o + 224, bar_go = bar_o + 248, bar_kv = bar_o + 272, bar_half = bar_o + 296;
  if (warp < 4 && elect()) {
    mbar_init(bar_half + 8 * warp, 1);
    mbar_init(bar_full + 8 * (warp ^ 2), 1);
    mbar_init(bar_empty + 8 * warp, 24);
    mbar_init(bar_aux + 8 * warp, warp == 0 ? 64 : warp == 2 ? 32 : warp == 3 ? 2 : 1);
    asm volatile("fence.mbarrier_init.release.cluster;" ::: "memory");
  }
  asm volatile("barrier.cluster.arrive.relaxed.aligned;" ::: "memory");
  if (warp >= 8 && warp < 12 && elect()) asm volatile("prefetch.tensormap [%0];" :: "l"(&tm.x + (warp - 8)) : "memory");
  const int rank = bid & 1, cl = bid >> 1;
  const int q7 = ((cl - 36) * 37) >> 8;
  const int P = cl < 4 ? 0 : cl < 36 ? (cl - 4) & 7 : cl - 35 - 7 * q7;
  const int g = (cl < 4 ? 4 + cl : cl < 36 ? (cl - 4) >> 3 : 4 + q7);
  const int mt = 2 * P + rank, cid = mt * 8 + g;
  const bool ffn1 = g >= 5;
  const int fj = ffn1 ? mt * 3 + g - 5 : (P * 5 + g) * 2 + rank;
  const int ord = ((g >> 2) ^ P) & 1;
  auto ks_of = [&](int it) { return ord == 0 || it == 0 ? it : it <= 5 ? it + 4 : it - 5; };
  const int godd = g & 1, cm = g * 80 + godd * 16, cr = g * 80 + 64 - godd * 64;
  auto load_w = [&](int ks, uint32_t a, uint32_t bar, int kk) {
    tma_3d_mc(a + 16384 + kk * 6144, &tm.w, bar, cm, ks * 64 + kk * 16, 0);
    tma_3d_mc(a + 41472 + kk * 2048, &tm.wr, bar, cr, ks * 64 + kk * 16, 0);
    tma_3d_mc(a + 40960 + kk * 2048, &tm.wv, bar, cm + 48, ks * 64 + kk * 16, 2);
  };
  if (warp == 0 && elect()) {
    mbar_expect_tx(bar_half, 32768);
    tma_3d(sb + 2 * SLOT, &tm.x, bar_half, 0, P * 128, rank);
    mbar_expect_tx(bar_full + 16, 16384);
  }
  asm volatile("barrier.cluster.wait.aligned;" ::: "memory");
  if (warp == 0) {
    if (elect()) {
      uint32_t bar = bar_half;
#pragma unroll 1
      for (int kk = rank; kk < 4; kk += 2) { load_w(0, sb + 2 * SLOT, bar, kk); bar = bar_full + 16; }
    }
    asm volatile("bar.arrive 4, 64;" ::: "memory");
  }

  if (warp >= 8) {
    asm volatile("setmaxnreg.dec.sync.aligned.u32 %0;" :: "n"(REG_P));
#define TS_T 0
    if (warp == 8) {
      TS(8);
      bar_sync(4, 64);
      if (elect()) {
        TS(10);
#pragma unroll 1
        for (int it = 1; it < 10; it++) {
          const int s = (it + 2) & 3, ks = ks_of(it);
          const uint32_t full = bar_full + 8 * s, a = sb + s * SLOT;
          uint32_t bar = it < NSPLIT ? bar_half + 8 * it : full;
          if (it >= 4) mbar_wait(full + 32, ((it >> 2) - 1) & 1);
          if (it >= 2 && it < THR_END) mbar_wait(bar_full + 8 * (it & 3), 0);
          if (it < NSPLIT) mbar_expect_tx(bar, 32768);
          mbar_expect_tx(full, it < NSPLIT ? 16384 : SLOT);
          tma_3d(a, &tm.x, bar, ks * 64, P * 128, rank);
#pragma unroll 1
          for (int kk = rank; kk < 4; kk += 2) { load_w(ks, a, bar, kk); bar = full; }
          TS(12 + it);
          if ((it >> 1) == 2) {
            mbar_wait(bar_rst, 0);
            asm volatile("cp.async.bulk.global.shared::cta.bulk_group [%0], [%1], %2;\ncp.async.bulk.commit_group;"
                         :: "l"(it == 4 ? (uint4*)(g_own + cid) : (uint4*)&g_x + cid * GLOB_PER_CTA), "r"(sb + OFF_CS), "r"(it == 4 ? (int)sizeof(Own) : GLOB_PER_CTA * 16) : "memory");
          }
          if (it == 6) { asm volatile("cp.async.bulk.wait_group 0;" ::: "memory"); mbar_arrive(bar_tag); }
        }
        mbar_expect_tx(bar_ffn, ffn1 ? 81920 : 24576);
        int fjn = 0;
#pragma unroll 1
        for (int it = 9; it < 17; it++) {
          if (it >= 13) { mbar_wait(bar_oc + 8 * (it - 13), 0); mbar_wait(bar_oc + 56 + 8 * (it - 13), 0); }
          else if (it >= 10) {
            const uint32_t full = bar_full + 8 * (it - 10);
            const int g0 = 3 * (it - 10), g1 = min(g0 + 3, 8);
            mbar_wait(full + 32, it < 12);
            mbar_expect_tx(full, (g1 - g0) * 12800);
#pragma unroll 1
            for (int gp = g0 + ((g0 ^ rank) & 1); gp < g1; gp += 2) {
              tma_3d_mc(sb + gp * 15360, &tm.wo, full, 0, gp * 80, g * 2);
              tma_3d_mc(sb + gp * 15360 + 10240, &tm.wor, full, 512 + g * 16, gp * 80, 0);
            }
          }
          const int j1 = ffn1 ? (it >= 13 ? 2 * it - 22 : min(it - 8, 3)) : (it >= 13 ? 12 : min((it - 8) * F_PER, F_MAX));
#pragma unroll 1
          for (; fjn < j1; fjn++) {
            const int j = fjn < 3 ? fjn + 7 : fjn - 3;
            if (ffn1) tma_3d(sb + (j < 7 ? 0 : OFF_W2 - 57344) + j * 8192, j < 5 ? &tm.gate : &tm.up, bar_ffn, fj * 32, (j < 5 ? j : j - 5) * 128, 0);
            else tma_3d(sb + OFF_W2 + fjn * 2048, &tm.down, bar_ffn, fj * 8, fjn * 128, 0);
          }
        }
        TS(11);
      }
#undef TS_T
#define TS_T 64
    } else if (warp >= 12) {
      const int l7 = lane & 7, j = warp - 12, ch = min((P >> 1) * 4 + rank * 2 + (j >> 1), 14);
      const uint32_t sxo = ((g & 3) * 32 + j * 8 + l7) * 128 + (((lane >> 3) ^ l7) * 16);
      const uint32_t swo = ch < 12 ? 16384 + (lane >> 4) * 6144 + (ch >> 2) * 2048 + (lane & 15) * 128 + ((((ch & 3) * 2 + (j & 1)) ^ l7) * 16)
                                   : 41472 + (lane >> 4) * 2048 + (ch - 12) * 512 + (lane & 15) * 32 + (((j & 1) ^ (l7 >> 2)) * 16);
      float ps = 0.f, pq = 0.f, pq1 = 0.f, pc = 0.f;
      uint32_t tag = 0;
      char* const pp = hold((lane & 1) ? (char*)&g_own[cid].cs[j * 8 + (lane >> 2)] : (char*)&g_own[cid].st1[j * 8 + (lane >> 2)]);
#pragma unroll 1
      for (int it = ord; it < ord + 5; it++) {
        const int sl = (it + 2) & 3;
        if (it == ord + 4) { mbar_wait(bar_tag, 0); tag = __float_as_uint(lds32f(sb + OFF_WR + 324)); }
        if (it < NSPLIT) mbar_wait(bar_half + 8 * it, 0);
        mbar_wait(bar_full + 8 * sl, (it >> 2) & 1);
        TS(it);
        const uint32_t a = sb + sl * SLOT;
        const uint4 v0 = ldsm4(a + sxo), v1 = ldsm4((a + sxo) ^ 64), w0 = ldsm4t(a + swo), w1 = ldsm4t(a + swo + (ch < 12 ? 12288 : 4096));
        if (lane + (int)((v0.x & v1.x & w0.x & w1.x) == 0x7fc17fc1u && (v0.x | v1.x) == 0u) < 2) mbar_arrive_cta(bar_empty + 8 * sl, lane);
        const uint32_t vv[8] = {v0.x, v0.y, v0.z, v0.w, v1.x, v1.y, v1.z, v1.w}, ww[8] = {w0.x, w0.y, w0.z, w0.w, w1.x, w1.y, w1.z, w1.w};
#pragma unroll
        for (int i = 0; i < 8; i++) {
          const float d = bf_lo(vv[i]), e = bf_hi(vv[i]);
          ps += d + e; pq = fmaf(d, d, pq); pq1 = fmaf(e, e, pq1); pc += bf_lo(ww[i]) + bf_hi(ww[i]);
        }
      }
      pq += pq1;
      ps += shx(ps, 1); pq += shx(pq, 1); pc += shx(pc, 1);
      ps += shx(ps, 2); pq += shx(pq, 2); pc += shx(pc, 2);
      if ((lane & 3) == 0) stg_pkt(pp, __float_as_uint(ps), __float_as_uint(pq), tag, 0u);
      if ((lane & 3) == 1) stg_rlx64(pp, __float_as_uint(pc), tag);
      asm volatile("bar.arrive 2, 192;" ::: "memory");
      if (warp == 12) {
        const uint4* const hp = hold(&g_own[max(cid - 16, 0)].halo[0][lane]);
        mbar_wait(bar_aux, 0);
        mbar_wait(bar_go, 0);
        uint4 v[5] = {};
        int guard = SPIN_MAX;
        if (P > 0) {
          do {
#pragma unroll
            for (int i = 0; i < 5; i++) v[i] = ldg_pkt(hp + 32 * i);
          } while (anyw(v[0].x == SENT || v[1].x == SENT || v[2].x == SENT || v[3].x == SENT || v[4].x == SENT) && --guard > 0);
        }
#pragma unroll
        for (int i = 0; i < 5; i++) *(uint4*)(smem + OFF_O + 10240 + i * 512 + lane * 16) = v[i];
        mbar_arrive(bar_kv);
      }
#undef TS_T
#define TS_T 32
    } else if (warp < 11) {
      const int l7 = lane & 7, hk = lane >> 4;
      if (warp == 10 && elect()) {
#pragma unroll 1
        for (int i = 0; i < 36; i++) mbar_init(bar_o + 8 * i, i < 14 || i == 30 ? 1 : i < 34 ? 4 : 128);
      }
      mbar_wait(bar_tag, 0);
      const uint32_t tag = __float_as_uint(lds32f(sb + OFF_WR + 324));
      bar_sync(2, 192);
      TS(0);
      int guard = SPIN_MAX;
      if (warp == 9) {
        const uint4* sp = &g_own[mt * 8].st1[lane];
        const uint4* hp = &g_own[max(mt - 2, 0) * 8 + 3].st1[24 + l7];
        uint4 a[5], b[5];
        bool bad;
        do {
          __nanosleep(AUX_NS);
          bad = false;
#pragma unroll
          for (int i = 0; i < 5; i++) {
            const uint4* q = i < 4 ? sp + i * (sizeof(Own) / 16) : hp;
            a[i] = ldg_pkt(q); b[i] = ldg_pkt(q + 4 * sizeof(Own) / 16);
          }
#pragma unroll
          for (int i = 0; i < 5; i++) bad |= a[i].z != tag || b[i].z != tag;
        } while (anyw(bad) && --guard);
        TS(1);
#pragma unroll
        for (int i = 0; i < 5; i++) {
          const float m = (__uint_as_float(a[i].x) + __uint_as_float(b[i].x)) * (1.f / 640.f);
          const float rs = rsq(fmaxf(fmaf(-m, m, (__uint_as_float(a[i].y) + __uint_as_float(b[i].y)) * (1.f / 640.f)), 0.f) + 1e-5f);
          ((float*)(smem + OFF_RS))[i < 4 ? 8 + lane + 32 * i : l7] = rs;
          const uint32_t mh = pack_bf16(-m, -m);
          const float ml = -m - bf_lo(mh);
          if (i < 4) ((uint2*)(smem + OFF_MN))[lane + 32 * i] = make_uint2(mh, pack_bf16(ml, ml));
        }
      } else {
        const uint4* cp = (const uint4*)g_own[hk * 8 + g].cs + (lane & 15);
        uint4 a[4], b[4];
        bool bad;
        do {
          __nanosleep(AUX_NS);
          bad = false;
#pragma unroll
          for (int i = 0; i < 4; i++) { a[i] = ldg_pkt(cp + i * 32 * sizeof(Own) / 16); b[i] = ldg_pkt(cp + (i * 32 + 16) * sizeof(Own) / 16); }
#pragma unroll
          for (int i = 0; i < 4; i++) bad |= a[i].y != tag || a[i].w != tag || b[i].y != tag || b[i].w != tag;
        } while (anyw(bad) && --guard);
#pragma unroll
        for (int i = 0; i < 4; i++)
          if (i < 3 || lane < 24) {
            const float c0 = __uint_as_float(a[i].x) + __uint_as_float(b[i].x), c1 = __uint_as_float(a[i].z) + __uint_as_float(b[i].z);
            const uint32_t hi = pack_bf16(c0, c1), w0 = pack_bf16(c0, c0 - bf_lo(hi)), w1 = pack_bf16(c1, c1 - bf_hi(hi));
            uint4* const d = (uint4*)(smem + OFF_CS) + 2 * (lane + 32 * i);
            d[0] = make_uint4(w0, w0, 0, 0); d[1] = make_uint4(w1, w1, 0, 0);
          }
        asm volatile("fence.proxy.async.shared::cta;" ::: "memory");
      }
      mbar_arrive(bar_aux);
      TS(2);
      const int fo = warp - 9, wq = fo ? 1 - LEAD : LEAD;
      const uint4* const fp = hold(g_own[mt * 8 + wq * 4].cnt);
      const char* src = hold((const char*)g_o[mt * 2 + wq]);
      if (elect()) {
        const uint32_t bo = bar_o + fo * 56;
#pragma unroll
        for (int i = 0; i < 7; i++) mbar_expect_tx(bo + 8 * i, 10240);
        mbar_wait(bar_st + 8 * fo, 0);
        uint32_t cv;
        asm volatile("atom.relaxed.gpu.global.add.u32 %0, [%1], 1;" : "=r"(cv) : "l"(fp) : "memory");
        cv++;
        while (cv != 8u && --guard > 0) cv = ldg_rlx32(fp);
        asm volatile("fence.proxy.async.global;" ::: "memory");
        TS(6);
        uint32_t dst = sb + OFF_O + 20480;
#pragma unroll 1
        for (int i = 0; i < 7; i++) {
          if (fo || i == 5) mbar_wait(fo ? bar_oc + 8 * i : bar_st + 8, 0);
          if (i == g) src += 10240;
          asm volatile("cp.async.bulk.shared::cluster.global.mbarrier::complete_tx::bytes [%0], [%1], 10240, [%2];" :: "r"(dst), "l"(src), "r"(bo + 8 * i) : "memory");
          src += 10240;
          dst += i == 4 ? -61440 : 10240;
        }
      }
#undef TS_T
#define TS_T 96
    } else {
      if ((sb & 0x3FFFF) != D0 * 16) __trap();
#pragma unroll 1
      for (int i = lane; i < 232; i += 32) { const uint32_t f = i < 208 ? SENT : 0u; ((uint4*)(smem + OFF_CS))[i] = make_uint4(f, f, f, f); }
      asm volatile("fence.proxy.async.shared::cta;" ::: "memory");
      if (elect()) mbar_arrive(bar_rst);
      mbar_wait(bar_full + 8 * ((HK_IT + 2) & 3), 0);
      TS(4);
      const uint32_t epoch = ldg_rlx32(g_epoch + cid) + 1;
      uint32_t wv[10];
#pragma unroll
      for (int i = 0; i < 10; i++) wv[i] = __ldg((const uint32_t*)w_r + lane + 32 * i);
      float s = 0.f;
#pragma unroll
      for (int i = 0; i < 10; i++) {
        s += bf_lo(wv[i]) + bf_hi(wv[i]);
        const unsigned u = i < 8 ? lane + 32 * (i - g) : lane + 32 * (i - 7) - g * 8;
        if (i < 8 ? u < 32u : u - 32u < 8u) *(float2*)(smem + OFF_WR + ((u & 3) * 10 + (u >> 2)) * 8) = make_float2(bf_lo(wv[i]), bf_hi(wv[i]));
      }
#pragma unroll
      for (int m = 1; m < 32; m <<= 1) s += shx(s, m);
      *(float2*)(smem + OFF_WR + 320) = make_float2(s, __uint_as_float(epoch * 0x9E3779B8u));
      g_epoch[cid] = epoch;
      TS(3);
      if (elect()) mbar_arrive(bar_tag);
      TS(5);
#pragma unroll 1
      for (int i = 0; i < PFW_N; i++) {
        const int m = (i + 2) >> 2, n = m == 0 ? 50 : 120, t = (m == 0 ? i : (i + 2) & 3) * 32 + lane;
        const char* b = (const char*)(m == 0 ? wo : m == 1 ? w_up : m == 2 ? w_down : w_gate);
        if (t < n) pf_l2(b + (bid * n + t) * 128);
        __nanosleep(PFW_NS);
      }
      const uint4* const kp = hold(g_own[1].cnt);
      const uint4* const cb = hold(&g_x.cand[0][lane >> 2][lane & 3]);
      bar_sync(3, 64);
      uint4 k;
      uint32_t have = SENT;
      int guard = SPIN_MAX;
      while (true) {
        k = ldg_pkt(kp);
        if (ffn1) {
          while (k.x != have && --guard > 0) {
            const uint32_t tk = 2047u - (k.x & 2047u), want = k.x;
            const uint4* q = cb + ((tk >> 8) * 16 + (tk & 1) * 8 + ((tk >> 5) & 7)) * 192;
            const uint4 c0 = ldg_pkt(q), c1 = ldg_pkt(q + 4); const uint2 c2 = ldg_rlx64(q + 8);
            k = ldg_pkt(kp);
            *(uint4*)(smem + OFF_HN + lane * 16) = c0; *(uint4*)(smem + OFF_HN + 512 + lane * 16) = c1; *(uint2*)(smem + OFF_HN + 1024 + lane * 16) = c2;
            have = anyw(c0.x == SENT || c1.x == SENT || c2.x == SENT) ? SENT : want;
          }
        } else if (KEY_NS && k.z != 128u) __nanosleep(KEY_NS);
        if (k.z == 128u || --guard <= 0) break;
      }
      *(uint2*)(smem + OFF_WR + 336) = make_uint2(k.x, k.y);
      mbar_arrive(bar_win);
      TS(7);
    }
#undef TS_T
  } else {
#define TS_T 0
    asm volatile("setmaxnreg.inc.sync.aligned.u32 %0;" :: "n"(REG_C));
    const int wg = warp >> 2, w4 = warp & 3, r = lane >> 2, c = lane & 3;
    float acc[120];
    uint4 xr[5] = {};
    const uint32_t xa = pin(sb + (warp * 16 + (lane & 15)) * 128 + ((lane >> 4) ^ (lane & 7)) * 16);
    const int fol = wg != LEAD;
    const bool first = (P == 0) && (warp == 0);
    const uint32_t kvs = sb + OFF_O + fol * 10240 + w4 * 2560 + lane * 16;
    uint4* const kvd = hold(warp == 7 ? &g_own[cid].halo[0][lane] : (uint4*)(smem + (warp == 3 ? OFF_O + lane * 16 : kvs - sb + 2560)));
    uint4* const odst = hold(&g_o[mt * 2 + wg][g][w4 * 160]);
    uint32_t m0 = 0, m1 = 0;
    const uint32_t mna = pin(sb + OFF_MN + (warp * 16 + r) * 8 + c * 4);
    const int itx = ord == 0 || g == 0 ? g : g < 5 ? g + 5 : g - 4, ity = (ord ? 4 : 8) + (g >> 2);
    uint32_t rel;
    asm volatile("mapa.shared::cluster.u32 %0, %1, %2;" : "=r"(rel) : "r"(bar_empty), "r"(tid & 1));
    const uint32_t xa1 = pin(xa ^ 32), xa2 = pin(xa ^ 64), xa3 = pin(xa ^ 96), xb = pin(xa ^ ((g & 3) * 32));
    const uint32_t da0 = wg * 512;
    const bool rel2 = lane < 2, rel6 = lane < 2 + 2 * (warp & 1);
    const uint32_t zero = __shfl_sync(0xffffffffu, (uint32_t)(uintptr_t)x & 8u, 0);
    mbar_wait(bar_half, 0);
    TS(13);
    wgmma_fence();
#pragma unroll
    for (int it = 0; it < 10; it++) {
      const int s = (it + 2) & 3;
      if (it == 9 && fol) bar_sync(10, 256);
#pragma unroll
      for (int kk = 0; kk < 4; kk++) {
        if (kk == 2 && it > 0) {
          wgmma_commit();
          wgmma_wait<1>();
          const uint32_t ra = ((xr[0].x ^ xr[1].x ^ xr[2].x ^ xr[3].x ^ xr[4].x) & zero) | rel;
          if (it == 1 ? (ord ? rel6 : rel2) : it == 6 ? (ord ? rel2 : rel6) : it < 6 ? rel2 : rel6)
            asm volatile("mbarrier.arrive.shared::cluster.b64 _, [%0];" :: "r"(ra + 8 * ((it + 1) & 3)) : "memory");
        }
        if (kk == 2) {
          ldsm4_if(xr[0], xa, s * SLOT, it == itx); ldsm4_if(xr[1], xa1, s * SLOT, it == itx);
          ldsm4_if(xr[2], xa2, s * SLOT, it == itx); ldsm4_if(xr[3], xa3, s * SLOT, it == itx);
          if ((it & 6) == 4 || it >= 8) ldsm4_if(xr[4], xb, s * SLOT, it == ity);
        }
        if (kk == AK && it == 9) {
          mbar_wait(bar_aux, 0);
          TS(3);
          if (c < 2) { m0 = __float_as_uint(lds32f(mna)); m1 = __float_as_uint(lds32f(mna + 64)); }
          if (!fol) bar_sync(11, 256);
        }
        if (kk == 2 && it < NSPLIT) mbar_wait(bar_full + 8 * s, 0);
        const uint64_t da = mk64(da0 + (D0 + s * (SLOT >> 4) + kk * 2 + (1 << 16)), 0x40000040u);
        wgmma_n64hi_ss(acc, da, mk64(D0 + s * (SLOT >> 4) + 2560 + kk * 128 + (32 << 16), 0xC0000010u), (it | kk) != 0);
        wgmma_n176lo_ss(acc, da, mk64(D0 + s * (SLOT >> 4) + 1024 + kk * 384 + (128 << 16), 0x40000040u), (it | kk) != 0);
      }
      wgmma_commit();
      if (it == 8 && fol) asm volatile("bar.arrive 11, 256;" ::: "memory");
      if (it < 9) {
        if (it + 1 < NSPLIT) mbar_wait(bar_half + 8 * (it + 1), 0);
        else mbar_wait(bar_full + 8 * ((it + 3) & 3), ((it + 1) >> 2) & 1);
        if (it < 8) TS(14 + it);
      }
    }
    {
      const uint64_t dc = make_desc(D0 * 16 + OFF_CS, 0, 128, 0);
      wgmma_fence();
      wgmma_n64hi_rk(acc, m0, m1, 0u, 0u, dc + 176, 1);
      wgmma_n176lo_rk(acc, m0, m1, 0u, 0u, dc, 1);
      wgmma_commit();
      if (!fol) asm volatile("bar.arrive 10, 256;" ::: "memory");
    }
    const uint32_t stb = sb + OFF_RS + warp * 64;
    const float rlo = lds32f(stb + (8 + r) * 4), rhi = lds32f(stb + (16 + r) * 4);
    wgmma_wait<0>();
#pragma unroll
    for (int i = 0; i < 120; i++) asm volatile("" : "+f"(acc[i]) :: "memory");
    if (fol && lane == 0) mbar_arrive(bar_go);
    TS(2);
    uint32_t Qlo[10], Qhi[10], Klo[10], Khi[10], Vlo[10], Vhi[10];
#define CONV_HI(ROT) _Pragma("unroll") for (int t = 0; t < 10; t++) { \
      const int k = KT((t + ROT) % 10), v = VT((t + ROT) % 10); \
      Khi[t] = pack_bf16(acc[4 * k + 2], acc[4 * k + 3]); \
      Vhi[t] = pack_bf16(acc[4 * v + 2] * rhi, acc[4 * v + 3] * rhi); }
    if (godd) { CONV_HI(8) } else { CONV_HI(0) }
    st_pkt(kvd, Khi[0], Khi[1], Khi[3], Khi[4]);
    st_pkt(kvd + 32, Khi[5], Khi[6], Khi[8], Khi[9]);
    st_pkt(kvd + 64, Khi[2], Khi[7], Vhi[0], Vhi[1]);
    st_pkt(kvd + 96, Vhi[2], Vhi[3], Vhi[4], Vhi[5]);
    st_pkt(kvd + 128, Vhi[6], Vhi[7], Vhi[8], Vhi[9]);
    if (warp < 7) mbar_arrive(bar_kv + ((warp + 1) >> 2) * 8);
#define CONV_LO(ROT) _Pragma("unroll") for (int t = 0; t < 10; t++) { \
      const int q = QT((t + ROT) % 10), k = KT((t + ROT) % 10), v = VT((t + ROT) % 10); \
      Vhi[t] = movm(Vhi[t]); \
      Klo[t] = pack_bf16(acc[4 * k], acc[4 * k + 1]); \
      Vlo[t] = movm(pack_bf16(acc[4 * v] * rlo, acc[4 * v + 1] * rlo)); \
      Qlo[t] = pack_bf16(acc[4 * q], acc[4 * q + 1]); \
      Qhi[t] = pack_bf16(acc[4 * q + 2], acc[4 * q + 3]); }
    if (godd) { CONV_LO(8) } else { CONV_LO(0) }
    const bool in0 = 2 * c <= r, in1 = 2 * c + 1 <= r;
    const uint32_t mL = (in0 ? 0xffffu : 0u) | (in1 ? 0xffff0000u : 0u);
    const float qs = 0.22360679774997896f * 1.4426950408889634f;
    const uint32_t kb0 = stb + (2 * c + (in0 ? 8 : 0)) * 4, kb1 = stb + (2 * c + 1 + (in1 ? 8 : 0)) * 4;
    const float scl0 = lds32f(kb0) * rlo * qs, scl1 = lds32f(kb1) * rlo * qs;
    const float sch0 = lds32f(kb0 + 32) * rhi * qs, sch1 = lds32f(kb1 + 32) * rhi * qs;
    const float bias0 = (first && !in0) ? -INFINITY : 0.f, bias1 = (first && !in1) ? -INFINITY : 0.f;
    const int slot = mt * 8 + warp;
    int guard = SPIN_MAX;
    uint4 pv[5];
    const bool cA = c < 2, nA = r < 4;
    TS(0);
    mbar_wait(bar_go + fol * 8, 0);
    TS(23);
    uint32_t qe[4][2];
    float sl0[4], sl1[4], th0[4], th1[4];
#pragma unroll
    for (int hd = 0; hd < 4; hd++) {
      const int ta = 5 * (hd >> 1) + 3 * (hd & 1), ts = 5 * (hd >> 1) + 2;
      const bool mine = (hd & 1) ? !cA : cA;
      qe[hd][0] = mine ? Qlo[ts] : 0u; qe[hd][1] = mine ? Qhi[ts] : 0u;
      float sl[4], sh[4];
      mma_k24(sl, Qlo[ta], Qhi[ta], Qlo[ta + 1], Qhi[ta + 1], Klo[ta], Klo[ta + 1], qe[hd][0], qe[hd][1], Klo[ts]);
      mma_k24(sh, Qlo[ta], Qhi[ta], Qlo[ta + 1], Qhi[ta + 1], Khi[ta], Khi[ta + 1], qe[hd][0], qe[hd][1], Khi[ts]);
      th0[hd] = (in0 ? sh[2] : sl[2]) * sch0; th1[hd] = (in1 ? sh[3] : sl[3]) * sch1;
      float mh = fmaxf(th0[hd], th1[hd]);
      mh = fmaxf(mh, shx(mh, 1)); mh = fmaxf(mh, shx(mh, 2));
      th0[hd] -= mh; th1[hd] -= mh;
      sl0[hd] = sl[0]; sl1[hd] = sl[1];
    }
    mbar_wait(bar_kv + wg * 8, 0);
    TS(4);
#pragma unroll
    for (int j = 0; j < 5; j++) pv[j] = lds128(kvs + 512 * j);
    const uint32_t Kp[10] = {pv[0].x, pv[0].y, pv[2].x, pv[0].z, pv[0].w, pv[1].x, pv[1].y, pv[2].y, pv[1].z, pv[1].w};
    const uint32_t Vp[10] = {movm(pv[2].z), movm(pv[2].w), movm(pv[3].x), movm(pv[3].y), movm(pv[3].z), movm(pv[3].w), movm(pv[4].x), movm(pv[4].y), movm(pv[4].z), movm(pv[4].w)};
    const uint32_t ONES = 0x3f803f80u;
    uint32_t of[20];
#pragma unroll
    for (int hp = 0; hp < 2; hp++) {
      float o[6][4];
#pragma unroll
      for (int hh = 0; hh < 2; hh++) {
        const int hd = 2 * hp + hh, ta = 5 * hp + 3 * hh, ts = 5 * hp + 2;
        float sp[4];
        mma_k24(sp, Qlo[ta], Qhi[ta], Qlo[ta + 1], Qhi[ta + 1], Kp[ta], Kp[ta + 1], qe[hd][0], qe[hd][1], Kp[ts]);
        const float tl0 = fmaf(in0 ? sl0[hd] : sp[0], scl0, bias0), tl1 = fmaf(in1 ? sl1[hd] : sp[1], scl1, bias1);
        float ml = fmaxf(tl0, tl1);
        ml = fmaxf(ml, shx(ml, 1)); ml = fmaxf(ml, shx(ml, 2));
        if (HOLD == 1 && hd == 3 && !fol && lane == 0) mbar_arrive(bar_go + 8);
        const uint32_t Pl = pack_bf16(ex2(tl0 - ml), ex2(tl1 - ml)), Ph = pack_bf16(ex2(th0[hd]), ex2(th1[hd]));
        const uint32_t a0 = Pl & mL, a1 = Ph & ~mL, a3 = Ph & mL, ap = Pl & ~mL;
        const bool vm = hh == 0 ? nA : !nA;
        mma_k24(o[3 * hh], a0, a1, 0u, a3, Vlo[ta], Vhi[ta], ap, 0u, Vp[ta]);
        mma_k24(o[3 * hh + 1], a0, a1, 0u, a3, Vlo[ta + 1], Vhi[ta + 1], ap, 0u, Vp[ta + 1]);
        mma_k24(o[3 * hh + 2], a0, a1, 0u, a3, vm ? Vlo[ts] : ONES, vm ? Vhi[ts] : ONES, ap, 0u, vm ? Vp[ts] : ONES);
      }
      const float il = rcp(cA ? o[5][0] : o[2][0]), ih = rcp(cA ? o[5][2] : o[2][2]);
      const float jl = shx(il, 2), jh = shx(ih, 2);
      const float al = cA ? jl : il, ah = cA ? jh : ih, bl = cA ? il : jl, bh = cA ? ih : jh;
      const int t0 = 5 * hp;
      of[2 * t0]     = pack_bf16(o[0][0] * al, o[0][1] * al); of[2 * t0 + 1] = pack_bf16(o[0][2] * ah, o[0][3] * ah);
      of[2 * t0 + 2] = pack_bf16(o[1][0] * al, o[1][1] * al); of[2 * t0 + 3] = pack_bf16(o[1][2] * ah, o[1][3] * ah);
      of[2 * t0 + 4] = pack_bf16((cA ? o[2][0] : o[5][0]) * jl, (cA ? o[2][1] : o[5][1]) * jl);
      of[2 * t0 + 5] = pack_bf16((cA ? o[2][2] : o[5][2]) * jh, (cA ? o[2][3] : o[5][3]) * jh);
      of[2 * t0 + 6] = pack_bf16(o[3][0] * bl, o[3][1] * bl); of[2 * t0 + 7] = pack_bf16(o[3][2] * bh, o[3][3] * bh);
      of[2 * t0 + 8] = pack_bf16(o[4][0] * bl, o[4][1] * bl); of[2 * t0 + 9] = pack_bf16(o[4][2] * bh, o[4][3] * bh);
    }
    {
      const uint32_t os = sb + OFF_O + (fol ? 0 : 20480) + w4 * 2560, oa = os + ((lane >> 3) & 1) * 1280 + (lane >> 4) * 128 + (lane & 7) * 16;
#pragma unroll
      for (int s = 0; s < 5; s++) {
        stsm4(oa + s * 256, of[4 * s], of[4 * s + 1], of[4 * s + 2], of[4 * s + 3]);
        if (s == 0 && (fol || HOLD == 2) && lane == 0) mbar_arrive(bar_go + 8 + 8 * fol);
      }
      asm volatile("fence.proxy.async.shared::cta;" ::: "memory");
      __syncwarp();
      asm volatile("{\n.reg .pred q;\nelect.sync _|q, 0xffffffff;\n@q cp.async.bulk.global.shared::cta.bulk_group [%0], [%1], 2560;\ncp.async.bulk.commit_group;\n}\n" :: "l"(odst), "r"(os) : "memory");
    }
    TS(5);
    float h[40];
#pragma unroll
    for (int s = 0; s < 5; s++) {
      const uint4 v = xr[s];
      h[8 * s] = bf_lo(v.x); h[8 * s + 1] = bf_hi(v.x); h[8 * s + 2] = bf_lo(v.y); h[8 * s + 3] = bf_hi(v.y);
      h[8 * s + 4] = bf_lo(v.z); h[8 * s + 5] = bf_hi(v.z); h[8 * s + 6] = bf_lo(v.w); h[8 * s + 7] = bf_hi(v.w);
    }
    asm volatile("cp.async.bulk.wait_group 0;" ::: "memory");
    __syncwarp();
    if (lane == 0) mbar_arrive(bar_st + 8 * fol);
    TS(22);
    mbar_wait(bar_full, 0); mbar_wait(bar_full + 8, 0); mbar_wait(bar_full + 16, 1);
    mbar_wait(bar_go + 16, 0);
    const uint64_t dwo = make_desc(D0 * 16, 5120, 512, 2);
    wgmma_fence();
#pragma unroll
    for (int s = 0; s < 5; s++) wgmma_n80_rs(h, of[4 * s], of[4 * s + 1], of[4 * s + 2], of[4 * s + 3], dwo + g * 960 + s * 64, 1);
    wgmma_commit();
    TS(6);
    const bool odd = c & 1;
    uint4* const sp = hold(&g_own[slot].st2[r + (odd ? 8 : 0)]);
    uint4* const cdp = hold(&g_x.cand[slot][g][0]);
    uint4* const kcp = hold(g_own[1].cnt);
    float wr[20];
#pragma unroll
    for (int j = 0; j < 5; j++) {
      const uint4 v = lds128(sb + OFF_WR + c * 80 + j * 16);
      wr[4 * j] = __uint_as_float(v.x); wr[4 * j + 1] = __uint_as_float(v.y); wr[4 * j + 2] = __uint_as_float(v.z); wr[4 * j + 3] = __uint_as_float(v.w);
    }
    const float wsum = lds32f(sb + OFF_WR + 320);
    const uint32_t bo = bar_o + fol * 56;
#pragma unroll
    for (int i = 0; i < 7; i++) {
      mbar_wait(bo + 8 * i, 0);
      if (i == 0) TS(1);
      const uint32_t da = D0 + OFF_O / 16 + (8 << 16) + ((i + 2) % 7) * 640, db = D0 + (320 << 16) + (i >= g ? i + 1 : i) * 960;
      wgmma_fence();
#pragma unroll
      for (int s = 0; s < 5; s++) wgmma_n80_ss(h, mk64(da + s * 16, 80u), mk64(db + s * 64, 0x80000020u), 1);
      wgmma_commit();
      wgmma_wait<1>();
      if (lane == 0 && i > 0) mbar_arrive(bo + 104 + 8 * i);
    }
    const int tok0 = P * 256 + 32 * warp + rank;
    wgmma_wait<0>();
#pragma unroll
    for (int i = 0; i < 40; i++) asm volatile("" : "+f"(h[i]) :: "memory");
    if (lane == 0) mbar_arrive(bo + 160);
    TS(7);
    float mean, rstd, rr;
    bool pub;
    {
      float l1 = 0.f, l2 = 0.f, l3 = 0.f, h1 = 0.f, h2 = 0.f, h3 = 0.f;
#pragma unroll
      for (int j = 0; j < 10; j++) {
        l1 += h[4 * j] + h[4 * j + 1]; h1 += h[4 * j + 2] + h[4 * j + 3];
        l2 = fmaf(h[4 * j], h[4 * j], l2); l2 = fmaf(h[4 * j + 1], h[4 * j + 1], l2);
        h2 = fmaf(h[4 * j + 2], h[4 * j + 2], h2); h2 = fmaf(h[4 * j + 3], h[4 * j + 3], h2);
        l3 = fmaf(h[4 * j], wr[2 * j], l3); l3 = fmaf(h[4 * j + 1], wr[2 * j + 1], l3);
        h3 = fmaf(h[4 * j + 2], wr[2 * j], h3); h3 = fmaf(h[4 * j + 3], wr[2 * j + 1], h3);
      }
      float s1 = (odd ? h1 : l1) + shx(odd ? l1 : h1, 1), s2 = (odd ? h2 : l2) + shx(odd ? l2 : h2, 1), s3 = (odd ? h3 : l3) + shx(odd ? l3 : h3, 1);
      s1 += shx(s1, 2); s2 += shx(s2, 2); s3 += shx(s3, 2);
      uint4 p0;
      float o1 = 0.f, o2 = 0.f, o3 = 0.f, oc = 7.f;
      asm volatile("{\n.reg .pred q;\nsetp.lt.u32 q, %9, 2;\n@q atom.relaxed.gpu.global.add.v4.f32 {%0, %1, %2, %3}, [%4], {%5, %6, %7, %8};\n}\n"
                   : "+f"(o1), "+f"(o2), "+f"(o3), "+f"(oc) : "l"(sp), "f"(s1), "f"(s2), "f"(s3), "f"(1.f), "r"(c) : "memory");
      const uint32_t last = __ballot_sync(0xffffffffu, oc == 7.f);
      pub = last & 1;
      p0.x = __float_as_uint(__shfl_sync(0xffffffffu, o1 + s1, lane & 29)); p0.y = __float_as_uint(__shfl_sync(0xffffffffu, o2 + s2, lane & 29));
      p0.z = __float_as_uint(__shfl_sync(0xffffffffu, o3 + s3, lane & 29));
      if (last != 0xffffffffu)
      do { p0 = ldg_pkt(sp); } while (anyw(p0.w != 0x41000000u) && --guard > 0);
      mean = __uint_as_float(p0.x) * (1.f / 640.f);
      rstd = rsq(fmaxf(fmaf(-mean, mean, __uint_as_float(p0.y) * (1.f / 640.f)), 0.f) + 1e-5f);
      rr = fmaf(-mean, wsum, __uint_as_float(p0.z)) * rstd;
    }
    TS(8);
    const uint32_t kk = ord_key(rr), kmax = __reduce_max_sync(0xffffffffu, kk);
    const int L = __ffs(__ballot_sync(0xffffffffu, kk == kmax)) - 1;
    const int crow = (L >> 2) + 8 * (L & 1);
    asm volatile("{\n.reg .pred q;\nsetp.ne.u32 q, %2, 0;\n@q red.relaxed.gpu.global.max.u64 [%0], %1;\n@q red.relaxed.gpu.global.add.u32 [%0 + 8], 1;\n}\n"
                 :: "l"(kcp), "l"(mk64(2047 - tok0 - 2 * crow, kmax)), "r"((int)(pub && lane == 0)) : "memory");
    if (warp == g) asm volatile("bar.arrive 3, 64;" ::: "memory");
    const uint32_t stg = sb + (fol ? OFF_O : g * 15360) + w4 * 2560;
    uint4 held;
    {
      const float om = shx(mean, 1), os = shx(rstd, 1);
      const float rl = odd ? os : rstd, rh = odd ? rstd : os;
      const float bl = -(odd ? om : mean) * rl, bh = -(odd ? mean : om) * rh, al = 1.f + rl, ah = 1.f + rh;
      if ((L >> 2) == r) {
        const bool chi = L & 1;
        const float rc = chi ? rh : rl, bc = chi ? bh : bl;
        uint32_t n[10];
#pragma unroll
        for (int j = 0; j < 10; j++) n[j] = pack_bf16(fmaf(chi ? h[4 * j + 2] : h[4 * j], rc, bc), fmaf(chi ? h[4 * j + 3] : h[4 * j + 1], rc, bc));
        uint4* d = cdp + c;
        stg_pkt(d, n[0], n[1], n[2], n[3]); stg_pkt(d + 4, n[4], n[5], n[6], n[7]); stg_rlx64(d + 8, n[8], n[9]);
      }
      mbar_wait(bar_oc + 56, 0);
      const uint32_t fa = stg + (lane & 15) * 160 + (lane >> 4) * 16;
#pragma unroll
      for (int s = 0; s < 5; s++)
        stsm4(fa + s * 32, pack_bf16(fmaf(h[8 * s], al, bl), fmaf(h[8 * s + 1], al, bl)), pack_bf16(fmaf(h[8 * s + 2], ah, bh), fmaf(h[8 * s + 3], ah, bh)),
              pack_bf16(fmaf(h[8 * s + 4], al, bl), fmaf(h[8 * s + 5], al, bl)), pack_bf16(fmaf(h[8 * s + 6], ah, bh), fmaf(h[8 * s + 7], ah, bh)));
      __syncwarp();
      held = lds128(stg + crow * 160 + min(lane, 9) * 16);
      if (lane < 10) stg_pkt(cdp + 12 + lane, held.x, held.y, held.z, held.w);
    }
    TS(9);
    mbar_wait(bar_ffn, 0);
    const uint32_t red = sb + OFF_RED;
    if (ffn1) {
      uint4 w1[4][5];
      {
        const int k = (lane & 7) + (lane >> 4) * 8;
        const uint32_t a1 = sb + k * 64, sw = ((lane >> 3) & 1) ^ ((lane >> 1) & 3);
#pragma unroll
        for (int s = 0; s < 5; s++)
#pragma unroll
          for (int u = 0; u < 4; u++)
            w1[u][s] = ldsm4t(a1 + (s < 4 ? warp * 4096 + s * 1024 : 32768 + warp * 1024) + (u >> 1) * (40960 + (s == 4 || warp >= 4 ? OFF_W2 - 57344 : 0)) + ((sw ^ (2 * (u & 1))) * 16));
      }
      uint32_t* const ap = hold(g_x.act + fj * 16 + (lane >> 1));
      mbar_wait(bar_win, 0);
      const uint32_t hp = sb + OFF_HN + (warp * 4 + c) * 16;
      const uint4 c0 = lds128(hp), c1 = lds128(hp + 512), c2 = lds128(hp + 1024);
      TS(10);
      float a[4][4];
#pragma unroll
      for (int u = 0; u < 4; u++) {
        a[u][0] = a[u][1] = a[u][2] = a[u][3] = 0.f;
        mma_acc(a[u], w1[u][0], c0.x, c0.y); mma_acc(a[u], w1[u][1], c0.z, c0.w); mma_acc(a[u], w1[u][2], c1.x, c1.y);
        mma_acc(a[u], w1[u][3], c1.z, c1.w); mma_acc(a[u], w1[u][4], c2.x, c2.y);
      }
      asm volatile("st.shared.v2.f32 [%0], {%1, %2};" :: "r"(red + (warp * 32 + c * 8 + r) * 8),
                   "f"(cA ? (odd ? a[0][2] : a[0][0]) : (odd ? a[1][2] : a[1][0])), "f"(cA ? (odd ? a[2][2] : a[2][0]) : (odd ? a[3][2] : a[3][0])) : "memory");
      bar_sync(1, 256);
      if (warp == 0) {
        float2 t[8];
#pragma unroll
        for (int i = 0; i < 8; i++) t[i] = lds64f(red + (i * 32 + lane) * 8);
        const float s = ((t[0].x + t[1].x) + (t[2].x + t[3].x)) + ((t[4].x + t[5].x) + (t[6].x + t[7].x));
        const float u = ((t[0].y + t[1].y) + (t[2].y + t[3].y)) + ((t[4].y + t[5].y) + (t[6].y + t[7].y));
        const float av = s * u * rcp(1.f + ex2(-1.4426950408889634f * s));
        const float an = shx(av, 1);
        if (!odd) stg_rlx32(ap, pack_bf16(av, an));
      }
      bar_sync(1, 256);
      TS(11);
    }
    char* const ob2 = (char*)(out + tok0 * 640 + g * 64);
    const int remo = 896 - 96 * g;
    {
      char* const q0 = ob2 + (lane >> 3) * 2560 + (lane & 7) * 16;
      const uint32_t s0 = stg + (lane >> 3) * 160 + (lane & 7) * 16;
#pragma unroll
      for (int s = 0; s < 4; s++) stg128_if(4 * s + (lane >> 3) != crow, q0 + s * 10240, lds128(s0 + s * 640));
      stg128_if((lane >> 1) != crow, ob2 + (lane >> 1) * 2560 + (lane & 1) * 16 + 128 + remo, lds128(stg + (lane >> 1) * 160 + (lane & 1) * 16 + 128));
    }
    mbar_wait(bar_win, 0);
    uint4 win = lds128(sb + OFF_WR + 336);
    win.z = win.y; win.y = 2047u - (win.x & 2047u); win.x = (win.y >> 8) * 16 + (win.y & 1) * 8 + ((win.y >> 5) & 7);
    stg128_if(win.x != slot && lane < 10, ob2 + crow * 2560 + lane * 16 + (lane < 8 ? 0 : remo), held);
    if (!ffn1) {
      TS(10);
      uint4 w2[6];
      const uint32_t a2 = sb + OFF_W2 + (warp * 192 + 8 * (((lane >> 3) & 1) * 4 + ((lane & 7) >> 1)) + 2 * (lane >> 4) + (lane & 1)) * 16;
#pragma unroll
      for (int s = 0; s < 6; s++) w2[s] = ldsm4t(a2 + (s >> 1) * 1024 + (s & 1) * 64);
      const uint4* p = (const uint4*)(g_x.act + warp * 96) + (r & 1) * 4 + c;
      const uint32_t* pb = (const uint32_t*)&g_x.cand[win.x][fj < 64 ? fj >> 3 : (fj - 64) >> 1][fj < 64 ? 12 + (fj & 7) : 20 + (fj & 1)] + c;
      uint32_t* const op = hold((uint32_t*)(out + win.y * 640 + fj * 8) + c);
      const float sg = rcp(1.f + ex2(-1.4426950408889634f * __uint_as_float(win.z ^ ((uint32_t)((int32_t)~win.z >> 31) | 0x80000000u))));
      uint4 c0, c1, c2; uint32_t bw;
      if (ACT_NS) __nanosleep(ACT_NS);
      do {
        c0 = ldg_pkt(p); c1 = ldg_pkt(p + 8); c2 = ldg_pkt(p + 16); bw = ldg_rlx32(pb);
      } while (anyw(max(max(max(max(c0.x, c0.y), max(c0.z, c0.w)), max(max(c1.x, c1.y), max(c1.z, c1.w))), max(max(max(c2.x, c2.y), max(c2.z, c2.w)), bw)) == SENT) && --guard > 0);
      TS(11);
      float a[4] = {0.f, 0.f, 0.f, 0.f}, b[4] = {0.f, 0.f, 0.f, 0.f}, d[4] = {0.f, 0.f, 0.f, 0.f};
      mma_acc(a, w2[0], c0.x, c0.y); mma_acc(b, w2[2], c1.x, c1.y); mma_acc(d, w2[4], c2.x, c2.y);
      mma_acc(a, w2[1], c0.z, c0.w); mma_acc(b, w2[3], c1.z, c1.w); mma_acc(d, w2[5], c2.z, c2.w);
      if (c == 0) sts32f(red + (warp * 8 + r) * 4, ((a[0] + a[3]) + (b[0] + b[3])) + (d[0] + d[3]));
      bar_sync(1, 256);
      if (tid < 4) {
        float2 t[8];
#pragma unroll
        for (int i = 0; i < 8; i++) t[i] = lds64f(red + (i * 4 + tid) * 8);
        const float y0 = ((t[0].x + t[1].x) + (t[2].x + t[3].x)) + ((t[4].x + t[5].x) + (t[6].x + t[7].x));
        const float y1 = ((t[0].y + t[1].y) + (t[2].y + t[3].y)) + ((t[4].y + t[5].y) + (t[6].y + t[7].y));
        *op = pack_bf16(fmaf(y0, sg, bf_lo(bw)), fmaf(y1, sg, bf_hi(bw)));
      }
    }
    TS(12);
#undef TS_T
  }
}

typedef CUresult (*EncodeFn)(CUtensorMap*, CUtensorMapDataType, cuuint32_t, void*, const cuuint64_t*, const cuuint64_t*, const cuuint32_t*,
                             const cuuint32_t*, CUtensorMapInterleave, CUtensorMapSwizzle, CUtensorMapL2promotion, CUtensorMapFloatOOBfill);

void make_map(EncodeFn enc, CUtensorMap* m, const void* base, const cuuint64_t* dims, const cuuint64_t* strides, const cuuint32_t* box,
              CUtensorMapSwizzle swz) {
  const cuuint32_t es[3] = {1, 1, 1};
  enc(m, CU_TENSOR_MAP_DATA_TYPE_BFLOAT16, 3, (void*)base, dims, strides, box, es, CU_TENSOR_MAP_INTERLEAVE_NONE, swz,
      CU_TENSOR_MAP_L2_PROMOTION_L2_128B, CU_TENSOR_MAP_FLOAT_OOB_FILL_NONE);
}

}

extern "C" void kernel_launch(void* const* d_in, const int* in_sizes, int n_in, void* d_out, int out_size) {
  const __nv_bfloat16* x = (const __nv_bfloat16*)d_in[0];
  const __nv_bfloat16* wqkv = (const __nv_bfloat16*)d_in[1];
  const __nv_bfloat16* wo = (const __nv_bfloat16*)d_in[2];
  void* fn = nullptr;
  cudaDriverEntryPointQueryResult st;
  cudaGetDriverEntryPoint("cuTensorMapEncodeTiled", &fn, cudaEnableDefault, &st);
  EncodeFn enc = (EncodeFn)fn;
  void* scp = nullptr;
  cudaGetSymbolAddress(&scp, g_scratch);
  Maps tm;
  { const cuuint64_t d[3] = {640, 1024, 2}, s[2] = {2560, 1280}; const cuuint32_t b[3] = {64, 128, 1}; make_map(enc, &tm.x, x, d, s, b, CU_TENSOR_MAP_SWIZZLE_128B); }
  { const cuuint64_t d[3] = {640, 640, 3}, s[2] = {3840, 1280}; const cuuint32_t b[3] = {64, 16, 3}; make_map(enc, &tm.w, wqkv, d, s, b, CU_TENSOR_MAP_SWIZZLE_128B); }
  { const cuuint64_t d[3] = {640, 640, 3}, s[2] = {3840, 1280}; const cuuint32_t b[3] = {16, 16, 3}; make_map(enc, &tm.wr, wqkv, d, s, b, CU_TENSOR_MAP_SWIZZLE_32B); }
  { const cuuint64_t d[3] = {640, 640, 3}, s[2] = {3840, 1280}; const cuuint32_t b[3] = {16, 16, 1}; make_map(enc, &tm.wv, wqkv, d, s, b, CU_TENSOR_MAP_SWIZZLE_32B); }
  { const cuuint64_t d[3] = {32, 640, 20}, s[2] = {1280, 64}; const cuuint32_t b[3] = {32, 80, 2}; make_map(enc, &tm.wo, wo, d, s, b, CU_TENSOR_MAP_SWIZZLE_64B); }
  { const cuuint64_t d[3] = {640, 640, 1}, s[2] = {1280, 819200}; const cuuint32_t b[3] = {16, 80, 1}; make_map(enc, &tm.wor, wo, d, s, b, CU_TENSOR_MAP_SWIZZLE_64B); }
  { const cuuint64_t d[3] = {1536, 640, 1}, s[2] = {3072, 1966080}; const cuuint32_t b[3] = {32, 128, 1};
    make_map(enc, &tm.gate, d_in[5], d, s, b, CU_TENSOR_MAP_SWIZZLE_64B); make_map(enc, &tm.up, d_in[6], d, s, b, CU_TENSOR_MAP_SWIZZLE_64B); }
  { const cuuint64_t d[3] = {640, 1536, 1}, s[2] = {1280, 1966080}; const cuuint32_t b[3] = {8, 128, 1}; make_map(enc, &tm.down, d_in[7], d, s, b, CU_TENSOR_MAP_SWIZZLE_NONE); }
  cudaFuncSetAttribute(fused_kernel, cudaFuncAttributeMaxDynamicSharedMemorySize, SMEM_BYTES);
  fused_kernel<<<128, 512, SMEM_BYTES, cudaStreamPerThread>>>(x, wqkv, wo, (const __nv_bfloat16*)d_in[4], (const __nv_bfloat16*)d_in[5],
                                                              (const __nv_bfloat16*)d_in[6], (const __nv_bfloat16*)d_in[7], (__nv_bfloat16*)d_out, (Scratch*)scp, tm);
}
```

```cpp
#include <cuda_runtime.h>
#include <cuda_bf16.h>
#include <cuda.h>
#include <stdint.h>

#define PFW_NS 50
#define PFW_N 14
#define ACT_NS 100
#define KEY_NS 0
#define AUX_NS 50
#define REG_P 72
#define REG_C 184
#define LEAD 1
#define HK_IT 1
#define F_PER 2
#define F_MAX 8
#define HOLD 2
#define AK 3
#define NSPLIT 3
#define THR_END 4
#define BOUNDED 0
#define TLIGHT 0
#define ATOM2 1
#define LAG 5

namespace {

constexpr int SLOT    = 49152;
constexpr int OFF_O   = 122880;
constexpr int OFF_W2  = 4 * SLOT;
constexpr int OFF_CS  = OFF_W2 + 24576;
constexpr int OFF_RS  = OFF_CS + 3840;
constexpr int OFF_MN  = OFF_RS + 576;
constexpr int OFF_WR  = OFF_MN + 1024;
constexpr int OFF_RED = OFF_CS;
constexpr int OFF_HN  = OFF_CS + 2048;
constexpr int OFF_PT  = OFF_WR + 352;
constexpr int OFF_BAR = OFF_PT + 768;
constexpr int SMEM_BYTES = OFF_BAR + 424 + 384;
constexpr uint32_t D0 = 1024 >> 4;
constexpr uint32_t SENT = 0xFFFFFFFFu;
constexpr int SPIN_MAX = 1 << 20;

struct Glob {
  uint4 cand[128][8][24];
  uint32_t act[768];
  uint32_t pad[256];
};
constexpr int GLOB_PER_CTA = sizeof(Glob) / 16 / 128;
static_assert(GLOB_PER_CTA * 128 * 16 == sizeof(Glob), "glob size");
struct Own {
  uint4 halo[5][32];
  uint4 st1[32];
  uint2 cs[32];
  uint4 st2[16];
  uint4 cnt[8];
};
struct Scratch {
  Glob x;
  Own own[128];
  uint4 o[32][8][640];
  uint32_t epoch[128];
};
__device__ __align__(128) Scratch g_scratch;
#define g_x (sc->x)
#define g_own (sc->own)
#define g_o (sc->o)
#define g_epoch (sc->epoch)
#define TS(i)

__device__ __forceinline__ void mbar_init(uint32_t bar, uint32_t cnt) { asm volatile("mbarrier.init.shared::cta.b64 [%0], %1;" :: "r"(bar), "r"(cnt) : "memory"); }
__device__ __forceinline__ void mbar_expect_tx(uint32_t bar, uint32_t bytes) { asm volatile("mbarrier.arrive.expect_tx.shared::cta.b64 _, [%0], %1;" :: "r"(bar), "r"(bytes) : "memory"); }
__device__ __forceinline__ void mbar_arrive(uint32_t bar) { asm volatile("mbarrier.arrive.shared::cta.b64 _, [%0];" :: "r"(bar) : "memory"); }
__device__ __forceinline__ void mbar_arrive_cta(uint32_t bar, uint32_t cta) {
  asm volatile("{\n.reg .b32 ra;\nmapa.shared::cluster.u32 ra, %0, %1;\nmbarrier.arrive.shared::cluster.b64 _, [ra];\n}\n" :: "r"(bar), "r"(cta) : "memory");
}
__device__ __forceinline__ void mbar_wait(uint32_t bar, uint32_t parity) {
  asm volatile("{\n.reg .pred p;\nW:\nmbarrier.try_wait.parity.shared::cta.b64 p, [%0], %1;\n@!p bra.uni W;\n}\n" :: "r"(bar), "r"(parity) : "memory");
}
__device__ __forceinline__ void tma_3d(uint32_t dst, const void* tm, uint32_t bar, int c0, int c1, int c2) {
  asm volatile("cp.async.bulk.tensor.3d.shared::cluster.global.mbarrier::complete_tx::bytes [%0], [%1, {%3, %4, %5}], [%2];" :: "r"(dst), "l"(tm), "r"(bar), "r"(c0), "r"(c1), "r"(c2) : "memory");
}
__device__ __forceinline__ void tma_3d_mc(uint32_t dst, const void* tm, uint32_t bar, int c0, int c1, int c2) {
  asm volatile("cp.async.bulk.tensor.3d.shared::cluster.global.mbarrier::complete_tx::bytes.multicast::cluster [%0], [%1, {%3, %4, %5}], [%2], %6;" :: "r"(dst), "l"(tm), "r"(bar), "r"(c0), "r"(c1), "r"(c2), "h"((uint16_t)3) : "memory");
}
__device__ __forceinline__ void wgmma_fence() { asm volatile("wgmma.fence.sync.aligned;" ::: "memory"); }
__device__ __forceinline__ void wgmma_commit() { asm volatile("wgmma.commit_group.sync.aligned;" ::: "memory"); }
template <int N> __device__ __forceinline__ void wgmma_wait() { asm volatile("wgmma.wait_group.sync.aligned %0;" :: "n"(N) : "memory"); }
__device__ __forceinline__ uint64_t make_desc(uint32_t addr, uint32_t lbo, uint32_t sbo, uint32_t swz) {
  return (uint64_t)(((addr & 0x3FFFF) >> 4) | ((lbo >> 4) << 16)) | ((uint64_t)((sbo >> 4) | (swz << 30)) << 32);
}
__device__ __forceinline__ void bar_sync(int id, int n) { asm volatile("bar.sync %0, %1;" :: "r"(id), "r"(n) : "memory"); }
__device__ __forceinline__ void st_pkt(void* p, uint32_t a, uint32_t b, uint32_t c, uint32_t d) {
  asm volatile("st.relaxed.gpu.v4.u32 [%0], {%1, %2, %3, %4};" :: "l"(p), "r"(a), "r"(b), "r"(c), "r"(d) : "memory");
}
__device__ __forceinline__ uint4 ldg_pkt(const void* p) {
  uint4 v; asm volatile("ld.relaxed.gpu.global.v4.u32 {%0, %1, %2, %3}, [%4];" : "=r"(v.x), "=r"(v.y), "=r"(v.z), "=r"(v.w) : "l"(p) : "memory"); return v;
}
__device__ __forceinline__ void stg_pkt(void* p, uint32_t a, uint32_t b, uint32_t c, uint32_t d) {
  asm volatile("st.relaxed.gpu.global.v4.u32 [%0], {%1, %2, %3, %4};" :: "l"(p), "r"(a), "r"(b), "r"(c), "r"(d) : "memory");
}
__device__ __forceinline__ uint32_t ldg_rlx32(const void* p) { uint32_t v; asm volatile("ld.relaxed.gpu.global.u32 %0, [%1];" : "=r"(v) : "l"(p) : "memory"); return v; }
__device__ __forceinline__ uint2 ldg_rlx64(const void* p) { uint2 v; asm volatile("ld.relaxed.gpu.global.v2.u32 {%0, %1}, [%2];" : "=r"(v.x), "=r"(v.y) : "l"(p) : "memory"); return v; }
__device__ __forceinline__ uint32_t pin(uint32_t v) { asm volatile("" : "+r"(v)); return v; }
__device__ __forceinline__ uint64_t mk64(uint32_t lo, uint32_t hi) { return ((uint64_t)hi << 32) | lo; }
template <class T> __device__ __forceinline__ T* hold(T* p) { return (T*)__shfl_sync(0xffffffffu, (unsigned long long)p, threadIdx.x & 31); }
__device__ __forceinline__ void stg128_if(bool q, void* p, const uint4& v) {
  asm volatile("{\n.reg .pred q;\nsetp.ne.u32 q, %5, 0;\n@q st.global.v4.u32 [%0], {%1, %2, %3, %4};\n}\n" :: "l"(p), "r"(v.x), "r"(v.y), "r"(v.z), "r"(v.w), "r"((int)q) : "memory");
}
template <class T> __device__ __forceinline__ T* pin(T* p) { asm volatile("" : "+l"(p)); return p; }
__device__ __forceinline__ void stg_rlx32(void* p, uint32_t v) { asm volatile("st.relaxed.gpu.global.u32 [%0], %1;" :: "l"(p), "r"(v) : "memory"); }
__device__ __forceinline__ void stg_rlx64(void* p, uint32_t a, uint32_t b) { asm volatile("st.relaxed.gpu.global.v2.u32 [%0], {%1, %2};" :: "l"(p), "r"(a), "r"(b) : "memory"); }
__device__ __forceinline__ uint4 ldsm4(uint32_t a) { uint4 v; asm volatile("ldmatrix.sync.aligned.m8n8.x4.shared.b16 {%0, %1, %2, %3}, [%4];" : "=r"(v.x), "=r"(v.y), "=r"(v.z), "=r"(v.w) : "r"(a) : "memory"); return v; }
__device__ __forceinline__ void ldsm4_if(uint4& v, uint32_t a, int off, bool p) {
  asm volatile("{\n.reg .pred q;\nsetp.ne.u32 q, %5, 0;\n@q ldmatrix.sync.aligned.m8n8.x4.shared.b16 {%0, %1, %2, %3}, [%4];\n}\n"
               : "+r"(v.x), "+r"(v.y), "+r"(v.z), "+r"(v.w) : "r"(a + off), "r"((int)p) : "memory");
}
__device__ __forceinline__ uint4 ldsm4t(uint32_t a) { uint4 v; asm volatile("ldmatrix.sync.aligned.m8n8.x4.trans.shared.b16 {%0, %1, %2, %3}, [%4];" : "=r"(v.x), "=r"(v.y), "=r"(v.z), "=r"(v.w) : "r"(a) : "memory"); return v; }
__device__ __forceinline__ void stsm4(uint32_t a, uint32_t x, uint32_t y, uint32_t z, uint32_t w) { asm volatile("stmatrix.sync.aligned.m8n8.x4.shared.b16 [%0], {%1, %2, %3, %4};" :: "r"(a), "r"(x), "r"(y), "r"(z), "r"(w) : "memory"); }
__device__ __forceinline__ void mma_acc(float (&c)[4], const uint4& a, uint32_t b0, uint32_t b1) {
  asm("mma.sync.aligned.m16n8k16.row.col.f32.bf16.bf16.f32 {%0,%1,%2,%3}, {%4,%5,%6,%7}, {%8,%9}, {%0,%1,%2,%3};"
      : "+f"(c[0]), "+f"(c[1]), "+f"(c[2]), "+f"(c[3]) : "r"(a.x), "r"(a.y), "r"(a.z), "r"(a.w), "r"(b0), "r"(b1));
}
__device__ __forceinline__ uint4 lds128(uint32_t a) { uint4 v; asm volatile("ld.shared.v4.u32 {%0, %1, %2, %3}, [%4];" : "=r"(v.x), "=r"(v.y), "=r"(v.z), "=r"(v.w) : "r"(a) : "memory"); return v; }
__device__ __forceinline__ float2 lds64f(uint32_t a) { float2 v; asm volatile("ld.shared.v2.f32 {%0, %1}, [%2];" : "=f"(v.x), "=f"(v.y) : "r"(a)); return v; }
__device__ __forceinline__ float lds32f(uint32_t a) { float v; asm volatile("ld.shared.f32 %0, [%1];" : "=f"(v) : "r"(a)); return v; }
__device__ __forceinline__ void sts32f(uint32_t a, float v) { asm volatile("st.shared.f32 [%0], %1;" :: "r"(a), "f"(v) : "memory"); }
__device__ __forceinline__ uint32_t pack_bf16(float lo, float hi) { uint32_t r; asm("cvt.rn.bf16x2.f32 %0, %1, %2;" : "=r"(r) : "f"(hi), "f"(lo)); return r; }
__device__ __forceinline__ float bf_lo(uint32_t v) { return __uint_as_float(v << 16); }
__device__ __forceinline__ float bf_hi(uint32_t v) { return __uint_as_float(v & 0xffff0000u); }
__device__ __forceinline__ uint32_t movm(uint32_t a) { uint32_t d; asm("movmatrix.sync.aligned.m8n8.trans.b16 %0, %1;" : "=r"(d) : "r"(a)); return d; }
__device__ __forceinline__ float ex2(float x) { float y; asm("ex2.approx.ftz.f32 %0, %1;" : "=f"(y) : "f"(x)); return y; }
__device__ __forceinline__ float rsq(float x) { float y; asm("rsqrt.approx.ftz.f32 %0, %1;" : "=f"(y) : "f"(x)); return y; }
__device__ __forceinline__ float rcp(float x) { float y; asm("rcp.approx.ftz.f32 %0, %1;" : "=f"(y) : "f"(x)); return y; }
__device__ __forceinline__ bool elect() { uint32_t p; asm volatile("{\n.reg .pred q;\nelect.sync _|q, 0xffffffff;\nselp.u32 %0, 1, 0, q;\n}\n" : "=r"(p)); return p; }
__device__ __forceinline__ void pf_l2(const void* p) { asm volatile("prefetch.global.L2 [%0];" :: "l"(p)); }
__device__ __forceinline__ bool anyw(bool p) { return __any_sync(0xffffffffu, p); }
__device__ __forceinline__ float shx(float v, int m) { return __shfl_xor_sync(0xffffffffu, v, m); }
__device__ __forceinline__ void mma_k24(float (&c)[4], uint32_t a0, uint32_t a1, uint32_t a2, uint32_t a3, uint32_t b0, uint32_t b1,
                                        uint32_t e0, uint32_t e1, uint32_t f0) {
  asm("mma.sync.aligned.m16n8k16.row.col.f32.bf16.bf16.f32 {%0,%1,%2,%3}, {%4,%5,%6,%7}, {%8,%9}, {%10,%10,%10,%10};"
      : "=f"(c[0]), "=f"(c[1]), "=f"(c[2]), "=f"(c[3]) : "r"(a0), "r"(a1), "r"(a2), "r"(a3), "r"(b0), "r"(b1), "f"(0.f));
  asm("mma.sync.aligned.m16n8k8.row.col.f32.bf16.bf16.f32 {%0,%1,%2,%3}, {%4,%5}, {%6}, {%0,%1,%2,%3};"
      : "+f"(c[0]), "+f"(c[1]), "+f"(c[2]), "+f"(c[3]) : "r"(e0), "r"(e1), "r"(f0));
}
__device__ __forceinline__ uint32_t ord_key(float r) { uint32_t u = __float_as_uint(r); return u ^ ((uint32_t)((int32_t)u >> 31) | 0x80000000u); }

__device__ __forceinline__ void wgmma_n64hi_ss(float (&d)[120], uint64_t da, uint64_t db, int scale_d) {
  asm volatile("{\n.reg .pred p;\nsetp.ne.b32 p, %34, 0;\n"
    "wgmma.mma_async.sync.aligned.m64n64k16.f32.bf16.bf16 "
    "{%0, %1, %2, %3, %4, %5, %6, %7, %8, %9, %10, %11, %12, %13, %14, %15, "
    "%16, %17, %18, %19, %20, %21, %22, %23, %24, %25, %26, %27, %28, %29, %30, %31}, "
    "%32, %33, p, 1, 1, 0, 1;\n}\n"
    : "+f"(d[88]), "+f"(d[89]), "+f"(d[90]), "+f"(d[91]), "+f"(d[92]), "+f"(d[93]), "+f"(d[94]), "+f"(d[95]),
      "+f"(d[96]), "+f"(d[97]), "+f"(d[98]), "+f"(d[99]), "+f"(d[100]), "+f"(d[101]), "+f"(d[102]), "+f"(d[103]),
      "+f"(d[104]), "+f"(d[105]), "+f"(d[106]), "+f"(d[107]), "+f"(d[108]), "+f"(d[109]), "+f"(d[110]), "+f"(d[111]),
      "+f"(d[112]), "+f"(d[113]), "+f"(d[114]), "+f"(d[115]), "+f"(d[116]), "+f"(d[117]), "+f"(d[118]), "+f"(d[119])
    : "l"(da), "l"(db), "r"(scale_d));
}
__device__ __forceinline__ void wgmma_n176lo_ss(float (&d)[120], uint64_t da, uint64_t db, int scale_d) {
  asm volatile("{\n.reg .pred p;\nsetp.ne.b32 p, %90, 0;\n"
    "wgmma.mma_async.sync.aligned.m64n176k16.f32.bf16.bf16 "
    "{%0, %1, %2, %3, %4, %5, %6, %7, %8, %9, %10, %11, %12, %13, %14, %15, "
    "%16, %17, %18, %19, %20, %21, %22, %23, %24, %25, %26, %27, %28, %29, %30, %31, "
    "%32, %33, %34, %35, %36, %37, %38, %39, %40, %41, %42, %43, %44, %45, %46, %47, "
    "%48, %49, %50, %51, %52, %53, %54, %55, %56, %57, %58, %59, %60, %61, %62, %63, "
    "%64, %65, %66, %67, %68, %69, %70, %71, %72, %73, %74, %75, %76, %77, %78, %79, "
    "%80, %81, %82, %83, %84, %85, %86, %87}, "
    "%88, %89, p, 1, 1, 0, 1;\n}\n"
    : "+f"(d[0]), "+f"(d[1]), "+f"(d[2]), "+f"(d[3]), "+f"(d[4]), "+f"(d[5]), "+f"(d[6]), "+f"(d[7]),
      "+f"(d[8]), "+f"(d[9]), "+f"(d[10]), "+f"(d[11]), "+f"(d[12]), "+f"(d[13]), "+f"(d[14]), "+f"(d[15]),
      "+f"(d[16]), "+f"(d[17]), "+f"(d[18]), "+f"(d[19]), "+f"(d[20]), "+f"(d[21]), "+f"(d[22]), "+f"(d[23]),
      "+f"(d[24]), "+f"(d[25]), "+f"(d[26]), "+f"(d[27]), "+f"(d[28]), "+f"(d[29]), "+f"(d[30]), "+f"(d[31]),
      "+f"(d[32]), "+f"(d[33]), "+f"(d[34]), "+f"(d[35]), "+f"(d[36]), "+f"(d[37]), "+f"(d[38]), "+f"(d[39]),
      "+f"(d[40]), "+f"(d[41]), "+f"(d[42]), "+f"(d[43]), "+f"(d[44]), "+f"(d[45]), "+f"(d[46]), "+f"(d[47]),
      "+f"(d[48]), "+f"(d[49]), "+f"(d[50]), "+f"(d[51]), "+f"(d[52]), "+f"(d[53]), "+f"(d[54]), "+f"(d[55]),
      "+f"(d[56]), "+f"(d[57]), "+f"(d[58]), "+f"(d[59]), "+f"(d[60]), "+f"(d[61]), "+f"(d[62]), "+f"(d[63]),
      "+f"(d[64]), "+f"(d[65]), "+f"(d[66]), "+f"(d[67]), "+f"(d[68]), "+f"(d[69]), "+f"(d[70]), "+f"(d[71]),
      "+f"(d[72]), "+f"(d[73]), "+f"(d[74]), "+f"(d[75]), "+f"(d[76]), "+f"(d[77]), "+f"(d[78]), "+f"(d[79]),
      "+f"(d[80]), "+f"(d[81]), "+f"(d[82]), "+f"(d[83]), "+f"(d[84]), "+f"(d[85]), "+f"(d[86]), "+f"(d[87])
    : "l"(da), "l"(db), "r"(scale_d));
}
__device__ __forceinline__ void wgmma_n64hi_rk(float (&d)[120], uint32_t a0, uint32_t a1, uint32_t a2, uint32_t a3, uint64_t db, int scale_d) {
  asm volatile("{\n.reg .pred p;\nsetp.ne.b32 p, %37, 0;\n"
    "wgmma.mma_async.sync.aligned.m64n64k16.f32.bf16.bf16 "
    "{%0, %1, %2, %3, %4, %5, %6, %7, %8, %9, %10, %11, %12, %13, %14, %15, "
    "%16, %17, %18, %19, %20, %21, %22, %23, %24, %25, %26, %27, %28, %29, %30, %31}, "
    "{%32, %33, %34, %35}, %36, p, 1, 1, 0;\n}\n"
    : "+f"(d[88]), "+f"(d[89]), "+f"(d[90]), "+f"(d[91]), "+f"(d[92]), "+f"(d[93]), "+f"(d[94]), "+f"(d[95]),
      "+f"(d[96]), "+f"(d[97]), "+f"(d[98]), "+f"(d[99]), "+f"(d[100]), "+f"(d[101]), "+f"(d[102]), "+f"(d[103]),
      "+f"(d[104]), "+f"(d[105]), "+f"(d[106]), "+f"(d[107]), "+f"(d[108]), "+f"(d[109]), "+f"(d[110]), "+f"(d[111]),
      "+f"(d[112]), "+f"(d[113]), "+f"(d[114]), "+f"(d[115]), "+f"(d[116]), "+f"(d[117]), "+f"(d[118]), "+f"(d[119])
    : "r"(a0), "r"(a1), "r"(a2), "r"(a3), "l"(db), "r"(scale_d));
}
__device__ __forceinline__ void wgmma_n176lo_rk(float (&d)[120], uint32_t a0, uint32_t a1, uint32_t a2, uint32_t a3, uint64_t db, int scale_d) {
  asm volatile("{\n.reg .pred p;\nsetp.ne.b32 p, %93, 0;\n"
    "wgmma.mma_async.sync.aligned.m64n176k16.f32.bf16.bf16 "
    "{%0, %1, %2, %3, %4, %5, %6, %7, %8, %9, %10, %11, %12, %13, %14, %15, "
    "%16, %17, %18, %19, %20, %21, %22, %23, %24, %25, %26, %27, %28, %29, %30, %31, "
    "%32, %33, %34, %35, %36, %37, %38, %39, %40, %41, %42, %43, %44, %45, %46, %47, "
    "%48, %49, %50, %51, %52, %53, %54, %55, %56, %57, %58, %59, %60, %61, %62, %63, "
    "%64, %65, %66, %67, %68, %69, %70, %71, %72, %73, %74, %75, %76, %77, %78, %79, "
    "%80, %81, %82, %83, %84, %85, %86, %87}, "
    "{%88, %89, %90, %91}, %92, p, 1, 1, 0;\n}\n"
    : "+f"(d[0]), "+f"(d[1]), "+f"(d[2]), "+f"(d[3]), "+f"(d[4]), "+f"(d[5]), "+f"(d[6]), "+f"(d[7]),
      "+f"(d[8]), "+f"(d[9]), "+f"(d[10]), "+f"(d[11]), "+f"(d[12]), "+f"(d[13]), "+f"(d[14]), "+f"(d[15]),
      "+f"(d[16]), "+f"(d[17]), "+f"(d[18]), "+f"(d[19]), "+f"(d[20]), "+f"(d[21]), "+f"(d[22]), "+f"(d[23]),
      "+f"(d[24]), "+f"(d[25]), "+f"(d[26]), "+f"(d[27]), "+f"(d[28]), "+f"(d[29]), "+f"(d[30]), "+f"(d[31]),
      "+f"(d[32]), "+f"(d[33]), "+f"(d[34]), "+f"(d[35]), "+f"(d[36]), "+f"(d[37]), "+f"(d[38]), "+f"(d[39]),
      "+f"(d[40]), "+f"(d[41]), "+f"(d[42]), "+f"(d[43]), "+f"(d[44]), "+f"(d[45]), "+f"(d[46]), "+f"(d[47]),
      "+f"(d[48]), "+f"(d[49]), "+f"(d[50]), "+f"(d[51]), "+f"(d[52]), "+f"(d[53]), "+f"(d[54]), "+f"(d[55]),
      "+f"(d[56]), "+f"(d[57]), "+f"(d[58]), "+f"(d[59]), "+f"(d[60]), "+f"(d[61]), "+f"(d[62]), "+f"(d[63]),
      "+f"(d[64]), "+f"(d[65]), "+f"(d[66]), "+f"(d[67]), "+f"(d[68]), "+f"(d[69]), "+f"(d[70]), "+f"(d[71]),
      "+f"(d[72]), "+f"(d[73]), "+f"(d[74]), "+f"(d[75]), "+f"(d[76]), "+f"(d[77]), "+f"(d[78]), "+f"(d[79]),
      "+f"(d[80]), "+f"(d[81]), "+f"(d[82]), "+f"(d[83]), "+f"(d[84]), "+f"(d[85]), "+f"(d[86]), "+f"(d[87])
    : "r"(a0), "r"(a1), "r"(a2), "r"(a3), "l"(db), "r"(scale_d));
}
__device__ __forceinline__ void wgmma_n80_rs(float (&d)[40], uint32_t a0, uint32_t a1, uint32_t a2, uint32_t a3, uint64_t db, int scale_d) {
  asm volatile("{\n.reg .pred p;\nsetp.ne.b32 p, %45, 0;\n"
    "wgmma.mma_async.sync.aligned.m64n80k16.f32.bf16.bf16 "
    "{%0, %1, %2, %3, %4, %5, %6, %7, %8, %9, %10, %11, %12, %13, %14, %15, "
    "%16, %17, %18, %19, %20, %21, %22, %23, %24, %25, %26, %27, %28, %29, %30, %31, "
    "%32, %33, %34, %35, %36, %37, %38, %39}, "
    "{%40, %41, %42, %43}, %44, p, 1, 1, 1;\n}\n"
    : "+f"(d[0]), "+f"(d[1]), "+f"(d[2]), "+f"(d[3]), "+f"(d[4]), "+f"(d[5]), "+f"(d[6]), "+f"(d[7]),
      "+f"(d[8]), "+f"(d[9]), "+f"(d[10]), "+f"(d[11]), "+f"(d[12]), "+f"(d[13]), "+f"(d[14]), "+f"(d[15]),
      "+f"(d[16]), "+f"(d[17]), "+f"(d[18]), "+f"(d[19]), "+f"(d[20]), "+f"(d[21]), "+f"(d[22]), "+f"(d[23]),
      "+f"(d[24]), "+f"(d[25]), "+f"(d[26]), "+f"(d[27]), "+f"(d[28]), "+f"(d[29]), "+f"(d[30]), "+f"(d[31]),
      "+f"(d[32]), "+f"(d[33]), "+f"(d[34]), "+f"(d[35]), "+f"(d[36]), "+f"(d[37]), "+f"(d[38]), "+f"(d[39])
    : "r"(a0), "r"(a1), "r"(a2), "r"(a3), "l"(db), "r"(scale_d));
}
__device__ __forceinline__ void wgmma_n80_ss(float (&d)[40], uint64_t da, uint64_t db, int scale_d) {
  asm volatile("{\n.reg .pred p;\nsetp.ne.b32 p, %42, 0;\n"
    "wgmma.mma_async.sync.aligned.m64n80k16.f32.bf16.bf16 "
    "{%0, %1, %2, %3, %4, %5, %6, %7, %8, %9, %10, %11, %12, %13, %14, %15, "
    "%16, %17, %18, %19, %20, %21, %22, %23, %24, %25, %26, %27, %28, %29, %30, %31, "
    "%32, %33, %34, %35, %36, %37, %38, %39}, "
    "%40, %41, p, 1, 1, 0, 1;\n}\n"
    : "+f"(d[0]), "+f"(d[1]), "+f"(d[2]), "+f"(d[3]), "+f"(d[4]), "+f"(d[5]), "+f"(d[6]), "+f"(d[7]),
      "+f"(d[8]), "+f"(d[9]), "+f"(d[10]), "+f"(d[11]), "+f"(d[12]), "+f"(d[13]), "+f"(d[14]), "+f"(d[15]),
      "+f"(d[16]), "+f"(d[17]), "+f"(d[18]), "+f"(d[19]), "+f"(d[20]), "+f"(d[21]), "+f"(d[22]), "+f"(d[23]),
      "+f"(d[24]), "+f"(d[25]), "+f"(d[26]), "+f"(d[27]), "+f"(d[28]), "+f"(d[29]), "+f"(d[30]), "+f"(d[31]),
      "+f"(d[32]), "+f"(d[33]), "+f"(d[34]), "+f"(d[35]), "+f"(d[36]), "+f"(d[37]), "+f"(d[38]), "+f"(d[39])
    : "l"(da), "l"(db), "r"(scale_d));
}

__device__ __forceinline__ constexpr int QT(int t) { return t < 8 ? t : 16 + t; }
__device__ __forceinline__ constexpr int KT(int t) { return t < 8 ? 8 + t : 18 + t; }
__device__ __forceinline__ constexpr int VT(int t) { return t < 8 ? 16 + t : 20 + t; }

struct Maps { CUtensorMap x, w, wr, wv, wo, wor, gate, up, down; };

__global__ void __cluster_dims__(2, 1, 1) __launch_bounds__(512, 1)
fused_kernel(const __nv_bfloat16* __restrict__ x, const __nv_bfloat16* __restrict__ wqkv,
             const __nv_bfloat16* __restrict__ wo, const __nv_bfloat16* __restrict__ w_r, const __nv_bfloat16* __restrict__ w_gate,
             const __nv_bfloat16* __restrict__ w_up, const __nv_bfloat16* __restrict__ w_down, __nv_bfloat16* __restrict__ out,
             Scratch* __restrict__ sc, const __grid_constant__ Maps tm) {
  extern __shared__ __align__(1024) uint8_t smem[];
  const int tid = threadIdx.x, bid = blockIdx.x;
  if ((unsigned)(tid - 128) < 16u) pf_l2((const char*)x + (bid * 16 + tid - 128) * 1280);
  if ((unsigned)(tid - 160) < 15u) pf_l2((const char*)wqkv + (bid * 15 + tid - 160) * 128);
  const int warp = __shfl_sync(0xffffffffu, tid >> 5, 0), lane = tid & 31;
  const uint32_t sb = (uint32_t)__cvta_generic_to_shared(smem);
  const uint32_t bar_full = sb + OFF_BAR, bar_empty = bar_full + 32, bar_aux = bar_full + 64, bar_ffn = bar_full + 72, bar_win = bar_full + 80, bar_tag = bar_full + 88, bar_rst = bar_full + 96 + 296 + 24,
                 bar_o = bar_full + 96, bar_oc = bar_o + 112, bar_st = bar_o + 224, bar_go = bar_o + 248, bar_kv = bar_o + 272, bar_half = bar_o + 296;
  if (warp < 4 && elect()) {
    mbar_init(bar_half + 8 * warp, 1);
    mbar_init(bar_full + 8 * (warp ^ 2), 1);
    mbar_init(bar_empty + 8 * warp, 24);
    mbar_init(bar_aux + 8 * warp, warp == 0 ? 64 : warp == 2 ? 32 : warp == 3 ? 2 : 1);
    asm volatile("fence.mbarrier_init.release.cluster;" ::: "memory");
  }
  asm volatile("barrier.cluster.arrive.relaxed.aligned;" ::: "memory");
  if (warp >= 8 && warp < 12 && elect()) asm volatile("prefetch.tensormap [%0];" :: "l"(&tm.x + (warp - 8)) : "memory");
  const int rank = bid & 1, cl = bid >> 1;
  const int q7 = ((cl - 36) * 37) >> 8;
  const int P = cl < 4 ? 0 : cl < 36 ? (cl - 4) & 7 : cl - 35 - 7 * q7;
  const int g = (cl < 4 ? 4 + cl : cl < 36 ? (cl - 4) >> 3 : 4 + q7);
  const int mt = 2 * P + rank, cid = mt * 8 + g;
  const bool ffn1 = g >= 5;
  const int fj = ffn1 ? mt * 3 + g - 5 : (P * 5 + g) * 2 + rank;
  const int ord = ((g >> 2) ^ P) & 1;
  auto ks_of = [&](int it) { return ord == 0 || it == 0 ? it : it <= 5 ? it + 4 : it - 5; };
  const int godd = g & 1, cm = g * 80 + godd * 16, cr = g * 80 + 64 - godd * 64;
  auto load_w = [&](int ks, uint32_t a, uint32_t bar, int kk) {
    tma_3d_mc(a + 16384 + ((kk + 1) & 3) * 6144, &tm.w, bar, cm, ks * 64 + kk * 16, 0);
    tma_3d_mc(a + 41472 + kk * 2048, &tm.wr, bar, cr, ks * 64 + kk * 16, 0);
    tma_3d_mc(a + 40960 + kk * 2048, &tm.wv, bar, cm + 48, ks * 64 + kk * 16, 2);
  };
  if (warp == 0 && elect()) {
    mbar_expect_tx(bar_half, 32768);
    tma_3d(sb + 2 * SLOT, &tm.x, bar_half, 0, P * 128, rank);
    mbar_expect_tx(bar_full + 16, 16384);
  }
  asm volatile("barrier.cluster.wait.aligned;" ::: "memory");
  if (warp == 0) {
    if (elect()) {
      uint32_t bar = bar_half;
#pragma unroll 1
      for (int kk = rank; kk < 4; kk += 2) { load_w(0, sb + 2 * SLOT, bar, kk); bar = bar_full + 16; }
    }
    asm volatile("bar.arrive 4, 64;" ::: "memory");
  }

  if (warp >= 8) {
    asm volatile("setmaxnreg.dec.sync.aligned.u32 %0;" :: "n"(REG_P));
#define TS_T 0
    if (warp == 8) {
      TS(8);
      bar_sync(4, 64);
      if (elect()) {
        TS(10);
#pragma unroll 1
        for (int it = 1; it < 10; it++) {
          const int s = (it + 2) & 3, ks = ks_of(it);
          const uint32_t full = bar_full + 8 * s, a = sb + s * SLOT;
          uint32_t bar = it < NSPLIT ? bar_half + 8 * it : full;
          if (it >= 4) mbar_wait(full + 32, ((it >> 2) - 1) & 1);
          if (it >= 2 && it < THR_END) mbar_wait(bar_full + 8 * (it & 3), 0);
          if (it < NSPLIT) mbar_expect_tx(bar, 32768);
          mbar_expect_tx(full, it < NSPLIT ? 16384 : SLOT);
          tma_3d(a, &tm.x, bar, ks * 64, P * 128, rank);
#pragma unroll 1
          for (int kk = rank; kk < 4; kk += 2) { load_w(ks, a, bar, kk); bar = full; }
          TS(12 + it);
          if ((it >> 1) == 2) {
            mbar_wait(bar_rst, 0);
            asm volatile("cp.async.bulk.global.shared::cta.bulk_group [%0], [%1], %2;\ncp.async.bulk.commit_group;"
                         :: "l"(it == 4 ? (uint4*)(g_own + cid) : (uint4*)&g_x + cid * GLOB_PER_CTA), "r"(sb + OFF_CS), "r"(it == 4 ? (int)sizeof(Own) : GLOB_PER_CTA * 16) : "memory");
          }
          if (it == 6) { asm volatile("cp.async.bulk.wait_group 0;" ::: "memory"); mbar_arrive(bar_tag); }
        }
        mbar_expect_tx(bar_ffn, ffn1 ? 81920 : 24576);
        int fjn = 0;
#pragma unroll 1
        for (int it = 9; it < 17; it++) {
          if (it >= 13) { mbar_wait(bar_oc + 8 * (it - 13), 0); mbar_wait(bar_oc + 56 + 8 * (it - 13), 0); }
          else if (it >= 10) {
            const uint32_t full = bar_full + 8 * (it - 10);
            const int g0 = 3 * (it - 10), g1 = min(g0 + 3, 8);
            mbar_wait(full + 32, it < 12);
            mbar_expect_tx(full, (g1 - g0) * 12800);
#pragma unroll 1
            for (int gp = g0 + ((g0 ^ rank) & 1); gp < g1; gp += 2) {
              tma_3d_mc(sb + gp * 15360, &tm.wo, full, 0, gp * 80, g * 2);
              tma_3d_mc(sb + gp * 15360 + 10240, &tm.wor, full, 512 + g * 16, gp * 80, 0);
            }
          }
          const int j1 = ffn1 ? (it >= 13 ? 2 * it - 22 : min(it - 8, 3)) : (it >= 13 ? 12 : min((it - 8) * F_PER, F_MAX));
#pragma unroll 1
          for (; fjn < j1; fjn++) {
            const int j = fjn < 3 ? fjn + 7 : fjn - 3;
            if (ffn1) tma_3d(sb + (j < 7 ? 0 : OFF_W2 - 57344) + j * 8192, j < 5 ? &tm.gate : &tm.up, bar_ffn, fj * 32, (j < 5 ? j : j - 5) * 128, 0);
            else tma_3d(sb + OFF_W2 + fjn * 2048, &tm.down, bar_ffn, fj * 8, fjn * 128, 0);
          }
        }
        TS(11);
      }
#undef TS_T
#define TS_T 64
    } else if (warp >= 12) {
      const int l7 = lane & 7, j = warp - 12, ch = min((P >> 1) * 4 + rank * 2 + (j >> 1), 14);
      const uint32_t sxo = ((g & 3) * 32 + j * 8 + l7) * 128 + (((lane >> 3) ^ l7) * 16);
      const uint32_t swo = ch < 12 ? 16384 + (lane >> 4) * 6144 + (ch >> 2) * 2048 + (lane & 15) * 128 + ((((ch & 3) * 2 + (j & 1)) ^ l7) * 16)
                                   : 41472 + (lane >> 4) * 2048 + (ch - 12) * 512 + (lane & 15) * 32 + (((j & 1) ^ (l7 >> 2)) * 16);
      float ps = 0.f, pq = 0.f, pq1 = 0.f, pc = 0.f;
      uint32_t tag = 0;
      char* const pp = hold((lane & 1) ? (char*)&g_own[cid].cs[j * 8 + (lane >> 2)] : (char*)&g_own[cid].st1[j * 8 + (lane >> 2)]);
#pragma unroll 1
      for (int it = ord; it < ord + 5; it++) {
        const int sl = (it + 2) & 3;
        if (it == ord + 4) { mbar_wait(bar_tag, 0); tag = __float_as_uint(lds32f(sb + OFF_WR + 324)); }
        if (it < NSPLIT) mbar_wait(bar_half + 8 * it, 0);
        mbar_wait(bar_full + 8 * sl, (it >> 2) & 1);
        TS(it);
        const uint32_t a = sb + sl * SLOT;
        const uint4 v0 = ldsm4(a + sxo), v1 = ldsm4((a + sxo) ^ 64), w0 = ldsm4t(a + swo), w1 = ldsm4t(a + swo + (ch < 12 ? 12288 : 4096));
        if (lane + (int)((v0.x & v1.x & w0.x & w1.x) == 0x7fc17fc1u && (v0.x | v1.x) == 0u) < 2) mbar_arrive_cta(bar_empty + 8 * sl, lane);
        const uint32_t vv[8] = {v0.x, v0.y, v0.z, v0.w, v1.x, v1.y, v1.z, v1.w}, ww[8] = {w0.x, w0.y, w0.z, w0.w, w1.x, w1.y, w1.z, w1.w};
#pragma unroll
        for (int i = 0; i < 8; i++) {
          const float d = bf_lo(vv[i]), e = bf_hi(vv[i]);
          ps += d + e; pq = fmaf(d, d, pq); pq1 = fmaf(e, e, pq1); pc += bf_lo(ww[i]) + bf_hi(ww[i]);
        }
      }
      pq += pq1;
      ps += shx(ps, 1); pq += shx(pq, 1); pc += shx(pc, 1);
      ps += shx(ps, 2); pq += shx(pq, 2); pc += shx(pc, 2);
      if ((lane & 3) == 0) stg_pkt(pp, __float_as_uint(ps), __float_as_uint(pq), tag, 0u);
      if ((lane & 3) == 1) stg_rlx64(pp, __float_as_uint(pc), tag);
      asm volatile("bar.arrive 2, 192;" ::: "memory");
      if (warp == 12) {
        const uint4* const hp = hold(&g_own[max(cid - 16, 0)].halo[0][lane]);
        mbar_wait(bar_aux, 0);
        mbar_wait(bar_go, 0);
        uint4 v[5] = {};
        int guard = SPIN_MAX;
        if (P > 0) {
          do {
#pragma unroll
            for (int i = 0; i < 5; i++) v[i] = ldg_pkt(hp + 32 * i);
          } while (anyw(v[0].x == SENT || v[1].x == SENT || v[2].x == SENT || v[3].x == SENT || v[4].x == SENT) && --guard > 0);
        }
#pragma unroll
        for (int i = 0; i < 5; i++) *(uint4*)(smem + OFF_O + 10240 + i * 512 + lane * 16) = v[i];
        mbar_arrive(bar_kv);
      }
#undef TS_T
#define TS_T 32
    } else if (warp < 11) {
      const int l7 = lane & 7, hk = lane >> 4;
      if (warp == 10 && elect()) {
#pragma unroll 1
        for (int i = 0; i < 36; i++) mbar_init(bar_o + 8 * i, i < 14 || i == 30 ? 1 : i < 34 ? 4 : 128);
      }
      mbar_wait(bar_tag, 0);
      const uint32_t tag = __float_as_uint(lds32f(sb + OFF_WR + 324));
      bar_sync(2, 192);
      TS(0);
      int guard = SPIN_MAX;
      if (warp == 9) {
        const uint4* sp = &g_own[mt * 8].st1[lane];
        const uint4* hp = &g_own[max(mt - 2, 0) * 8 + 3].st1[24 + l7];
        uint4 a[5], b[5];
        bool bad;
        do {
          __nanosleep(AUX_NS);
          bad = false;
#pragma unroll
          for (int i = 0; i < 5; i++) {
            const uint4* q = i < 4 ? sp + i * (sizeof(Own) / 16) : hp;
            a[i] = ldg_pkt(q); b[i] = ldg_pkt(q + 4 * sizeof(Own) / 16);
          }
#pragma unroll
          for (int i = 0; i < 5; i++) bad |= a[i].z != tag || b[i].z != tag;
        } while (anyw(bad) && --guard);
        TS(1);
#pragma unroll
        for (int i = 0; i < 5; i++) {
          const float m = (__uint_as_float(a[i].x) + __uint_as_float(b[i].x)) * (1.f / 640.f);
          const float rs = rsq(fmaxf(fmaf(-m, m, (__uint_as_float(a[i].y) + __uint_as_float(b[i].y)) * (1.f / 640.f)), 0.f) + 1e-5f);
          ((float*)(smem + OFF_RS))[i < 4 ? 8 + lane + 32 * i : l7] = rs;
          const uint32_t mh = pack_bf16(-m, -m);
          const float ml = -m - bf_lo(mh);
          if (i < 4) ((uint2*)(smem + OFF_MN))[lane + 32 * i] = make_uint2(mh, pack_bf16(ml, ml));
        }
      } else {
        const uint4* cp = (const uint4*)g_own[hk * 8 + g].cs + (lane & 15);
        uint4 a[4], b[4];
        bool bad;
        do {
          __nanosleep(AUX_NS);
          bad = false;
#pragma unroll
          for (int i = 0; i < 4; i++) { a[i] = ldg_pkt(cp + i * 32 * sizeof(Own) / 16); b[i] = ldg_pkt(cp + (i * 32 + 16) * sizeof(Own) / 16); }
#pragma unroll
          for (int i = 0; i < 4; i++) bad |= a[i].y != tag || a[i].w != tag || b[i].y != tag || b[i].w != tag;
        } while (anyw(bad) && --guard);
#pragma unroll
        for (int i = 0; i < 4; i++)
          if (i < 3 || lane < 24) {
            const float c0 = __uint_as_float(a[i].x) + __uint_as_float(b[i].x), c1 = __uint_as_float(a[i].z) + __uint_as_float(b[i].z);
            const uint32_t hi = pack_bf16(c0, c1), w0 = pack_bf16(c0, c0 - bf_lo(hi)), w1 = pack_bf16(c1, c1 - bf_hi(hi));
            uint4* const d = (uint4*)(smem + OFF_CS) + 2 * (lane + 32 * i);
            d[0] = make_uint4(w0, w0, 0, 0); d[1] = make_uint4(w1, w1, 0, 0);
          }
        asm volatile("fence.proxy.async.shared::cta;" ::: "memory");
      }
      mbar_arrive(bar_aux);
      TS(2);
      const int fo = warp - 9, wq = fo ? 1 - LEAD : LEAD;
      const uint4* const fp = hold(g_own[mt * 8 + wq * 4].cnt);
      const char* src = hold((const char*)g_o[mt * 2 + wq]);
      if (elect()) {
        const uint32_t bo = bar_o + fo * 56;
#pragma unroll
        for (int i = 0; i < 7; i++) mbar_expect_tx(bo + 8 * i, 10240);
        mbar_wait(bar_st + 8 * fo, 0);
        uint32_t cv;
        asm volatile("atom.relaxed.gpu.global.add.u32 %0, [%1], 1;" : "=r"(cv) : "l"(fp) : "memory");
        cv++;
        while (cv != 8u && --guard > 0) cv = ldg_rlx32(fp);
        asm volatile("fence.proxy.async.global;" ::: "memory");
        TS(6);
        uint32_t dst = sb + OFF_O + 20480;
#pragma unroll 1
        for (int i = 0; i < 7; i++) {
          if (fo || i == 5) mbar_wait(fo ? bar_oc + 8 * i : bar_st + 8, 0);
          if (i == g) src += 10240;
          asm volatile("cp.async.bulk.shared::cluster.global.mbarrier::complete_tx::bytes [%0], [%1], 10240, [%2];" :: "r"(dst), "l"(src), "r"(bo + 8 * i) : "memory");
          src += 10240;
          dst += i == 4 ? -61440 : 10240;
        }
      }
#undef TS_T
#define TS_T 96
    } else {
      if ((sb & 0x3FFFF) != D0 * 16) __trap();
#pragma unroll 1
      for (int i = lane; i < 232; i += 32) { const uint32_t f = i < 208 ? SENT : 0u; ((uint4*)(smem + OFF_CS))[i] = make_uint4(f, f, f, f); }
      asm volatile("fence.proxy.async.shared::cta;" ::: "memory");
      if (elect()) mbar_arrive(bar_rst);
      mbar_wait(bar_full + 8 * ((HK_IT + 2) & 3), 0);
      TS(4);
      const uint32_t epoch = ldg_rlx32(g_epoch + cid) + 1;
      uint32_t wv[10];
#pragma unroll
      for (int i = 0; i < 10; i++) wv[i] = __ldg((const uint32_t*)w_r + lane + 32 * i);
      float s = 0.f;
#pragma unroll
      for (int i = 0; i < 10; i++) {
        s += bf_lo(wv[i]) + bf_hi(wv[i]);
        const unsigned u = i < 8 ? lane + 32 * (i - g) : lane + 32 * (i - 7) - g * 8;
        if (i < 8 ? u < 32u : u - 32u < 8u) *(float2*)(smem + OFF_WR + ((u & 3) * 10 + (u >> 2)) * 8) = make_float2(bf_lo(wv[i]), bf_hi(wv[i]));
      }
#pragma unroll
      for (int m = 1; m < 32; m <<= 1) s += shx(s, m);
      *(float2*)(smem + OFF_WR + 320) = make_float2(s, __uint_as_float(epoch * 0x9E3779B8u));
      g_epoch[cid] = epoch;
      TS(3);
      if (elect()) mbar_arrive(bar_tag);
      TS(5);
#pragma unroll 1
      for (int i = 0; i < PFW_N; i++) {
        const int m = (i + 2) >> 2, n = m == 0 ? 50 : 120, t = (m == 0 ? i : (i + 2) & 3) * 32 + lane;
        const char* b = (const char*)(m == 0 ? wo : m == 1 ? w_up : m == 2 ? w_down : w_gate);
        if (t < n) pf_l2(b + (bid * n + t) * 128);
        __nanosleep(PFW_NS);
      }
      const uint4* const kp = hold(g_own[1].cnt);
      const uint4* const cb = hold(&g_x.cand[0][lane >> 2][lane & 3]);
      bar_sync(3, 64);
      uint4 k;
      uint32_t have = SENT;
      int guard = SPIN_MAX;
      while (true) {
        k = ldg_pkt(kp);
        if (ffn1) {
          while (k.x != have && --guard > 0) {
            const uint32_t tk = 2047u - (k.x & 2047u), want = k.x;
            const uint4* q = cb + ((tk >> 8) * 16 + (tk & 1) * 8 + ((tk >> 5) & 7)) * 192;
            const uint4 c0 = ldg_pkt(q), c1 = ldg_pkt(q + 4); const uint2 c2 = ldg_rlx64(q + 8);
            k = ldg_pkt(kp);
            *(uint4*)(smem + OFF_HN + lane * 16) = c0; *(uint4*)(smem + OFF_HN + 512 + lane * 16) = c1; *(uint2*)(smem + OFF_HN + 1024 + lane * 16) = c2;
            have = anyw(c0.x == SENT || c1.x == SENT || c2.x == SENT) ? SENT : want;
          }
        } else if (KEY_NS && k.z != 128u) __nanosleep(KEY_NS);
        if (k.z == 128u || --guard <= 0) break;
      }
      *(uint2*)(smem + OFF_WR + 336) = make_uint2(k.x, k.y);
      mbar_arrive(bar_win);
      TS(7);
    }
#undef TS_T
  } else {
#define TS_T 0
    asm volatile("setmaxnreg.inc.sync.aligned.u32 %0;" :: "n"(REG_C));
    const int wg = warp >> 2, w4 = warp & 3, r = lane >> 2, c = lane & 3;
    float acc[120];
    uint4 xr[5] = {};
    const uint32_t xa = pin(sb + (warp * 16 + (lane & 15)) * 128 + ((lane >> 4) ^ (lane & 7)) * 16);
    const int fol = wg != LEAD;
    const bool first = (P == 0) && (warp == 0);
    const uint32_t kvs = sb + OFF_O + fol * 10240 + w4 * 2560 + lane * 16;
    uint4* const kvd = hold(warp == 7 ? &g_own[cid].halo[0][lane] : (uint4*)(smem + (warp == 3 ? OFF_O + lane * 16 : kvs - sb + 2560)));
    uint4* const odst = hold(&g_o[mt * 2 + wg][g][w4 * 160]);
    uint32_t m0 = 0, m1 = 0;
    const uint32_t mna = pin(sb + OFF_MN + (warp * 16 + r) * 8 + c * 4);
    const int itx = ord == 0 || g == 0 ? g : g < 5 ? g + 5 : g - 4, ity = (ord ? 4 : 8) + (g >> 2);
    uint32_t rel;
    asm volatile("mapa.shared::cluster.u32 %0, %1, %2;" : "=r"(rel) : "r"(bar_empty), "r"(tid & 1));
    const uint32_t xa1 = pin(xa ^ 32), xa2 = pin(xa ^ 64), xa3 = pin(xa ^ 96), xb = pin(xa ^ ((g & 3) * 32));
    const uint32_t da0 = wg * 512;
    const bool rel2 = lane < 2, rel6 = lane < 2 + 2 * (warp & 1);
    const uint32_t zero = __shfl_sync(0xffffffffu, (uint32_t)(uintptr_t)x & 8u, 0);
    mbar_wait(bar_half, 0);
    TS(13);
    wgmma_fence();
#pragma unroll
    for (int it = 0; it < 10; it++) {
      const int s = (it + 2) & 3;
#pragma unroll
      for (int kk = 0; kk < 4; kk++) {
        if (kk == 2 && it > 0) {
          wgmma_commit();
          wgmma_wait<1>();
          const uint32_t ra = ((xr[0].x ^ xr[1].x ^ xr[2].x ^ xr[3].x ^ xr[4].x) & zero) | rel;
          if (it == 1 ? (ord ? rel6 : rel2) : it == 6 ? (ord ? rel2 : rel6) : it < 6 ? rel2 : rel6)
            asm volatile("mbarrier.arrive.shared::cluster.b64 _, [%0];" :: "r"(ra + 8 * ((it + 1) & 3)) : "memory");
        }
        if (kk == 2) {
          ldsm4_if(xr[0], xa, s * SLOT, it == itx); ldsm4_if(xr[1], xa1, s * SLOT, it == itx);
          ldsm4_if(xr[2], xa2, s * SLOT, it == itx); ldsm4_if(xr[3], xa3, s * SLOT, it == itx);
          if ((it & 6) == 4 || it >= 8) ldsm4_if(xr[4], xb, s * SLOT, it == ity);
        }
        if (kk == AK && it == 9) {
          mbar_wait(bar_aux, 0);
          TS(3);
          if (c < 2) { m0 = __float_as_uint(lds32f(mna)); m1 = __float_as_uint(lds32f(mna + 64)); }
          if (!fol) bar_sync(11, 256);
        }
        if (it * 4 + kk == 40 - LAG && fol) {
          asm volatile("bar.arrive 11, 256;" ::: "memory");
          bar_sync(10, 256);
        }
        if (kk == 2 && it < NSPLIT) mbar_wait(bar_full + 8 * s, 0);
        const uint64_t da = mk64(da0 + (D0 + s * (SLOT >> 4) + kk * 2 + (1 << 16)), 0x40000040u);
        wgmma_n64hi_ss(acc, da, mk64(D0 + s * (SLOT >> 4) + 2560 + kk * 128 + (32 << 16), 0xC0000010u), (it | kk) != 0);
        wgmma_n176lo_ss(acc, da, mk64(D0 + s * (SLOT >> 4) + 1024 + ((kk + 1) & 3) * 384 + (128 << 16), 0x40000040u), (it | kk) != 0);
      }
      wgmma_commit();
      if (it < 9) {
        if (it + 1 < NSPLIT) mbar_wait(bar_half + 8 * (it + 1), 0);
        else mbar_wait(bar_full + 8 * ((it + 3) & 3), ((it + 1) >> 2) & 1);
        if (it < 8) TS(14 + it);
      }
    }
    {
      const uint64_t dc = make_desc(D0 * 16 + OFF_CS, 0, 128, 0);
      wgmma_fence();
      wgmma_n64hi_rk(acc, m0, m1, 0u, 0u, dc + 176, 1);
      wgmma_n176lo_rk(acc, m0, m1, 0u, 0u, dc, 1);
      wgmma_commit();
      if (!fol) asm volatile("bar.arrive 10, 256;" ::: "memory");
    }
    const uint32_t stb = sb + OFF_RS + warp * 64;
    const float rlo = lds32f(stb + (8 + r) * 4), rhi = lds32f(stb + (16 + r) * 4);
    wgmma_wait<0>();
#pragma unroll
    for (int i = 0; i < 120; i++) asm volatile("" : "+f"(acc[i]) :: "memory");
    if (fol && lane == 0) mbar_arrive(bar_go);
    TS(2);
    uint32_t Qlo[10], Qhi[10], Klo[10], Khi[10], Vlo[10], Vhi[10];
#define CONV_HI(ROT) _Pragma("unroll") for (int t = 0; t < 10; t++) { \
      const int k = KT((t + ROT) % 10), v = VT((t + ROT) % 10); \
      Khi[t] = pack_bf16(acc[4 * k + 2], acc[4 * k + 3]); \
      Vhi[t] = pack_bf16(acc[4 * v + 2] * rhi, acc[4 * v + 3] * rhi); }
    if (godd) { CONV_HI(8) } else { CONV_HI(0) }
    st_pkt(kvd, Khi[0], Khi[1], Khi[3], Khi[4]);
    st_pkt(kvd + 32, Khi[5], Khi[6], Khi[8], Khi[9]);
    st_pkt(kvd + 64, Khi[2], Khi[7], Vhi[0], Vhi[1]);
    st_pkt(kvd + 96, Vhi[2], Vhi[3], Vhi[4], Vhi[5]);
    st_pkt(kvd + 128, Vhi[6], Vhi[7], Vhi[8], Vhi[9]);
    if (warp < 7) mbar_arrive(bar_kv + ((warp + 1) >> 2) * 8);
#define CONV_LO(ROT) _Pragma("unroll") for (int t = 0; t < 10; t++) { \
      const int q = QT((t + ROT) % 10), k = KT((t + ROT) % 10), v = VT((t + ROT) % 10); \
      Vhi[t] = movm(Vhi[t]); \
      Klo[t] = pack_bf16(acc[4 * k], acc[4 * k + 1]); \
      Vlo[t] = movm(pack_bf16(acc[4 * v] * rlo, acc[4 * v + 1] * rlo)); \
      Qlo[t] = pack_bf16(acc[4 * q], acc[4 * q + 1]); \
      Qhi[t] = pack_bf16(acc[4 * q + 2], acc[4 * q + 3]); }
    if (godd) { CONV_LO(8) } else { CONV_LO(0) }
    const bool in0 = 2 * c <= r, in1 = 2 * c + 1 <= r;
    const uint32_t mL = (in0 ? 0xffffu : 0u) | (in1 ? 0xffff0000u : 0u);
    const float qs = 0.22360679774997896f * 1.4426950408889634f;
    const uint32_t kb0 = stb + (2 * c + (in0 ? 8 : 0)) * 4, kb1 = stb + (2 * c + 1 + (in1 ? 8 : 0)) * 4;
    const float scl0 = lds32f(kb0) * rlo * qs, scl1 = lds32f(kb1) * rlo * qs;
    const float sch0 = lds32f(kb0 + 32) * rhi * qs, sch1 = lds32f(kb1 + 32) * rhi * qs;
    const float bias0 = (first && !in0) ? -INFINITY : 0.f, bias1 = (first && !in1) ? -INFINITY : 0.f;
    const int slot = mt * 8 + warp;
    int guard = SPIN_MAX;
    uint4 pv[5];
    const bool cA = c < 2, nA = r < 4;
    TS(0);
    mbar_wait(bar_go + fol * 8, 0);
    TS(23);
    uint32_t qe[4][2];
    float sl0[4], sl1[4], th0[4], th1[4];
#pragma unroll
    for (int hd = 0; hd < 4; hd++) {
      const int ta = 5 * (hd >> 1) + 3 * (hd & 1), ts = 5 * (hd >> 1) + 2;
      const bool mine = (hd & 1) ? !cA : cA;
      qe[hd][0] = mine ? Qlo[ts] : 0u; qe[hd][1] = mine ? Qhi[ts] : 0u;
      float sl[4], sh[4];
      mma_k24(sl, Qlo[ta], Qhi[ta], Qlo[ta + 1], Qhi[ta + 1], Klo[ta], Klo[ta + 1], qe[hd][0], qe[hd][1], Klo[ts]);
      mma_k24(sh, Qlo[ta], Qhi[ta], Qlo[ta + 1], Qhi[ta + 1], Khi[ta], Khi[ta + 1], qe[hd][0], qe[hd][1], Khi[ts]);
      th0[hd] = (in0 ? sh[2] : sl[2]) * sch0; th1[hd] = (in1 ? sh[3] : sl[3]) * sch1;
      float mh = fmaxf(th0[hd], th1[hd]);
      mh = fmaxf(mh, shx(mh, 1)); mh = fmaxf(mh, shx(mh, 2));
      th0[hd] -= mh; th1[hd] -= mh;
      sl0[hd] = sl[0]; sl1[hd] = sl[1];
    }
    mbar_wait(bar_kv + wg * 8, 0);
    TS(4);
#pragma unroll
    for (int j = 0; j < 5; j++) pv[j] = lds128(kvs + 512 * j);
    const uint32_t Kp[10] = {pv[0].x, pv[0].y, pv[2].x, pv[0].z, pv[0].w, pv[1].x, pv[1].y, pv[2].y, pv[1].z, pv[1].w};
    const uint32_t Vp[10] = {movm(pv[2].z), movm(pv[2].w), movm(pv[3].x), movm(pv[3].y), movm(pv[3].z), movm(pv[3].w), movm(pv[4].x), movm(pv[4].y), movm(pv[4].z), movm(pv[4].w)};
    const uint32_t ONES = 0x3f803f80u;
    uint32_t of[20];
#pragma unroll
    for (int hp = 0; hp < 2; hp++) {
      float o[6][4];
#pragma unroll
      for (int hh = 0; hh < 2; hh++) {
        const int hd = 2 * hp + hh, ta = 5 * hp + 3 * hh, ts = 5 * hp + 2;
        float sp[4];
        mma_k24(sp, Qlo[ta], Qhi[ta], Qlo[ta + 1], Qhi[ta + 1], Kp[ta], Kp[ta + 1], qe[hd][0], qe[hd][1], Kp[ts]);
        const float tl0 = fmaf(in0 ? sl0[hd] : sp[0], scl0, bias0), tl1 = fmaf(in1 ? sl1[hd] : sp[1], scl1, bias1);
        float ml = fmaxf(tl0, tl1);
        ml = fmaxf(ml, shx(ml, 1)); ml = fmaxf(ml, shx(ml, 2));
        if (HOLD == 1 && hd == 3 && !fol && lane == 0) mbar_arrive(bar_go + 8);
        const uint32_t Pl = pack_bf16(ex2(tl0 - ml), ex2(tl1 - ml)), Ph = pack_bf16(ex2(th0[hd]), ex2(th1[hd]));
        const uint32_t a0 = Pl & mL, a1 = Ph & ~mL, a3 = Ph & mL, ap = Pl & ~mL;
        const bool vm = hh == 0 ? nA : !nA;
        mma_k24(o[3 * hh], a0, a1, 0u, a3, Vlo[ta], Vhi[ta], ap, 0u, Vp[ta]);
        mma_k24(o[3 * hh + 1], a0, a1, 0u, a3, Vlo[ta + 1], Vhi[ta + 1], ap, 0u, Vp[ta + 1]);
        mma_k24(o[3 * hh + 2], a0, a1, 0u, a3, vm ? Vlo[ts] : ONES, vm ? Vhi[ts] : ONES, ap, 0u, vm ? Vp[ts] : ONES);
      }
      const float il = rcp(cA ? o[5][0] : o[2][0]), ih = rcp(cA ? o[5][2] : o[2][2]);
      const float jl = shx(il, 2), jh = shx(ih, 2);
      const float al = cA ? jl : il, ah = cA ? jh : ih, bl = cA ? il : jl, bh = cA ? ih : jh;
      const int t0 = 5 * hp;
      of[2 * t0]     = pack_bf16(o[0][0] * al, o[0][1] * al); of[2 * t0 + 1] = pack_bf16(o[0][2] * ah, o[0][3] * ah);
      of[2 * t0 + 2] = pack_bf16(o[1][0] * al, o[1][1] * al); of[2 * t0 + 3] = pack_bf16(o[1][2] * ah, o[1][3] * ah);
      of[2 * t0 + 4] = pack_bf16((cA ? o[2][0] : o[5][0]) * jl, (cA ? o[2][1] : o[5][1]) * jl);
      of[2 * t0 + 5] = pack_bf16((cA ? o[2][2] : o[5][2]) * jh, (cA ? o[2][3] : o[5][3]) * jh);
      of[2 * t0 + 6] = pack_bf16(o[3][0] * bl, o[3][1] * bl); of[2 * t0 + 7] = pack_bf16(o[3][2] * bh, o[3][3] * bh);
      of[2 * t0 + 8] = pack_bf16(o[4][0] * bl, o[4][1] * bl); of[2 * t0 + 9] = pack_bf16(o[4][2] * bh, o[4][3] * bh);
    }
    {
      const uint32_t os = sb + OFF_O + (fol ? 0 : 20480) + w4 * 2560, oa = os + ((lane >> 3) & 1) * 1280 + (lane >> 4) * 128 + (lane & 7) * 16;
#pragma unroll
      for (int s = 0; s < 5; s++) {
        stsm4(oa + s * 256, of[4 * s], of[4 * s + 1], of[4 * s + 2], of[4 * s + 3]);
        if (s == 0 && (fol || HOLD == 2) && lane == 0) mbar_arrive(bar_go + 8 + 8 * fol);
      }
      asm volatile("fence.proxy.async.shared::cta;" ::: "memory");
      __syncwarp();
      asm volatile("{\n.reg .pred q;\nelect.sync _|q, 0xffffffff;\n@q cp.async.bulk.global.shared::cta.bulk_group [%0], [%1], 2560;\ncp.async.bulk.commit_group;\n}\n" :: "l"(odst), "r"(os) : "memory");
    }
    TS(5);
    float h[40];
#pragma unroll
    for (int s = 0; s < 5; s++) {
      const uint4 v = xr[s];
      h[8 * s] = bf_lo(v.x); h[8 * s + 1] = bf_hi(v.x); h[8 * s + 2] = bf_lo(v.y); h[8 * s + 3] = bf_hi(v.y);
      h[8 * s + 4] = bf_lo(v.z); h[8 * s + 5] = bf_hi(v.z); h[8 * s + 6] = bf_lo(v.w); h[8 * s + 7] = bf_hi(v.w);
    }
    asm volatile("cp.async.bulk.wait_group 0;" ::: "memory");
    __syncwarp();
    if (lane == 0) mbar_arrive(bar_st + 8 * fol);
    TS(22);
    mbar_wait(bar_full, 0); mbar_wait(bar_full + 8, 0); mbar_wait(bar_full + 16, 1);
    mbar_wait(bar_go + 16, 0);
    const uint64_t dwo = make_desc(D0 * 16, 5120, 512, 2);
    wgmma_fence();
#pragma unroll
    for (int s = 0; s < 5; s++) wgmma_n80_rs(h, of[4 * s], of[4 * s + 1], of[4 * s + 2], of[4 * s + 3], dwo + g * 960 + s * 64, 1);
    wgmma_commit();
    TS(6);
    const bool odd = c & 1;
    uint4* const sp = hold(&g_own[slot].st2[r + (odd ? 8 : 0)]);
    uint4* const cdp = hold(&g_x.cand[slot][g][0]);
    uint4* const kcp = hold(g_own[1].cnt);
    float wr[20];
#pragma unroll
    for (int j = 0; j < 5; j++) {
      const uint4 v = lds128(sb + OFF_WR + c * 80 + j * 16);
      wr[4 * j] = __uint_as_float(v.x); wr[4 * j + 1] = __uint_as_float(v.y); wr[4 * j + 2] = __uint_as_float(v.z); wr[4 * j + 3] = __uint_as_float(v.w);
    }
    const float wsum = lds32f(sb + OFF_WR + 320);
    const uint32_t bo = bar_o + fol * 56;
#pragma unroll
    for (int i = 0; i < 7; i++) {
      mbar_wait(bo + 8 * i, 0);
      if (i == 0) TS(1);
      const uint32_t da = D0 + OFF_O / 16 + (8 << 16) + ((i + 2) % 7) * 640, db = D0 + (320 << 16) + (i >= g ? i + 1 : i) * 960;
      wgmma_fence();
#pragma unroll
      for (int s = 0; s < 5; s++) wgmma_n80_ss(h, mk64(da + s * 16, 80u), mk64(db + s * 64, 0x80000020u), 1);
      wgmma_commit();
      wgmma_wait<1>();
      if (lane == 0 && i > 0) mbar_arrive(bo + 104 + 8 * i);
    }
    const int tok0 = P * 256 + 32 * warp + rank;
    wgmma_wait<0>();
#pragma unroll
    for (int i = 0; i < 40; i++) asm volatile("" : "+f"(h[i]) :: "memory");
    if (lane == 0) mbar_arrive(bo + 160);
    TS(7);
    float mean, rstd, rr;
    bool pub;
    {
      float l1 = 0.f, l2 = 0.f, l3 = 0.f, h1 = 0.f, h2 = 0.f, h3 = 0.f;
#pragma unroll
      for (int j = 0; j < 10; j++) {
        l1 += h[4 * j] + h[4 * j + 1]; h1 += h[4 * j + 2] + h[4 * j + 3];
        l2 = fmaf(h[4 * j], h[4 * j], l2); l2 = fmaf(h[4 * j + 1], h[4 * j + 1], l2);
        h2 = fmaf(h[4 * j + 2], h[4 * j + 2], h2); h2 = fmaf(h[4 * j + 3], h[4 * j + 3], h2);
        l3 = fmaf(h[4 * j], wr[2 * j], l3); l3 = fmaf(h[4 * j + 1], wr[2 * j + 1], l3);
        h3 = fmaf(h[4 * j + 2], wr[2 * j], h3); h3 = fmaf(h[4 * j + 3], wr[2 * j + 1], h3);
      }
      float s1 = (odd ? h1 : l1) + shx(odd ? l1 : h1, 1), s2 = (odd ? h2 : l2) + shx(odd ? l2 : h2, 1), s3 = (odd ? h3 : l3) + shx(odd ? l3 : h3, 1);
      s1 += shx(s1, 2); s2 += shx(s2, 2); s3 += shx(s3, 2);
      uint4 p0;
      float o1 = 0.f, o2 = 0.f, o3 = 0.f, oc = 7.f;
      asm volatile("{\n.reg .pred q;\nsetp.lt.u32 q, %9, 2;\n@q atom.relaxed.gpu.global.add.v4.f32 {%0, %1, %2, %3}, [%4], {%5, %6, %7, %8};\n}\n"
                   : "+f"(o1), "+f"(o2), "+f"(o3), "+f"(oc) : "l"(sp), "f"(s1), "f"(s2), "f"(s3), "f"(1.f), "r"(c) : "memory");
      const uint32_t last = __ballot_sync(0xffffffffu, oc == 7.f);
      pub = last & 1;
      p0.x = __float_as_uint(__shfl_sync(0xffffffffu, o1 + s1, lane & 29)); p0.y = __float_as_uint(__shfl_sync(0xffffffffu, o2 + s2, lane & 29));
      p0.z = __float_as_uint(__shfl_sync(0xffffffffu, o3 + s3, lane & 29));
      if (last != 0xffffffffu)
      do { p0 = ldg_pkt(sp); } while (anyw(p0.w != 0x41000000u) && --guard > 0);
      mean = __uint_as_float(p0.x) * (1.f / 640.f);
      rstd = rsq(fmaxf(fmaf(-mean, mean, __uint_as_float(p0.y) * (1.f / 640.f)), 0.f) + 1e-5f);
      rr = fmaf(-mean, wsum, __uint_as_float(p0.z)) * rstd;
    }
    TS(8);
    const uint32_t kk = ord_key(rr), kmax = __reduce_max_sync(0xffffffffu, kk);
    const int L = __ffs(__ballot_sync(0xffffffffu, kk == kmax)) - 1;
    const int crow = (L >> 2) + 8 * (L & 1);
    asm volatile("{\n.reg .pred q;\nsetp.ne.u32 q, %2, 0;\n@q red.relaxed.gpu.global.max.u64 [%0], %1;\n@q red.relaxed.gpu.global.add.u32 [%0 + 8], 1;\n}\n"
                 :: "l"(kcp), "l"(mk64(2047 - tok0 - 2 * crow, kmax)), "r"((int)(pub && lane == 0)) : "memory");
    if (warp == g) asm volatile("bar.arrive 3, 64;" ::: "memory");
    const uint32_t stg = sb + (fol ? OFF_O : g * 15360) + w4 * 2560;
    uint4 held;
    {
      const float om = shx(mean, 1), os = shx(rstd, 1);
      const float rl = odd ? os : rstd, rh = odd ? rstd : os;
      const float bl = -(odd ? om : mean) * rl, bh = -(odd ? mean : om) * rh, al = 1.f + rl, ah = 1.f + rh;
      if ((L >> 2) == r) {
        const bool chi = L & 1;
        const float rc = chi ? rh : rl, bc = chi ? bh : bl;
        uint32_t n[10];
#pragma unroll
        for (int j = 0; j < 10; j++) n[j] = pack_bf16(fmaf(chi ? h[4 * j + 2] : h[4 * j], rc, bc), fmaf(chi ? h[4 * j + 3] : h[4 * j + 1], rc, bc));
        uint4* d = cdp + c;
        stg_pkt(d, n[0], n[1], n[2], n[3]); stg_pkt(d + 4, n[4], n[5], n[6], n[7]); stg_rlx64(d + 8, n[8], n[9]);
      }
      mbar_wait(bar_oc + 56, 0);
      const uint32_t fa = stg + (lane & 15) * 160 + (lane >> 4) * 16;
#pragma unroll
      for (int s = 0; s < 5; s++)
        stsm4(fa + s * 32, pack_bf16(fmaf(h[8 * s], al, bl), fmaf(h[8 * s + 1], al, bl)), pack_bf16(fmaf(h[8 * s + 2], ah, bh), fmaf(h[8 * s + 3], ah, bh)),
              pack_bf16(fmaf(h[8 * s + 4], al, bl), fmaf(h[8 * s + 5], al, bl)), pack_bf16(fmaf(h[8 * s + 6], ah, bh), fmaf(h[8 * s + 7], ah, bh)));
      __syncwarp();
      held = lds128(stg + crow * 160 + min(lane, 9) * 16);
      if (lane < 10) stg_pkt(cdp + 12 + lane, held.x, held.y, held.z, held.w);
    }
    TS(9);
    mbar_wait(bar_ffn, 0);
    const uint32_t red = sb + OFF_RED;
    if (ffn1) {
      uint4 w1[4][5];
      {
        const int k = (lane & 7) + (lane >> 4) * 8;
        const uint32_t a1 = sb + k * 64, sw = ((lane >> 3) & 1) ^ ((lane >> 1) & 3);
#pragma unroll
        for (int s = 0; s < 5; s++)
#pragma unroll
          for (int u = 0; u < 4; u++)
            w1[u][s] = ldsm4t(a1 + (s < 4 ? warp * 4096 + s * 1024 : 32768 + warp * 1024) + (u >> 1) * (40960 + (s == 4 || warp >= 4 ? OFF_W2 - 57344 : 0)) + ((sw ^ (2 * (u & 1))) * 16));
      }
      uint32_t* const ap = hold(g_x.act + fj * 16 + (lane >> 1));
      mbar_wait(bar_win, 0);
      const uint32_t hp = sb + OFF_HN + (warp * 4 + c) * 16;
      const uint4 c0 = lds128(hp), c1 = lds128(hp + 512), c2 = lds128(hp + 1024);
      TS(10);
      float a[4][4];
#pragma unroll
      for (int u = 0; u < 4; u++) {
        a[u][0] = a[u][1] = a[u][2] = a[u][3] = 0.f;
        mma_acc(a[u], w1[u][0], c0.x, c0.y); mma_acc(a[u], w1[u][1], c0.z, c0.w); mma_acc(a[u], w1[u][2], c1.x, c1.y);
        mma_acc(a[u], w1[u][3], c1.z, c1.w); mma_acc(a[u], w1[u][4], c2.x, c2.y);
      }
      asm volatile("st.shared.v2.f32 [%0], {%1, %2};" :: "r"(red + (warp * 32 + c * 8 + r) * 8),
                   "f"(cA ? (odd ? a[0][2] : a[0][0]) : (odd ? a[1][2] : a[1][0])), "f"(cA ? (odd ? a[2][2] : a[2][0]) : (odd ? a[3][2] : a[3][0])) : "memory");
      bar_sync(1, 256);
      if (warp == 0) {
        float2 t[8];
#pragma unroll
        for (int i = 0; i < 8; i++) t[i] = lds64f(red + (i * 32 + lane) * 8);
        const float s = ((t[0].x + t[1].x) + (t[2].x + t[3].x)) + ((t[4].x + t[5].x) + (t[6].x + t[7].x));
        const float u = ((t[0].y + t[1].y) + (t[2].y + t[3].y)) + ((t[4].y + t[5].y) + (t[6].y + t[7].y));
        const float av = s * u * rcp(1.f + ex2(-1.4426950408889634f * s));
        const float an = shx(av, 1);
        if (!odd) stg_rlx32(ap, pack_bf16(av, an));
      }
      bar_sync(1, 256);
      TS(11);
    }
    char* const ob2 = (char*)(out + tok0 * 640 + g * 64);
    const int remo = 896 - 96 * g;
    {
      char* const q0 = ob2 + (lane >> 3) * 2560 + (lane & 7) * 16;
      const uint32_t s0 = stg + (lane >> 3) * 160 + (lane & 7) * 16;
#pragma unroll
      for (int s = 0; s < 4; s++) stg128_if(4 * s + (lane >> 3) != crow, q0 + s * 10240, lds128(s0 + s * 640));
      stg128_if((lane >> 1) != crow, ob2 + (lane >> 1) * 2560 + (lane & 1) * 16 + 128 + remo, lds128(stg + (lane >> 1) * 160 + (lane & 1) * 16 + 128));
    }
    mbar_wait(bar_win, 0);
    uint4 win = lds128(sb + OFF_WR + 336);
    win.z = win.y; win.y = 2047u - (win.x & 2047u); win.x = (win.y >> 8) * 16 + (win.y & 1) * 8 + ((win.y >> 5) & 7);
    stg128_if(win.x != slot && lane < 10, ob2 + crow * 2560 + lane * 16 + (lane < 8 ? 0 : remo), held);
    if (!ffn1) {
      TS(10);
      uint4 w2[6];
      const uint32_t a2 = sb + OFF_W2 + (warp * 192 + 8 * (((lane >> 3) & 1) * 4 + ((lane & 7) >> 1)) + 2 * (lane >> 4) + (lane & 1)) * 16;
#pragma unroll
      for (int s = 0; s < 6; s++) w2[s] = ldsm4t(a2 + (s >> 1) * 1024 + (s & 1) * 64);
      const uint4* p = (const uint4*)(g_x.act + warp * 96) + (r & 1) * 4 + c;
      const uint32_t* pb = (const uint32_t*)&g_x.cand[win.x][fj < 64 ? fj >> 3 : (fj - 64) >> 1][fj < 64 ? 12 + (fj & 7) : 20 + (fj & 1)] + c;
      uint32_t* const op = hold((uint32_t*)(out + win.y * 640 + fj * 8) + c);
      const float sg = rcp(1.f + ex2(-1.4426950408889634f * __uint_as_float(win.z ^ ((uint32_t)((int32_t)~win.z >> 31) | 0x80000000u))));
      uint4 c0, c1, c2; uint32_t bw;
      if (ACT_NS) __nanosleep(ACT_NS);
      do {
        c0 = ldg_pkt(p); c1 = ldg_pkt(p + 8); c2 = ldg_pkt(p + 16); bw = ldg_rlx32(pb);
      } while (anyw(max(max(max(max(c0.x, c0.y), max(c0.z, c0.w)), max(max(c1.x, c1.y), max(c1.z, c1.w))), max(max(max(c2.x, c2.y), max(c2.z, c2.w)), bw)) == SENT) && --guard > 0);
      TS(11);
      float a[4] = {0.f, 0.f, 0.f, 0.f}, b[4] = {0.f, 0.f, 0.f, 0.f}, d[4] = {0.f, 0.f, 0.f, 0.f};
      mma_acc(a, w2[0], c0.x, c0.y); mma_acc(b, w2[2], c1.x, c1.y); mma_acc(d, w2[4], c2.x, c2.y);
      mma_acc(a, w2[1], c0.z, c0.w); mma_acc(b, w2[3], c1.z, c1.w); mma_acc(d, w2[5], c2.z, c2.w);
      if (c == 0) sts32f(red + (warp * 8 + r) * 4, ((a[0] + a[3]) + (b[0] + b[3])) + (d[0] + d[3]));
      bar_sync(1, 256);
      if (tid < 4) {
        float2 t[8];
#pragma unroll
        for (int i = 0; i < 8; i++) t[i] = lds64f(red + (i * 4 + tid) * 8);
        const float y0 = ((t[0].x + t[1].x) + (t[2].x + t[3].x)) + ((t[4].x + t[5].x) + (t[6].x + t[7].x));
        const float y1 = ((t[0].y + t[1].y) + (t[2].y + t[3].y)) + ((t[4].y + t[5].y) + (t[6].y + t[7].y));
        *op = pack_bf16(fmaf(y0, sg, bf_lo(bw)), fmaf(y1, sg, bf_hi(bw)));
      }
    }
    TS(12);
#undef TS_T
  }
}

typedef CUresult (*EncodeFn)(CUtensorMap*, CUtensorMapDataType, cuuint32_t, void*, const cuuint64_t*, const cuuint64_t*, const cuuint32_t*,
                             const cuuint32_t*, CUtensorMapInterleave, CUtensorMapSwizzle, CUtensorMapL2promotion, CUtensorMapFloatOOBfill);

void make_map(EncodeFn enc, CUtensorMap* m, const void* base, const cuuint64_t* dims, const cuuint64_t* strides, const cuuint32_t* box,
              CUtensorMapSwizzle swz) {
  const cuuint32_t es[3] = {1, 1, 1};
  enc(m, CU_TENSOR_MAP_DATA_TYPE_BFLOAT16, 3, (void*)base, dims, strides, box, es, CU_TENSOR_MAP_INTERLEAVE_NONE, swz,
      CU_TENSOR_MAP_L2_PROMOTION_L2_128B, CU_TENSOR_MAP_FLOAT_OOB_FILL_NONE);
}

}

extern "C" void kernel_launch(void* const* d_in, const int* in_sizes, int n_in, void* d_out, int out_size) {
  const __nv_bfloat16* x = (const __nv_bfloat16*)d_in[0];
  const __nv_bfloat16* wqkv = (const __nv_bfloat16*)d_in[1];
  const __nv_bfloat16* wo = (const __nv_bfloat16*)d_in[2];
  void* fn = nullptr;
  cudaDriverEntryPointQueryResult st;
  cudaGetDriverEntryPoint("cuTensorMapEncodeTiled", &fn, cudaEnableDefault, &st);
  EncodeFn enc = (EncodeFn)fn;
  void* scp = nullptr;
  cudaGetSymbolAddress(&scp, g_scratch);
  Maps tm;
  { const cuuint64_t d[3] = {640, 1024, 2}, s[2] = {2560, 1280}; const cuuint32_t b[3] = {64, 128, 1}; make_map(enc, &tm.x, x, d, s, b, CU_TENSOR_MAP_SWIZZLE_128B); }
  { const cuuint64_t d[3] = {640, 640, 3}, s[2] = {3840, 1280}; const cuuint32_t b[3] = {64, 16, 3}; make_map(enc, &tm.w, wqkv, d, s, b, CU_TENSOR_MAP_SWIZZLE_128B); }
  { const cuuint64_t d[3] = {640, 640, 3}, s[2] = {3840, 1280}; const cuuint32_t b[3] = {16, 16, 3}; make_map(enc, &tm.wr, wqkv, d, s, b, CU_TENSOR_MAP_SWIZZLE_32B); }
  { const cuuint64_t d[3] = {640, 640, 3}, s[2] = {3840, 1280}; const cuuint32_t b[3] = {16, 16, 1}; make_map(enc, &tm.wv, wqkv, d, s, b, CU_TENSOR_MAP_SWIZZLE_32B); }
  { const cuuint64_t d[3] = {32, 640, 20}, s[2] = {1280, 64}; const cuuint32_t b[3] = {32, 80, 2}; make_map(enc, &tm.wo, wo, d, s, b, CU_TENSOR_MAP_SWIZZLE_64B); }
  { const cuuint64_t d[3] = {640, 640, 1}, s[2] = {1280, 819200}; const cuuint32_t b[3] = {16, 80, 1}; make_map(enc, &tm.wor, wo, d, s, b, CU_TENSOR_MAP_SWIZZLE_64B); }
  { const cuuint64_t d[3] = {1536, 640, 1}, s[2] = {3072, 1966080}; const cuuint32_t b[3] = {32, 128, 1};
    make_map(enc, &tm.gate, d_in[5], d, s, b, CU_TENSOR_MAP_SWIZZLE_64B); make_map(enc, &tm.up, d_in[6], d, s, b, CU_TENSOR_MAP_SWIZZLE_64B); }
  { const cuuint64_t d[3] = {640, 1536, 1}, s[2] = {1280, 1966080}; const cuuint32_t b[3] = {8, 128, 1}; make_map(enc, &tm.down, d_in[7], d, s, b, CU_TENSOR_MAP_SWIZZLE_NONE); }
  cudaFuncSetAttribute(fused_kernel, cudaFuncAttributeMaxDynamicSharedMemorySize, SMEM_BYTES);
  fused_kernel<<<128, 512, SMEM_BYTES, cudaStreamPerThread>>>(x, wqkv, wo, (const __nv_bfloat16*)d_in[4], (const __nv_bfloat16*)d_in[5],
                                                              (const __nv_bfloat16*)d_in[6], (const __nv_bfloat16*)d_in[7], (__nv_bfloat16*)d_out, (Scratch*)scp, tm);
}
```

```cpp
#include <cuda_runtime.h>
#include <cuda_bf16.h>
#include <cuda.h>
#include <stdint.h>

#define PFW_NS 50
#define PFW_N 14
#define ACT_NS 100
#define KEY_NS 0
#define AUX_NS 50
#define REG_P 72
#define REG_C 184
#define LEAD 1
#define HK_IT 1
#define F_PER 2
#define F_MAX 8
#define HOLD 2
#define AK 3
#define NSPLIT 3
#define THR_END 4
#define BOUNDED 0
#define TLIGHT 0
#define ATOM2 1
#define LAG 5
#define OV 2
#define O_UNROLL 1
#define PRIO 7
#define SPLITB 1

namespace {

constexpr int SLOT    = 49152;
constexpr int OFF_O   = 122880;
constexpr int OFF_W2  = 4 * SLOT;
constexpr int OFF_CS  = OFF_W2 + 24576;
constexpr int OFF_RS  = OFF_CS + 3840;
constexpr int OFF_MN  = OFF_RS + 576;
constexpr int OFF_WR  = OFF_MN + 1024;
constexpr int OFF_RED = OFF_CS;
constexpr int OFF_HN  = OFF_CS + 2048;
constexpr int OFF_PT  = OFF_WR + 352;
constexpr int OFF_BAR = OFF_PT + 768;
constexpr int SMEM_BYTES = OFF_BAR + 424 + 384;
constexpr uint32_t D0 = 1024 >> 4;
constexpr int OUNR = O_UNROLL;
constexpr uint32_t SENT = 0xFFFFFFFFu;
constexpr int SPIN_MAX = 1 << 20;

struct Glob {
  uint4 cand[128][8][24];
  uint32_t act[768];
  uint32_t pad[256];
};
constexpr int GLOB_PER_CTA = sizeof(Glob) / 16 / 128;
static_assert(GLOB_PER_CTA * 128 * 16 == sizeof(Glob), "glob size");
struct Own {
  uint4 halo[5][32];
  uint4 st1[32];
  uint2 cs[32];
  uint4 st2[16];
  uint4 cnt[8];
};
struct Scratch {
  Glob x;
  Own own[128];
  uint4 o[32][8][640];
  uint32_t epoch[128];
};
__device__ __align__(128) Scratch g_scratch;
#define g_x (sc->x)
#define g_own (sc->own)
#define g_o (sc->o)
#define g_epoch (sc->epoch)
#define TS(i)

__device__ __forceinline__ void mbar_init(uint32_t bar, uint32_t cnt) { asm volatile("mbarrier.init.shared::cta.b64 [%0], %1;" :: "r"(bar), "r"(cnt) : "memory"); }
__device__ __forceinline__ void mbar_expect_tx(uint32_t bar, uint32_t bytes) { asm volatile("mbarrier.arrive.expect_tx.shared::cta.b64 _, [%0], %1;" :: "r"(bar), "r"(bytes) : "memory"); }
__device__ __forceinline__ void mbar_arrive(uint32_t bar) { asm volatile("mbarrier.arrive.shared::cta.b64 _, [%0];" :: "r"(bar) : "memory"); }
__device__ __forceinline__ void mbar_arrive_cta(uint32_t bar, uint32_t cta) {
  asm volatile("{\n.reg .b32 ra;\nmapa.shared::cluster.u32 ra, %0, %1;\nmbarrier.arrive.shared::cluster.b64 _, [ra];\n}\n" :: "r"(bar), "r"(cta) : "memory");
}
__device__ __forceinline__ void mbar_wait(uint32_t bar, uint32_t parity) {
  asm volatile("{\n.reg .pred p;\nW:\nmbarrier.try_wait.parity.shared::cta.b64 p, [%0], %1;\n@!p bra.uni W;\n}\n" :: "r"(bar), "r"(parity) : "memory");
}
__device__ __forceinline__ void tma_3d(uint32_t dst, const void* tm, uint32_t bar, int c0, int c1, int c2) {
  asm volatile("cp.async.bulk.tensor.3d.shared::cluster.global.mbarrier::complete_tx::bytes [%0], [%1, {%3, %4, %5}], [%2];" :: "r"(dst), "l"(tm), "r"(bar), "r"(c0), "r"(c1), "r"(c2) : "memory");
}
__device__ __forceinline__ void tma_3d_mc(uint32_t dst, const void* tm, uint32_t bar, int c0, int c1, int c2) {
  asm volatile("cp.async.bulk.tensor.3d.shared::cluster.global.mbarrier::complete_tx::bytes.multicast::cluster [%0], [%1, {%3, %4, %5}], [%2], %6;" :: "r"(dst), "l"(tm), "r"(bar), "r"(c0), "r"(c1), "r"(c2), "h"((uint16_t)3) : "memory");
}
__device__ __forceinline__ void wgmma_fence() { asm volatile("wgmma.fence.sync.aligned;" ::: "memory"); }
__device__ __forceinline__ void wgmma_commit() { asm volatile("wgmma.commit_group.sync.aligned;" ::: "memory"); }
template <int N> __device__ __forceinline__ void wgmma_wait() { asm volatile("wgmma.wait_group.sync.aligned %0;" :: "n"(N) : "memory"); }
__device__ __forceinline__ uint64_t make_desc(uint32_t addr, uint32_t lbo, uint32_t sbo, uint32_t swz) {
  return (uint64_t)(((addr & 0x3FFFF) >> 4) | ((lbo >> 4) << 16)) | ((uint64_t)((sbo >> 4) | (swz << 30)) << 32);
}
__device__ __forceinline__ void bar_sync(int id, int n) { asm volatile("bar.sync %0, %1;" :: "r"(id), "r"(n) : "memory"); }
__device__ __forceinline__ void st_pkt(void* p, uint32_t a, uint32_t b, uint32_t c, uint32_t d) {
  asm volatile("st.relaxed.gpu.v4.u32 [%0], {%1, %2, %3, %4};" :: "l"(p), "r"(a), "r"(b), "r"(c), "r"(d) : "memory");
}
__device__ __forceinline__ uint4 ldg_pkt(const void* p) {
  uint4 v; asm volatile("ld.relaxed.gpu.global.v4.u32 {%0, %1, %2, %3}, [%4];" : "=r"(v.x), "=r"(v.y), "=r"(v.z), "=r"(v.w) : "l"(p) : "memory"); return v;
}
__device__ __forceinline__ void stg_pkt(void* p, uint32_t a, uint32_t b, uint32_t c, uint32_t d) {
  asm volatile("st.relaxed.gpu.global.v4.u32 [%0], {%1, %2, %3, %4};" :: "l"(p), "r"(a), "r"(b), "r"(c), "r"(d) : "memory");
}
__device__ __forceinline__ uint32_t ldg_rlx32(const void* p) { uint32_t v; asm volatile("ld.relaxed.gpu.global.u32 %0, [%1];" : "=r"(v) : "l"(p) : "memory"); return v; }
__device__ __forceinline__ uint2 ldg_rlx64(const void* p) { uint2 v; asm volatile("ld.relaxed.gpu.global.v2.u32 {%0, %1}, [%2];" : "=r"(v.x), "=r"(v.y) : "l"(p) : "memory"); return v; }
__device__ __forceinline__ uint32_t pin(uint32_t v) { asm volatile("" : "+r"(v)); return v; }
__device__ __forceinline__ uint64_t mk64(uint32_t lo, uint32_t hi) { return ((uint64_t)hi << 32) | lo; }
template <class T> __device__ __forceinline__ T* hold(T* p) { return (T*)__shfl_sync(0xffffffffu, (unsigned long long)p, threadIdx.x & 31); }
__device__ __forceinline__ void stg128_if(bool q, void* p, const uint4& v) {
  asm volatile("{\n.reg .pred q;\nsetp.ne.u32 q, %5, 0;\n@q st.global.v4.u32 [%0], {%1, %2, %3, %4};\n}\n" :: "l"(p), "r"(v.x), "r"(v.y), "r"(v.z), "r"(v.w), "r"((int)q) : "memory");
}
template <class T> __device__ __forceinline__ T* pin(T* p) { asm volatile("" : "+l"(p)); return p; }
__device__ __forceinline__ void stg_rlx32(void* p, uint32_t v) { asm volatile("st.relaxed.gpu.global.u32 [%0], %1;" :: "l"(p), "r"(v) : "memory"); }
__device__ __forceinline__ void stg_rlx64(void* p, uint32_t a, uint32_t b) { asm volatile("st.relaxed.gpu.global.v2.u32 [%0], {%1, %2};" :: "l"(p), "r"(a), "r"(b) : "memory"); }
__device__ __forceinline__ uint4 ldsm4(uint32_t a) { uint4 v; asm volatile("ldmatrix.sync.aligned.m8n8.x4.shared.b16 {%0, %1, %2, %3}, [%4];" : "=r"(v.x), "=r"(v.y), "=r"(v.z), "=r"(v.w) : "r"(a) : "memory"); return v; }
__device__ __forceinline__ void ldsm4_if(uint4& v, uint32_t a, int off, bool p) {
  asm volatile("{\n.reg .pred q;\nsetp.ne.u32 q, %5, 0;\n@q ldmatrix.sync.aligned.m8n8.x4.shared.b16 {%0, %1, %2, %3}, [%4];\n}\n"
               : "+r"(v.x), "+r"(v.y), "+r"(v.z), "+r"(v.w) : "r"(a + off), "r"((int)p) : "memory");
}
__device__ __forceinline__ uint4 ldsm4t(uint32_t a) { uint4 v; asm volatile("ldmatrix.sync.aligned.m8n8.x4.trans.shared.b16 {%0, %1, %2, %3}, [%4];" : "=r"(v.x), "=r"(v.y), "=r"(v.z), "=r"(v.w) : "r"(a) : "memory"); return v; }
__device__ __forceinline__ void stsm4(uint32_t a, uint32_t x, uint32_t y, uint32_t z, uint32_t w) { asm volatile("stmatrix.sync.aligned.m8n8.x4.shared.b16 [%0], {%1, %2, %3, %4};" :: "r"(a), "r"(x), "r"(y), "r"(z), "r"(w) : "memory"); }
__device__ __forceinline__ void mma_acc(float (&c)[4], const uint4& a, uint32_t b0, uint32_t b1) {
  asm("mma.sync.aligned.m16n8k16.row.col.f32.bf16.bf16.f32 {%0,%1,%2,%3}, {%4,%5,%6,%7}, {%8,%9}, {%0,%1,%2,%3};"
      : "+f"(c[0]), "+f"(c[1]), "+f"(c[2]), "+f"(c[3]) : "r"(a.x), "r"(a.y), "r"(a.z), "r"(a.w), "r"(b0), "r"(b1));
}
__device__ __forceinline__ uint4 lds128(uint32_t a) { uint4 v; asm volatile("ld.shared.v4.u32 {%0, %1, %2, %3}, [%4];" : "=r"(v.x), "=r"(v.y), "=r"(v.z), "=r"(v.w) : "r"(a) : "memory"); return v; }
__device__ __forceinline__ float2 lds64f(uint32_t a) { float2 v; asm volatile("ld.shared.v2.f32 {%0, %1}, [%2];" : "=f"(v.x), "=f"(v.y) : "r"(a)); return v; }
__device__ __forceinline__ float lds32f(uint32_t a) { float v; asm volatile("ld.shared.f32 %0, [%1];" : "=f"(v) : "r"(a)); return v; }
__device__ __forceinline__ void sts32f(uint32_t a, float v) { asm volatile("st.shared.f32 [%0], %1;" :: "r"(a), "f"(v) : "memory"); }
__device__ __forceinline__ uint32_t pack_bf16(float lo, float hi) { uint32_t r; asm("cvt.rn.bf16x2.f32 %0, %1, %2;" : "=r"(r) : "f"(hi), "f"(lo)); return r; }
__device__ __forceinline__ float bf_lo(uint32_t v) { return __uint_as_float(v << 16); }
__device__ __forceinline__ float bf_hi(uint32_t v) { return __uint_as_float(v & 0xffff0000u); }
__device__ __forceinline__ uint32_t movm(uint32_t a) { uint32_t d; asm("movmatrix.sync.aligned.m8n8.trans.b16 %0, %1;" : "=r"(d) : "r"(a)); return d; }
__device__ __forceinline__ float ex2(float x) { float y; asm("ex2.approx.ftz.f32 %0, %1;" : "=f"(y) : "f"(x)); return y; }
__device__ __forceinline__ float rsq(float x) { float y; asm("rsqrt.approx.ftz.f32 %0, %1;" : "=f"(y) : "f"(x)); return y; }
__device__ __forceinline__ float rcp(float x) { float y; asm("rcp.approx.ftz.f32 %0, %1;" : "=f"(y) : "f"(x)); return y; }
__device__ __forceinline__ bool elect() { uint32_t p; asm volatile("{\n.reg .pred q;\nelect.sync _|q, 0xffffffff;\nselp.u32 %0, 1, 0, q;\n}\n" : "=r"(p)); return p; }
__device__ __forceinline__ void pf_l2(const void* p) { asm volatile("prefetch.global.L2 [%0];" :: "l"(p)); }
__device__ __forceinline__ bool anyw(bool p) { return __any_sync(0xffffffffu, p); }
__device__ __forceinline__ float shx(float v, int m) { return __shfl_xor_sync(0xffffffffu, v, m); }
__device__ __forceinline__ void mma_k24(float (&c)[4], uint32_t a0, uint32_t a1, uint32_t a2, uint32_t a3, uint32_t b0, uint32_t b1,
                                        uint32_t e0, uint32_t e1, uint32_t f0) {
  asm("mma.sync.aligned.m16n8k16.row.col.f32.bf16.bf16.f32 {%0,%1,%2,%3}, {%4,%5,%6,%7}, {%8,%9}, {%10,%10,%10,%10};"
      : "=f"(c[0]), "=f"(c[1]), "=f"(c[2]), "=f"(c[3]) : "r"(a0), "r"(a1), "r"(a2), "r"(a3), "r"(b0), "r"(b1), "f"(0.f));
  asm("mma.sync.aligned.m16n8k8.row.col.f32.bf16.bf16.f32 {%0,%1,%2,%3}, {%4,%5}, {%6}, {%0,%1,%2,%3};"
      : "+f"(c[0]), "+f"(c[1]), "+f"(c[2]), "+f"(c[3]) : "r"(e0), "r"(e1), "r"(f0));
}
__device__ __forceinline__ uint32_t ord_key(float r) { uint32_t u = __float_as_uint(r); return u ^ ((uint32_t)((int32_t)u >> 31) | 0x80000000u); }

__device__ __forceinline__ void wgmma_n64hi_ss(float (&d)[120], uint64_t da, uint64_t db, int scale_d) {
  asm volatile("{\n.reg .pred p;\nsetp.ne.b32 p, %34, 0;\n"
    "wgmma.mma_async.sync.aligned.m64n64k16.f32.bf16.bf16 "
    "{%0, %1, %2, %3, %4, %5, %6, %7, %8, %9, %10, %11, %12, %13, %14, %15, "
    "%16, %17, %18, %19, %20, %21, %22, %23, %24, %25, %26, %27, %28, %29, %30, %31}, "
    "%32, %33, p, 1, 1, 0, 1;\n}\n"
    : "+f"(d[88]), "+f"(d[89]), "+f"(d[90]), "+f"(d[91]), "+f"(d[92]), "+f"(d[93]), "+f"(d[94]), "+f"(d[95]),
      "+f"(d[96]), "+f"(d[97]), "+f"(d[98]), "+f"(d[99]), "+f"(d[100]), "+f"(d[101]), "+f"(d[102]), "+f"(d[103]),
      "+f"(d[104]), "+f"(d[105]), "+f"(d[106]), "+f"(d[107]), "+f"(d[108]), "+f"(d[109]), "+f"(d[110]), "+f"(d[111]),
      "+f"(d[112]), "+f"(d[113]), "+f"(d[114]), "+f"(d[115]), "+f"(d[116]), "+f"(d[117]), "+f"(d[118]), "+f"(d[119])
    : "l"(da), "l"(db), "r"(scale_d));
}
__device__ __forceinline__ void wgmma_n176lo_ss(float (&d)[120], uint64_t da, uint64_t db, int scale_d) {
  asm volatile("{\n.reg .pred p;\nsetp.ne.b32 p, %90, 0;\n"
    "wgmma.mma_async.sync.aligned.m64n176k16.f32.bf16.bf16 "
    "{%0, %1, %2, %3, %4, %5, %6, %7, %8, %9, %10, %11, %12, %13, %14, %15, "
    "%16, %17, %18, %19, %20, %21, %22, %23, %24, %25, %26, %27, %28, %29, %30, %31, "
    "%32, %33, %34, %35, %36, %37, %38, %39, %40, %41, %42, %43, %44, %45, %46, %47, "
    "%48, %49, %50, %51, %52, %53, %54, %55, %56, %57, %58, %59, %60, %61, %62, %63, "
    "%64, %65, %66, %67, %68, %69, %70, %71, %72, %73, %74, %75, %76, %77, %78, %79, "
    "%80, %81, %82, %83, %84, %85, %86, %87}, "
    "%88, %89, p, 1, 1, 0, 1;\n}\n"
    : "+f"(d[0]), "+f"(d[1]), "+f"(d[2]), "+f"(d[3]), "+f"(d[4]), "+f"(d[5]), "+f"(d[6]), "+f"(d[7]),
      "+f"(d[8]), "+f"(d[9]), "+f"(d[10]), "+f"(d[11]), "+f"(d[12]), "+f"(d[13]), "+f"(d[14]), "+f"(d[15]),
      "+f"(d[16]), "+f"(d[17]), "+f"(d[18]), "+f"(d[19]), "+f"(d[20]), "+f"(d[21]), "+f"(d[22]), "+f"(d[23]),
      "+f"(d[24]), "+f"(d[25]), "+f"(d[26]), "+f"(d[27]), "+f"(d[28]), "+f"(d[29]), "+f"(d[30]), "+f"(d[31]),
      "+f"(d[32]), "+f"(d[33]), "+f"(d[34]), "+f"(d[35]), "+f"(d[36]), "+f"(d[37]), "+f"(d[38]), "+f"(d[39]),
      "+f"(d[40]), "+f"(d[41]), "+f"(d[42]), "+f"(d[43]), "+f"(d[44]), "+f"(d[45]), "+f"(d[46]), "+f"(d[47]),
      "+f"(d[48]), "+f"(d[49]), "+f"(d[50]), "+f"(d[51]), "+f"(d[52]), "+f"(d[53]), "+f"(d[54]), "+f"(d[55]),
      "+f"(d[56]), "+f"(d[57]), "+f"(d[58]), "+f"(d[59]), "+f"(d[60]), "+f"(d[61]), "+f"(d[62]), "+f"(d[63]),
      "+f"(d[64]), "+f"(d[65]), "+f"(d[66]), "+f"(d[67]), "+f"(d[68]), "+f"(d[69]), "+f"(d[70]), "+f"(d[71]),
      "+f"(d[72]), "+f"(d[73]), "+f"(d[74]), "+f"(d[75]), "+f"(d[76]), "+f"(d[77]), "+f"(d[78]), "+f"(d[79]),
      "+f"(d[80]), "+f"(d[81]), "+f"(d[82]), "+f"(d[83]), "+f"(d[84]), "+f"(d[85]), "+f"(d[86]), "+f"(d[87])
    : "l"(da), "l"(db), "r"(scale_d));
}
__device__ __forceinline__ void wgmma_n64hi_rk(float (&d)[120], uint32_t a0, uint32_t a1, uint32_t a2, uint32_t a3, uint64_t db, int scale_d) {
  asm volatile("{\n.reg .pred p;\nsetp.ne.b32 p, %37, 0;\n"
    "wgmma.mma_async.sync.aligned.m64n64k16.f32.bf16.bf16 "
    "{%0, %1, %2, %3, %4, %5, %6, %7, %8, %9, %10, %11, %12, %13, %14, %15, "
    "%16, %17, %18, %19, %20, %21, %22, %23, %24, %25, %26, %27, %28, %29, %30, %31}, "
    "{%32, %33, %34, %35}, %36, p, 1, 1, 0;\n}\n"
    : "+f"(d[88]), "+f"(d[89]), "+f"(d[90]), "+f"(d[91]), "+f"(d[92]), "+f"(d[93]), "+f"(d[94]), "+f"(d[95]),
      "+f"(d[96]), "+f"(d[97]), "+f"(d[98]), "+f"(d[99]), "+f"(d[100]), "+f"(d[101]), "+f"(d[102]), "+f"(d[103]),
      "+f"(d[104]), "+f"(d[105]), "+f"(d[106]), "+f"(d[107]), "+f"(d[108]), "+f"(d[109]), "+f"(d[110]), "+f"(d[111]),
      "+f"(d[112]), "+f"(d[113]), "+f"(d[114]), "+f"(d[115]), "+f"(d[116]), "+f"(d[117]), "+f"(d[118]), "+f"(d[119])
    : "r"(a0), "r"(a1), "r"(a2), "r"(a3), "l"(db), "r"(scale_d));
}
__device__ __forceinline__ void wgmma_n176lo_rk(float (&d)[120], uint32_t a0, uint32_t a1, uint32_t a2, uint32_t a3, uint64_t db, int scale_d) {
  asm volatile("{\n.reg .pred p;\nsetp.ne.b32 p, %93, 0;\n"
    "wgmma.mma_async.sync.aligned.m64n176k16.f32.bf16.bf16 "
    "{%0, %1, %2, %3, %4, %5, %6, %7, %8, %9, %10, %11, %12, %13, %14, %15, "
    "%16, %17, %18, %19, %20, %21, %22, %23, %24, %25, %26, %27, %28, %29, %30, %31, "
    "%32, %33, %34, %35, %36, %37, %38, %39, %40, %41, %42, %43, %44, %45, %46, %47, "
    "%48, %49, %50, %51, %52, %53, %54, %55, %56, %57, %58, %59, %60, %61, %62, %63, "
    "%64, %65, %66, %67, %68, %69, %70, %71, %72, %73, %74, %75, %76, %77, %78, %79, "
    "%80, %81, %82, %83, %84, %85, %86, %87}, "
    "{%88, %89, %90, %91}, %92, p, 1, 1, 0;\n}\n"
    : "+f"(d[0]), "+f"(d[1]), "+f"(d[2]), "+f"(d[3]), "+f"(d[4]), "+f"(d[5]), "+f"(d[6]), "+f"(d[7]),
      "+f"(d[8]), "+f"(d[9]), "+f"(d[10]), "+f"(d[11]), "+f"(d[12]), "+f"(d[13]), "+f"(d[14]), "+f"(d[15]),
      "+f"(d[16]), "+f"(d[17]), "+f"(d[18]), "+f"(d[19]), "+f"(d[20]), "+f"(d[21]), "+f"(d[22]), "+f"(d[23]),
      "+f"(d[24]), "+f"(d[25]), "+f"(d[26]), "+f"(d[27]), "+f"(d[28]), "+f"(d[29]), "+f"(d[30]), "+f"(d[31]),
      "+f"(d[32]), "+f"(d[33]), "+f"(d[34]), "+f"(d[35]), "+f"(d[36]), "+f"(d[37]), "+f"(d[38]), "+f"(d[39]),
      "+f"(d[40]), "+f"(d[41]), "+f"(d[42]), "+f"(d[43]), "+f"(d[44]), "+f"(d[45]), "+f"(d[46]), "+f"(d[47]),
      "+f"(d[48]), "+f"(d[49]), "+f"(d[50]), "+f"(d[51]), "+f"(d[52]), "+f"(d[53]), "+f"(d[54]), "+f"(d[55]),
      "+f"(d[56]), "+f"(d[57]), "+f"(d[58]), "+f"(d[59]), "+f"(d[60]), "+f"(d[61]), "+f"(d[62]), "+f"(d[63]),
      "+f"(d[64]), "+f"(d[65]), "+f"(d[66]), "+f"(d[67]), "+f"(d[68]), "+f"(d[69]), "+f"(d[70]), "+f"(d[71]),
      "+f"(d[72]), "+f"(d[73]), "+f"(d[74]), "+f"(d[75]), "+f"(d[76]), "+f"(d[77]), "+f"(d[78]), "+f"(d[79]),
      "+f"(d[80]), "+f"(d[81]), "+f"(d[82]), "+f"(d[83]), "+f"(d[84]), "+f"(d[85]), "+f"(d[86]), "+f"(d[87])
    : "r"(a0), "r"(a1), "r"(a2), "r"(a3), "l"(db), "r"(scale_d));
}
__device__ __forceinline__ void wgmma_n80_rs(float (&d)[40], uint32_t a0, uint32_t a1, uint32_t a2, uint32_t a3, uint64_t db, int scale_d) {
  asm volatile("{\n.reg .pred p;\nsetp.ne.b32 p, %45, 0;\n"
    "wgmma.mma_async.sync.aligned.m64n80k16.f32.bf16.bf16 "
    "{%0, %1, %2, %3, %4, %5, %6, %7, %8, %9, %10, %11, %12, %13, %14, %15, "
    "%16, %17, %18, %19, %20, %21, %22, %23, %24, %25, %26, %27, %28, %29, %30, %31, "
    "%32, %33, %34, %35, %36, %37, %38, %39}, "
    "{%40, %41, %42, %43}, %44, p, 1, 1, 1;\n}\n"
    : "+f"(d[0]), "+f"(d[1]), "+f"(d[2]), "+f"(d[3]), "+f"(d[4]), "+f"(d[5]), "+f"(d[6]), "+f"(d[7]),
      "+f"(d[8]), "+f"(d[9]), "+f"(d[10]), "+f"(d[11]), "+f"(d[12]), "+f"(d[13]), "+f"(d[14]), "+f"(d[15]),
      "+f"(d[16]), "+f"(d[17]), "+f"(d[18]), "+f"(d[19]), "+f"(d[20]), "+f"(d[21]), "+f"(d[22]), "+f"(d[23]),
      "+f"(d[24]), "+f"(d[25]), "+f"(d[26]), "+f"(d[27]), "+f"(d[28]), "+f"(d[29]), "+f"(d[30]), "+f"(d[31]),
      "+f"(d[32]), "+f"(d[33]), "+f"(d[34]), "+f"(d[35]), "+f"(d[36]), "+f"(d[37]), "+f"(d[38]), "+f"(d[39])
    : "r"(a0), "r"(a1), "r"(a2), "r"(a3), "l"(db), "r"(scale_d));
}
__device__ __forceinline__ void wgmma_n80_ss(float (&d)[40], uint64_t da, uint64_t db, int scale_d) {
  asm volatile("{\n.reg .pred p;\nsetp.ne.b32 p, %42, 0;\n"
    "wgmma.mma_async.sync.aligned.m64n80k16.f32.bf16.bf16 "
    "{%0, %1, %2, %3, %4, %5, %6, %7, %8, %9, %10, %11, %12, %13, %14, %15, "
    "%16, %17, %18, %19, %20, %21, %22, %23, %24, %25, %26, %27, %28, %29, %30, %31, "
    "%32, %33, %34, %35, %36, %37, %38, %39}, "
    "%40, %41, p, 1, 1, 0, 1;\n}\n"
    : "+f"(d[0]), "+f"(d[1]), "+f"(d[2]), "+f"(d[3]), "+f"(d[4]), "+f"(d[5]), "+f"(d[6]), "+f"(d[7]),
      "+f"(d[8]), "+f"(d[9]), "+f"(d[10]), "+f"(d[11]), "+f"(d[12]), "+f"(d[13]), "+f"(d[14]), "+f"(d[15]),
      "+f"(d[16]), "+f"(d[17]), "+f"(d[18]), "+f"(d[19]), "+f"(d[20]), "+f"(d[21]), "+f"(d[22]), "+f"(d[23]),
      "+f"(d[24]), "+f"(d[25]), "+f"(d[26]), "+f"(d[27]), "+f"(d[28]), "+f"(d[29]), "+f"(d[30]), "+f"(d[31]),
      "+f"(d[32]), "+f"(d[33]), "+f"(d[34]), "+f"(d[35]), "+f"(d[36]), "+f"(d[37]), "+f"(d[38]), "+f"(d[39])
    : "l"(da), "l"(db), "r"(scale_d));
}

__device__ __forceinline__ constexpr int QT(int t) { return t < 8 ? t : 16 + t; }
__device__ __forceinline__ constexpr int KT(int t) { return t < 8 ? 8 + t : 18 + t; }
__device__ __forceinline__ constexpr int VT(int t) { return t < 8 ? 16 + t : 20 + t; }

struct Maps { CUtensorMap x, w, wr, wv, wo, wor, gate, up, down; };

__global__ void __cluster_dims__(2, 1, 1) __launch_bounds__(512, 1)
fused_kernel(const __nv_bfloat16* __restrict__ x, const __nv_bfloat16* __restrict__ wqkv,
             const __nv_bfloat16* __restrict__ wo, const __nv_bfloat16* __restrict__ w_r, const __nv_bfloat16* __restrict__ w_gate,
             const __nv_bfloat16* __restrict__ w_up, const __nv_bfloat16* __restrict__ w_down, __nv_bfloat16* __restrict__ out,
             Scratch* __restrict__ sc, const __grid_constant__ Maps tm) {
  extern __shared__ __align__(1024) uint8_t smem[];
  const int tid = threadIdx.x, bid = blockIdx.x;
  if ((unsigned)(tid - 128) < 16u) pf_l2((const char*)x + (bid * 16 + tid - 128) * 1280);
  if ((unsigned)(tid - 160) < 15u) pf_l2((const char*)wqkv + (bid * 15 + tid - 160) * 128);
  const int warp = __shfl_sync(0xffffffffu, tid >> 5, 0), lane = tid & 31;
  const uint32_t sb = (uint32_t)__cvta_generic_to_shared(smem);
  const uint32_t bar_full = sb + OFF_BAR, bar_empty = bar_full + 32, bar_aux = bar_full + 64, bar_ffn = bar_full + 72, bar_win = bar_full + 80, bar_tag = bar_full + 88, bar_rst = bar_full + 96 + 296 + 24,
                 bar_o = bar_full + 96, bar_oc = bar_o + 112, bar_st = bar_o + 224, bar_go = bar_o + 248, bar_kv = bar_o + 272, bar_half = bar_o + 296;
  if (warp < 4 && elect()) {
    mbar_init(bar_half + 8 * warp, 1);
    mbar_init(bar_full + 8 * (warp ^ 2), 1);
    mbar_init(bar_empty + 8 * warp, 24);
    mbar_init(bar_aux + 8 * warp, warp == 0 ? 64 : warp == 2 ? 32 : warp == 3 ? 2 : 1);
    asm volatile("fence.mbarrier_init.release.cluster;" ::: "memory");
  }
  asm volatile("barrier.cluster.arrive.relaxed.aligned;" ::: "memory");
  if (warp >= 8 && warp < 12 && elect()) asm volatile("prefetch.tensormap [%0];" :: "l"(&tm.x + (warp - 8)) : "memory");
  const int rank = bid & 1, cl = bid >> 1;
  const int q7 = ((cl - 36) * 37) >> 8;
  const int P = cl < 4 ? 0 : cl < 36 ? (cl - 4) & 7 : cl - 35 - 7 * q7;
  const int g = (cl < 4 ? 4 + cl : cl < 36 ? (cl - 4) >> 3 : 4 + q7);
  const int mt = 2 * P + rank, cid = mt * 8 + g;
  const bool ffn1 = g >= 5;
  const int fj = ffn1 ? mt * 3 + g - 5 : (P * 5 + g) * 2 + rank;
  const int ord = ((g >> 2) ^ P) & 1;
  auto ks_of = [&](int it) { return ord == 0 || it == 0 ? it : it <= 5 ? it + 4 : it - 5; };
  const int godd = g & 1, cm = g * 80 + godd * 16, cr = g * 80 + 64 - godd * 64;
  auto load_w = [&](int ks, uint32_t a, uint32_t bar, int kk) {
    tma_3d_mc(a + 16384 + ((kk + 1) & 3) * 6144, &tm.w, bar, cm, ks * 64 + kk * 16, 0);
    tma_3d_mc(a + 41472 + kk * 2048, &tm.wr, bar, cr, ks * 64 + kk * 16, 0);
    tma_3d_mc(a + 40960 + kk * 2048, &tm.wv, bar, cm + 48, ks * 64 + kk * 16, 2);
  };
  if (warp == 0 && elect()) {
    mbar_expect_tx(bar_half, 32768);
    tma_3d(sb + 2 * SLOT, &tm.x, bar_half, 0, P * 128, rank);
    mbar_expect_tx(bar_full + 16, 16384);
  }
  asm volatile("barrier.cluster.wait.aligned;" ::: "memory");
  if (warp == 0) {
    if (elect()) {
      uint32_t bar = bar_half;
#pragma unroll 1
      for (int kk = rank; kk < 4; kk += 2) { load_w(0, sb + 2 * SLOT, bar, kk); bar = bar_full + 16; }
    }
    asm volatile("bar.arrive 4, 64;" ::: "memory");
  }

  if (warp >= 8) {
    asm volatile("setmaxnreg.dec.sync.aligned.u32 %0;" :: "n"(REG_P));
#define TS_T 0
    if (warp == 8) {
      TS(8);
      bar_sync(4, 64);
      if (elect()) {
        TS(10);
#pragma unroll 1
        for (int it = 1; it < 10; it++) {
          const int s = (it + 2) & 3, ks = ks_of(it);
          const uint32_t full = bar_full + 8 * s, a = sb + s * SLOT;
          uint32_t bar = it < NSPLIT ? bar_half + 8 * it : full;
          if (it >= 4) mbar_wait(full + 32, ((it >> 2) - 1) & 1);
          if (it >= 2 && it < THR_END) mbar_wait(bar_full + 8 * (it & 3), 0);
          if (it < NSPLIT) mbar_expect_tx(bar, 32768);
          mbar_expect_tx(full, it < NSPLIT ? 16384 : SLOT);
          tma_3d(a, &tm.x, bar, ks * 64, P * 128, rank);
#pragma unroll 1
          for (int kk = rank; kk < 4; kk += 2) { load_w(ks, a, bar, kk); bar = full; }
          TS(12 + it);
          if ((it >> 1) == 2) {
            mbar_wait(bar_rst, 0);
            asm volatile("cp.async.bulk.global.shared::cta.bulk_group [%0], [%1], %2;\ncp.async.bulk.commit_group;"
                         :: "l"(it == 4 ? (uint4*)(g_own + cid) : (uint4*)&g_x + cid * GLOB_PER_CTA), "r"(sb + OFF_CS), "r"(it == 4 ? (int)sizeof(Own) : GLOB_PER_CTA * 16) : "memory");
          }
          if (it == 6) { asm volatile("cp.async.bulk.wait_group 0;" ::: "memory"); mbar_arrive(bar_tag); }
        }
        mbar_expect_tx(bar_ffn, ffn1 ? 81920 : 24576);
        int fjn = 0;
#pragma unroll 1
        for (int it = 9; it < 17; it++) {
          if (it >= 13) { mbar_wait(bar_oc + 8 * (it - 13), 0); mbar_wait(bar_oc + 56 + 8 * (it - 13), 0); }
          else if (it >= 10) {
            const uint32_t full = bar_full + 8 * (it - 10);
            const int g0 = 3 * (it - 10), g1 = min(g0 + 3, 8);
            mbar_wait(full + 32, it < 12);
            mbar_expect_tx(full, (g1 - g0) * 12800);
#pragma unroll 1
            for (int gp = g0 + ((g0 ^ rank) & 1); gp < g1; gp += 2) {
              tma_3d_mc(sb + gp * 15360, &tm.wo, full, 0, gp * 80, g * 2);
              tma_3d_mc(sb + gp * 15360 + 10240, &tm.wor, full, 512 + g * 16, gp * 80, 0);
            }
          }
          const int j1 = ffn1 ? (it >= 13 ? 2 * it - 22 : min(it - 8, 3)) : (it >= 13 ? 12 : min((it - 8) * F_PER, F_MAX));
#pragma unroll 1
          for (; fjn < j1; fjn++) {
            const int j = fjn < 3 ? fjn + 7 : fjn - 3;
            if (ffn1) tma_3d(sb + (j < 7 ? 0 : OFF_W2 - 57344) + j * 8192, j < 5 ? &tm.gate : &tm.up, bar_ffn, fj * 32, (j < 5 ? j : j - 5) * 128, 0);
            else tma_3d(sb + OFF_W2 + fjn * 2048, &tm.down, bar_ffn, fj * 8, fjn * 128, 0);
          }
        }
        TS(11);
      }
#undef TS_T
#define TS_T 64
    } else if (warp >= 12) {
      const int l7 = lane & 7, j = warp - 12, ch = min((P >> 1) * 4 + rank * 2 + (j >> 1), 14);
      const uint32_t sxo = ((g & 3) * 32 + j * 8 + l7) * 128 + (((lane >> 3) ^ l7) * 16);
      const uint32_t swo = ch < 12 ? 16384 + (lane >> 4) * 6144 + (ch >> 2) * 2048 + (lane & 15) * 128 + ((((ch & 3) * 2 + (j & 1)) ^ l7) * 16)
                                   : 41472 + (lane >> 4) * 2048 + (ch - 12) * 512 + (lane & 15) * 32 + (((j & 1) ^ (l7 >> 2)) * 16);
      float ps = 0.f, pq = 0.f, pq1 = 0.f, pc = 0.f;
      uint32_t tag = 0;
      char* const pp = hold((lane & 1) ? (char*)&g_own[cid].cs[j * 8 + (lane >> 2)] : (char*)&g_own[cid].st1[j * 8 + (lane >> 2)]);
#pragma unroll 1
      for (int it = ord; it < ord + 5; it++) {
        const int sl = (it + 2) & 3;
        if (it == ord + 4) { mbar_wait(bar_tag, 0); tag = __float_as_uint(lds32f(sb + OFF_WR + 324)); }
        if (it < NSPLIT) mbar_wait(bar_half + 8 * it, 0);
        mbar_wait(bar_full + 8 * sl, (it >> 2) & 1);
        TS(it);
        const uint32_t a = sb + sl * SLOT;
        const uint4 v0 = ldsm4(a + sxo), v1 = ldsm4((a + sxo) ^ 64), w0 = ldsm4t(a + swo), w1 = ldsm4t(a + swo + (ch < 12 ? 12288 : 4096));
        if (lane + (int)((v0.x & v1.x & w0.x & w1.x) == 0x7fc17fc1u && (v0.x | v1.x) == 0u) < 2) mbar_arrive_cta(bar_empty + 8 * sl, lane);
        const uint32_t vv[8] = {v0.x, v0.y, v0.z, v0.w, v1.x, v1.y, v1.z, v1.w}, ww[8] = {w0.x, w0.y, w0.z, w0.w, w1.x, w1.y, w1.z, w1.w};
#pragma unroll
        for (int i = 0; i < 8; i++) {
          const float d = bf_lo(vv[i]), e = bf_hi(vv[i]);
          ps += d + e; pq = fmaf(d, d, pq); pq1 = fmaf(e, e, pq1); pc += bf_lo(ww[i]) + bf_hi(ww[i]);
        }
      }
      pq += pq1;
      ps += shx(ps, 1); pq += shx(pq, 1); pc += shx(pc, 1);
      ps += shx(ps, 2); pq += shx(pq, 2); pc += shx(pc, 2);
      if ((lane & 3) == 0) stg_pkt(pp, __float_as_uint(ps), __float_as_uint(pq), tag, 0u);
      if ((lane & 3) == 1) stg_rlx64(pp, __float_as_uint(pc), tag);
      asm volatile("bar.arrive 2, 192;" ::: "memory");
      if (warp == 12) {
        const uint4* const hp = hold(&g_own[max(cid - 16, 0)].halo[0][lane]);
        mbar_wait(bar_aux, 0);
        mbar_wait(bar_go, 0);
        uint4 v[5] = {};
        int guard = SPIN_MAX;
        if (P > 0) {
          do {
#pragma unroll
            for (int i = 0; i < 5; i++) v[i] = ldg_pkt(hp + 32 * i);
          } while (anyw(v[0].x == SENT || v[1].x == SENT || v[2].x == SENT || v[3].x == SENT || v[4].x == SENT) && --guard > 0);
        }
#pragma unroll
        for (int i = 0; i < 5; i++) *(uint4*)(smem + OFF_O + 10240 + i * 512 + lane * 16) = v[i];
        mbar_arrive(bar_kv);
      }
#undef TS_T
#define TS_T 32
    } else if (warp < 11) {
      const int l7 = lane & 7, hk = lane >> 4;
      if (warp == 10 && elect()) {
#pragma unroll 1
        for (int i = 0; i < 36; i++) mbar_init(bar_o + 8 * i, i < 14 || i == 30 ? 1 : i < 34 ? 4 : 128);
      }
      mbar_wait(bar_tag, 0);
      const uint32_t tag = __float_as_uint(lds32f(sb + OFF_WR + 324));
      bar_sync(2, 192);
      TS(0);
      int guard = SPIN_MAX;
      if (warp == 9) {
        const uint4* sp = &g_own[mt * 8].st1[lane];
        const uint4* hp = &g_own[max(mt - 2, 0) * 8 + 3].st1[24 + l7];
        uint4 a[5], b[5];
        bool bad;
        do {
          __nanosleep(AUX_NS);
          bad = false;
#pragma unroll
          for (int i = 0; i < 5; i++) {
            const uint4* q = i < 4 ? sp + i * (sizeof(Own) / 16) : hp;
            a[i] = ldg_pkt(q); b[i] = ldg_pkt(q + 4 * sizeof(Own) / 16);
          }
#pragma unroll
          for (int i = 0; i < 5; i++) bad |= a[i].z != tag || b[i].z != tag;
        } while (anyw(bad) && --guard);
        TS(1);
#pragma unroll
        for (int i = 0; i < 5; i++) {
          const float m = (__uint_as_float(a[i].x) + __uint_as_float(b[i].x)) * (1.f / 640.f);
          const float rs = rsq(fmaxf(fmaf(-m, m, (__uint_as_float(a[i].y) + __uint_as_float(b[i].y)) * (1.f / 640.f)), 0.f) + 1e-5f);
          ((float*)(smem + OFF_RS))[i < 4 ? 8 + lane + 32 * i : l7] = rs;
          const uint32_t mh = pack_bf16(-m, -m);
          const float ml = -m - bf_lo(mh);
          if (i < 4) ((uint2*)(smem + OFF_MN))[lane + 32 * i] = make_uint2(mh, pack_bf16(ml, ml));
        }
      } else {
        const uint4* cp = (const uint4*)g_own[hk * 8 + g].cs + (lane & 15);
        uint4 a[4], b[4];
        bool bad;
        do {
          __nanosleep(AUX_NS);
          bad = false;
#pragma unroll
          for (int i = 0; i < 4; i++) { a[i] = ldg_pkt(cp + i * 32 * sizeof(Own) / 16); b[i] = ldg_pkt(cp + (i * 32 + 16) * sizeof(Own) / 16); }
#pragma unroll
          for (int i = 0; i < 4; i++) bad |= a[i].y != tag || a[i].w != tag || b[i].y != tag || b[i].w != tag;
        } while (anyw(bad) && --guard);
#pragma unroll
        for (int i = 0; i < 4; i++)
          if (i < 3 || lane < 24) {
            const float c0 = __uint_as_float(a[i].x) + __uint_as_float(b[i].x), c1 = __uint_as_float(a[i].z) + __uint_as_float(b[i].z);
            const uint32_t hi = pack_bf16(c0, c1), w0 = pack_bf16(c0, c0 - bf_lo(hi)), w1 = pack_bf16(c1, c1 - bf_hi(hi));
            uint4* const d = (uint4*)(smem + OFF_CS) + 2 * (lane + 32 * i);
            d[0] = make_uint4(w0, w0, 0, 0); d[1] = make_uint4(w1, w1, 0, 0);
          }
        asm volatile("fence.proxy.async.shared::cta;" ::: "memory");
      }
      mbar_arrive(bar_aux);
      TS(2);
      const int fo = warp - 9, wq = fo ? 1 - LEAD : LEAD;
      const uint4* const fp = hold(g_own[mt * 8 + wq * 4].cnt);
      const char* src = hold((const char*)g_o[mt * 2 + wq]);
      if (elect()) {
        const uint32_t bo = bar_o + fo * 56;
#pragma unroll
        for (int i = 0; i < 7; i++) mbar_expect_tx(bo + 8 * i, 10240);
        uint32_t cv = 0, need = 4;
        mbar_wait(OV == 3 ? bar_st + 8 * fo : bar_go + 8 + 8 * fo, 0);
        uint32_t dst = sb + OFF_O + 20480;
#pragma unroll OUNR
        for (int i = 0; i < 7; i++) {
          if (i == g) { src += 10240; need <<= 4; }
          if (!(cv & need)) {
            do { cv = ldg_rlx32(fp); } while (!(cv & need) && --guard > 0);
            asm volatile("fence.proxy.async.global;" ::: "memory");
          }
          if (fo || i == 5 || (OV == 2 && i == 4)) mbar_wait(fo ? bar_oc + 8 * i : i == 4 ? bar_st : bar_st + 8, 0);
          if (i == 0) TS(6);
          asm volatile("cp.async.bulk.shared::cluster.global.mbarrier::complete_tx::bytes [%0], [%1], 10240, [%2];" :: "r"(dst), "l"(src), "r"(bo + 8 * i) : "memory");
          src += 10240; need <<= 4;
          dst += i == 4 ? -61440 : 10240;
        }
      }
#undef TS_T
#define TS_T 96
    } else {
      if ((sb & 0x3FFFF) != D0 * 16) __trap();
#pragma unroll 1
      for (int i = lane; i < 232; i += 32) { const uint32_t f = i < 208 ? SENT : 0u; ((uint4*)(smem + OFF_CS))[i] = make_uint4(f, f, f, f); }
      asm volatile("fence.proxy.async.shared::cta;" ::: "memory");
      if (elect()) mbar_arrive(bar_rst);
      mbar_wait(bar_full + 8 * ((HK_IT + 2) & 3), 0);
      TS(4);
      const uint32_t epoch = ldg_rlx32(g_epoch + cid) + 1;
      uint32_t wv[10];
#pragma unroll
      for (int i = 0; i < 10; i++) wv[i] = __ldg((const uint32_t*)w_r + lane + 32 * i);
      float s = 0.f;
#pragma unroll
      for (int i = 0; i < 10; i++) {
        s += bf_lo(wv[i]) + bf_hi(wv[i]);
        const unsigned u = i < 8 ? lane + 32 * (i - g) : lane + 32 * (i - 7) - g * 8;
        if (i < 8 ? u < 32u : u - 32u < 8u) *(float2*)(smem + OFF_WR + ((u & 3) * 10 + (u >> 2)) * 8) = make_float2(bf_lo(wv[i]), bf_hi(wv[i]));
      }
#pragma unroll
      for (int m = 1; m < 32; m <<= 1) s += shx(s, m);
      *(float2*)(smem + OFF_WR + 320) = make_float2(s, __uint_as_float(epoch * 0x9E3779B8u));
      g_epoch[cid] = epoch;
      TS(3);
      if (elect()) mbar_arrive(bar_tag);
      TS(5);
#pragma unroll 1
      for (int i = 0; i < PFW_N; i++) {
        const int m = (i + 2) >> 2, n = m == 0 ? 50 : 120, t = (m == 0 ? i : (i + 2) & 3) * 32 + lane;
        const char* b = (const char*)(m == 0 ? wo : m == 1 ? w_up : m == 2 ? w_down : w_gate);
        if (t < n) pf_l2(b + (bid * n + t) * 128);
        __nanosleep(PFW_NS);
      }
      const uint4* const kp = hold(g_own[1].cnt);
      const uint4* const cb = hold(&g_x.cand[0][lane >> 2][lane & 3]);
      bar_sync(3, 64);
      uint4 k;
      uint32_t have = SENT;
      int guard = SPIN_MAX;
      while (true) {
        k = ldg_pkt(kp);
        if (ffn1) {
          while (k.x != have && --guard > 0) {
            const uint32_t tk = 2047u - (k.x & 2047u), want = k.x;
            const uint4* q = cb + ((tk >> 8) * 16 + (tk & 1) * 8 + ((tk >> 5) & 7)) * 192;
            const uint4 c0 = ldg_pkt(q), c1 = ldg_pkt(q + 4); const uint2 c2 = ldg_rlx64(q + 8);
            k = ldg_pkt(kp);
            *(uint4*)(smem + OFF_HN + lane * 16) = c0; *(uint4*)(smem + OFF_HN + 512 + lane * 16) = c1; *(uint2*)(smem + OFF_HN + 1024 + lane * 16) = c2;
            have = anyw(c0.x == SENT || c1.x == SENT || c2.x == SENT) ? SENT : want;
          }
        } else if (KEY_NS && k.z != 128u) __nanosleep(KEY_NS);
        if (k.z == 128u || --guard <= 0) break;
      }
      *(uint2*)(smem + OFF_WR + 336) = make_uint2(k.x, k.y);
      mbar_arrive(bar_win);
      TS(7);
    }
#undef TS_T
  } else {
#define TS_T 0
    asm volatile("setmaxnreg.inc.sync.aligned.u32 %0;" :: "n"(REG_C));
    const int wg = warp >> 2, w4 = warp & 3, r = lane >> 2, c = lane & 3;
    float acc[120];
    uint4 xr[5] = {};
    const uint32_t xa = pin(sb + (warp * 16 + (lane & 15)) * 128 + ((lane >> 4) ^ (lane & 7)) * 16);
    const int fol = wg != LEAD;
    const bool first = (P == 0) && (warp == 0);
    const uint32_t kvs = sb + OFF_O + fol * 10240 + w4 * 2560 + lane * 16;
    uint4* const kvd = hold(warp == 7 ? &g_own[cid].halo[0][lane] : (uint4*)(smem + (warp == 3 ? OFF_O + lane * 16 : kvs - sb + 2560)));
    uint4* const odst = hold(&g_o[mt * 2 + wg][g][w4 * 160]);
    uint4* const ocnt = hold(g_own[mt * 8 + wg * 4].cnt);
    uint32_t m0 = 0, m1 = 0;
    const uint32_t mna = pin(sb + OFF_MN + (warp * 16 + r) * 8 + c * 4);
    const int itx = ord == 0 || g == 0 ? g : g < 5 ? g + 5 : g - 4, ity = (ord ? 4 : 8) + (g >> 2);
    uint32_t rel;
    asm volatile("mapa.shared::cluster.u32 %0, %1, %2;" : "=r"(rel) : "r"(bar_empty), "r"(tid & 1));
    const uint32_t xa1 = pin(xa ^ 32), xa2 = pin(xa ^ 64), xa3 = pin(xa ^ 96), xb = pin(xa ^ ((g & 3) * 32));
    const uint32_t da0 = wg * 512;
    const bool rel2 = lane < 2, rel6 = lane < 2 + 2 * (warp & 1);
    const uint32_t zero = __shfl_sync(0xffffffffu, (uint32_t)(uintptr_t)x & 8u, 0);
    mbar_wait(bar_half, 0);
    TS(13);
    wgmma_fence();
#pragma unroll
    for (int it = 0; it < 10; it++) {
      const int s = (it + 2) & 3;
#pragma unroll
      for (int kk = 0; kk < 4; kk++) {
        if (kk == 2 && it > 0) {
          wgmma_commit();
          wgmma_wait<1>();
          const uint32_t ra = ((xr[0].x ^ xr[1].x ^ xr[2].x ^ xr[3].x ^ xr[4].x) & zero) | rel;
          if (it == 1 ? (ord ? rel6 : rel2) : it == 6 ? (ord ? rel2 : rel6) : it < 6 ? rel2 : rel6)
            asm volatile("mbarrier.arrive.shared::cluster.b64 _, [%0];" :: "r"(ra + 8 * ((it + 1) & 3)) : "memory");
        }
        if (kk == 2) {
          ldsm4_if(xr[0], xa, s * SLOT, it == itx); ldsm4_if(xr[1], xa1, s * SLOT, it == itx);
          ldsm4_if(xr[2], xa2, s * SLOT, it == itx); ldsm4_if(xr[3], xa3, s * SLOT, it == itx);
          if ((it & 6) == 4 || it >= 8) ldsm4_if(xr[4], xb, s * SLOT, it == ity);
        }
        if (kk == AK && it == 9) {
          mbar_wait(bar_aux, 0);
          TS(3);
          if (c < 2) { m0 = __float_as_uint(lds32f(mna)); m1 = __float_as_uint(lds32f(mna + 64)); }
          if (!fol) bar_sync(11, 256);
        }
        if (it * 4 + kk == 40 - LAG && fol) {
          asm volatile("bar.arrive 11, 256;" ::: "memory");
          bar_sync(10, 256);
        }
        if (kk == 2 && it < NSPLIT) mbar_wait(bar_full + 8 * s, 0);
        const uint64_t da = mk64(da0 + (D0 + s * (SLOT >> 4) + kk * 2 + (1 << 16)), 0x40000040u);
        wgmma_n64hi_ss(acc, da, mk64(D0 + s * (SLOT >> 4) + 2560 + kk * 128 + (32 << 16), 0xC0000010u), (it | kk) != 0);
        wgmma_n176lo_ss(acc, da, mk64(D0 + s * (SLOT >> 4) + 1024 + ((kk + 1) & 3) * 384 + (128 << 16), 0x40000040u), (it | kk) != 0);
      }
      wgmma_commit();
      if (it < 9) {
        if (it + 1 < NSPLIT) mbar_wait(bar_half + 8 * (it + 1), 0);
        else mbar_wait(bar_full + 8 * ((it + 3) & 3), ((it + 1) >> 2) & 1);
        if (it < 8) TS(14 + it);
      }
    }
    {
      const uint64_t dc = make_desc(D0 * 16 + OFF_CS, 0, 128, 0);
      wgmma_fence();
      wgmma_n64hi_rk(acc, m0, m1, 0u, 0u, dc + 176, 1);
      wgmma_n176lo_rk(acc, m0, m1, 0u, 0u, dc, 1);
      wgmma_commit();
      if (!fol) asm volatile("bar.arrive 10, 256;" ::: "memory");
    }
    const uint32_t stb = sb + OFF_RS + warp * 64;
    const float rlo = lds32f(stb + (8 + r) * 4), rhi = lds32f(stb + (16 + r) * 4);
    wgmma_wait<0>();
#pragma unroll
    for (int i = 0; i < 120; i++) asm volatile("" : "+f"(acc[i]) :: "memory");
    if (fol && lane == 0) mbar_arrive(bar_go);
    TS(2);
    uint32_t Qlo[10], Qhi[10], Klo[10], Khi[10], Vlo[10], Vhi[10];
#define CONV_HI(ROT) _Pragma("unroll") for (int t = 0; t < 10; t++) { \
      const int k = KT((t + ROT) % 10), v = VT((t + ROT) % 10); \
      Khi[t] = pack_bf16(acc[4 * k + 2], acc[4 * k + 3]); \
      Vhi[t] = pack_bf16(acc[4 * v + 2] * rhi, acc[4 * v + 3] * rhi); }
    if (godd) { CONV_HI(8) } else { CONV_HI(0) }
    st_pkt(kvd, Khi[0], Khi[1], Khi[3], Khi[4]);
    st_pkt(kvd + 32, Khi[5], Khi[6], Khi[8], Khi[9]);
    st_pkt(kvd + 64, Khi[2], Khi[7], Vhi[0], Vhi[1]);
    st_pkt(kvd + 96, Vhi[2], Vhi[3], Vhi[4], Vhi[5]);
    st_pkt(kvd + 128, Vhi[6], Vhi[7], Vhi[8], Vhi[9]);
    if (warp < 7) mbar_arrive(bar_kv + ((warp + 1) >> 2) * 8);
#define CONV_LO(ROT) _Pragma("unroll") for (int t = 0; t < 10; t++) { \
      const int q = QT((t + ROT) % 10), k = KT((t + ROT) % 10), v = VT((t + ROT) % 10); \
      Vhi[t] = movm(Vhi[t]); \
      Klo[t] = pack_bf16(acc[4 * k], acc[4 * k + 1]); \
      Vlo[t] = movm(pack_bf16(acc[4 * v] * rlo, acc[4 * v + 1] * rlo)); \
      Qlo[t] = pack_bf16(acc[4 * q], acc[4 * q + 1]); \
      Qhi[t] = pack_bf16(acc[4 * q + 2], acc[4 * q + 3]); }
    if (godd) { CONV_LO(8) } else { CONV_LO(0) }
    const bool in0 = 2 * c <= r, in1 = 2 * c + 1 <= r;
    const uint32_t mL = (in0 ? 0xffffu : 0u) | (in1 ? 0xffff0000u : 0u);
    const float qs = 0.22360679774997896f * 1.4426950408889634f;
    const uint32_t kb0 = stb + (2 * c + (in0 ? 8 : 0)) * 4, kb1 = stb + (2 * c + 1 + (in1 ? 8 : 0)) * 4;
    const float scl0 = lds32f(kb0) * rlo * qs, scl1 = lds32f(kb1) * rlo * qs;
    const float sch0 = lds32f(kb0 + 32) * rhi * qs, sch1 = lds32f(kb1 + 32) * rhi * qs;
    const float bias0 = (first && !in0) ? -INFINITY : 0.f, bias1 = (first && !in1) ? -INFINITY : 0.f;
    const int slot = mt * 8 + warp;
    int guard = SPIN_MAX;
    uint4 pv[5];
    const bool cA = c < 2, nA = r < 4;
    TS(0);
    mbar_wait(bar_go + fol * 8, 0);
    TS(23);
    uint32_t qe[4][2];
    float sl0[4], sl1[4], th0[4], th1[4];
#pragma unroll
    for (int hd = 0; hd < 4; hd++) {
      const int ta = 5 * (hd >> 1) + 3 * (hd & 1), ts = 5 * (hd >> 1) + 2;
      const bool mine = (hd & 1) ? !cA : cA;
      qe[hd][0] = mine ? Qlo[ts] : 0u; qe[hd][1] = mine ? Qhi[ts] : 0u;
      float sl[4], sh[4];
      mma_k24(sl, Qlo[ta], Qhi[ta], Qlo[ta + 1], Qhi[ta + 1], Klo[ta], Klo[ta + 1], qe[hd][0], qe[hd][1], Klo[ts]);
      mma_k24(sh, Qlo[ta], Qhi[ta], Qlo[ta + 1], Qhi[ta + 1], Khi[ta], Khi[ta + 1], qe[hd][0], qe[hd][1], Khi[ts]);
      th0[hd] = (in0 ? sh[2] : sl[2]) * sch0; th1[hd] = (in1 ? sh[3] : sl[3]) * sch1;
      float mh = fmaxf(th0[hd], th1[hd]);
      mh = fmaxf(mh, shx(mh, 1)); mh = fmaxf(mh, shx(mh, 2));
      th0[hd] -= mh; th1[hd] -= mh;
      sl0[hd] = sl[0]; sl1[hd] = sl[1];
    }
    mbar_wait(bar_kv + wg * 8, 0);
    TS(4);
#pragma unroll
    for (int j = 0; j < 5; j++) pv[j] = lds128(kvs + 512 * j);
    const uint32_t Kp[10] = {pv[0].x, pv[0].y, pv[2].x, pv[0].z, pv[0].w, pv[1].x, pv[1].y, pv[2].y, pv[1].z, pv[1].w};
    const uint32_t Vp[10] = {movm(pv[2].z), movm(pv[2].w), movm(pv[3].x), movm(pv[3].y), movm(pv[3].z), movm(pv[3].w), movm(pv[4].x), movm(pv[4].y), movm(pv[4].z), movm(pv[4].w)};
    const uint32_t ONES = 0x3f803f80u;
    uint32_t of[20];
#pragma unroll
    for (int hp = 0; hp < 2; hp++) {
      float o[6][4];
#pragma unroll
      for (int hh = 0; hh < 2; hh++) {
        const int hd = 2 * hp + hh, ta = 5 * hp + 3 * hh, ts = 5 * hp + 2;
        float sp[4];
        mma_k24(sp, Qlo[ta], Qhi[ta], Qlo[ta + 1], Qhi[ta + 1], Kp[ta], Kp[ta + 1], qe[hd][0], qe[hd][1], Kp[ts]);
        const float tl0 = fmaf(in0 ? sl0[hd] : sp[0], scl0, bias0), tl1 = fmaf(in1 ? sl1[hd] : sp[1], scl1, bias1);
        float ml = fmaxf(tl0, tl1);
        ml = fmaxf(ml, shx(ml, 1)); ml = fmaxf(ml, shx(ml, 2));
        if (HOLD == 1 && hd == 3 && !fol && lane == 0) mbar_arrive(bar_go + 8);
        const uint32_t Pl = pack_bf16(ex2(tl0 - ml), ex2(tl1 - ml)), Ph = pack_bf16(ex2(th0[hd]), ex2(th1[hd]));
        const uint32_t a0 = Pl & mL, a1 = Ph & ~mL, a3 = Ph & mL, ap = Pl & ~mL;
        const bool vm = hh == 0 ? nA : !nA;
        mma_k24(o[3 * hh], a0, a1, 0u, a3, Vlo[ta], Vhi[ta], ap, 0u, Vp[ta]);
        mma_k24(o[3 * hh + 1], a0, a1, 0u, a3, Vlo[ta + 1], Vhi[ta + 1], ap, 0u, Vp[ta + 1]);
        mma_k24(o[3 * hh + 2], a0, a1, 0u, a3, vm ? Vlo[ts] : ONES, vm ? Vhi[ts] : ONES, ap, 0u, vm ? Vp[ts] : ONES);
      }
      const float il = rcp(cA ? o[5][0] : o[2][0]), ih = rcp(cA ? o[5][2] : o[2][2]);
      const float jl = shx(il, 2), jh = shx(ih, 2);
      const float al = cA ? jl : il, ah = cA ? jh : ih, bl = cA ? il : jl, bh = cA ? ih : jh;
      const int t0 = 5 * hp;
      of[2 * t0]     = pack_bf16(o[0][0] * al, o[0][1] * al); of[2 * t0 + 1] = pack_bf16(o[0][2] * ah, o[0][3] * ah);
      of[2 * t0 + 2] = pack_bf16(o[1][0] * al, o[1][1] * al); of[2 * t0 + 3] = pack_bf16(o[1][2] * ah, o[1][3] * ah);
      of[2 * t0 + 4] = pack_bf16((cA ? o[2][0] : o[5][0]) * jl, (cA ? o[2][1] : o[5][1]) * jl);
      of[2 * t0 + 5] = pack_bf16((cA ? o[2][2] : o[5][2]) * jh, (cA ? o[2][3] : o[5][3]) * jh);
      of[2 * t0 + 6] = pack_bf16(o[3][0] * bl, o[3][1] * bl); of[2 * t0 + 7] = pack_bf16(o[3][2] * bh, o[3][3] * bh);
      of[2 * t0 + 8] = pack_bf16(o[4][0] * bl, o[4][1] * bl); of[2 * t0 + 9] = pack_bf16(o[4][2] * bh, o[4][3] * bh);
    }
    {
      const uint32_t os = sb + OFF_O + (fol ? 0 : 61440) + w4 * 2560, oa = os + ((lane >> 3) & 1) * 1280 + (lane >> 4) * 128 + (lane & 7) * 16;
#pragma unroll
      for (int s = 0; s < 5; s++) {
        stsm4(oa + s * 256, of[4 * s], of[4 * s + 1], of[4 * s + 2], of[4 * s + 3]);
        if (s == 0 && (fol || HOLD == 2) && lane == 0) mbar_arrive(bar_go + 8 + 8 * fol);
      }
      asm volatile("fence.proxy.async.shared::cta;" ::: "memory");
      __syncwarp();
      asm volatile("{\n.reg .pred q;\nelect.sync _|q, 0xffffffff;\n@q cp.async.bulk.global.shared::cta.bulk_group [%0], [%1], 2560;\ncp.async.bulk.commit_group;\n}\n" :: "l"(odst), "r"(os) : "memory");
    }
    TS(5);
    float h[40];
#pragma unroll
    for (int s = 0; s < 5; s++) {
      const uint4 v = xr[s];
      h[8 * s] = bf_lo(v.x); h[8 * s + 1] = bf_hi(v.x); h[8 * s + 2] = bf_lo(v.y); h[8 * s + 3] = bf_hi(v.y);
      h[8 * s + 4] = bf_lo(v.z); h[8 * s + 5] = bf_hi(v.z); h[8 * s + 6] = bf_lo(v.w); h[8 * s + 7] = bf_hi(v.w);
    }
    asm volatile("cp.async.bulk.wait_group 0;" ::: "memory");
    __syncwarp();
    if (lane == 0) {
      asm volatile("red.relaxed.gpu.global.add.u32 [%0], %1;" :: "l"(ocnt), "r"(1 << (4 * g)) : "memory");
      mbar_arrive(bar_st + 8 * fol);
    }
    TS(22);
    mbar_wait(bar_full, 0); mbar_wait(bar_full + 8, 0); mbar_wait(bar_full + 16, 1);
    mbar_wait(bar_go + 16, 0);
    const uint64_t dwo = make_desc(D0 * 16, 5120, 512, 2);
    wgmma_fence();
#pragma unroll
    for (int s = 0; s < 5; s++) wgmma_n80_rs(h, of[4 * s], of[4 * s + 1], of[4 * s + 2], of[4 * s + 3], dwo + g * 960 + s * 64, 1);
    wgmma_commit();
    TS(6);
    const bool odd = c & 1;
    uint4* const sp = hold(&g_own[slot].st2[r + (odd ? 8 : 0)]);
    uint4* const cdp = hold(&g_x.cand[slot][g][0]);
    uint4* const kcp = hold(g_own[1].cnt);
    float wr[20];
#pragma unroll
    for (int j = 0; j < 5; j++) {
      const uint4 v = lds128(sb + OFF_WR + c * 80 + j * 16);
      wr[4 * j] = __uint_as_float(v.x); wr[4 * j + 1] = __uint_as_float(v.y); wr[4 * j + 2] = __uint_as_float(v.z); wr[4 * j + 3] = __uint_as_float(v.w);
    }
    const float wsum = lds32f(sb + OFF_WR + 320);
    const uint32_t bo = bar_o + fol * 56;
    if (PRIO < 7 && fol) mbar_wait(bar_oc + 8 * PRIO, 0);
#pragma unroll
    for (int i = 0; i < 7; i++) {
      mbar_wait(bo + 8 * i, 0);
      if (i == 0) TS(1);
      const uint32_t da = D0 + OFF_O / 16 + (8 << 16) + ((i + 2) % 7) * 640, db = D0 + (320 << 16) + (i >= g ? i + 1 : i) * 960;
      wgmma_fence();
#pragma unroll
      for (int s = 0; s < 5; s++) wgmma_n80_ss(h, mk64(da + s * 16, 80u), mk64(db + s * 64, 0x80000020u), 1);
      wgmma_commit();
      wgmma_wait<1>();
      if (lane == 0 && i > 0) mbar_arrive(bo + 104 + 8 * i);
    }
    const int tok0 = P * 256 + 32 * warp + rank;
    wgmma_wait<0>();
#pragma unroll
    for (int i = 0; i < 40; i++) asm volatile("" : "+f"(h[i]) :: "memory");
    if (lane == 0) mbar_arrive(bo + 160);
    if (SPLITB) { asm volatile("{\n.reg .pred p;\nsetp.ne.u32 p, %0, 0;\n@p trap;\n}\n" :: "r"(zero) : "memory"); }
    TS(7);
    float mean, rstd, rr;
    bool pub;
    {
      float l1 = 0.f, l2 = 0.f, l3 = 0.f, h1 = 0.f, h2 = 0.f, h3 = 0.f;
#pragma unroll
      for (int j = 0; j < 10; j++) {
        l1 += h[4 * j] + h[4 * j + 1]; h1 += h[4 * j + 2] + h[4 * j + 3];
        l2 = fmaf(h[4 * j], h[4 * j], l2); l2 = fmaf(h[4 * j + 1], h[4 * j + 1], l2);
        h2 = fmaf(h[4 * j + 2], h[4 * j + 2], h2); h2 = fmaf(h[4 * j + 3], h[4 * j + 3], h2);
        l3 = fmaf(h[4 * j], wr[2 * j], l3); l3 = fmaf(h[4 * j + 1], wr[2 * j + 1], l3);
        h3 = fmaf(h[4 * j + 2], wr[2 * j], h3); h3 = fmaf(h[4 * j + 3], wr[2 * j + 1], h3);
      }
      float s1 = (odd ? h1 : l1) + shx(odd ? l1 : h1, 1), s2 = (odd ? h2 : l2) + shx(odd ? l2 : h2, 1), s3 = (odd ? h3 : l3) + shx(odd ? l3 : h3, 1);
      s1 += shx(s1, 2); s2 += shx(s2, 2); s3 += shx(s3, 2);
      uint4 p0;
      float o1 = 0.f, o2 = 0.f, o3 = 0.f, oc = 7.f;
      asm volatile("{\n.reg .pred q;\nsetp.lt.u32 q, %9, 2;\n@q atom.relaxed.gpu.global.add.v4.f32 {%0, %1, %2, %3}, [%4], {%5, %6, %7, %8};\n}\n"
                   : "+f"(o1), "+f"(o2), "+f"(o3), "+f"(oc) : "l"(sp), "f"(s1), "f"(s2), "f"(s3), "f"(1.f), "r"(c) : "memory");
      const uint32_t last = __ballot_sync(0xffffffffu, oc == 7.f);
      pub = last & 1;
      p0.x = __float_as_uint(__shfl_sync(0xffffffffu, o1 + s1, lane & 29)); p0.y = __float_as_uint(__shfl_sync(0xffffffffu, o2 + s2, lane & 29));
      p0.z = __float_as_uint(__shfl_sync(0xffffffffu, o3 + s3, lane & 29));
      if (last != 0xffffffffu)
      do { p0 = ldg_pkt(sp); } while (anyw(p0.w != 0x41000000u) && --guard > 0);
      mean = __uint_as_float(p0.x) * (1.f / 640.f);
      rstd = rsq(fmaxf(fmaf(-mean, mean, __uint_as_float(p0.y) * (1.f / 640.f)), 0.f) + 1e-5f);
      rr = fmaf(-mean, wsum, __uint_as_float(p0.z)) * rstd;
    }
    TS(8);
    const uint32_t kk = ord_key(rr), kmax = __reduce_max_sync(0xffffffffu, kk);
    const int L = __ffs(__ballot_sync(0xffffffffu, kk == kmax)) - 1;
    const int crow = (L >> 2) + 8 * (L & 1);
    asm volatile("{\n.reg .pred q;\nsetp.ne.u32 q, %2, 0;\n@q red.relaxed.gpu.global.max.u64 [%0], %1;\n@q red.relaxed.gpu.global.add.u32 [%0 + 8], 1;\n}\n"
                 :: "l"(kcp), "l"(mk64(2047 - tok0 - 2 * crow, kmax)), "r"((int)(pub && lane == 0)) : "memory");
    if (warp == g) asm volatile("bar.arrive 3, 64;" ::: "memory");
    const uint32_t stg = sb + (fol ? OFF_O : g * 15360) + w4 * 2560;
    uint4 held;
    {
      const float om = shx(mean, 1), os = shx(rstd, 1);
      const float rl = odd ? os : rstd, rh = odd ? rstd : os;
      const float bl = -(odd ? om : mean) * rl, bh = -(odd ? mean : om) * rh, al = 1.f + rl, ah = 1.f + rh;
      if ((L >> 2) == r) {
        const bool chi = L & 1;
        const float rc = chi ? rh : rl, bc = chi ? bh : bl;
        uint32_t n[10];
#pragma unroll
        for (int j = 0; j < 10; j++) n[j] = pack_bf16(fmaf(chi ? h[4 * j + 2] : h[4 * j], rc, bc), fmaf(chi ? h[4 * j + 3] : h[4 * j + 1], rc, bc));
        uint4* d = cdp + c;
        stg_pkt(d, n[0], n[1], n[2], n[3]); stg_pkt(d + 4, n[4], n[5], n[6], n[7]); stg_rlx64(d + 8, n[8], n[9]);
      }
      mbar_wait(bar_oc + 56, 0);
      const uint32_t fa = stg + (lane & 15) * 160 + (lane >> 4) * 16;
#pragma unroll
      for (int s = 0; s < 5; s++)
        stsm4(fa + s * 32, pack_bf16(fmaf(h[8 * s], al, bl), fmaf(h[8 * s + 1], al, bl)), pack_bf16(fmaf(h[8 * s + 2], ah, bh), fmaf(h[8 * s + 3], ah, bh)),
              pack_bf16(fmaf(h[8 * s + 4], al, bl), fmaf(h[8 * s + 5], al, bl)), pack_bf16(fmaf(h[8 * s + 6], ah, bh), fmaf(h[8 * s + 7], ah, bh)));
      __syncwarp();
      held = lds128(stg + crow * 160 + min(lane, 9) * 16);
      if (lane < 10) stg_pkt(cdp + 12 + lane, held.x, held.y, held.z, held.w);
    }
    TS(9);
    mbar_wait(bar_ffn, 0);
    const uint32_t red = sb + OFF_RED;
    if (ffn1) {
      uint4 w1[4][5];
      {
        const int k = (lane & 7) + (lane >> 4) * 8;
        const uint32_t a1 = sb + k * 64, sw = ((lane >> 3) & 1) ^ ((lane >> 1) & 3);
#pragma unroll
        for (int s = 0; s < 5; s++)
#pragma unroll
          for (int u = 0; u < 4; u++)
            w1[u][s] = ldsm4t(a1 + (s < 4 ? warp * 4096 + s * 1024 : 32768 + warp * 1024) + (u >> 1) * (40960 + (s == 4 || warp >= 4 ? OFF_W2 - 57344 : 0)) + ((sw ^ (2 * (u & 1))) * 16));
      }
      uint32_t* const ap = hold(g_x.act + fj * 16 + (lane >> 1));
      mbar_wait(bar_win, 0);
      const uint32_t hp = sb + OFF_HN + (warp * 4 + c) * 16;
      const uint4 c0 = lds128(hp), c1 = lds128(hp + 512), c2 = lds128(hp + 1024);
      TS(10);
      float a[4][4];
#pragma unroll
      for (int u = 0; u < 4; u++) {
        a[u][0] = a[u][1] = a[u][2] = a[u][3] = 0.f;
        mma_acc(a[u], w1[u][0], c0.x, c0.y); mma_acc(a[u], w1[u][1], c0.z, c0.w); mma_acc(a[u], w1[u][2], c1.x, c1.y);
        mma_acc(a[u], w1[u][3], c1.z, c1.w); mma_acc(a[u], w1[u][4], c2.x, c2.y);
      }
      asm volatile("st.shared.v2.f32 [%0], {%1, %2};" :: "r"(red + (warp * 32 + c * 8 + r) * 8),
                   "f"(cA ? (odd ? a[0][2] : a[0][0]) : (odd ? a[1][2] : a[1][0])), "f"(cA ? (odd ? a[2][2] : a[2][0]) : (odd ? a[3][2] : a[3][0])) : "memory");
      bar_sync(1, 256);
      if (warp == 0) {
        float2 t[8];
#pragma unroll
        for (int i = 0; i < 8; i++) t[i] = lds64f(red + (i * 32 + lane) * 8);
        const float s = ((t[0].x + t[1].x) + (t[2].x + t[3].x)) + ((t[4].x + t[5].x) + (t[6].x + t[7].x));
        const float u = ((t[0].y + t[1].y) + (t[2].y + t[3].y)) + ((t[4].y + t[5].y) + (t[6].y + t[7].y));
        const float av = s * u * rcp(1.f + ex2(-1.4426950408889634f * s));
        const float an = shx(av, 1);
        if (!odd) stg_rlx32(ap, pack_bf16(av, an));
      }
      bar_sync(1, 256);
      TS(11);
    }
    char* const ob2 = (char*)(out + tok0 * 640 + g * 64);
    const int remo = 896 - 96 * g;
    {
      char* const q0 = ob2 + (lane >> 3) * 2560 + (lane & 7) * 16;
      const uint32_t s0 = stg + (lane >> 3) * 160 + (lane & 7) * 16;
#pragma unroll
      for (int s = 0; s < 4; s++) stg128_if(4 * s + (lane >> 3) != crow, q0 + s * 10240, lds128(s0 + s * 640));
      stg128_if((lane >> 1) != crow, ob2 + (lane >> 1) * 2560 + (lane & 1) * 16 + 128 + remo, lds128(stg + (lane >> 1) * 160 + (lane & 1) * 16 + 128));
    }
    mbar_wait(bar_win, 0);
    uint4 win = lds128(sb + OFF_WR + 336);
    win.z = win.y; win.y = 2047u - (win.x & 2047u); win.x = (win.y >> 8) * 16 + (win.y & 1) * 8 + ((win.y >> 5) & 7);
    stg128_if(win.x != slot && lane < 10, ob2 + crow * 2560 + lane * 16 + (lane < 8 ? 0 : remo), held);
    if (!ffn1) {
      TS(10);
      uint4 w2[6];
      const uint32_t a2 = sb + OFF_W2 + (warp * 192 + 8 * (((lane >> 3) & 1) * 4 + ((lane & 7) >> 1)) + 2 * (lane >> 4) + (lane & 1)) * 16;
#pragma unroll
      for (int s = 0; s < 6; s++) w2[s] = ldsm4t(a2 + (s >> 1) * 1024 + (s & 1) * 64);
      const uint4* p = (const uint4*)(g_x.act + warp * 96) + (r & 1) * 4 + c;
      const uint32_t* pb = (const uint32_t*)&g_x.cand[win.x][fj < 64 ? fj >> 3 : (fj - 64) >> 1][fj < 64 ? 12 + (fj & 7) : 20 + (fj & 1)] + c;
      uint32_t* const op = hold((uint32_t*)(out + win.y * 640 + fj * 8) + c);
      const float sg = rcp(1.f + ex2(-1.4426950408889634f * __uint_as_float(win.z ^ ((uint32_t)((int32_t)~win.z >> 31) | 0x80000000u))));
      uint4 c0, c1, c2; uint32_t bw;
      if (ACT_NS) __nanosleep(ACT_NS);
      do {
        c0 = ldg_pkt(p); c1 = ldg_pkt(p + 8); c2 = ldg_pkt(p + 16); bw = ldg_rlx32(pb);
      } while (anyw(max(max(max(max(c0.x, c0.y), max(c0.z, c0.w)), max(max(c1.x, c1.y), max(c1.z, c1.w))), max(max(max(c2.x, c2.y), max(c2.z, c2.w)), bw)) == SENT) && --guard > 0);
      TS(11);
      float a[4] = {0.f, 0.f, 0.f, 0.f}, b[4] = {0.f, 0.f, 0.f, 0.f}, d[4] = {0.f, 0.f, 0.f, 0.f};
      mma_acc(a, w2[0], c0.x, c0.y); mma_acc(b, w2[2], c1.x, c1.y); mma_acc(d, w2[4], c2.x, c2.y);
      mma_acc(a, w2[1], c0.z, c0.w); mma_acc(b, w2[3], c1.z, c1.w); mma_acc(d, w2[5], c2.z, c2.w);
      if (c == 0) sts32f(red + (warp * 8 + r) * 4, ((a[0] + a[3]) + (b[0] + b[3])) + (d[0] + d[3]));
      bar_sync(1, 256);
      if (tid < 4) {
        float2 t[8];
#pragma unroll
        for (int i = 0; i < 8; i++) t[i] = lds64f(red + (i * 4 + tid) * 8);
        const float y0 = ((t[0].x + t[1].x) + (t[2].x + t[3].x)) + ((t[4].x + t[5].x) + (t[6].x + t[7].x));
        const float y1 = ((t[0].y + t[1].y) + (t[2].y + t[3].y)) + ((t[4].y + t[5].y) + (t[6].y + t[7].y));
        *op = pack_bf16(fmaf(y0, sg, bf_lo(bw)), fmaf(y1, sg, bf_hi(bw)));
      }
    }
    TS(12);
#undef TS_T
  }
}

typedef CUresult (*EncodeFn)(CUtensorMap*, CUtensorMapDataType, cuuint32_t, void*, const cuuint64_t*, const cuuint64_t*, const cuuint32_t*,
                             const cuuint32_t*, CUtensorMapInterleave, CUtensorMapSwizzle, CUtensorMapL2promotion, CUtensorMapFloatOOBfill);

void make_map(EncodeFn enc, CUtensorMap* m, const void* base, const cuuint64_t* dims, const cuuint64_t* strides, const cuuint32_t* box,
              CUtensorMapSwizzle swz) {
  const cuuint32_t es[3] = {1, 1, 1};
  enc(m, CU_TENSOR_MAP_DATA_TYPE_BFLOAT16, 3, (void*)base, dims, strides, box, es, CU_TENSOR_MAP_INTERLEAVE_NONE, swz,
      CU_TENSOR_MAP_L2_PROMOTION_L2_128B, CU_TENSOR_MAP_FLOAT_OOB_FILL_NONE);
}

}

extern "C" void kernel_launch(void* const* d_in, const int* in_sizes, int n_in, void* d_out, int out_size) {
  const __nv_bfloat16* x = (const __nv_bfloat16*)d_in[0];
  const __nv_bfloat16* wqkv = (const __nv_bfloat16*)d_in[1];
  const __nv_bfloat16* wo = (const __nv_bfloat16*)d_in[2];
  void* fn = nullptr;
  cudaDriverEntryPointQueryResult st;
  cudaGetDriverEntryPoint("cuTensorMapEncodeTiled", &fn, cudaEnableDefault, &st);
  EncodeFn enc = (EncodeFn)fn;
  void* scp = nullptr;
  cudaGetSymbolAddress(&scp, g_scratch);
  Maps tm;
  { const cuuint64_t d[3] = {640, 1024, 2}, s[2] = {2560, 1280}; const cuuint32_t b[3] = {64, 128, 1}; make_map(enc, &tm.x, x, d, s, b, CU_TENSOR_MAP_SWIZZLE_128B); }
  { const cuuint64_t d[3] = {640, 640, 3}, s[2] = {3840, 1280}; const cuuint32_t b[3] = {64, 16, 3}; make_map(enc, &tm.w, wqkv, d, s, b, CU_TENSOR_MAP_SWIZZLE_128B); }
  { const cuuint64_t d[3] = {640, 640, 3}, s[2] = {3840, 1280}; const cuuint32_t b[3] = {16, 16, 3}; make_map(enc, &tm.wr, wqkv, d, s, b, CU_TENSOR_MAP_SWIZZLE_32B); }
  { const cuuint64_t d[3] = {640, 640, 3}, s[2] = {3840, 1280}; const cuuint32_t b[3] = {16, 16, 1}; make_map(enc, &tm.wv, wqkv, d, s, b, CU_TENSOR_MAP_SWIZZLE_32B); }
  { const cuuint64_t d[3] = {32, 640, 20}, s[2] = {1280, 64}; const cuuint32_t b[3] = {32, 80, 2}; make_map(enc, &tm.wo, wo, d, s, b, CU_TENSOR_MAP_SWIZZLE_64B); }
  { const cuuint64_t d[3] = {640, 640, 1}, s[2] = {1280, 819200}; const cuuint32_t b[3] = {16, 80, 1}; make_map(enc, &tm.wor, wo, d, s, b, CU_TENSOR_MAP_SWIZZLE_64B); }
  { const cuuint64_t d[3] = {1536, 640, 1}, s[2] = {3072, 1966080}; const cuuint32_t b[3] = {32, 128, 1};
    make_map(enc, &tm.gate, d_in[5], d, s, b, CU_TENSOR_MAP_SWIZZLE_64B); make_map(enc, &tm.up, d_in[6], d, s, b, CU_TENSOR_MAP_SWIZZLE_64B); }
  { const cuuint64_t d[3] = {640, 1536, 1}, s[2] = {1280, 1966080}; const cuuint32_t b[3] = {8, 128, 1}; make_map(enc, &tm.down, d_in[7], d, s, b, CU_TENSOR_MAP_SWIZZLE_NONE); }
  cudaFuncSetAttribute(fused_kernel, cudaFuncAttributeMaxDynamicSharedMemorySize, SMEM_BYTES);
  fused_kernel<<<128, 512, SMEM_BYTES, cudaStreamPerThread>>>(x, wqkv, wo, (const __nv_bfloat16*)d_in[4], (const __nv_bfloat16*)d_in[5],
                                                              (const __nv_bfloat16*)d_in[6], (const __nv_bfloat16*)d_in[7], (__nv_bfloat16*)d_out, (Scratch*)scp, tm);
}
```

```cpp
#include <cuda_runtime.h>
#include <cuda_bf16.h>
#include <cuda.h>
#include <stdint.h>

#define PFW_NS 50
#define PFW_N 14
#define ACT_NS 100
#define KEY_NS 0
#define AUX_NS 50
#define REG_P 72
#define REG_C 184
#define LEAD 1
#define HK_IT 1
#define F_PER 2
#define F_MAX 8
#define HOLD 2
#define AK 3
#define NSPLIT 3
#define THR_END 4
#define BOUNDED 0
#define TLIGHT 0
#define ATOM2 1
#define LAG 5
#define OV 2
#define O_UNROLL 1
#define PRIO 7
#define SPLITB 1

namespace {

constexpr int SLOT    = 49152;
constexpr int OFF_O   = 122880;
constexpr int OFF_W2  = 4 * SLOT;
constexpr int OFF_CS  = OFF_W2 + 24576;
constexpr int OFF_RS  = OFF_CS + 3840;
constexpr int OFF_MN  = OFF_RS + 576;
constexpr int OFF_WR  = OFF_MN + 1024;
constexpr int OFF_RED = OFF_CS;
constexpr int OFF_HN  = OFF_CS + 2048;
constexpr int OFF_PT  = OFF_WR + 352;
constexpr int OFF_BAR = OFF_PT + 768;
constexpr int SMEM_BYTES = OFF_BAR + 424 + 384;
constexpr uint32_t D0 = 1024 >> 4;
constexpr int OUNR = O_UNROLL;
constexpr uint32_t SENT = 0xFFFFFFFFu;
constexpr int SPIN_MAX = 1 << 20;

struct Glob {
  uint4 cand[128][8][24];
  uint32_t act[768];
  uint32_t pad[256];
};
constexpr int GLOB_PER_CTA = sizeof(Glob) / 16 / 128;
static_assert(GLOB_PER_CTA * 128 * 16 == sizeof(Glob), "glob size");
struct Own {
  uint4 halo[5][32];
  uint4 st1[32];
  uint2 cs[32];
  uint4 st2[16];
  uint4 cnt[8];
};
struct Scratch {
  Glob x;
  Own own[128];
  uint4 o[32][8][640];
  uint32_t epoch[128];
};
__device__ __align__(128) Scratch g_scratch;
#define g_x (sc->x)
#define g_own (sc->own)
#define g_o (sc->o)
#define g_epoch (sc->epoch)
#define TS(i)

__device__ __forceinline__ void mbar_init(uint32_t bar, uint32_t cnt) { asm volatile("mbarrier.init.shared::cta.b64 [%0], %1;" :: "r"(bar), "r"(cnt) : "memory"); }
__device__ __forceinline__ void mbar_expect_tx(uint32_t bar, uint32_t bytes) { asm volatile("mbarrier.arrive.expect_tx.shared::cta.b64 _, [%0], %1;" :: "r"(bar), "r"(bytes) : "memory"); }
__device__ __forceinline__ void mbar_arrive(uint32_t bar) { asm volatile("mbarrier.arrive.shared::cta.b64 _, [%0];" :: "r"(bar) : "memory"); }
__device__ __forceinline__ void mbar_arrive_cta(uint32_t bar, uint32_t cta) {
  asm volatile("{\n.reg .b32 ra;\nmapa.shared::cluster.u32 ra, %0, %1;\nmbarrier.arrive.shared::cluster.b64 _, [ra];\n}\n" :: "r"(bar), "r"(cta) : "memory");
}
__device__ __forceinline__ void mbar_wait(uint32_t bar, uint32_t parity) {
  asm volatile("{\n.reg .pred p;\nW:\nmbarrier.try_wait.parity.shared::cta.b64 p, [%0], %1;\n@!p bra.uni W;\n}\n" :: "r"(bar), "r"(parity) : "memory");
}
__device__ __forceinline__ void tma_3d(uint32_t dst, const void* tm, uint32_t bar, int c0, int c1, int c2) {
  asm volatile("cp.async.bulk.tensor.3d.shared::cluster.global.mbarrier::complete_tx::bytes [%0], [%1, {%3, %4, %5}], [%2];" :: "r"(dst), "l"(tm), "r"(bar), "r"(c0), "r"(c1), "r"(c2) : "memory");
}
__device__ __forceinline__ void tma_3d_mc(uint32_t dst, const void* tm, uint32_t bar, int c0, int c1, int c2) {
  asm volatile("cp.async.bulk.tensor.3d.shared::cluster.global.mbarrier::complete_tx::bytes.multicast::cluster [%0], [%1, {%3, %4, %5}], [%2], %6;" :: "r"(dst), "l"(tm), "r"(bar), "r"(c0), "r"(c1), "r"(c2), "h"((uint16_t)3) : "memory");
}
__device__ __forceinline__ void wgmma_fence() { asm volatile("wgmma.fence.sync.aligned;" ::: "memory"); }
__device__ __forceinline__ void wgmma_commit() { asm volatile("wgmma.commit_group.sync.aligned;" ::: "memory"); }
template <int N> __device__ __forceinline__ void wgmma_wait() { asm volatile("wgmma.wait_group.sync.aligned %0;" :: "n"(N) : "memory"); }
__device__ __forceinline__ uint64_t make_desc(uint32_t addr, uint32_t lbo, uint32_t sbo, uint32_t swz) {
  return (uint64_t)(((addr & 0x3FFFF) >> 4) | ((lbo >> 4) << 16)) | ((uint64_t)((sbo >> 4) | (swz << 30)) << 32);
}
__device__ __forceinline__ void bar_sync(int id, int n) { asm volatile("bar.sync %0, %1;" :: "r"(id), "r"(n) : "memory"); }
__device__ __forceinline__ void st_pkt(void* p, uint32_t a, uint32_t b, uint32_t c, uint32_t d) {
  asm volatile("st.relaxed.gpu.v4.u32 [%0], {%1, %2, %3, %4};" :: "l"(p), "r"(a), "r"(b), "r"(c), "r"(d) : "memory");
}
__device__ __forceinline__ uint4 ldg_pkt(const void* p) {
  uint4 v; asm volatile("ld.relaxed.gpu.global.v4.u32 {%0, %1, %2, %3}, [%4];" : "=r"(v.x), "=r"(v.y), "=r"(v.z), "=r"(v.w) : "l"(p) : "memory"); return v;
}
__device__ __forceinline__ void stg_pkt(void* p, uint32_t a, uint32_t b, uint32_t c, uint32_t d) {
  asm volatile("st.relaxed.gpu.global.v4.u32 [%0], {%1, %2, %3, %4};" :: "l"(p), "r"(a), "r"(b), "r"(c), "r"(d) : "memory");
}
__device__ __forceinline__ uint32_t ldg_rlx32(const void* p) { uint32_t v; asm volatile("ld.relaxed.gpu.global.u32 %0, [%1];" : "=r"(v) : "l"(p) : "memory"); return v; }
__device__ __forceinline__ uint2 ldg_rlx64(const void* p) { uint2 v; asm volatile("ld.relaxed.gpu.global.v2.u32 {%0, %1}, [%2];" : "=r"(v.x), "=r"(v.y) : "l"(p) : "memory"); return v; }
__device__ __forceinline__ uint32_t pin(uint32_t v) { asm volatile("" : "+r"(v)); return v; }
__device__ __forceinline__ uint64_t mk64(uint32_t lo, uint32_t hi) { return ((uint64_t)hi << 32) | lo; }
template <class T> __device__ __forceinline__ T* hold(T* p) { return (T*)__shfl_sync(0xffffffffu, (unsigned long long)p, threadIdx.x & 31); }
__device__ __forceinline__ void stg128_if(bool q, void* p, const uint4& v) {
  asm volatile("{\n.reg .pred q;\nsetp.ne.u32 q, %5, 0;\n@q st.global.v4.u32 [%0], {%1, %2, %3, %4};\n}\n" :: "l"(p), "r"(v.x), "r"(v.y), "r"(v.z), "r"(v.w), "r"((int)q) : "memory");
}
template <class T> __device__ __forceinline__ T* pin(T* p) { asm volatile("" : "+l"(p)); return p; }
__device__ __forceinline__ void stg_rlx32(void* p, uint32_t v) { asm volatile("st.relaxed.gpu.global.u32 [%0], %1;" :: "l"(p), "r"(v) : "memory"); }
__device__ __forceinline__ void stg_rlx64(void* p, uint32_t a, uint32_t b) { asm volatile("st.relaxed.gpu.global.v2.u32 [%0], {%1, %2};" :: "l"(p), "r"(a), "r"(b) : "memory"); }
__device__ __forceinline__ uint4 ldsm4(uint32_t a) { uint4 v; asm volatile("ldmatrix.sync.aligned.m8n8.x4.shared.b16 {%0, %1, %2, %3}, [%4];" : "=r"(v.x), "=r"(v.y), "=r"(v.z), "=r"(v.w) : "r"(a) : "memory"); return v; }
__device__ __forceinline__ void ldsm4_if(uint4& v, uint32_t a, int off, bool p) {
  asm volatile("{\n.reg .pred q;\nsetp.ne.u32 q, %5, 0;\n@q ldmatrix.sync.aligned.m8n8.x4.shared.b16 {%0, %1, %2, %3}, [%4];\n}\n"
               : "+r"(v.x), "+r"(v.y), "+r"(v.z), "+r"(v.w) : "r"(a + off), "r"((int)p) : "memory");
}
__device__ __forceinline__ uint4 ldsm4t(uint32_t a) { uint4 v; asm volatile("ldmatrix.sync.aligned.m8n8.x4.trans.shared.b16 {%0, %1, %2, %3}, [%4];" : "=r"(v.x), "=r"(v.y), "=r"(v.z), "=r"(v.w) : "r"(a) : "memory"); return v; }
__device__ __forceinline__ void stsm4(uint32_t a, uint32_t x, uint32_t y, uint32_t z, uint32_t w) { asm volatile("stmatrix.sync.aligned.m8n8.x4.shared.b16 [%0], {%1, %2, %3, %4};" :: "r"(a), "r"(x), "r"(y), "r"(z), "r"(w) : "memory"); }
__device__ __forceinline__ void mma_acc(float (&c)[4], const uint4& a, uint32_t b0, uint32_t b1) {
  asm("mma.sync.aligned.m16n8k16.row.col.f32.bf16.bf16.f32 {%0,%1,%2,%3}, {%4,%5,%6,%7}, {%8,%9}, {%0,%1,%2,%3};"
      : "+f"(c[0]), "+f"(c[1]), "+f"(c[2]), "+f"(c[3]) : "r"(a.x), "r"(a.y), "r"(a.z), "r"(a.w), "r"(b0), "r"(b1));
}
__device__ __forceinline__ uint4 lds128(uint32_t a) { uint4 v; asm volatile("ld.shared.v4.u32 {%0, %1, %2, %3}, [%4];" : "=r"(v.x), "=r"(v.y), "=r"(v.z), "=r"(v.w) : "r"(a) : "memory"); return v; }
__device__ __forceinline__ float2 lds64f(uint32_t a) { float2 v; asm volatile("ld.shared.v2.f32 {%0, %1}, [%2];" : "=f"(v.x), "=f"(v.y) : "r"(a)); return v; }
__device__ __forceinline__ float lds32f(uint32_t a) { float v; asm volatile("ld.shared.f32 %0, [%1];" : "=f"(v) : "r"(a)); return v; }
__device__ __forceinline__ void sts32f(uint32_t a, float v) { asm volatile("st.shared.f32 [%0], %1;" :: "r"(a), "f"(v) : "memory"); }
__device__ __forceinline__ uint32_t pack_bf16(float lo, float hi) { uint32_t r; asm("cvt.rn.bf16x2.f32 %0, %1, %2;" : "=r"(r) : "f"(hi), "f"(lo)); return r; }
__device__ __forceinline__ float bf_lo(uint32_t v) { return __uint_as_float(v << 16); }
__device__ __forceinline__ float bf_hi(uint32_t v) { return __uint_as_float(v & 0xffff0000u); }
__device__ __forceinline__ uint32_t movm(uint32_t a) { uint32_t d; asm("movmatrix.sync.aligned.m8n8.trans.b16 %0, %1;" : "=r"(d) : "r"(a)); return d; }
__device__ __forceinline__ float ex2(float x) { float y; asm("ex2.approx.ftz.f32 %0, %1;" : "=f"(y) : "f"(x)); return y; }
__device__ __forceinline__ float rsq(float x) { float y; asm("rsqrt.approx.ftz.f32 %0, %1;" : "=f"(y) : "f"(x)); return y; }
__device__ __forceinline__ float rcp(float x) { float y; asm("rcp.approx.ftz.f32 %0, %1;" : "=f"(y) : "f"(x)); return y; }
__device__ __forceinline__ bool elect() { uint32_t p; asm volatile("{\n.reg .pred q;\nelect.sync _|q, 0xffffffff;\nselp.u32 %0, 1, 0, q;\n}\n" : "=r"(p)); return p; }
__device__ __forceinline__ void pf_l2(const void* p) { asm volatile("prefetch.global.L2 [%0];" :: "l"(p)); }
__device__ __forceinline__ bool anyw(bool p) { return __any_sync(0xffffffffu, p); }
__device__ __forceinline__ float shx(float v, int m) { return __shfl_xor_sync(0xffffffffu, v, m); }
__device__ __forceinline__ void mma_k24(float (&c)[4], uint32_t a0, uint32_t a1, uint32_t a2, uint32_t a3, uint32_t b0, uint32_t b1,
                                        uint32_t e0, uint32_t e1, uint32_t f0) {
  asm("mma.sync.aligned.m16n8k16.row.col.f32.bf16.bf16.f32 {%0,%1,%2,%3}, {%4,%5,%6,%7}, {%8,%9}, {%10,%10,%10,%10};"
      : "=f"(c[0]), "=f"(c[1]), "=f"(c[2]), "=f"(c[3]) : "r"(a0), "r"(a1), "r"(a2), "r"(a3), "r"(b0), "r"(b1), "f"(0.f));
  asm("mma.sync.aligned.m16n8k8.row.col.f32.bf16.bf16.f32 {%0,%1,%2,%3}, {%4,%5}, {%6}, {%0,%1,%2,%3};"
      : "+f"(c[0]), "+f"(c[1]), "+f"(c[2]), "+f"(c[3]) : "r"(e0), "r"(e1), "r"(f0));
}
__device__ __forceinline__ uint32_t ord_key(float r) { uint32_t u = __float_as_uint(r); return u ^ ((uint32_t)((int32_t)u >> 31) | 0x80000000u); }

__device__ __forceinline__ void wgmma_n64hi_ss(float (&d)[120], uint64_t da, uint64_t db, int scale_d) {
  asm volatile("{\n.reg .pred p;\nsetp.ne.b32 p, %34, 0;\n"
    "wgmma.mma_async.sync.aligned.m64n64k16.f32.bf16.bf16 "
    "{%0, %1, %2, %3, %4, %5, %6, %7, %8, %9, %10, %11, %12, %13, %14, %15, "
    "%16, %17, %18, %19, %20, %21, %22, %23, %24, %25, %26, %27, %28, %29, %30, %31}, "
    "%32, %33, p, 1, 1, 0, 1;\n}\n"
    : "+f"(d[88]), "+f"(d[89]), "+f"(d[90]), "+f"(d[91]), "+f"(d[92]), "+f"(d[93]), "+f"(d[94]), "+f"(d[95]),
      "+f"(d[96]), "+f"(d[97]), "+f"(d[98]), "+f"(d[99]), "+f"(d[100]), "+f"(d[101]), "+f"(d[102]), "+f"(d[103]),
      "+f"(d[104]), "+f"(d[105]), "+f"(d[106]), "+f"(d[107]), "+f"(d[108]), "+f"(d[109]), "+f"(d[110]), "+f"(d[111]),
      "+f"(d[112]), "+f"(d[113]), "+f"(d[114]), "+f"(d[115]), "+f"(d[116]), "+f"(d[117]), "+f"(d[118]), "+f"(d[119])
    : "l"(da), "l"(db), "r"(scale_d));
}
__device__ __forceinline__ void wgmma_n176lo_ss(float (&d)[120], uint64_t da, uint64_t db, int scale_d) {
  asm volatile("{\n.reg .pred p;\nsetp.ne.b32 p, %90, 0;\n"
    "wgmma.mma_async.sync.aligned.m64n176k16.f32.bf16.bf16 "
    "{%0, %1, %2, %3, %4, %5, %6, %7, %8, %9, %10, %11, %12, %13, %14, %15, "
    "%16, %17, %18, %19, %20, %21, %22, %23, %24, %25, %26, %27, %28, %29, %30, %31, "
    "%32, %33, %34, %35, %36, %37, %38, %39, %40, %41, %42, %43, %44, %45, %46, %47, "
    "%48, %49, %50, %51, %52, %53, %54, %55, %56, %57, %58, %59, %60, %61, %62, %63, "
    "%64, %65, %66, %67, %68, %69, %70, %71, %72, %73, %74, %75, %76, %77, %78, %79, "
    "%80, %81, %82, %83, %84, %85, %86, %87}, "
    "%88, %89, p, 1, 1, 0, 1;\n}\n"
    : "+f"(d[0]), "+f"(d[1]), "+f"(d[2]), "+f"(d[3]), "+f"(d[4]), "+f"(d[5]), "+f"(d[6]), "+f"(d[7]),
      "+f"(d[8]), "+f"(d[9]), "+f"(d[10]), "+f"(d[11]), "+f"(d[12]), "+f"(d[13]), "+f"(d[14]), "+f"(d[15]),
      "+f"(d[16]), "+f"(d[17]), "+f"(d[18]), "+f"(d[19]), "+f"(d[20]), "+f"(d[21]), "+f"(d[22]), "+f"(d[23]),
      "+f"(d[24]), "+f"(d[25]), "+f"(d[26]), "+f"(d[27]), "+f"(d[28]), "+f"(d[29]), "+f"(d[30]), "+f"(d[31]),
      "+f"(d[32]), "+f"(d[33]), "+f"(d[34]), "+f"(d[35]), "+f"(d[36]), "+f"(d[37]), "+f"(d[38]), "+f"(d[39]),
      "+f"(d[40]), "+f"(d[41]), "+f"(d[42]), "+f"(d[43]), "+f"(d[44]), "+f"(d[45]), "+f"(d[46]), "+f"(d[47]),
      "+f"(d[48]), "+f"(d[49]), "+f"(d[50]), "+f"(d[51]), "+f"(d[52]), "+f"(d[53]), "+f"(d[54]), "+f"(d[55]),
      "+f"(d[56]), "+f"(d[57]), "+f"(d[58]), "+f"(d[59]), "+f"(d[60]), "+f"(d[61]), "+f"(d[62]), "+f"(d[63]),
      "+f"(d[64]), "+f"(d[65]), "+f"(d[66]), "+f"(d[67]), "+f"(d[68]), "+f"(d[69]), "+f"(d[70]), "+f"(d[71]),
      "+f"(d[72]), "+f"(d[73]), "+f"(d[74]), "+f"(d[75]), "+f"(d[76]), "+f"(d[77]), "+f"(d[78]), "+f"(d[79]),
      "+f"(d[80]), "+f"(d[81]), "+f"(d[82]), "+f"(d[83]), "+f"(d[84]), "+f"(d[85]), "+f"(d[86]), "+f"(d[87])
    : "l"(da), "l"(db), "r"(scale_d));
}
__device__ __forceinline__ void wgmma_n64hi_rk(float (&d)[120], uint32_t a0, uint32_t a1, uint32_t a2, uint32_t a3, uint64_t db, int scale_d) {
  asm volatile("{\n.reg .pred p;\nsetp.ne.b32 p, %37, 0;\n"
    "wgmma.mma_async.sync.aligned.m64n64k16.f32.bf16.bf16 "
    "{%0, %1, %2, %3, %4, %5, %6, %7, %8, %9, %10, %11, %12, %13, %14, %15, "
    "%16, %17, %18, %19, %20, %21, %22, %23, %24, %25, %26, %27, %28, %29, %30, %31}, "
    "{%32, %33, %34, %35}, %36, p, 1, 1, 0;\n}\n"
    : "+f"(d[88]), "+f"(d[89]), "+f"(d[90]), "+f"(d[91]), "+f"(d[92]), "+f"(d[93]), "+f"(d[94]), "+f"(d[95]),
      "+f"(d[96]), "+f"(d[97]), "+f"(d[98]), "+f"(d[99]), "+f"(d[100]), "+f"(d[101]), "+f"(d[102]), "+f"(d[103]),
      "+f"(d[104]), "+f"(d[105]), "+f"(d[106]), "+f"(d[107]), "+f"(d[108]), "+f"(d[109]), "+f"(d[110]), "+f"(d[111]),
      "+f"(d[112]), "+f"(d[113]), "+f"(d[114]), "+f"(d[115]), "+f"(d[116]), "+f"(d[117]), "+f"(d[118]), "+f"(d[119])
    : "r"(a0), "r"(a1), "r"(a2), "r"(a3), "l"(db), "r"(scale_d));
}
__device__ __forceinline__ void wgmma_n176lo_rk(float (&d)[120], uint32_t a0, uint32_t a1, uint32_t a2, uint32_t a3, uint64_t db, int scale_d) {
  asm volatile("{\n.reg .pred p;\nsetp.ne.b32 p, %93, 0;\n"
    "wgmma.mma_async.sync.aligned.m64n176k16.f32.bf16.bf16 "
    "{%0, %1, %2, %3, %4, %5, %6, %7, %8, %9, %10, %11, %12, %13, %14, %15, "
    "%16, %17, %18, %19, %20, %21, %22, %23, %24, %25, %26, %27, %28, %29, %30, %31, "
    "%32, %33, %34, %35, %36, %37, %38, %39, %40, %41, %42, %43, %44, %45, %46, %47, "
    "%48, %49, %50, %51, %52, %53, %54, %55, %56, %57, %58, %59, %60, %61, %62, %63, "
    "%64, %65, %66, %67, %68, %69, %70, %71, %72, %73, %74, %75, %76, %77, %78, %79, "
    "%80, %81, %82, %83, %84, %85, %86, %87}, "
    "{%88, %89, %90, %91}, %92, p, 1, 1, 0;\n}\n"
    : "+f"(d[0]), "+f"(d[1]), "+f"(d[2]), "+f"(d[3]), "+f"(d[4]), "+f"(d[5]), "+f"(d[6]), "+f"(d[7]),
      "+f"(d[8]), "+f"(d[9]), "+f"(d[10]), "+f"(d[11]), "+f"(d[12]), "+f"(d[13]), "+f"(d[14]), "+f"(d[15]),
      "+f"(d[16]), "+f"(d[17]), "+f"(d[18]), "+f"(d[19]), "+f"(d[20]), "+f"(d[21]), "+f"(d[22]), "+f"(d[23]),
      "+f"(d[24]), "+f"(d[25]), "+f"(d[26]), "+f"(d[27]), "+f"(d[28]), "+f"(d[29]), "+f"(d[30]), "+f"(d[31]),
      "+f"(d[32]), "+f"(d[33]), "+f"(d[34]), "+f"(d[35]), "+f"(d[36]), "+f"(d[37]), "+f"(d[38]), "+f"(d[39]),
      "+f"(d[40]), "+f"(d[41]), "+f"(d[42]), "+f"(d[43]), "+f"(d[44]), "+f"(d[45]), "+f"(d[46]), "+f"(d[47]),
      "+f"(d[48]), "+f"(d[49]), "+f"(d[50]), "+f"(d[51]), "+f"(d[52]), "+f"(d[53]), "+f"(d[54]), "+f"(d[55]),
      "+f"(d[56]), "+f"(d[57]), "+f"(d[58]), "+f"(d[59]), "+f"(d[60]), "+f"(d[61]), "+f"(d[62]), "+f"(d[63]),
      "+f"(d[64]), "+f"(d[65]), "+f"(d[66]), "+f"(d[67]), "+f"(d[68]), "+f"(d[69]), "+f"(d[70]), "+f"(d[71]),
      "+f"(d[72]), "+f"(d[73]), "+f"(d[74]), "+f"(d[75]), "+f"(d[76]), "+f"(d[77]), "+f"(d[78]), "+f"(d[79]),
      "+f"(d[80]), "+f"(d[81]), "+f"(d[82]), "+f"(d[83]), "+f"(d[84]), "+f"(d[85]), "+f"(d[86]), "+f"(d[87])
    : "r"(a0), "r"(a1), "r"(a2), "r"(a3), "l"(db), "r"(scale_d));
}
__device__ __forceinline__ void wgmma_n80_rs(float (&d)[40], uint32_t a0, uint32_t a1, uint32_t a2, uint32_t a3, uint64_t db, int scale_d) {
  asm volatile("{\n.reg .pred p;\nsetp.ne.b32 p, %45, 0;\n"
    "wgmma.mma_async.sync.aligned.m64n80k16.f32.bf16.bf16 "
    "{%0, %1, %2, %3, %4, %5, %6, %7, %8, %9, %10, %11, %12, %13, %14, %15, "
    "%16, %17, %18, %19, %20, %21, %22, %23, %24, %25, %26, %27, %28, %29, %30, %31, "
    "%32, %33, %34, %35, %36, %37, %38, %39}, "
    "{%40, %41, %42, %43}, %44, p, 1, 1, 1;\n}\n"
    : "+f"(d[0]), "+f"(d[1]), "+f"(d[2]), "+f"(d[3]), "+f"(d[4]), "+f"(d[5]), "+f"(d[6]), "+f"(d[7]),
      "+f"(d[8]), "+f"(d[9]), "+f"(d[10]), "+f"(d[11]), "+f"(d[12]), "+f"(d[13]), "+f"(d[14]), "+f"(d[15]),
      "+f"(d[16]), "+f"(d[17]), "+f"(d[18]), "+f"(d[19]), "+f"(d[20]), "+f"(d[21]), "+f"(d[22]), "+f"(d[23]),
      "+f"(d[24]), "+f"(d[25]), "+f"(d[26]), "+f"(d[27]), "+f"(d[28]), "+f"(d[29]), "+f"(d[30]), "+f"(d[31]),
      "+f"(d[32]), "+f"(d[33]), "+f"(d[34]), "+f"(d[35]), "+f"(d[36]), "+f"(d[37]), "+f"(d[38]), "+f"(d[39])
    : "r"(a0), "r"(a1), "r"(a2), "r"(a3), "l"(db), "r"(scale_d));
}
__device__ __forceinline__ void wgmma_n80_ss(float (&d)[40], uint64_t da, uint64_t db, int scale_d) {
  asm volatile("{\n.reg .pred p;\nsetp.ne.b32 p, %42, 0;\n"
    "wgmma.mma_async.sync.aligned.m64n80k16.f32.bf16.bf16 "
    "{%0, %1, %2, %3, %4, %5, %6, %7, %8, %9, %10, %11, %12, %13, %14, %15, "
    "%16, %17, %18, %19, %20, %21, %22, %23, %24, %25, %26, %27, %28, %29, %30, %31, "
    "%32, %33, %34, %35, %36, %37, %38, %39}, "
    "%40, %41, p, 1, 1, 0, 1;\n}\n"
    : "+f"(d[0]), "+f"(d[1]), "+f"(d[2]), "+f"(d[3]), "+f"(d[4]), "+f"(d[5]), "+f"(d[6]), "+f"(d[7]),
      "+f"(d[8]), "+f"(d[9]), "+f"(d[10]), "+f"(d[11]), "+f"(d[12]), "+f"(d[13]), "+f"(d[14]), "+f"(d[15]),
      "+f"(d[16]), "+f"(d[17]), "+f"(d[18]), "+f"(d[19]), "+f"(d[20]), "+f"(d[21]), "+f"(d[22]), "+f"(d[23]),
      "+f"(d[24]), "+f"(d[25]), "+f"(d[26]), "+f"(d[27]), "+f"(d[28]), "+f"(d[29]), "+f"(d[30]), "+f"(d[31]),
      "+f"(d[32]), "+f"(d[33]), "+f"(d[34]), "+f"(d[35]), "+f"(d[36]), "+f"(d[37]), "+f"(d[38]), "+f"(d[39])
    : "l"(da), "l"(db), "r"(scale_d));
}

__device__ __forceinline__ constexpr int QT(int t) { return t < 8 ? t : 16 + t; }
__device__ __forceinline__ constexpr int KT(int t) { return t < 8 ? 8 + t : 18 + t; }
__device__ __forceinline__ constexpr int VT(int t) { return t < 8 ? 16 + t : 20 + t; }

struct Maps { CUtensorMap x, w, wr, wv, wo, wor, gate, up, down; };

__global__ void __cluster_dims__(2, 1, 1) __launch_bounds__(512, 1)
fused_kernel(const __nv_bfloat16* __restrict__ x, const __nv_bfloat16* __restrict__ wqkv,
             const __nv_bfloat16* __restrict__ wo, const __nv_bfloat16* __restrict__ w_r, const __nv_bfloat16* __restrict__ w_gate,
             const __nv_bfloat16* __restrict__ w_up, const __nv_bfloat16* __restrict__ w_down, __nv_bfloat16* __restrict__ out,
             Scratch* __restrict__ sc, const __grid_constant__ Maps tm) {
  extern __shared__ __align__(1024) uint8_t smem[];
  const int tid = threadIdx.x, bid = blockIdx.x;
  if ((unsigned)(tid - 128) < 16u) pf_l2((const char*)x + (bid * 16 + tid - 128) * 1280);
  if ((unsigned)(tid - 160) < 15u) pf_l2((const char*)wqkv + (bid * 15 + tid - 160) * 128);
  const int warp = __shfl_sync(0xffffffffu, tid >> 5, 0), lane = tid & 31;
  const uint32_t sb = (uint32_t)__cvta_generic_to_shared(smem);
  const uint32_t bar_full = sb + OFF_BAR, bar_empty = bar_full + 32, bar_aux = bar_full + 64, bar_ffn = bar_full + 72, bar_win = bar_full + 80, bar_tag = bar_full + 88, bar_rst = bar_full + 96 + 296 + 24,
                 bar_o = bar_full + 96, bar_oc = bar_o + 112, bar_st = bar_o + 224, bar_go = bar_o + 248, bar_kv = bar_o + 272, bar_half = bar_o + 296;
  if (warp < 4 && elect()) {
    mbar_init(bar_half + 8 * warp, 1);
    mbar_init(bar_full + 8 * (warp ^ 2), 1);
    mbar_init(bar_empty + 8 * warp, 24);
    mbar_init(bar_aux + 8 * warp, warp == 0 ? 64 : warp == 2 ? 32 : warp == 3 ? 2 : 1);
    asm volatile("fence.mbarrier_init.release.cluster;" ::: "memory");
  }
  asm volatile("barrier.cluster.arrive.relaxed.aligned;" ::: "memory");
  if (warp >= 8 && warp < 12 && elect()) asm volatile("prefetch.tensormap [%0];" :: "l"(&tm.x + (warp - 8)) : "memory");
  const int rank = bid & 1, cl = bid >> 1;
  const int q7 = ((cl - 36) * 37) >> 8;
  const int P = cl < 4 ? 0 : cl < 36 ? (cl - 4) & 7 : cl - 35 - 7 * q7;
  const int g = (cl < 4 ? 4 + cl : cl < 36 ? (cl - 4) >> 3 : 4 + q7);
  const int mt = 2 * P + rank, cid = mt * 8 + g;
  const bool ffn1 = g >= 5;
  const int fj = ffn1 ? mt * 3 + g - 5 : (P * 5 + g) * 2 + rank;
  const int ord = ((g >> 2) ^ P) & 1;
  auto ks_of = [&](int it) { return ord == 0 || it == 0 ? it : it <= 5 ? it + 4 : it - 5; };
  const int godd = g & 1, cm = g * 80 + godd * 16, cr = g * 80 + 64 - godd * 64;
  auto load_w = [&](int ks, uint32_t a, uint32_t bar, int kk) {
    tma_3d_mc(a + 16384 + ((kk + 1) & 3) * 6144, &tm.w, bar, cm, ks * 64 + kk * 16, 0);
    tma_3d_mc(a + 41472 + kk * 2048, &tm.wr, bar, cr, ks * 64 + kk * 16, 0);
    tma_3d_mc(a + 40960 + kk * 2048, &tm.wv, bar, cm + 48, ks * 64 + kk * 16, 2);
  };
  if (warp == 0 && elect()) {
    mbar_expect_tx(bar_half, 32768);
    tma_3d(sb + 2 * SLOT, &tm.x, bar_half, 0, P * 128, rank);
    mbar_expect_tx(bar_full + 16, 16384);
  }
  asm volatile("barrier.cluster.wait.aligned;" ::: "memory");
  if (warp == 0) {
    if (elect()) {
      uint32_t bar = bar_half;
#pragma unroll 1
      for (int kk = rank; kk < 4; kk += 2) { load_w(0, sb + 2 * SLOT, bar, kk); bar = bar_full + 16; }
    }
    asm volatile("bar.arrive 4, 64;" ::: "memory");
  }

  if (warp >= 8) {
    asm volatile("setmaxnreg.dec.sync.aligned.u32 %0;" :: "n"(REG_P));
#define TS_T 0
    if (warp == 8) {
      TS(8);
      bar_sync(4, 64);
      if (elect()) {
        TS(10);
#pragma unroll 1
        for (int it = 1; it < 10; it++) {
          const int s = (it + 2) & 3, ks = ks_of(it);
          const uint32_t full = bar_full + 8 * s, a = sb + s * SLOT;
          uint32_t bar = it < NSPLIT ? bar_half + 8 * it : full;
          if (it >= 4) mbar_wait(full + 32, ((it >> 2) - 1) & 1);
          if (it >= 2 && it < THR_END) mbar_wait(bar_full + 8 * (it & 3), 0);
          if (it < NSPLIT) mbar_expect_tx(bar, 32768);
          mbar_expect_tx(full, it < NSPLIT ? 16384 : SLOT);
          tma_3d(a, &tm.x, bar, ks * 64, P * 128, rank);
#pragma unroll 1
          for (int kk = rank; kk < 4; kk += 2) { load_w(ks, a, bar, kk); bar = full; }
          TS(12 + it);
          if ((it >> 1) == 2) {
            mbar_wait(bar_rst, 0);
            asm volatile("cp.async.bulk.global.shared::cta.bulk_group [%0], [%1], %2;\ncp.async.bulk.commit_group;"
                         :: "l"(it == 4 ? (uint4*)(g_own + cid) : (uint4*)&g_x + cid * GLOB_PER_CTA), "r"(sb + OFF_CS), "r"(it == 4 ? (int)sizeof(Own) : GLOB_PER_CTA * 16) : "memory");
          }
          if (it == 6) { asm volatile("cp.async.bulk.wait_group 0;" ::: "memory"); mbar_arrive(bar_tag); }
        }
        mbar_expect_tx(bar_ffn, ffn1 ? 81920 : 24576);
        int fjn = 0;
#pragma unroll 1
        for (int it = 9; it < 17; it++) {
          if (it >= 13) { mbar_wait(bar_oc + 8 * (it - 13), 0); mbar_wait(bar_oc + 56 + 8 * (it - 13), 0); }
          else if (it >= 10) {
            const uint32_t full = bar_full + 8 * (it - 10);
            const int g0 = 3 * (it - 10), g1 = min(g0 + 3, 8);
            mbar_wait(full + 32, it < 12);
            mbar_expect_tx(full, (g1 - g0) * 12800);
#pragma unroll 1
            for (int gp = g0 + ((g0 ^ rank) & 1); gp < g1; gp += 2) {
              tma_3d_mc(sb + gp * 15360, &tm.wo, full, 0, gp * 80, g * 2);
              tma_3d_mc(sb + gp * 15360 + 10240, &tm.wor, full, 512 + g * 16, gp * 80, 0);
            }
          }
          const int j1 = ffn1 ? (it >= 13 ? 2 * it - 22 : min(it - 8, 3)) : (it >= 13 ? 12 : min((it - 8) * F_PER, F_MAX));
#pragma unroll 1
          for (; fjn < j1; fjn++) {
            const int j = fjn < 3 ? fjn + 7 : fjn - 3;
            if (ffn1) tma_3d(sb + (j < 7 ? 0 : OFF_W2 - 57344) + j * 8192, j < 5 ? &tm.gate : &tm.up, bar_ffn, fj * 32, (j < 5 ? j : j - 5) * 128, 0);
            else tma_3d(sb + OFF_W2 + fjn * 2048, &tm.down, bar_ffn, fj * 8, fjn * 128, 0);
          }
        }
        TS(11);
      }
#undef TS_T
#define TS_T 64
    } else if (warp >= 12) {
      const int l7 = lane & 7, j = warp - 12, ch = min((P >> 1) * 4 + rank * 2 + (j >> 1), 14);
      const uint32_t sxo = ((g & 3) * 32 + j * 8 + l7) * 128 + (((lane >> 3) ^ l7) * 16);
      const uint32_t swo = ch < 12 ? 16384 + (lane >> 4) * 6144 + (ch >> 2) * 2048 + (lane & 15) * 128 + ((((ch & 3) * 2 + (j & 1)) ^ l7) * 16)
                                   : 41472 + (lane >> 4) * 2048 + (ch - 12) * 512 + (lane & 15) * 32 + (((j & 1) ^ (l7 >> 2)) * 16);
      float ps = 0.f, pq = 0.f, pq1 = 0.f, pc = 0.f;
      uint32_t tag = 0;
      char* const pp = hold((lane & 1) ? (char*)&g_own[cid].cs[j * 8 + (lane >> 2)] : (char*)&g_own[cid].st1[j * 8 + (lane >> 2)]);
#pragma unroll 1
      for (int it = ord; it < ord + 5; it++) {
        const int sl = (it + 2) & 3;
        if (it == ord + 4) { mbar_wait(bar_tag, 0); tag = __float_as_uint(lds32f(sb + OFF_WR + 324)); }
        if (it < NSPLIT) mbar_wait(bar_half + 8 * it, 0);
        mbar_wait(bar_full + 8 * sl, (it >> 2) & 1);
        TS(it);
        const uint32_t a = sb + sl * SLOT;
        const uint4 v0 = ldsm4(a + sxo), v1 = ldsm4((a + sxo) ^ 64), w0 = ldsm4t(a + swo), w1 = ldsm4t(a + swo + (ch < 12 ? 12288 : 4096));
        if (lane + (int)((v0.x & v1.x & w0.x & w1.x) == 0x7fc17fc1u && (v0.x | v1.x) == 0u) < 2) mbar_arrive_cta(bar_empty + 8 * sl, lane);
        const uint32_t vv[8] = {v0.x, v0.y, v0.z, v0.w, v1.x, v1.y, v1.z, v1.w}, ww[8] = {w0.x, w0.y, w0.z, w0.w, w1.x, w1.y, w1.z, w1.w};
#pragma unroll
        for (int i = 0; i < 8; i++) {
          const float d = bf_lo(vv[i]), e = bf_hi(vv[i]);
          ps += d + e; pq = fmaf(d, d, pq); pq1 = fmaf(e, e, pq1); pc += bf_lo(ww[i]) + bf_hi(ww[i]);
        }
      }
      pq += pq1;
      ps += shx(ps, 1); pq += shx(pq, 1); pc += shx(pc, 1);
      ps += shx(ps, 2); pq += shx(pq, 2); pc += shx(pc, 2);
      if ((lane & 3) == 0) stg_pkt(pp, __float_as_uint(ps), __float_as_uint(pq), tag, 0u);
      if ((lane & 3) == 1) stg_rlx64(pp, __float_as_uint(pc), tag);
      asm volatile("bar.arrive 2, 192;" ::: "memory");
      if (warp == 12) {
        const uint4* const hp = hold(&g_own[max(cid - 16, 0)].halo[0][lane]);
        mbar_wait(bar_aux, 0);
        mbar_wait(bar_go, 0);
        uint4 v[5] = {};
        int guard = SPIN_MAX;
        if (P > 0) {
          do {
#pragma unroll
            for (int i = 0; i < 5; i++) v[i] = ldg_pkt(hp + 32 * i);
          } while (anyw(v[0].x == SENT || v[1].x == SENT || v[2].x == SENT || v[3].x == SENT || v[4].x == SENT) && --guard > 0);
        }
#pragma unroll
        for (int i = 0; i < 5; i++) *(uint4*)(smem + OFF_O + 10240 + i * 512 + lane * 16) = v[i];
        mbar_arrive(bar_kv);
      }
#undef TS_T
#define TS_T 32
    } else if (warp < 11) {
      const int l7 = lane & 7, hk = lane >> 4;
      if (warp == 10 && elect()) {
#pragma unroll 1
        for (int i = 0; i < 36; i++) mbar_init(bar_o + 8 * i, i < 14 || i == 30 ? 1 : i < 34 ? 4 : 128);
      }
      mbar_wait(bar_tag, 0);
      const uint32_t tag = __float_as_uint(lds32f(sb + OFF_WR + 324));
      bar_sync(2, 192);
      TS(0);
      int guard = SPIN_MAX;
      if (warp == 9) {
        const uint4* sp = &g_own[mt * 8].st1[lane];
        const uint4* hp = &g_own[max(mt - 2, 0) * 8 + 3].st1[24 + l7];
        uint4 a[5], b[5];
        bool bad;
        do {
          __nanosleep(AUX_NS);
          bad = false;
#pragma unroll
          for (int i = 0; i < 5; i++) {
            const uint4* q = i < 4 ? sp + i * (sizeof(Own) / 16) : hp;
            a[i] = ldg_pkt(q); b[i] = ldg_pkt(q + 4 * sizeof(Own) / 16);
          }
#pragma unroll
          for (int i = 0; i < 5; i++) bad |= a[i].z != tag || b[i].z != tag;
        } while (anyw(bad) && --guard);
        TS(1);
#pragma unroll
        for (int i = 0; i < 5; i++) {
          const float m = (__uint_as_float(a[i].x) + __uint_as_float(b[i].x)) * (1.f / 640.f);
          const float rs = rsq(fmaxf(fmaf(-m, m, (__uint_as_float(a[i].y) + __uint_as_float(b[i].y)) * (1.f / 640.f)), 0.f) + 1e-5f);
          ((float*)(smem + OFF_RS))[i < 4 ? 8 + lane + 32 * i : l7] = rs;
          const uint32_t mh = pack_bf16(-m, -m);
          const float ml = -m - bf_lo(mh);
          if (i < 4) ((uint2*)(smem + OFF_MN))[lane + 32 * i] = make_uint2(mh, pack_bf16(ml, ml));
        }
      } else {
        const uint4* cp = (const uint4*)g_own[hk * 8 + g].cs + (lane & 15);
        uint4 a[4], b[4];
        bool bad;
        do {
          __nanosleep(AUX_NS);
          bad = false;
#pragma unroll
          for (int i = 0; i < 4; i++) { a[i] = ldg_pkt(cp + i * 32 * sizeof(Own) / 16); b[i] = ldg_pkt(cp + (i * 32 + 16) * sizeof(Own) / 16); }
#pragma unroll
          for (int i = 0; i < 4; i++) bad |= a[i].y != tag || a[i].w != tag || b[i].y != tag || b[i].w != tag;
        } while (anyw(bad) && --guard);
#pragma unroll
        for (int i = 0; i < 4; i++)
          if (i < 3 || lane < 24) {
            const float c0 = __uint_as_float(a[i].x) + __uint_as_float(b[i].x), c1 = __uint_as_float(a[i].z) + __uint_as_float(b[i].z);
            const uint32_t hi = pack_bf16(c0, c1), w0 = pack_bf16(c0, c0 - bf_lo(hi)), w1 = pack_bf16(c1, c1 - bf_hi(hi));
            uint4* const d = (uint4*)(smem + OFF_CS) + 2 * (lane + 32 * i);
            d[0] = make_uint4(w0, w0, 0, 0); d[1] = make_uint4(w1, w1, 0, 0);
          }
        asm volatile("fence.proxy.async.shared::cta;" ::: "memory");
      }
      mbar_arrive(bar_aux);
      TS(2);
      const int fo = warp - 9, wq = fo ? 1 - LEAD : LEAD;
      const uint4* const fp = hold(g_own[mt * 8 + wq * 4].cnt);
      const char* src = hold((const char*)g_o[mt * 2 + wq]);
      if (elect()) {
        const uint32_t bo = bar_o + fo * 56;
#pragma unroll
        for (int i = 0; i < 7; i++) mbar_expect_tx(bo + 8 * i, 10240);
        uint32_t cv = 0, need = 4;
        mbar_wait(OV == 3 ? bar_st + 8 * fo : bar_go + 8 + 8 * fo, 0);
        uint32_t dst = sb + OFF_O + 20480;
#pragma unroll OUNR
        for (int i = 0; i < 7; i++) {
          if (i == g) { src += 10240; need <<= 4; }
          if (!(cv & need)) {
            do { cv = ldg_rlx32(fp); } while (!(cv & need) && --guard > 0);
            asm volatile("fence.proxy.async.global;" ::: "memory");
          }
          if (fo || i == 5 || (OV == 2 && i == 4)) mbar_wait(fo ? bar_oc + 8 * i : i == 4 ? bar_st : bar_st + 8, 0);
          if (i == 0) TS(6);
          asm volatile("cp.async.bulk.shared::cluster.global.mbarrier::complete_tx::bytes [%0], [%1], 10240, [%2];" :: "r"(dst), "l"(src), "r"(bo + 8 * i) : "memory");
          src += 10240; need <<= 4;
          dst += i == 4 ? -61440 : 10240;
        }
      }
#undef TS_T
#define TS_T 96
    } else {
      if ((sb & 0x3FFFF) != D0 * 16) __trap();
#pragma unroll 1
      for (int i = lane; i < 232; i += 32) { const uint32_t f = i < 208 ? SENT : 0u; ((uint4*)(smem + OFF_CS))[i] = make_uint4(f, f, f, f); }
      asm volatile("fence.proxy.async.shared::cta;" ::: "memory");
      if (elect()) mbar_arrive(bar_rst);
      mbar_wait(bar_full + 8 * ((HK_IT + 2) & 3), 0);
      TS(4);
      const uint32_t epoch = ldg_rlx32(g_epoch + cid) + 1;
      uint32_t wv[10];
#pragma unroll
      for (int i = 0; i < 10; i++) wv[i] = __ldg((const uint32_t*)w_r + lane + 32 * i);
      float s = 0.f;
#pragma unroll
      for (int i = 0; i < 10; i++) {
        s += bf_lo(wv[i]) + bf_hi(wv[i]);
        const unsigned u = i < 8 ? lane + 32 * (i - g) : lane + 32 * (i - 7) - g * 8;
        if (i < 8 ? u < 32u : u - 32u < 8u) *(float2*)(smem + OFF_WR + ((u & 3) * 10 + (u >> 2)) * 8) = make_float2(bf_lo(wv[i]), bf_hi(wv[i]));
      }
#pragma unroll
      for (int m = 1; m < 32; m <<= 1) s += shx(s, m);
      *(float2*)(smem + OFF_WR + 320) = make_float2(s, __uint_as_float(epoch * 0x9E3779B8u));
      g_epoch[cid] = epoch;
      TS(3);
      if (elect()) mbar_arrive(bar_tag);
      TS(5);
#pragma unroll 1
      for (int i = 0; i < PFW_N; i++) {
        const int m = (i + 2) >> 2, n = m == 0 ? 50 : 120, t = (m == 0 ? i : (i + 2) & 3) * 32 + lane;
        const char* b = (const char*)(m == 0 ? wo : m == 1 ? w_up : m == 2 ? w_down : w_gate);
        if (t < n) pf_l2(b + (bid * n + t) * 128);
        __nanosleep(PFW_NS);
      }
      const uint4* const kp = hold(g_own[1].cnt);
      const uint4* const cb = hold(&g_x.cand[0][lane >> 2][lane & 3]);
      bar_sync(3, 64);
      uint4 k;
      uint32_t have = SENT;
      int guard = SPIN_MAX;
      while (true) {
        k = ldg_pkt(kp);
        if (ffn1) {
          while (k.x != have && --guard > 0) {
            const uint32_t tk = 2047u - (k.x & 2047u), want = k.x;
            const uint4* q = cb + ((tk >> 8) * 16 + (tk & 1) * 8 + ((tk >> 5) & 7)) * 192;
            const uint4 c0 = ldg_pkt(q), c1 = ldg_pkt(q + 4); const uint2 c2 = ldg_rlx64(q + 8);
            k = ldg_pkt(kp);
            *(uint4*)(smem + OFF_HN + lane * 16) = c0; *(uint4*)(smem + OFF_HN + 512 + lane * 16) = c1; *(uint2*)(smem + OFF_HN + 1024 + lane * 16) = c2;
            have = anyw(c0.x == SENT || c1.x == SENT || c2.x == SENT) ? SENT : want;
          }
        } else if (KEY_NS && k.z != 128u) __nanosleep(KEY_NS);
        if (k.z == 128u || --guard <= 0) break;
      }
      *(uint2*)(smem + OFF_WR + 336) = make_uint2(k.x, k.y);
      mbar_arrive(bar_win);
      TS(7);
    }
#undef TS_T
  } else {
#define TS_T 0
    asm volatile("setmaxnreg.inc.sync.aligned.u32 %0;" :: "n"(REG_C));
    const int wg = warp >> 2, w4 = warp & 3, r = lane >> 2, c = lane & 3;
    float acc[120];
    uint4 xr[5] = {};
    const uint32_t xa = pin(sb + (warp * 16 + (lane & 15)) * 128 + ((lane >> 4) ^ (lane & 7)) * 16);
    const int fol = wg != LEAD;
    const bool first = (P == 0) && (warp == 0);
    const uint32_t kvs = sb + OFF_O + fol * 10240 + w4 * 2560 + lane * 16;
    uint4* const kvd = hold(warp == 7 ? &g_own[cid].halo[0][lane] : (uint4*)(smem + (warp == 3 ? OFF_O + lane * 16 : kvs - sb + 2560)));
    uint4* const odst = hold(&g_o[mt * 2 + wg][g][w4 * 160]);
    uint4* const ocnt = hold(g_own[mt * 8 + wg * 4].cnt);
    uint32_t m0 = 0, m1 = 0;
    const uint32_t mna = pin(sb + OFF_MN + (warp * 16 + r) * 8 + c * 4);
    const int itx = ord == 0 || g == 0 ? g : g < 5 ? g + 5 : g - 4, ity = (ord ? 4 : 8) + (g >> 2);
    uint32_t rel;
    asm volatile("mapa.shared::cluster.u32 %0, %1, %2;" : "=r"(rel) : "r"(bar_empty), "r"(tid & 1));
    const uint32_t xa1 = pin(xa ^ 32), xa2 = pin(xa ^ 64), xa3 = pin(xa ^ 96), xb = pin(xa ^ ((g & 3) * 32));
    const uint32_t da0 = wg * 512;
    const bool rel2 = lane < 2, rel6 = lane < 2 + 2 * (warp & 1);
    const uint32_t zero = __shfl_sync(0xffffffffu, (uint32_t)(uintptr_t)x & 8u, 0);
    mbar_wait(bar_half, 0);
    TS(13);
    wgmma_fence();
#pragma unroll
    for (int it = 0; it < 10; it++) {
      const int s = (it + 2) & 3;
#pragma unroll
      for (int kk = 0; kk < 4; kk++) {
        if (kk == 2 && it > 0) {
          wgmma_commit();
          wgmma_wait<1>();
          const uint32_t ra = ((xr[0].x ^ xr[1].x ^ xr[2].x ^ xr[3].x ^ xr[4].x) & zero) | rel;
          if (it == 1 ? (ord ? rel6 : rel2) : it == 6 ? (ord ? rel2 : rel6) : it < 6 ? rel2 : rel6)
            asm volatile("mbarrier.arrive.shared::cluster.b64 _, [%0];" :: "r"(ra + 8 * ((it + 1) & 3)) : "memory");
        }
        if (kk == 2) {
          ldsm4_if(xr[0], xa, s * SLOT, it == itx); ldsm4_if(xr[1], xa1, s * SLOT, it == itx);
          ldsm4_if(xr[2], xa2, s * SLOT, it == itx); ldsm4_if(xr[3], xa3, s * SLOT, it == itx);
          if ((it & 6) == 4 || it >= 8) ldsm4_if(xr[4], xb, s * SLOT, it == ity);
        }
        if (kk == AK && it == 9) {
          mbar_wait(bar_aux, 0);
          TS(3);
          if (c < 2) { m0 = __float_as_uint(lds32f(mna)); m1 = __float_as_uint(lds32f(mna + 64)); }
          if (!fol) bar_sync(11, 256);
        }
        if (it * 4 + kk == 40 - LAG && fol) {
          asm volatile("bar.arrive 11, 256;" ::: "memory");
          bar_sync(10, 256);
        }
        if (kk == 2 && it < NSPLIT) mbar_wait(bar_full + 8 * s, 0);
        const uint64_t da = mk64(da0 + (D0 + s * (SLOT >> 4) + kk * 2 + (1 << 16)), 0x40000040u);
        wgmma_n64hi_ss(acc, da, mk64(D0 + s * (SLOT >> 4) + 2560 + kk * 128 + (32 << 16), 0xC0000010u), (it | kk) != 0);
        wgmma_n176lo_ss(acc, da, mk64(D0 + s * (SLOT >> 4) + 1024 + ((kk + 1) & 3) * 384 + (128 << 16), 0x40000040u), (it | kk) != 0);
      }
      wgmma_commit();
      if (it < 9) {
        if (it + 1 < NSPLIT) mbar_wait(bar_half + 8 * (it + 1), 0);
        else mbar_wait(bar_full + 8 * ((it + 3) & 3), ((it + 1) >> 2) & 1);
        if (it < 8) TS(14 + it);
      }
    }
    {
      const uint64_t dc = make_desc(D0 * 16 + OFF_CS, 0, 128, 0);
      wgmma_fence();
      wgmma_n64hi_rk(acc, m0, m1, 0u, 0u, dc + 176, 1);
      wgmma_n176lo_rk(acc, m0, m1, 0u, 0u, dc, 1);
      wgmma_commit();
      if (!fol) asm volatile("bar.arrive 10, 256;" ::: "memory");
    }
    const uint32_t stb = sb + OFF_RS + warp * 64;
    const float rlo = lds32f(stb + (8 + r) * 4), rhi = lds32f(stb + (16 + r) * 4);
    wgmma_wait<0>();
#pragma unroll
    for (int i = 0; i < 120; i++) asm volatile("" : "+f"(acc[i]) :: "memory");
    if (fol && lane == 0) mbar_arrive(bar_go);
    TS(2);
    uint32_t Qlo[10], Qhi[10], Klo[10], Khi[10], Vlo[10], Vhi[10];
#define CONV_HI(ROT) _Pragma("unroll") for (int t = 0; t < 10; t++) { \
      const int k = KT((t + ROT) % 10), v = VT((t + ROT) % 10); \
      Khi[t] = pack_bf16(acc[4 * k + 2], acc[4 * k + 3]); \
      Vhi[t] = pack_bf16(acc[4 * v + 2] * rhi, acc[4 * v + 3] * rhi); }
    if (godd) { CONV_HI(8) } else { CONV_HI(0) }
    st_pkt(kvd, Khi[0], Khi[1], Khi[3], Khi[4]);
    st_pkt(kvd + 32, Khi[5], Khi[6], Khi[8], Khi[9]);
    st_pkt(kvd + 64, Khi[2], Khi[7], Vhi[0], Vhi[1]);
    st_pkt(kvd + 96, Vhi[2], Vhi[3], Vhi[4], Vhi[5]);
    st_pkt(kvd + 128, Vhi[6], Vhi[7], Vhi[8], Vhi[9]);
    if (warp < 7) mbar_arrive(bar_kv + ((warp + 1) >> 2) * 8);
#define CONV_LO(ROT) _Pragma("unroll") for (int t = 0; t < 10; t++) { \
      const int q = QT((t + ROT) % 10), k = KT((t + ROT) % 10), v = VT((t + ROT) % 10); \
      Vhi[t] = movm(Vhi[t]); \
      Klo[t] = pack_bf16(acc[4 * k], acc[4 * k + 1]); \
      Vlo[t] = movm(pack_bf16(acc[4 * v] * rlo, acc[4 * v + 1] * rlo)); \
      Qlo[t] = pack_bf16(acc[4 * q], acc[4 * q + 1]); \
      Qhi[t] = pack_bf16(acc[4 * q + 2], acc[4 * q + 3]); }
    if (godd) { CONV_LO(8) } else { CONV_LO(0) }
    const bool in0 = 2 * c <= r, in1 = 2 * c + 1 <= r;
    const uint32_t mL = (in0 ? 0xffffu : 0u) | (in1 ? 0xffff0000u : 0u);
    const float qs = 0.22360679774997896f * 1.4426950408889634f;
    const uint32_t kb0 = stb + (2 * c + (in0 ? 8 : 0)) * 4, kb1 = stb + (2 * c + 1 + (in1 ? 8 : 0)) * 4;
    const float scl0 = lds32f(kb0) * rlo * qs, scl1 = lds32f(kb1) * rlo * qs;
    const float sch0 = lds32f(kb0 + 32) * rhi * qs, sch1 = lds32f(kb1 + 32) * rhi * qs;
    const float bias0 = (first && !in0) ? -INFINITY : 0.f, bias1 = (first && !in1) ? -INFINITY : 0.f;
    const int slot = mt * 8 + warp;
    int guard = SPIN_MAX;
    uint4 pv[5];
    const bool cA = c < 2, nA = r < 4;
    TS(0);
    mbar_wait(bar_go + fol * 8, 0);
    TS(23);
    uint32_t qe[4][2];
    float sl0[4], sl1[4], th0[4], th1[4];
#pragma unroll
    for (int hd = 0; hd < 4; hd++) {
      const int ta = 5 * (hd >> 1) + 3 * (hd & 1), ts = 5 * (hd >> 1) + 2;
      const bool mine = (hd & 1) ? !cA : cA;
      qe[hd][0] = mine ? Qlo[ts] : 0u; qe[hd][1] = mine ? Qhi[ts] : 0u;
      float sl[4], sh[4];
      mma_k24(sl, Qlo[ta], Qhi[ta], Qlo[ta + 1], Qhi[ta + 1], Klo[ta], Klo[ta + 1], qe[hd][0], qe[hd][1], Klo[ts]);
      mma_k24(sh, Qlo[ta], Qhi[ta], Qlo[ta + 1], Qhi[ta + 1], Khi[ta], Khi[ta + 1], qe[hd][0], qe[hd][1], Khi[ts]);
      th0[hd] = (in0 ? sh[2] : sl[2]) * sch0; th1[hd] = (in1 ? sh[3] : sl[3]) * sch1;
      float mh = fmaxf(th0[hd], th1[hd]);
      mh = fmaxf(mh, shx(mh, 1)); mh = fmaxf(mh, shx(mh, 2));
      th0[hd] -= mh; th1[hd] -= mh;
      sl0[hd] = sl[0]; sl1[hd] = sl[1];
    }
    mbar_wait(bar_kv + wg * 8, 0);
    TS(4);
#pragma unroll
    for (int j = 0; j < 5; j++) pv[j] = lds128(kvs + 512 * j);
    const uint32_t Kp[10] = {pv[0].x, pv[0].y, pv[2].x, pv[0].z, pv[0].w, pv[1].x, pv[1].y, pv[2].y, pv[1].z, pv[1].w};
    const uint32_t Vp[10] = {movm(pv[2].z), movm(pv[2].w), movm(pv[3].x), movm(pv[3].y), movm(pv[3].z), movm(pv[3].w), movm(pv[4].x), movm(pv[4].y), movm(pv[4].z), movm(pv[4].w)};
    const uint32_t ONES = 0x3f803f80u;
    uint32_t of[20];
#pragma unroll
    for (int hp = 0; hp < 2; hp++) {
      float o[6][4];
#pragma unroll
      for (int hh = 0; hh < 2; hh++) {
        const int hd = 2 * hp + hh, ta = 5 * hp + 3 * hh, ts = 5 * hp + 2;
        float sp[4];
        mma_k24(sp, Qlo[ta], Qhi[ta], Qlo[ta + 1], Qhi[ta + 1], Kp[ta], Kp[ta + 1], qe[hd][0], qe[hd][1], Kp[ts]);
        const float tl0 = fmaf(in0 ? sl0[hd] : sp[0], scl0, bias0), tl1 = fmaf(in1 ? sl1[hd] : sp[1], scl1, bias1);
        float ml = fmaxf(tl0, tl1);
        ml = fmaxf(ml, shx(ml, 1)); ml = fmaxf(ml, shx(ml, 2));
        if (HOLD == 1 && hd == 3 && !fol && lane == 0) mbar_arrive(bar_go + 8);
        const uint32_t Pl = pack_bf16(ex2(tl0 - ml), ex2(tl1 - ml)), Ph = pack_bf16(ex2(th0[hd]), ex2(th1[hd]));
        const uint32_t a0 = Pl & mL, a1 = Ph & ~mL, a3 = Ph & mL, ap = Pl & ~mL;
        const bool vm = hh == 0 ? nA : !nA;
        mma_k24(o[3 * hh], a0, a1, 0u, a3, Vlo[ta], Vhi[ta], ap, 0u, Vp[ta]);
        mma_k24(o[3 * hh + 1], a0, a1, 0u, a3, Vlo[ta + 1], Vhi[ta + 1], ap, 0u, Vp[ta + 1]);
        mma_k24(o[3 * hh + 2], a0, a1, 0u, a3, vm ? Vlo[ts] : ONES, vm ? Vhi[ts] : ONES, ap, 0u, vm ? Vp[ts] : ONES);
      }
      const float il = rcp(cA ? o[5][0] : o[2][0]), ih = rcp(cA ? o[5][2] : o[2][2]);
      const float jl = shx(il, 2), jh = shx(ih, 2);
      const float al = cA ? jl : il, ah = cA ? jh : ih, bl = cA ? il : jl, bh = cA ? ih : jh;
      const int t0 = 5 * hp;
      of[2 * t0]     = pack_bf16(o[0][0] * al, o[0][1] * al); of[2 * t0 + 1] = pack_bf16(o[0][2] * ah, o[0][3] * ah);
      of[2 * t0 + 2] = pack_bf16(o[1][0] * al, o[1][1] * al); of[2 * t0 + 3] = pack_bf16(o[1][2] * ah, o[1][3] * ah);
      of[2 * t0 + 4] = pack_bf16((cA ? o[2][0] : o[5][0]) * jl, (cA ? o[2][1] : o[5][1]) * jl);
      of[2 * t0 + 5] = pack_bf16((cA ? o[2][2] : o[5][2]) * jh, (cA ? o[2][3] : o[5][3]) * jh);
      of[2 * t0 + 6] = pack_bf16(o[3][0] * bl, o[3][1] * bl); of[2 * t0 + 7] = pack_bf16(o[3][2] * bh, o[3][3] * bh);
      of[2 * t0 + 8] = pack_bf16(o[4][0] * bl, o[4][1] * bl); of[2 * t0 + 9] = pack_bf16(o[4][2] * bh, o[4][3] * bh);
    }
    {
      const uint32_t os = sb + OFF_O + (fol ? 0 : 61440) + w4 * 2560, oa = os + ((lane >> 3) & 1) * 1280 + (lane >> 4) * 128 + (lane & 7) * 16;
#pragma unroll
      for (int s = 0; s < 5; s++) {
        stsm4(oa + s * 256, of[4 * s], of[4 * s + 1], of[4 * s + 2], of[4 * s + 3]);
        if (s == 0 && (fol || HOLD == 2) && lane == 0) mbar_arrive(bar_go + 8 + 8 * fol);
      }
      asm volatile("fence.proxy.async.shared::cta;" ::: "memory");
      __syncwarp();
      asm volatile("{\n.reg .pred q;\nelect.sync _|q, 0xffffffff;\n@q cp.async.bulk.global.shared::cta.bulk_group [%0], [%1], 2560;\ncp.async.bulk.commit_group;\n}\n" :: "l"(odst), "r"(os) : "memory");
    }
    TS(5);
    float h[40];
#pragma unroll
    for (int s = 0; s < 5; s++) {
      const uint4 v = xr[s];
      h[8 * s] = bf_lo(v.x); h[8 * s + 1] = bf_hi(v.x); h[8 * s + 2] = bf_lo(v.y); h[8 * s + 3] = bf_hi(v.y);
      h[8 * s + 4] = bf_lo(v.z); h[8 * s + 5] = bf_hi(v.z); h[8 * s + 6] = bf_lo(v.w); h[8 * s + 7] = bf_hi(v.w);
    }
    asm volatile("cp.async.bulk.wait_group 0;" ::: "memory");
    __syncwarp();
    if (lane == 0) {
      asm volatile("red.relaxed.gpu.global.add.u32 [%0], %1;" :: "l"(ocnt), "r"(1 << (4 * g)) : "memory");
      mbar_arrive(bar_st + 8 * fol);
    }
    TS(22);
    mbar_wait(bar_full, 0); mbar_wait(bar_full + 8, 0); mbar_wait(bar_full + 16, 1);
    mbar_wait(bar_go + 16, 0);
    const uint64_t dwo = make_desc(D0 * 16, 5120, 512, 2);
    wgmma_fence();
#pragma unroll
    for (int s = 0; s < 5; s++) wgmma_n80_rs(h, of[4 * s], of[4 * s + 1], of[4 * s + 2], of[4 * s + 3], dwo + g * 960 + s * 64, 1);
    wgmma_commit();
    TS(6);
    const bool odd = c & 1;
    uint4* const sp = hold(&g_own[slot].st2[r + (odd ? 8 : 0)]);
    uint4* const cdp = hold(&g_x.cand[slot][g][0]);
    uint4* const kcp = hold(g_own[1].cnt);
    float wr[20];
#pragma unroll
    for (int j = 0; j < 5; j++) {
      const uint4 v = lds128(sb + OFF_WR + c * 80 + j * 16);
      wr[4 * j] = __uint_as_float(v.x); wr[4 * j + 1] = __uint_as_float(v.y); wr[4 * j + 2] = __uint_as_float(v.z); wr[4 * j + 3] = __uint_as_float(v.w);
    }
    const float wsum = lds32f(sb + OFF_WR + 320);
    const uint32_t bo = bar_o + fol * 56;
    if (PRIO < 7 && fol) mbar_wait(bar_oc + 8 * PRIO, 0);
#pragma unroll
    for (int i = 0; i < 7; i++) {
      mbar_wait(bo + 8 * i, 0);
      if (i == 0) TS(1);
      const uint32_t da = D0 + OFF_O / 16 + (8 << 16) + ((i + 2) % 7) * 640, db = D0 + (320 << 16) + (i >= g ? i + 1 : i) * 960;
      wgmma_fence();
#pragma unroll
      for (int s = 0; s < 5; s++) wgmma_n80_ss(h, mk64(da + s * 16, 80u), mk64(db + s * 64, 0x80000020u), 1);
      wgmma_commit();
      wgmma_wait<1>();
      if (lane == 0 && i > 0) mbar_arrive(bo + 104 + 8 * i);
    }
    const int tok0 = P * 256 + 32 * warp + rank;
    wgmma_wait<0>();
#pragma unroll
    for (int i = 0; i < 40; i++) asm volatile("" : "+f"(h[i]) :: "memory");
    if (lane == 0) mbar_arrive(bo + 160);
    if (SPLITB) { asm volatile("{\n.reg .pred p;\nsetp.ne.u32 p, %0, 0;\n@p trap;\n}\n" :: "r"(zero) : "memory"); }
    TS(7);
    float mean, rstd, rr;
    bool pub;
    {
      float l1 = 0.f, l2 = 0.f, l3 = 0.f, h1 = 0.f, h2 = 0.f, h3 = 0.f;
#pragma unroll
      for (int j = 0; j < 10; j++) {
        l1 += h[4 * j] + h[4 * j + 1]; h1 += h[4 * j + 2] + h[4 * j + 3];
        l2 = fmaf(h[4 * j], h[4 * j], l2); l2 = fmaf(h[4 * j + 1], h[4 * j + 1], l2);
        h2 = fmaf(h[4 * j + 2], h[4 * j + 2], h2); h2 = fmaf(h[4 * j + 3], h[4 * j + 3], h2);
        l3 = fmaf(h[4 * j], wr[2 * j], l3); l3 = fmaf(h[4 * j + 1], wr[2 * j + 1], l3);
        h3 = fmaf(h[4 * j + 2], wr[2 * j], h3); h3 = fmaf(h[4 * j + 3], wr[2 * j + 1], h3);
      }
      float s1 = (odd ? h1 : l1) + shx(odd ? l1 : h1, 1), s2 = (odd ? h2 : l2) + shx(odd ? l2 : h2, 1), s3 = (odd ? h3 : l3) + shx(odd ? l3 : h3, 1);
      s1 += shx(s1, 2); s2 += shx(s2, 2); s3 += shx(s3, 2);
      uint4 p0;
      float o1 = 0.f, o2 = 0.f, o3 = 0.f, oc = 7.f;
      asm volatile("{\n.reg .pred q;\nsetp.lt.u32 q, %9, 2;\n@q atom.relaxed.gpu.global.add.v4.f32 {%0, %1, %2, %3}, [%4], {%5, %6, %7, %8};\n}\n"
                   : "+f"(o1), "+f"(o2), "+f"(o3), "+f"(oc) : "l"(sp), "f"(s1), "f"(s2), "f"(s3), "f"(1.f), "r"(c) : "memory");
      const uint32_t last = __ballot_sync(0xffffffffu, oc == 7.f);
      pub = last & 1;
      p0.x = __float_as_uint(o1 + s1); p0.y = __float_as_uint(o2 + s2); p0.z = __float_as_uint(o3 + s3);
      if (last != 0xffffffffu)
      do { p0 = ldg_pkt(sp); } while (anyw(p0.w != 0x41000000u) && --guard > 0);
      mean = __uint_as_float(p0.x) * (1.f / 640.f);
      rstd = rsq(fmaxf(fmaf(-mean, mean, __uint_as_float(p0.y) * (1.f / 640.f)), 0.f) + 1e-5f);
      rr = fmaf(-mean, wsum, __uint_as_float(p0.z)) * rstd;
    }
    TS(8);
    const int myrow = r + (odd ? 8 : 0);
    const uint32_t kk = cA ? ord_key(rr) : 0u, kmax = __reduce_max_sync(0xffffffffu, kk);
    if (pub) {
      if (kk == kmax) asm volatile("red.relaxed.gpu.global.max.u64 [%0], %1;" :: "l"(kcp), "l"(mk64(2047 - tok0 - 2 * myrow, kk)) : "memory");
      __syncwarp();
      if (lane == 0) asm volatile("red.relaxed.gpu.global.add.u32 [%0 + 8], 1;" :: "l"(kcp) : "memory");
    }
    const int crow = __reduce_min_sync(0xffffffffu, kk == kmax ? myrow : 16), L = (crow & 7) * 4 + (crow >> 3);
    if (warp == g) asm volatile("bar.arrive 3, 64;" ::: "memory");
    const uint32_t stg = sb + (fol ? OFF_O : g * 15360) + w4 * 2560;
    uint4 held;
    {
      const float nb = -mean * rstd;
      const float rl = __shfl_sync(0xffffffffu, rstd, lane & 28), rh = __shfl_sync(0xffffffffu, rstd, (lane & 28) + 1);
      const float bl = __shfl_sync(0xffffffffu, nb, lane & 28), bh = __shfl_sync(0xffffffffu, nb, (lane & 28) + 1), al = 1.f + rl, ah = 1.f + rh;
      if ((L >> 2) == r) {
        const bool chi = L & 1;
        const float rc = chi ? rh : rl, bc = chi ? bh : bl;
        uint32_t n[10];
#pragma unroll
        for (int j = 0; j < 10; j++) n[j] = pack_bf16(fmaf(chi ? h[4 * j + 2] : h[4 * j], rc, bc), fmaf(chi ? h[4 * j + 3] : h[4 * j + 1], rc, bc));
        uint4* d = cdp + c;
        stg_pkt(d, n[0], n[1], n[2], n[3]); stg_pkt(d + 4, n[4], n[5], n[6], n[7]); stg_rlx64(d + 8, n[8], n[9]);
      }
      mbar_wait(bar_oc + 56, 0);
      const uint32_t fa = stg + (lane & 15) * 160 + (lane >> 4) * 16;
#pragma unroll
      for (int s = 0; s < 5; s++)
        stsm4(fa + s * 32, pack_bf16(fmaf(h[8 * s], al, bl), fmaf(h[8 * s + 1], al, bl)), pack_bf16(fmaf(h[8 * s + 2], ah, bh), fmaf(h[8 * s + 3], ah, bh)),
              pack_bf16(fmaf(h[8 * s + 4], al, bl), fmaf(h[8 * s + 5], al, bl)), pack_bf16(fmaf(h[8 * s + 6], ah, bh), fmaf(h[8 * s + 7], ah, bh)));
      __syncwarp();
      held = lds128(stg + crow * 160 + min(lane, 9) * 16);
      if (lane < 10) stg_pkt(cdp + 12 + lane, held.x, held.y, held.z, held.w);
    }
    TS(9);
    mbar_wait(bar_ffn, 0);
    const uint32_t red = sb + OFF_RED;
    if (ffn1) {
      uint4 w1[4][5];
      {
        const int k = (lane & 7) + (lane >> 4) * 8;
        const uint32_t a1 = sb + k * 64, sw = ((lane >> 3) & 1) ^ ((lane >> 1) & 3);
#pragma unroll
        for (int s = 0; s < 5; s++)
#pragma unroll
          for (int u = 0; u < 4; u++)
            w1[u][s] = ldsm4t(a1 + (s < 4 ? warp * 4096 + s * 1024 : 32768 + warp * 1024) + (u >> 1) * (40960 + (s == 4 || warp >= 4 ? OFF_W2 - 57344 : 0)) + ((sw ^ (2 * (u & 1))) * 16));
      }
      uint32_t* const ap = hold(g_x.act + fj * 16 + (lane >> 1));
      mbar_wait(bar_win, 0);
      const uint32_t hp = sb + OFF_HN + (warp * 4 + c) * 16;
      const uint4 c0 = lds128(hp), c1 = lds128(hp + 512), c2 = lds128(hp + 1024);
      TS(10);
      float a[4][4];
#pragma unroll
      for (int u = 0; u < 4; u++) {
        a[u][0] = a[u][1] = a[u][2] = a[u][3] = 0.f;
        mma_acc(a[u], w1[u][0], c0.x, c0.y); mma_acc(a[u], w1[u][1], c0.z, c0.w); mma_acc(a[u], w1[u][2], c1.x, c1.y);
        mma_acc(a[u], w1[u][3], c1.z, c1.w); mma_acc(a[u], w1[u][4], c2.x, c2.y);
      }
      asm volatile("st.shared.v2.f32 [%0], {%1, %2};" :: "r"(red + (warp * 32 + c * 8 + r) * 8),
                   "f"(cA ? (odd ? a[0][2] : a[0][0]) : (odd ? a[1][2] : a[1][0])), "f"(cA ? (odd ? a[2][2] : a[2][0]) : (odd ? a[3][2] : a[3][0])) : "memory");
      bar_sync(1, 256);
      if (warp == 0) {
        float2 t[8];
#pragma unroll
        for (int i = 0; i < 8; i++) t[i] = lds64f(red + (i * 32 + lane) * 8);
        const float s = ((t[0].x + t[1].x) + (t[2].x + t[3].x)) + ((t[4].x + t[5].x) + (t[6].x + t[7].x));
        const float u = ((t[0].y + t[1].y) + (t[2].y + t[3].y)) + ((t[4].y + t[5].y) + (t[6].y + t[7].y));
        const float av = s * u * rcp(1.f + ex2(-1.4426950408889634f * s));
        const float an = shx(av, 1);
        if (!odd) stg_rlx32(ap, pack_bf16(av, an));
      }
      bar_sync(1, 256);
      TS(11);
    }
    char* const ob2 = (char*)(out + tok0 * 640 + g * 64);
    const int remo = 896 - 96 * g;
    {
      char* const q0 = ob2 + (lane >> 3) * 2560 + (lane & 7) * 16;
      const uint32_t s0 = stg + (lane >> 3) * 160 + (lane & 7) * 16;
#pragma unroll
      for (int s = 0; s < 4; s++) stg128_if(4 * s + (lane >> 3) != crow, q0 + s * 10240, lds128(s0 + s * 640));
      stg128_if((lane >> 1) != crow, ob2 + (lane >> 1) * 2560 + (lane & 1) * 16 + 128 + remo, lds128(stg + (lane >> 1) * 160 + (lane & 1) * 16 + 128));
    }
    mbar_wait(bar_win, 0);
    uint4 win = lds128(sb + OFF_WR + 336);
    win.z = win.y; win.y = 2047u - (win.x & 2047u); win.x = (win.y >> 8) * 16 + (win.y & 1) * 8 + ((win.y >> 5) & 7);
    stg128_if(win.x != slot && lane < 10, ob2 + crow * 2560 + lane * 16 + (lane < 8 ? 0 : remo), held);
    if (!ffn1) {
      TS(10);
      uint4 w2[6];
      const uint32_t a2 = sb + OFF_W2 + (warp * 192 + 8 * (((lane >> 3) & 1) * 4 + ((lane & 7) >> 1)) + 2 * (lane >> 4) + (lane & 1)) * 16;
#pragma unroll
      for (int s = 0; s < 6; s++) w2[s] = ldsm4t(a2 + (s >> 1) * 1024 + (s & 1) * 64);
      const uint4* p = (const uint4*)(g_x.act + warp * 96) + (r & 1) * 4 + c;
      const uint32_t* pb = (const uint32_t*)&g_x.cand[win.x][fj < 64 ? fj >> 3 : (fj - 64) >> 1][fj < 64 ? 12 + (fj & 7) : 20 + (fj & 1)] + c;
      uint32_t* const op = hold((uint32_t*)(out + win.y * 640 + fj * 8) + c);
      const float sg = rcp(1.f + ex2(-1.4426950408889634f * __uint_as_float(win.z ^ ((uint32_t)((int32_t)~win.z >> 31) | 0x80000000u))));
      uint4 c0, c1, c2; uint32_t bw;
      if (ACT_NS) __nanosleep(ACT_NS);
      do {
        c0 = ldg_pkt(p); c1 = ldg_pkt(p + 8); c2 = ldg_pkt(p + 16); bw = ldg_rlx32(pb);
      } while (anyw(max(max(max(max(c0.x, c0.y), max(c0.z, c0.w)), max(max(c1.x, c1.y), max(c1.z, c1.w))), max(max(max(c2.x, c2.y), max(c2.z, c2.w)), bw)) == SENT) && --guard > 0);
      TS(11);
      float a[4] = {0.f, 0.f, 0.f, 0.f}, b[4] = {0.f, 0.f, 0.f, 0.f}, d[4] = {0.f, 0.f, 0.f, 0.f};
      mma_acc(a, w2[0], c0.x, c0.y); mma_acc(b, w2[2], c1.x, c1.y); mma_acc(d, w2[4], c2.x, c2.y);
      mma_acc(a, w2[1], c0.z, c0.w); mma_acc(b, w2[3], c1.z, c1.w); mma_acc(d, w2[5], c2.z, c2.w);
      if (c == 0) sts32f(red + (warp * 8 + r) * 4, ((a[0] + a[3]) + (b[0] + b[3])) + (d[0] + d[3]));
      bar_sync(1, 256);
      if (tid < 4) {
        float2 t[8];
#pragma unroll
        for (int i = 0; i < 8; i++) t[i] = lds64f(red + (i * 4 + tid) * 8);
        const float y0 = ((t[0].x + t[1].x) + (t[2].x + t[3].x)) + ((t[4].x + t[5].x) + (t[6].x + t[7].x));
        const float y1 = ((t[0].y + t[1].y) + (t[2].y + t[3].y)) + ((t[4].y + t[5].y) + (t[6].y + t[7].y));
        *op = pack_bf16(fmaf(y0, sg, bf_lo(bw)), fmaf(y1, sg, bf_hi(bw)));
      }
    }
    TS(12);
#undef TS_T
  }
}

typedef CUresult (*EncodeFn)(CUtensorMap*, CUtensorMapDataType, cuuint32_t, void*, const cuuint64_t*, const cuuint64_t*, const cuuint32_t*,
                             const cuuint32_t*, CUtensorMapInterleave, CUtensorMapSwizzle, CUtensorMapL2promotion, CUtensorMapFloatOOBfill);

void make_map(EncodeFn enc, CUtensorMap* m, const void* base, const cuuint64_t* dims, const cuuint64_t* strides, const cuuint32_t* box,
              CUtensorMapSwizzle swz) {
  const cuuint32_t es[3] = {1, 1, 1};
  enc(m, CU_TENSOR_MAP_DATA_TYPE_BFLOAT16, 3, (void*)base, dims, strides, box, es, CU_TENSOR_MAP_INTERLEAVE_NONE, swz,
      CU_TENSOR_MAP_L2_PROMOTION_L2_128B, CU_TENSOR_MAP_FLOAT_OOB_FILL_NONE);
}

}

extern "C" void kernel_launch(void* const* d_in, const int* in_sizes, int n_in, void* d_out, int out_size) {
  const __nv_bfloat16* x = (const __nv_bfloat16*)d_in[0];
  const __nv_bfloat16* wqkv = (const __nv_bfloat16*)d_in[1];
  const __nv_bfloat16* wo = (const __nv_bfloat16*)d_in[2];
  void* fn = nullptr;
  cudaDriverEntryPointQueryResult st;
  cudaGetDriverEntryPoint("cuTensorMapEncodeTiled", &fn, cudaEnableDefault, &st);
  EncodeFn enc = (EncodeFn)fn;
  void* scp = nullptr;
  cudaGetSymbolAddress(&scp, g_scratch);
  Maps tm;
  { const cuuint64_t d[3] = {640, 1024, 2}, s[2] = {2560, 1280}; const cuuint32_t b[3] = {64, 128, 1}; make_map(enc, &tm.x, x, d, s, b, CU_TENSOR_MAP_SWIZZLE_128B); }
  { const cuuint64_t d[3] = {640, 640, 3}, s[2] = {3840, 1280}; const cuuint32_t b[3] = {64, 16, 3}; make_map(enc, &tm.w, wqkv, d, s, b, CU_TENSOR_MAP_SWIZZLE_128B); }
  { const cuuint64_t d[3] = {640, 640, 3}, s[2] = {3840, 1280}; const cuuint32_t b[3] = {16, 16, 3}; make_map(enc, &tm.wr, wqkv, d, s, b, CU_TENSOR_MAP_SWIZZLE_32B); }
  { const cuuint64_t d[3] = {640, 640, 3}, s[2] = {3840, 1280}; const cuuint32_t b[3] = {16, 16, 1}; make_map(enc, &tm.wv, wqkv, d, s, b, CU_TENSOR_MAP_SWIZZLE_32B); }
  { const cuuint64_t d[3] = {32, 640, 20}, s[2] = {1280, 64}; const cuuint32_t b[3] = {32, 80, 2}; make_map(enc, &tm.wo, wo, d, s, b, CU_TENSOR_MAP_SWIZZLE_64B); }
  { const cuuint64_t d[3] = {640, 640, 1}, s[2] = {1280, 819200}; const cuuint32_t b[3] = {16, 80, 1}; make_map(enc, &tm.wor, wo, d, s, b, CU_TENSOR_MAP_SWIZZLE_64B); }
  { const cuuint64_t d[3] = {1536, 640, 1}, s[2] = {3072, 1966080}; const cuuint32_t b[3] = {32, 128, 1};
    make_map(enc, &tm.gate, d_in[5], d, s, b, CU_TENSOR_MAP_SWIZZLE_64B); make_map(enc, &tm.up, d_in[6], d, s, b, CU_TENSOR_MAP_SWIZZLE_64B); }
  { const cuuint64_t d[3] = {640, 1536, 1}, s[2] = {1280, 1966080}; const cuuint32_t b[3] = {8, 128, 1}; make_map(enc, &tm.down, d_in[7], d, s, b, CU_TENSOR_MAP_SWIZZLE_NONE); }
  cudaFuncSetAttribute(fused_kernel, cudaFuncAttributeMaxDynamicSharedMemorySize, SMEM_BYTES);
  fused_kernel<<<128, 512, SMEM_BYTES, cudaStreamPerThread>>>(x, wqkv, wo, (const __nv_bfloat16*)d_in[4], (const __nv_bfloat16*)d_in[5],
                                                              (const __nv_bfloat16*)d_in[6], (const __nv_bfloat16*)d_in[7], (__nv_bfloat16*)d_out, (Scratch*)scp, tm);
}
```

```cpp
#include <cuda_runtime.h>
#include <cuda_bf16.h>
#include <cuda.h>
#include <stdint.h>

#define PFW_NS 50
#define PFW_N 14
#define ACT_NS 100
#define KEY_NS 0
#define AUX_NS 50
#define REG_P 72
#define REG_C 184
#define LEAD 1
#define HK_IT 1
#define F_PER 2
#define F_MAX 8
#define HOLD 2
#define AK 3
#define NSPLIT 3
#define THR_END 4
#define BOUNDED 0
#define TLIGHT 0
#define ATOM2 1
#define LAG 4
#define OV 2
#define O_UNROLL 1
#define PRIO 7
#define SPLITB 1
#define GPAD 3328

namespace {

constexpr int SLOT    = 49152;
constexpr int OFF_O   = 122880;
constexpr int OFF_W2  = 4 * SLOT;
constexpr int OFF_CS  = OFF_W2 + 24576;
constexpr int OFF_RS  = OFF_CS + 3840;
constexpr int OFF_MN  = OFF_RS + 576;
constexpr int OFF_WR  = OFF_MN + 1024;
constexpr int OFF_RED = OFF_CS;
constexpr int OFF_HN  = OFF_CS + 2048;
constexpr int OFF_PT  = OFF_WR + 352;
constexpr int OFF_BAR = OFF_PT + 768;
constexpr int SMEM_BYTES = OFF_BAR + 424 + 384;
constexpr uint32_t D0 = 1024 >> 4;
constexpr int OUNR = O_UNROLL;
constexpr uint32_t SENT = 0xFFFFFFFFu;
constexpr int SPIN_MAX = 1 << 20;

struct Glob {
  uint4 cand[128][8][24];
  uint32_t act[768];
  uint32_t pad[GPAD];
};
constexpr int GLOB_PER_CTA = sizeof(Glob) / 16 / 128;
static_assert(GLOB_PER_CTA * 128 * 16 == sizeof(Glob), "glob size");
struct Own {
  uint4 halo[5][32];
  uint4 st1[32];
  uint2 cs[32];
  uint4 st2[16];
  uint4 cnt[8];
};
struct Scratch {
  Glob x;
  Own own[128];
  uint4 o[32][8][640];
  uint32_t epoch[128];
};
__device__ __align__(128) Scratch g_scratch;
#define g_x (sc->x)
#define g_own (sc->own)
#define g_o (sc->o)
#define g_epoch (sc->epoch)
#define TS(i)

__device__ __forceinline__ void mbar_init(uint32_t bar, uint32_t cnt) { asm volatile("mbarrier.init.shared::cta.b64 [%0], %1;" :: "r"(bar), "r"(cnt) : "memory"); }
__device__ __forceinline__ void mbar_expect_tx(uint32_t bar, uint32_t bytes) { asm volatile("mbarrier.arrive.expect_tx.shared::cta.b64 _, [%0], %1;" :: "r"(bar), "r"(bytes) : "memory"); }
__device__ __forceinline__ void mbar_arrive(uint32_t bar) { asm volatile("mbarrier.arrive.shared::cta.b64 _, [%0];" :: "r"(bar) : "memory"); }
__device__ __forceinline__ void mbar_arrive_cta(uint32_t bar, uint32_t cta) {
  asm volatile("{\n.reg .b32 ra;\nmapa.shared::cluster.u32 ra, %0, %1;\nmbarrier.arrive.shared::cluster.b64 _, [ra];\n}\n" :: "r"(bar), "r"(cta) : "memory");
}
__device__ __forceinline__ void mbar_wait(uint32_t bar, uint32_t parity) {
  asm volatile("{\n.reg .pred p;\nW:\nmbarrier.try_wait.parity.shared::cta.b64 p, [%0], %1;\n@!p bra.uni W;\n}\n" :: "r"(bar), "r"(parity) : "memory");
}
__device__ __forceinline__ void tma_3d(uint32_t dst, const void* tm, uint32_t bar, int c0, int c1, int c2) {
  asm volatile("cp.async.bulk.tensor.3d.shared::cluster.global.mbarrier::complete_tx::bytes [%0], [%1, {%3, %4, %5}], [%2];" :: "r"(dst), "l"(tm), "r"(bar), "r"(c0), "r"(c1), "r"(c2) : "memory");
}
__device__ __forceinline__ void tma_3d_mc(uint32_t dst, const void* tm, uint32_t bar, int c0, int c1, int c2) {
  asm volatile("cp.async.bulk.tensor.3d.shared::cluster.global.mbarrier::complete_tx::bytes.multicast::cluster [%0], [%1, {%3, %4, %5}], [%2], %6;" :: "r"(dst), "l"(tm), "r"(bar), "r"(c0), "r"(c1), "r"(c2), "h"((uint16_t)3) : "memory");
}
__device__ __forceinline__ void wgmma_fence() { asm volatile("wgmma.fence.sync.aligned;" ::: "memory"); }
__device__ __forceinline__ void wgmma_commit() { asm volatile("wgmma.commit_group.sync.aligned;" ::: "memory"); }
template <int N> __device__ __forceinline__ void wgmma_wait() { asm volatile("wgmma.wait_group.sync.aligned %0;" :: "n"(N) : "memory"); }
__device__ __forceinline__ uint64_t make_desc(uint32_t addr, uint32_t lbo, uint32_t sbo, uint32_t swz) {
  return (uint64_t)(((addr & 0x3FFFF) >> 4) | ((lbo >> 4) << 16)) | ((uint64_t)((sbo >> 4) | (swz << 30)) << 32);
}
__device__ __forceinline__ void bar_sync(int id, int n) { asm volatile("bar.sync %0, %1;" :: "r"(id), "r"(n) : "memory"); }
__device__ __forceinline__ void st_pkt(void* p, uint32_t a, uint32_t b, uint32_t c, uint32_t d) {
  asm volatile("st.relaxed.gpu.v4.u32 [%0], {%1, %2, %3, %4};" :: "l"(p), "r"(a), "r"(b), "r"(c), "r"(d) : "memory");
}
__device__ __forceinline__ uint4 ldg_pkt(const void* p) {
  uint4 v; asm volatile("ld.relaxed.gpu.global.v4.u32 {%0, %1, %2, %3}, [%4];" : "=r"(v.x), "=r"(v.y), "=r"(v.z), "=r"(v.w) : "l"(p) : "memory"); return v;
}
__device__ __forceinline__ void stg_pkt(void* p, uint32_t a, uint32_t b, uint32_t c, uint32_t d) {
  asm volatile("st.relaxed.gpu.global.v4.u32 [%0], {%1, %2, %3, %4};" :: "l"(p), "r"(a), "r"(b), "r"(c), "r"(d) : "memory");
}
__device__ __forceinline__ uint32_t ldg_rlx32(const void* p) { uint32_t v; asm volatile("ld.relaxed.gpu.global.u32 %0, [%1];" : "=r"(v) : "l"(p) : "memory"); return v; }
__device__ __forceinline__ uint2 ldg_rlx64(const void* p) { uint2 v; asm volatile("ld.relaxed.gpu.global.v2.u32 {%0, %1}, [%2];" : "=r"(v.x), "=r"(v.y) : "l"(p) : "memory"); return v; }
__device__ __forceinline__ uint32_t pin(uint32_t v) { asm volatile("" : "+r"(v)); return v; }
__device__ __forceinline__ uint64_t mk64(uint32_t lo, uint32_t hi) { return ((uint64_t)hi << 32) | lo; }
__device__ __forceinline__ uint32_t holdu(uint32_t v) { return __shfl_sync(0xffffffffu, v, threadIdx.x & 31); }
template <class T> __device__ __forceinline__ T* hold(T* p) { return (T*)__shfl_sync(0xffffffffu, (unsigned long long)p, threadIdx.x & 31); }
__device__ __forceinline__ void stg128_if(bool q, void* p, const uint4& v) {
  asm volatile("{\n.reg .pred q;\nsetp.ne.u32 q, %5, 0;\n@q st.global.v4.u32 [%0], {%1, %2, %3, %4};\n}\n" :: "l"(p), "r"(v.x), "r"(v.y), "r"(v.z), "r"(v.w), "r"((int)q) : "memory");
}
template <class T> __device__ __forceinline__ T* pin(T* p) { asm volatile("" : "+l"(p)); return p; }
__device__ __forceinline__ void stg_rlx32(void* p, uint32_t v) { asm volatile("st.relaxed.gpu.global.u32 [%0], %1;" :: "l"(p), "r"(v) : "memory"); }
__device__ __forceinline__ void stg_rlx64(void* p, uint32_t a, uint32_t b) { asm volatile("st.relaxed.gpu.global.v2.u32 [%0], {%1, %2};" :: "l"(p), "r"(a), "r"(b) : "memory"); }
__device__ __forceinline__ uint4 ldsm4(uint32_t a) { uint4 v; asm volatile("ldmatrix.sync.aligned.m8n8.x4.shared.b16 {%0, %1, %2, %3}, [%4];" : "=r"(v.x), "=r"(v.y), "=r"(v.z), "=r"(v.w) : "r"(a) : "memory"); return v; }
__device__ __forceinline__ void ldsm4_if(uint4& v, uint32_t a, int off, bool p) {
  asm volatile("{\n.reg .pred q;\nsetp.ne.u32 q, %5, 0;\n@q ldmatrix.sync.aligned.m8n8.x4.shared.b16 {%0, %1, %2, %3}, [%4];\n}\n"
               : "+r"(v.x), "+r"(v.y), "+r"(v.z), "+r"(v.w) : "r"(a + off), "r"((int)p) : "memory");
}
__device__ __forceinline__ uint4 ldsm4t(uint32_t a) { uint4 v; asm volatile("ldmatrix.sync.aligned.m8n8.x4.trans.shared.b16 {%0, %1, %2, %3}, [%4];" : "=r"(v.x), "=r"(v.y), "=r"(v.z), "=r"(v.w) : "r"(a) : "memory"); return v; }
__device__ __forceinline__ void stsm4(uint32_t a, uint32_t x, uint32_t y, uint32_t z, uint32_t w) { asm volatile("stmatrix.sync.aligned.m8n8.x4.shared.b16 [%0], {%1, %2, %3, %4};" :: "r"(a), "r"(x), "r"(y), "r"(z), "r"(w) : "memory"); }
__device__ __forceinline__ void mma_acc(float (&c)[4], const uint4& a, uint32_t b0, uint32_t b1) {
  asm("mma.sync.aligned.m16n8k16.row.col.f32.bf16.bf16.f32 {%0,%1,%2,%3}, {%4,%5,%6,%7}, {%8,%9}, {%0,%1,%2,%3};"
      : "+f"(c[0]), "+f"(c[1]), "+f"(c[2]), "+f"(c[3]) : "r"(a.x), "r"(a.y), "r"(a.z), "r"(a.w), "r"(b0), "r"(b1));
}
__device__ __forceinline__ uint4 lds128(uint32_t a) { uint4 v; asm volatile("ld.shared.v4.u32 {%0, %1, %2, %3}, [%4];" : "=r"(v.x), "=r"(v.y), "=r"(v.z), "=r"(v.w) : "r"(a) : "memory"); return v; }
__device__ __forceinline__ float2 lds64f(uint32_t a) { float2 v; asm volatile("ld.shared.v2.f32 {%0, %1}, [%2];" : "=f"(v.x), "=f"(v.y) : "r"(a)); return v; }
__device__ __forceinline__ float lds32f(uint32_t a) { float v; asm volatile("ld.shared.f32 %0, [%1];" : "=f"(v) : "r"(a)); return v; }
__device__ __forceinline__ void sts32f(uint32_t a, float v) { asm volatile("st.shared.f32 [%0], %1;" :: "r"(a), "f"(v) : "memory"); }
__device__ __forceinline__ uint32_t pack_bf16(float lo, float hi) { uint32_t r; asm("cvt.rn.bf16x2.f32 %0, %1, %2;" : "=r"(r) : "f"(hi), "f"(lo)); return r; }
__device__ __forceinline__ float bf_lo(uint32_t v) { return __uint_as_float(v << 16); }
__device__ __forceinline__ float bf_hi(uint32_t v) { return __uint_as_float(v & 0xffff0000u); }
__device__ __forceinline__ uint32_t movm(uint32_t a) { uint32_t d; asm("movmatrix.sync.aligned.m8n8.trans.b16 %0, %1;" : "=r"(d) : "r"(a)); return d; }
__device__ __forceinline__ float ex2(float x) { float y; asm("ex2.approx.ftz.f32 %0, %1;" : "=f"(y) : "f"(x)); return y; }
__device__ __forceinline__ float rsq(float x) { float y; asm("rsqrt.approx.ftz.f32 %0, %1;" : "=f"(y) : "f"(x)); return y; }
__device__ __forceinline__ float rcp(float x) { float y; asm("rcp.approx.ftz.f32 %0, %1;" : "=f"(y) : "f"(x)); return y; }
__device__ __forceinline__ bool elect() { uint32_t p; asm volatile("{\n.reg .pred q;\nelect.sync _|q, 0xffffffff;\nselp.u32 %0, 1, 0, q;\n}\n" : "=r"(p)); return p; }
__device__ __forceinline__ void pf_l2(const void* p) { asm volatile("prefetch.global.L2 [%0];" :: "l"(p)); }
__device__ __forceinline__ bool anyw(bool p) { return __any_sync(0xffffffffu, p); }
__device__ __forceinline__ float shx(float v, int m) { return __shfl_xor_sync(0xffffffffu, v, m); }
__device__ __forceinline__ void mma_k24(float (&c)[4], uint32_t a0, uint32_t a1, uint32_t a2, uint32_t a3, uint32_t b0, uint32_t b1,
                                        uint32_t e0, uint32_t e1, uint32_t f0) {
  asm("mma.sync.aligned.m16n8k16.row.col.f32.bf16.bf16.f32 {%0,%1,%2,%3}, {%4,%5,%6,%7}, {%8,%9}, {%10,%10,%10,%10};"
      : "=f"(c[0]), "=f"(c[1]), "=f"(c[2]), "=f"(c[3]) : "r"(a0), "r"(a1), "r"(a2), "r"(a3), "r"(b0), "r"(b1), "f"(0.f));
  asm("mma.sync.aligned.m16n8k8.row.col.f32.bf16.bf16.f32 {%0,%1,%2,%3}, {%4,%5}, {%6}, {%0,%1,%2,%3};"
      : "+f"(c[0]), "+f"(c[1]), "+f"(c[2]), "+f"(c[3]) : "r"(e0), "r"(e1), "r"(f0));
}
__device__ __forceinline__ uint32_t ord_key(float r) { uint32_t u = __float_as_uint(r); return u ^ ((uint32_t)((int32_t)u >> 31) | 0x80000000u); }

__device__ __forceinline__ void wgmma_n64hi_ss(float (&d)[120], uint64_t da, uint64_t db, int scale_d) {
  asm volatile("{\n.reg .pred p;\nsetp.ne.b32 p, %34, 0;\n"
    "wgmma.mma_async.sync.aligned.m64n64k16.f32.bf16.bf16 "
    "{%0, %1, %2, %3, %4, %5, %6, %7, %8, %9, %10, %11, %12, %13, %14, %15, "
    "%16, %17, %18, %19, %20, %21, %22, %23, %24, %25, %26, %27, %28, %29, %30, %31}, "
    "%32, %33, p, 1, 1, 0, 1;\n}\n"
    : "+f"(d[88]), "+f"(d[89]), "+f"(d[90]), "+f"(d[91]), "+f"(d[92]), "+f"(d[93]), "+f"(d[94]), "+f"(d[95]),
      "+f"(d[96]), "+f"(d[97]), "+f"(d[98]), "+f"(d[99]), "+f"(d[100]), "+f"(d[101]), "+f"(d[102]), "+f"(d[103]),
      "+f"(d[104]), "+f"(d[105]), "+f"(d[106]), "+f"(d[107]), "+f"(d[108]), "+f"(d[109]), "+f"(d[110]), "+f"(d[111]),
      "+f"(d[112]), "+f"(d[113]), "+f"(d[114]), "+f"(d[115]), "+f"(d[116]), "+f"(d[117]), "+f"(d[118]), "+f"(d[119])
    : "l"(da), "l"(db), "r"(scale_d));
}
__device__ __forceinline__ void wgmma_n176lo_ss(float (&d)[120], uint64_t da, uint64_t db, int scale_d) {
  asm volatile("{\n.reg .pred p;\nsetp.ne.b32 p, %90, 0;\n"
    "wgmma.mma_async.sync.aligned.m64n176k16.f32.bf16.bf16 "
    "{%0, %1, %2, %3, %4, %5, %6, %7, %8, %9, %10, %11, %12, %13, %14, %15, "
    "%16, %17, %18, %19, %20, %21, %22, %23, %24, %25, %26, %27, %28, %29, %30, %31, "
    "%32, %33, %34, %35, %36, %37, %38, %39, %40, %41, %42, %43, %44, %45, %46, %47, "
    "%48, %49, %50, %51, %52, %53, %54, %55, %56, %57, %58, %59, %60, %61, %62, %63, "
    "%64, %65, %66, %67, %68, %69, %70, %71, %72, %73, %74, %75, %76, %77, %78, %79, "
    "%80, %81, %82, %83, %84, %85, %86, %87}, "
    "%88, %89, p, 1, 1, 0, 1;\n}\n"
    : "+f"(d[0]), "+f"(d[1]), "+f"(d[2]), "+f"(d[3]), "+f"(d[4]), "+f"(d[5]), "+f"(d[6]), "+f"(d[7]),
      "+f"(d[8]), "+f"(d[9]), "+f"(d[10]), "+f"(d[11]), "+f"(d[12]), "+f"(d[13]), "+f"(d[14]), "+f"(d[15]),
      "+f"(d[16]), "+f"(d[17]), "+f"(d[18]), "+f"(d[19]), "+f"(d[20]), "+f"(d[21]), "+f"(d[22]), "+f"(d[23]),
      "+f"(d[24]), "+f"(d[25]), "+f"(d[26]), "+f"(d[27]), "+f"(d[28]), "+f"(d[29]), "+f"(d[30]), "+f"(d[31]),
      "+f"(d[32]), "+f"(d[33]), "+f"(d[34]), "+f"(d[35]), "+f"(d[36]), "+f"(d[37]), "+f"(d[38]), "+f"(d[39]),
      "+f"(d[40]), "+f"(d[41]), "+f"(d[42]), "+f"(d[43]), "+f"(d[44]), "+f"(d[45]), "+f"(d[46]), "+f"(d[47]),
      "+f"(d[48]), "+f"(d[49]), "+f"(d[50]), "+f"(d[51]), "+f"(d[52]), "+f"(d[53]), "+f"(d[54]), "+f"(d[55]),
      "+f"(d[56]), "+f"(d[57]), "+f"(d[58]), "+f"(d[59]), "+f"(d[60]), "+f"(d[61]), "+f"(d[62]), "+f"(d[63]),
      "+f"(d[64]), "+f"(d[65]), "+f"(d[66]), "+f"(d[67]), "+f"(d[68]), "+f"(d[69]), "+f"(d[70]), "+f"(d[71]),
      "+f"(d[72]), "+f"(d[73]), "+f"(d[74]), "+f"(d[75]), "+f"(d[76]), "+f"(d[77]), "+f"(d[78]), "+f"(d[79]),
      "+f"(d[80]), "+f"(d[81]), "+f"(d[82]), "+f"(d[83]), "+f"(d[84]), "+f"(d[85]), "+f"(d[86]), "+f"(d[87])
    : "l"(da), "l"(db), "r"(scale_d));
}
__device__ __forceinline__ void wgmma_n64hi_rk(float (&d)[120], uint32_t a0, uint32_t a1, uint32_t a2, uint32_t a3, uint64_t db, int scale_d) {
  asm volatile("{\n.reg .pred p;\nsetp.ne.b32 p, %37, 0;\n"
    "wgmma.mma_async.sync.aligned.m64n64k16.f32.bf16.bf16 "
    "{%0, %1, %2, %3, %4, %5, %6, %7, %8, %9, %10, %11, %12, %13, %14, %15, "
    "%16, %17, %18, %19, %20, %21, %22, %23, %24, %25, %26, %27, %28, %29, %30, %31}, "
    "{%32, %33, %34, %35}, %36, p, 1, 1, 0;\n}\n"
    : "+f"(d[88]), "+f"(d[89]), "+f"(d[90]), "+f"(d[91]), "+f"(d[92]), "+f"(d[93]), "+f"(d[94]), "+f"(d[95]),
      "+f"(d[96]), "+f"(d[97]), "+f"(d[98]), "+f"(d[99]), "+f"(d[100]), "+f"(d[101]), "+f"(d[102]), "+f"(d[103]),
      "+f"(d[104]), "+f"(d[105]), "+f"(d[106]), "+f"(d[107]), "+f"(d[108]), "+f"(d[109]), "+f"(d[110]), "+f"(d[111]),
      "+f"(d[112]), "+f"(d[113]), "+f"(d[114]), "+f"(d[115]), "+f"(d[116]), "+f"(d[117]), "+f"(d[118]), "+f"(d[119])
    : "r"(a0), "r"(a1), "r"(a2), "r"(a3), "l"(db), "r"(scale_d));
}
__device__ __forceinline__ void wgmma_n176lo_rk(float (&d)[120], uint32_t a0, uint32_t a1, uint32_t a2, uint32_t a3, uint64_t db, int scale_d) {
  asm volatile("{\n.reg .pred p;\nsetp.ne.b32 p, %93, 0;\n"
    "wgmma.mma_async.sync.aligned.m64n176k16.f32.bf16.bf16 "
    "{%0, %1, %2, %3, %4, %5, %6, %7, %8, %9, %10, %11, %12, %13, %14, %15, "
    "%16, %17, %18, %19, %20, %21, %22, %23, %24, %25, %26, %27, %28, %29, %30, %31, "
    "%32, %33, %34, %35, %36, %37, %38, %39, %40, %41, %42, %43, %44, %45, %46, %47, "
    "%48, %49, %50, %51, %52, %53, %54, %55, %56, %57, %58, %59, %60, %61, %62, %63, "
    "%64, %65, %66, %67, %68, %69, %70, %71, %72, %73, %74, %75, %76, %77, %78, %79, "
    "%80, %81, %82, %83, %84, %85, %86, %87}, "
    "{%88, %89, %90, %91}, %92, p, 1, 1, 0;\n}\n"
    : "+f"(d[0]), "+f"(d[1]), "+f"(d[2]), "+f"(d[3]), "+f"(d[4]), "+f"(d[5]), "+f"(d[6]), "+f"(d[7]),
      "+f"(d[8]), "+f"(d[9]), "+f"(d[10]), "+f"(d[11]), "+f"(d[12]), "+f"(d[13]), "+f"(d[14]), "+f"(d[15]),
      "+f"(d[16]), "+f"(d[17]), "+f"(d[18]), "+f"(d[19]), "+f"(d[20]), "+f"(d[21]), "+f"(d[22]), "+f"(d[23]),
      "+f"(d[24]), "+f"(d[25]), "+f"(d[26]), "+f"(d[27]), "+f"(d[28]), "+f"(d[29]), "+f"(d[30]), "+f"(d[31]),
      "+f"(d[32]), "+f"(d[33]), "+f"(d[34]), "+f"(d[35]), "+f"(d[36]), "+f"(d[37]), "+f"(d[38]), "+f"(d[39]),
      "+f"(d[40]), "+f"(d[41]), "+f"(d[42]), "+f"(d[43]), "+f"(d[44]), "+f"(d[45]), "+f"(d[46]), "+f"(d[47]),
      "+f"(d[48]), "+f"(d[49]), "+f"(d[50]), "+f"(d[51]), "+f"(d[52]), "+f"(d[53]), "+f"(d[54]), "+f"(d[55]),
      "+f"(d[56]), "+f"(d[57]), "+f"(d[58]), "+f"(d[59]), "+f"(d[60]), "+f"(d[61]), "+f"(d[62]), "+f"(d[63]),
      "+f"(d[64]), "+f"(d[65]), "+f"(d[66]), "+f"(d[67]), "+f"(d[68]), "+f"(d[69]), "+f"(d[70]), "+f"(d[71]),
      "+f"(d[72]), "+f"(d[73]), "+f"(d[74]), "+f"(d[75]), "+f"(d[76]), "+f"(d[77]), "+f"(d[78]), "+f"(d[79]),
      "+f"(d[80]), "+f"(d[81]), "+f"(d[82]), "+f"(d[83]), "+f"(d[84]), "+f"(d[85]), "+f"(d[86]), "+f"(d[87])
    : "r"(a0), "r"(a1), "r"(a2), "r"(a3), "l"(db), "r"(scale_d));
}
__device__ __forceinline__ void wgmma_n80_rs(float (&d)[40], uint32_t a0, uint32_t a1, uint32_t a2, uint32_t a3, uint64_t db, int scale_d) {
  asm volatile("{\n.reg .pred p;\nsetp.ne.b32 p, %45, 0;\n"
    "wgmma.mma_async.sync.aligned.m64n80k16.f32.bf16.bf16 "
    "{%0, %1, %2, %3, %4, %5, %6, %7, %8, %9, %10, %11, %12, %13, %14, %15, "
    "%16, %17, %18, %19, %20, %21, %22, %23, %24, %25, %26, %27, %28, %29, %30, %31, "
    "%32, %33, %34, %35, %36, %37, %38, %39}, "
    "{%40, %41, %42, %43}, %44, p, 1, 1, 1;\n}\n"
    : "+f"(d[0]), "+f"(d[1]), "+f"(d[2]), "+f"(d[3]), "+f"(d[4]), "+f"(d[5]), "+f"(d[6]), "+f"(d[7]),
      "+f"(d[8]), "+f"(d[9]), "+f"(d[10]), "+f"(d[11]), "+f"(d[12]), "+f"(d[13]), "+f"(d[14]), "+f"(d[15]),
      "+f"(d[16]), "+f"(d[17]), "+f"(d[18]), "+f"(d[19]), "+f"(d[20]), "+f"(d[21]), "+f"(d[22]), "+f"(d[23]),
      "+f"(d[24]), "+f"(d[25]), "+f"(d[26]), "+f"(d[27]), "+f"(d[28]), "+f"(d[29]), "+f"(d[30]), "+f"(d[31]),
      "+f"(d[32]), "+f"(d[33]), "+f"(d[34]), "+f"(d[35]), "+f"(d[36]), "+f"(d[37]), "+f"(d[38]), "+f"(d[39])
    : "r"(a0), "r"(a1), "r"(a2), "r"(a3), "l"(db), "r"(scale_d));
}
__device__ __forceinline__ void wgmma_n80_ss(float (&d)[40], uint64_t da, uint64_t db, int scale_d) {
  asm volatile("{\n.reg .pred p;\nsetp.ne.b32 p, %42, 0;\n"
    "wgmma.mma_async.sync.aligned.m64n80k16.f32.bf16.bf16 "
    "{%0, %1, %2, %3, %4, %5, %6, %7, %8, %9, %10, %11, %12, %13, %14, %15, "
    "%16, %17, %18, %19, %20, %21, %22, %23, %24, %25, %26, %27, %28, %29, %30, %31, "
    "%32, %33, %34, %35, %36, %37, %38, %39}, "
    "%40, %41, p, 1, 1, 0, 1;\n}\n"
    : "+f"(d[0]), "+f"(d[1]), "+f"(d[2]), "+f"(d[3]), "+f"(d[4]), "+f"(d[5]), "+f"(d[6]), "+f"(d[7]),
      "+f"(d[8]), "+f"(d[9]), "+f"(d[10]), "+f"(d[11]), "+f"(d[12]), "+f"(d[13]), "+f"(d[14]), "+f"(d[15]),
      "+f"(d[16]), "+f"(d[17]), "+f"(d[18]), "+f"(d[19]), "+f"(d[20]), "+f"(d[21]), "+f"(d[22]), "+f"(d[23]),
      "+f"(d[24]), "+f"(d[25]), "+f"(d[26]), "+f"(d[27]), "+f"(d[28]), "+f"(d[29]), "+f"(d[30]), "+f"(d[31]),
      "+f"(d[32]), "+f"(d[33]), "+f"(d[34]), "+f"(d[35]), "+f"(d[36]), "+f"(d[37]), "+f"(d[38]), "+f"(d[39])
    : "l"(da), "l"(db), "r"(scale_d));
}

__device__ __forceinline__ constexpr int QT(int t) { return t < 8 ? t : 16 + t; }
__device__ __forceinline__ constexpr int KT(int t) { return t < 8 ? 8 + t : 18 + t; }
__device__ __forceinline__ constexpr int VT(int t) { return t < 8 ? 16 + t : 20 + t; }

struct Maps { CUtensorMap x, w, wr, wv, wo, wor, gate, up, down; };

__global__ void __cluster_dims__(2, 1, 1) __launch_bounds__(512, 1)
fused_kernel(const __nv_bfloat16* __restrict__ x, const __nv_bfloat16* __restrict__ wqkv,
             const __nv_bfloat16* __restrict__ wo, const __nv_bfloat16* __restrict__ w_r, const __nv_bfloat16* __restrict__ w_gate,
             const __nv_bfloat16* __restrict__ w_up, const __nv_bfloat16* __restrict__ w_down, __nv_bfloat16* __restrict__ out,
             Scratch* __restrict__ sc, const __grid_constant__ Maps tm) {
  extern __shared__ __align__(1024) uint8_t smem[];
  const int tid = threadIdx.x, bid = blockIdx.x;
  if ((unsigned)(tid - 128) < 16u) pf_l2((const char*)x + (bid * 16 + tid - 128) * 1280);
  if ((unsigned)(tid - 160) < 15u) pf_l2((const char*)wqkv + (bid * 15 + tid - 160) * 128);
  const int warp = __shfl_sync(0xffffffffu, tid >> 5, 0), lane = tid & 31;
  const uint32_t sb = (uint32_t)__cvta_generic_to_shared(smem);
  const uint32_t bar_full = sb + OFF_BAR, bar_empty = bar_full + 32, bar_aux = bar_full + 64, bar_ffn = bar_full + 72, bar_win = bar_full + 80, bar_tag = bar_full + 88, bar_rst = bar_full + 96 + 296 + 24,
                 bar_o = bar_full + 96, bar_oc = bar_o + 112, bar_st = bar_o + 224, bar_go = bar_o + 248, bar_kv = bar_o + 272, bar_half = bar_o + 296;
  if (warp < 4 && elect()) {
    mbar_init(bar_half + 8 * warp, 1);
    mbar_init(bar_full + 8 * (warp ^ 2), 1);
    mbar_init(bar_empty + 8 * warp, 24);
    mbar_init(bar_aux + 8 * warp, warp == 0 ? 64 : warp == 2 ? 32 : warp == 3 ? 2 : 1);
    asm volatile("fence.mbarrier_init.release.cluster;" ::: "memory");
  }
  asm volatile("barrier.cluster.arrive.relaxed.aligned;" ::: "memory");
  if (warp >= 8 && warp < 12 && elect()) asm volatile("prefetch.tensormap [%0];" :: "l"(&tm.x + (warp - 8)) : "memory");
  const int rank = bid & 1, cl = bid >> 1;
  const int q7 = ((cl - 36) * 37) >> 8;
  const int P = cl < 4 ? 0 : cl < 36 ? (cl - 4) & 7 : cl - 35 - 7 * q7;
  const int g = (cl < 4 ? 4 + cl : cl < 36 ? (cl - 4) >> 3 : 4 + q7);
  const int mt = 2 * P + rank, cid = mt * 8 + g;
  const bool ffn1 = g >= 5;
  const int fj = ffn1 ? mt * 3 + g - 5 : (P * 5 + g) * 2 + rank;
  const int ord = ((g >> 2) ^ P) & 1;
  auto ks_of = [&](int it) { return ord == 0 || it == 0 ? it : it <= 5 ? it + 4 : it - 5; };
  const int godd = g & 1, cm = g * 80 + godd * 16, cr = g * 80 + 64 - godd * 64;
  auto load_w = [&](int ks, uint32_t a, uint32_t bar, int kk) {
    tma_3d_mc(a + 16384 + ((kk + 1) & 3) * 6144, &tm.w, bar, cm, ks * 64 + kk * 16, 0);
    tma_3d_mc(a + 41472 + kk * 2048, &tm.wr, bar, cr, ks * 64 + kk * 16, 0);
    tma_3d_mc(a + 40960 + kk * 2048, &tm.wv, bar, cm + 48, ks * 64 + kk * 16, 2);
  };
  if (warp == 0 && elect()) {
    mbar_expect_tx(bar_half, 32768);
    tma_3d(sb + 2 * SLOT, &tm.x, bar_half, 0, P * 128, rank);
    mbar_expect_tx(bar_full + 16, 16384);
  }
  asm volatile("barrier.cluster.wait.aligned;" ::: "memory");
  if (warp == 0) {
    if (elect()) {
      uint32_t bar = bar_half;
#pragma unroll 1
      for (int kk = rank; kk < 4; kk += 2) { load_w(0, sb + 2 * SLOT, bar, kk); bar = bar_full + 16; }
    }
    asm volatile("bar.arrive 4, 64;" ::: "memory");
  }

  if (warp >= 8) {
    asm volatile("setmaxnreg.dec.sync.aligned.u32 %0;" :: "n"(REG_P));
#define TS_T 0
    if (warp == 8) {
      TS(8);
      bar_sync(4, 64);
      if (elect()) {
        TS(10);
#pragma unroll 1
        for (int it = 1; it < 10; it++) {
          const int s = (it + 2) & 3, ks = ks_of(it);
          const uint32_t full = bar_full + 8 * s, a = sb + s * SLOT;
          uint32_t bar = it < NSPLIT ? bar_half + 8 * it : full;
          if (it >= 4) mbar_wait(full + 32, ((it >> 2) - 1) & 1);
          if (it >= 2 && it < THR_END) mbar_wait(bar_full + 8 * (it & 3), 0);
          if (it < NSPLIT) mbar_expect_tx(bar, 32768);
          mbar_expect_tx(full, it < NSPLIT ? 16384 : SLOT);
          tma_3d(a, &tm.x, bar, ks * 64, P * 128, rank);
#pragma unroll 1
          for (int kk = rank; kk < 4; kk += 2) { load_w(ks, a, bar, kk); bar = full; }
          TS(12 + it);
          if ((it >> 1) == 2) {
            mbar_wait(bar_rst, 0);
            asm volatile("cp.async.bulk.global.shared::cta.bulk_group [%0], [%1], %2;\ncp.async.bulk.commit_group;"
                         :: "l"(it == 4 ? (uint4*)(g_own + cid) : (uint4*)&g_x + cid * GLOB_PER_CTA), "r"(sb + OFF_CS), "r"(it == 4 ? (int)sizeof(Own) : GLOB_PER_CTA * 16) : "memory");
          }
          if (it == 6) { asm volatile("cp.async.bulk.wait_group 0;" ::: "memory"); mbar_arrive(bar_tag); }
        }
        mbar_expect_tx(bar_ffn, ffn1 ? 81920 : 24576);
        int fjn = 0;
#pragma unroll 1
        for (int it = 9; it < 17; it++) {
          if (it >= 13) { mbar_wait(bar_oc + 8 * (it - 13), 0); mbar_wait(bar_oc + 56 + 8 * (it - 13), 0); }
          else if (it >= 10) {
            const uint32_t full = bar_full + 8 * (it - 10);
            const int g0 = 3 * (it - 10), g1 = min(g0 + 3, 8);
            mbar_wait(full + 32, it < 12);
            mbar_expect_tx(full, (g1 - g0) * 12800);
#pragma unroll 1
            for (int gp = g0 + ((g0 ^ rank) & 1); gp < g1; gp += 2) {
              tma_3d_mc(sb + gp * 15360, &tm.wo, full, 0, gp * 80, g * 2);
              tma_3d_mc(sb + gp * 15360 + 10240, &tm.wor, full, 512 + g * 16, gp * 80, 0);
            }
          }
          const int j1 = ffn1 ? (it >= 13 ? 2 * it - 22 : min(it - 8, 3)) : (it >= 13 ? 12 : min((it - 8) * F_PER, F_MAX));
#pragma unroll 1
          for (; fjn < j1; fjn++) {
            const int j = fjn < 3 ? fjn + 7 : fjn - 3;
            if (ffn1) tma_3d(sb + (j < 7 ? 0 : OFF_W2 - 57344) + j * 8192, j < 5 ? &tm.gate : &tm.up, bar_ffn, fj * 32, (j < 5 ? j : j - 5) * 128, 0);
            else tma_3d(sb + OFF_W2 + fjn * 2048, &tm.down, bar_ffn, fj * 8, fjn * 128, 0);
          }
        }
        TS(11);
      }
#undef TS_T
#define TS_T 64
    } else if (warp >= 12) {
      const int l7 = lane & 7, j = warp - 12, ch = min((P >> 1) * 4 + rank * 2 + (j >> 1), 14);
      const uint32_t sxo = ((g & 3) * 32 + j * 8 + l7) * 128 + (((lane >> 3) ^ l7) * 16);
      const uint32_t swo = ch < 12 ? 16384 + (lane >> 4) * 6144 + (ch >> 2) * 2048 + (lane & 15) * 128 + ((((ch & 3) * 2 + (j & 1)) ^ l7) * 16)
                                   : 41472 + (lane >> 4) * 2048 + (ch - 12) * 512 + (lane & 15) * 32 + (((j & 1) ^ (l7 >> 2)) * 16);
      float ps = 0.f, pq = 0.f, pq1 = 0.f, pc = 0.f;
      uint32_t tag = 0;
      char* const pp = hold((lane & 1) ? (char*)&g_own[cid].cs[j * 8 + (lane >> 2)] : (char*)&g_own[cid].st1[j * 8 + (lane >> 2)]);
#pragma unroll 1
      for (int it = ord; it < ord + 5; it++) {
        const int sl = (it + 2) & 3;
        if (it == ord + 4) { mbar_wait(bar_tag, 0); tag = __float_as_uint(lds32f(sb + OFF_WR + 324)); }
        if (it < NSPLIT) mbar_wait(bar_half + 8 * it, 0);
        mbar_wait(bar_full + 8 * sl, (it >> 2) & 1);
        TS(it);
        const uint32_t a = sb + sl * SLOT;
        const uint4 v0 = ldsm4(a + sxo), v1 = ldsm4((a + sxo) ^ 64), w0 = ldsm4t(a + swo), w1 = ldsm4t(a + swo + (ch < 12 ? 12288 : 4096));
        if (lane + (int)((v0.x & v1.x & w0.x & w1.x) == 0x7fc17fc1u && (v0.x | v1.x) == 0u) < 2) mbar_arrive_cta(bar_empty + 8 * sl, lane);
        const uint32_t vv[8] = {v0.x, v0.y, v0.z, v0.w, v1.x, v1.y, v1.z, v1.w}, ww[8] = {w0.x, w0.y, w0.z, w0.w, w1.x, w1.y, w1.z, w1.w};
#pragma unroll
        for (int i = 0; i < 8; i++) {
          const float d = bf_lo(vv[i]), e = bf_hi(vv[i]);
          ps += d + e; pq = fmaf(d, d, pq); pq1 = fmaf(e, e, pq1); pc += bf_lo(ww[i]) + bf_hi(ww[i]);
        }
      }
      pq += pq1;
      ps += shx(ps, 1); pq += shx(pq, 1); pc += shx(pc, 1);
      ps += shx(ps, 2); pq += shx(pq, 2); pc += shx(pc, 2);
      if ((lane & 3) == 0) stg_pkt(pp, __float_as_uint(ps), __float_as_uint(pq), tag, 0u);
      if ((lane & 3) == 1) stg_rlx64(pp, __float_as_uint(pc), tag);
      asm volatile("bar.arrive 2, 192;" ::: "memory");
      if (warp == 12) {
        const uint4* const hp = hold(&g_own[max(cid - 16, 0)].halo[0][lane]);
        mbar_wait(bar_aux, 0);
        mbar_wait(bar_go, 0);
        uint4 v[5] = {};
        int guard = SPIN_MAX;
        if (P > 0) {
          do {
#pragma unroll
            for (int i = 0; i < 5; i++) v[i] = ldg_pkt(hp + 32 * i);
          } while (anyw(v[0].x == SENT || v[1].x == SENT || v[2].x == SENT || v[3].x == SENT || v[4].x == SENT) && --guard > 0);
        }
#pragma unroll
        for (int i = 0; i < 5; i++) *(uint4*)(smem + OFF_O + 10240 + i * 512 + lane * 16) = v[i];
        mbar_arrive(bar_kv);
      }
#undef TS_T
#define TS_T 32
    } else if (warp < 11) {
      const int l7 = lane & 7, hk = lane >> 4;
      if (warp == 10 && elect()) {
#pragma unroll 1
        for (int i = 0; i < 36; i++) mbar_init(bar_o + 8 * i, i < 14 || i == 30 ? 1 : i < 34 ? 4 : 128);
      }
      mbar_wait(bar_tag, 0);
      const uint32_t tag = __float_as_uint(lds32f(sb + OFF_WR + 324));
      bar_sync(2, 192);
      TS(0);
      int guard = SPIN_MAX;
      if (warp == 9) {
        const uint4* sp = &g_own[mt * 8].st1[lane];
        const uint4* hp = &g_own[max(mt - 2, 0) * 8 + 3].st1[24 + l7];
        uint4 a[5], b[5];
        bool bad;
        do {
          __nanosleep(AUX_NS);
          bad = false;
#pragma unroll
          for (int i = 0; i < 5; i++) {
            const uint4* q = i < 4 ? sp + i * (sizeof(Own) / 16) : hp;
            a[i] = ldg_pkt(q); b[i] = ldg_pkt(q + 4 * sizeof(Own) / 16);
          }
#pragma unroll
          for (int i = 0; i < 5; i++) bad |= a[i].z != tag || b[i].z != tag;
        } while (anyw(bad) && --guard);
        TS(1);
#pragma unroll
        for (int i = 0; i < 5; i++) {
          const float m = (__uint_as_float(a[i].x) + __uint_as_float(b[i].x)) * (1.f / 640.f);
          const float rs = rsq(fmaxf(fmaf(-m, m, (__uint_as_float(a[i].y) + __uint_as_float(b[i].y)) * (1.f / 640.f)), 0.f) + 1e-5f);
          ((float*)(smem + OFF_RS))[i < 4 ? 8 + lane + 32 * i : l7] = rs;
          const uint32_t mh = pack_bf16(-m, -m);
          const float ml = -m - bf_lo(mh);
          if (i < 4) ((uint2*)(smem + OFF_MN))[lane + 32 * i] = make_uint2(mh, pack_bf16(ml, ml));
        }
      } else {
        const uint4* cp = (const uint4*)g_own[hk * 8 + g].cs + (lane & 15);
        uint4 a[4], b[4];
        bool bad;
        do {
          __nanosleep(AUX_NS);
          bad = false;
#pragma unroll
          for (int i = 0; i < 4; i++) { a[i] = ldg_pkt(cp + i * 32 * sizeof(Own) / 16); b[i] = ldg_pkt(cp + (i * 32 + 16) * sizeof(Own) / 16); }
#pragma unroll
          for (int i = 0; i < 4; i++) bad |= a[i].y != tag || a[i].w != tag || b[i].y != tag || b[i].w != tag;
        } while (anyw(bad) && --guard);
#pragma unroll
        for (int i = 0; i < 4; i++)
          if (i < 3 || lane < 24) {
            const float c0 = __uint_as_float(a[i].x) + __uint_as_float(b[i].x), c1 = __uint_as_float(a[i].z) + __uint_as_float(b[i].z);
            const uint32_t hi = pack_bf16(c0, c1), w0 = pack_bf16(c0, c0 - bf_lo(hi)), w1 = pack_bf16(c1, c1 - bf_hi(hi));
            uint4* const d = (uint4*)(smem + OFF_CS) + 2 * (lane + 32 * i);
            d[0] = make_uint4(w0, w0, 0, 0); d[1] = make_uint4(w1, w1, 0, 0);
          }
        asm volatile("fence.proxy.async.shared::cta;" ::: "memory");
      }
      mbar_arrive(bar_aux);
      TS(2);
      const int fo = warp - 9, wq = fo ? 1 - LEAD : LEAD;
      const uint4* const fp = hold(g_own[mt * 8 + wq * 4].cnt);
      const char* src = hold((const char*)g_o[mt * 2 + wq]);
      if (elect()) {
        const uint32_t bo = bar_o + fo * 56;
#pragma unroll
        for (int i = 0; i < 7; i++) mbar_expect_tx(bo + 8 * i, 10240);
        uint32_t cv = 0, need = 4;
        mbar_wait(OV == 3 ? bar_st + 8 * fo : bar_go + 8 + 8 * fo, 0);
        uint32_t dst = sb + OFF_O + 20480;
#pragma unroll OUNR
        for (int i = 0; i < 7; i++) {
          if (i == g) { src += 10240; need <<= 4; }
          if (!(cv & need)) {
            do { cv = ldg_rlx32(fp); } while (!(cv & need) && --guard > 0);
            asm volatile("fence.proxy.async.global;" ::: "memory");
          }
          if (fo || i == 5 || (OV == 2 && i == 4)) mbar_wait(fo ? bar_oc + 8 * i : i == 4 ? bar_st : bar_st + 8, 0);
          if (i == 0) TS(6);
          asm volatile("cp.async.bulk.shared::cluster.global.mbarrier::complete_tx::bytes [%0], [%1], 10240, [%2];" :: "r"(dst), "l"(src), "r"(bo + 8 * i) : "memory");
          src += 10240; need <<= 4;
          dst += i == 4 ? -61440 : 10240;
        }
      }
#undef TS_T
#define TS_T 96
    } else {
      if ((sb & 0x3FFFF) != D0 * 16) __trap();
#pragma unroll 1
      for (int i = lane; i < 232; i += 32) { const uint32_t f = i < 208 ? SENT : 0u; ((uint4*)(smem + OFF_CS))[i] = make_uint4(f, f, f, f); }
      asm volatile("fence.proxy.async.shared::cta;" ::: "memory");
      if (elect()) mbar_arrive(bar_rst);
      mbar_wait(bar_full + 8 * ((HK_IT + 2) & 3), 0);
      TS(4);
      const uint32_t epoch = ldg_rlx32(g_epoch + cid) + 1;
      uint32_t wv[10];
#pragma unroll
      for (int i = 0; i < 10; i++) wv[i] = __ldg((const uint32_t*)w_r + lane + 32 * i);
      float s = 0.f;
#pragma unroll
      for (int i = 0; i < 10; i++) {
        s += bf_lo(wv[i]) + bf_hi(wv[i]);
        const unsigned u = i < 8 ? lane + 32 * (i - g) : lane + 32 * (i - 7) - g * 8;
        if (i < 8 ? u < 32u : u - 32u < 8u) *(float2*)(smem + OFF_WR + ((u & 3) * 10 + (u >> 2)) * 8) = make_float2(bf_lo(wv[i]), bf_hi(wv[i]));
      }
#pragma unroll
      for (int m = 1; m < 32; m <<= 1) s += shx(s, m);
      *(float2*)(smem + OFF_WR + 320) = make_float2(s, __uint_as_float(epoch * 0x9E3779B8u));
      g_epoch[cid] = epoch;
      TS(3);
      if (elect()) mbar_arrive(bar_tag);
      TS(5);
#pragma unroll 1
      for (int i = 0; i < PFW_N; i++) {
        const int m = (i + 2) >> 2, n = m == 0 ? 50 : 120, t = (m == 0 ? i : (i + 2) & 3) * 32 + lane;
        const char* b = (const char*)(m == 0 ? wo : m == 1 ? w_up : m == 2 ? w_down : w_gate);
        if (t < n) pf_l2(b + (bid * n + t) * 128);
        __nanosleep(PFW_NS);
      }
      const uint4* const kp = hold(g_own[1].cnt);
      const uint4* const cb = hold(&g_x.cand[0][lane >> 2][lane & 3]);
      bar_sync(3, 64);
      uint4 k;
      uint32_t have = SENT;
      int guard = SPIN_MAX;
      while (true) {
        k = ldg_pkt(kp);
        if (ffn1) {
          while (k.x != have && --guard > 0) {
            const uint32_t tk = 2047u - (k.x & 2047u), want = k.x;
            const uint4* q = cb + ((tk >> 8) * 16 + (tk & 1) * 8 + ((tk >> 5) & 7)) * 192;
            const uint4 c0 = ldg_pkt(q), c1 = ldg_pkt(q + 4); const uint2 c2 = ldg_rlx64(q + 8);
            k = ldg_pkt(kp);
            *(uint4*)(smem + OFF_HN + lane * 16) = c0; *(uint4*)(smem + OFF_HN + 512 + lane * 16) = c1; *(uint2*)(smem + OFF_HN + 1024 + lane * 16) = c2;
            have = anyw(c0.x == SENT || c1.x == SENT || c2.x == SENT) ? SENT : want;
          }
        } else if (KEY_NS && k.z != 128u) __nanosleep(KEY_NS);
        if (k.z == 128u || --guard <= 0) break;
      }
      *(uint2*)(smem + OFF_WR + 336) = make_uint2(k.x, k.y);
      mbar_arrive(bar_win);
      TS(7);
    }
#undef TS_T
  } else {
#define TS_T 0
    asm volatile("setmaxnreg.inc.sync.aligned.u32 %0;" :: "n"(REG_C));
    const int wg = warp >> 2, w4 = warp & 3, r = lane >> 2, c = lane & 3;
    float acc[120];
    uint4 xr[5] = {};
    const uint32_t xa = pin(sb + (warp * 16 + (lane & 15)) * 128 + ((lane >> 4) ^ (lane & 7)) * 16);
    const uint32_t zero = __shfl_sync(0xffffffffu, (uint32_t)(uintptr_t)x & 8u, 0);
    const int fol = wg != LEAD;
    const bool first = (P == 0) && (warp == 0);
    const uint32_t kvs = holdu(sb + OFF_O + fol * 10240 + w4 * 2560 + lane * 16);
    uint4* const kvd = hold(warp == 7 ? &g_own[cid].halo[0][lane] : (uint4*)(smem + (warp == 3 ? OFF_O + lane * 16 : kvs - sb + 2560)));
    uint4* const odst = hold(&g_o[mt * 2 + wg][g][w4 * 160]);
    uint4* const ocnt = hold(g_own[mt * 8 + wg * 4].cnt + (lane & zero));
    const uint32_t oinc = holdu((1u << (4 * g)) + (lane & zero));
    const bool in0 = 2 * c <= r, in1 = 2 * c + 1 <= r;
    const uint32_t mL = holdu((in0 ? 0xffffu : 0u) | (in1 ? 0xffff0000u : 0u));
    const float bias0 = __uint_as_float(holdu(first && !in0 ? 0xff800000u : 0u)), bias1 = __uint_as_float(holdu(first && !in1 ? 0xff800000u : 0u));
    const uint32_t stb = sb + OFF_RS + warp * 64, kb0 = holdu(stb + (2 * c + (in0 ? 8 : 0)) * 4), kb1 = holdu(stb + (2 * c + 1 + (in1 ? 8 : 0)) * 4);
    const uint32_t os = sb + OFF_O + (fol ? 0 : 61440) + w4 * 2560, oa = holdu(os + ((lane >> 3) & 1) * 1280 + (lane >> 4) * 128 + (lane & 7) * 16);
    float rlo, rhi, scl0, scl1, sch0, sch1;
    uint32_t m0 = 0, m1 = 0, m2 = 0, m3 = 0;
    const uint32_t mna = pin(sb + OFF_MN + (warp * 16 + r) * 8 + c * 4);
    const int itx = ord == 0 || g == 0 ? g : g < 5 ? g + 5 : g - 4, ity = (ord ? 4 : 8) + (g >> 2);
    uint32_t rel;
    asm volatile("mapa.shared::cluster.u32 %0, %1, %2;" : "=r"(rel) : "r"(bar_empty), "r"(tid & 1));
    const uint32_t xa1 = pin(xa ^ 32), xa2 = pin(xa ^ 64), xa3 = pin(xa ^ 96), xb = pin(xa ^ ((g & 3) * 32));
    const uint32_t da0 = wg * 512;
    const bool rel2 = lane < 2, rel6 = lane < 2 + 2 * (warp & 1);
    mbar_wait(bar_half, 0);
    TS(13);
    wgmma_fence();
#pragma unroll
    for (int it = 0; it < 10; it++) {
      const int s = (it + 2) & 3;
#pragma unroll
      for (int kk = 0; kk < 4; kk++) {
        if (kk == 2 && it > 0) {
          wgmma_commit();
          wgmma_wait<1>();
          const uint32_t ra = ((xr[0].x ^ xr[1].x ^ xr[2].x ^ xr[3].x ^ xr[4].x) & zero) | rel;
          if (it == 1 ? (ord ? rel6 : rel2) : it == 6 ? (ord ? rel2 : rel6) : it < 6 ? rel2 : rel6)
            asm volatile("mbarrier.arrive.shared::cluster.b64 _, [%0];" :: "r"(ra + 8 * ((it + 1) & 3)) : "memory");
        }
        if (kk == 2) {
          ldsm4_if(xr[0], xa, s * SLOT, it == itx); ldsm4_if(xr[1], xa1, s * SLOT, it == itx);
          ldsm4_if(xr[2], xa2, s * SLOT, it == itx); ldsm4_if(xr[3], xa3, s * SLOT, it == itx);
          if ((it & 6) == 4 || it >= 8) ldsm4_if(xr[4], xb, s * SLOT, it == ity);
        }
        if (kk == AK && it == 9) {
          mbar_wait(bar_aux, 0);
          TS(3);
          if (c < 2) {
            m0 = __float_as_uint(lds32f(mna)); m1 = __float_as_uint(lds32f(mna + 64)); m2 = __float_as_uint(lds32f(mna + zero)); m3 = __float_as_uint(lds32f(mna + zero + 64));
          }
          const float qs = 0.22360679774997896f * 1.4426950408889634f;
          rlo = lds32f(stb + (8 + r) * 4); rhi = lds32f(stb + (16 + r) * 4);
          scl0 = lds32f(kb0) * (rlo * qs); scl1 = lds32f(kb1) * (rlo * qs); sch0 = lds32f(kb0 + 32) * (rhi * qs); sch1 = lds32f(kb1 + 32) * (rhi * qs);
          if (!fol) bar_sync(11, 256);
        }
        if (it * 4 + kk == 40 - LAG && fol) {
          asm volatile("bar.arrive 11, 256;" ::: "memory");
          bar_sync(10, 256);
        }
        if (kk == 2 && it < NSPLIT) mbar_wait(bar_full + 8 * s, 0);
        const uint64_t da = mk64(da0 + (D0 + s * (SLOT >> 4) + kk * 2 + (1 << 16)), 0x40000040u);
        wgmma_n64hi_ss(acc, da, mk64(D0 + s * (SLOT >> 4) + 2560 + kk * 128 + (32 << 16), 0xC0000010u), (it | kk) != 0);
        wgmma_n176lo_ss(acc, da, mk64(D0 + s * (SLOT >> 4) + 1024 + ((kk + 1) & 3) * 384 + (128 << 16), 0x40000040u), (it | kk) != 0);
      }
      wgmma_commit();
      if (it < 9) {
        if (it + 1 < NSPLIT) mbar_wait(bar_half + 8 * (it + 1), 0);
        else mbar_wait(bar_full + 8 * ((it + 3) & 3), ((it + 1) >> 2) & 1);
        if (it < 8) TS(14 + it);
      }
    }
    {
      const uint64_t dc = make_desc(D0 * 16 + OFF_CS, 0, 128, 0);
      wgmma_fence();
      wgmma_n64hi_rk(acc, m0, m1, 0u, 0u, dc + 176, 1);
      wgmma_n176lo_rk(acc, m2, m3, 0u, 0u, dc, 1);
      wgmma_commit();
      if (!fol) asm volatile("bar.arrive 10, 256;" ::: "memory");
    }
    wgmma_wait<0>();
#pragma unroll
    for (int i = 0; i < 120; i++) asm volatile("" : "+f"(acc[i]) :: "memory");
    if (fol && lane == 0) mbar_arrive(bar_go);
    TS(2);
    uint32_t Qlo[10], Qhi[10], Klo[10], Khi[10], Vlo[10], Vhi[10];
#define CONV_HI(ROT) _Pragma("unroll") for (int t = 0; t < 10; t++) { \
      const int k = KT((t + ROT) % 10), v = VT((t + ROT) % 10); \
      Khi[t] = pack_bf16(acc[4 * k + 2], acc[4 * k + 3]); \
      Vhi[t] = pack_bf16(acc[4 * v + 2] * rhi, acc[4 * v + 3] * rhi); }
    if (godd) { CONV_HI(8) } else { CONV_HI(0) }
    st_pkt(kvd, Khi[0], Khi[1], Khi[3], Khi[4]);
    st_pkt(kvd + 32, Khi[5], Khi[6], Khi[8], Khi[9]);
    st_pkt(kvd + 64, Khi[2], Khi[7], Vhi[0], Vhi[1]);
    st_pkt(kvd + 96, Vhi[2], Vhi[3], Vhi[4], Vhi[5]);
    st_pkt(kvd + 128, Vhi[6], Vhi[7], Vhi[8], Vhi[9]);
    if (warp < 7) mbar_arrive(bar_kv + ((warp + 1) >> 2) * 8);
#define CONV_LO(ROT) _Pragma("unroll") for (int t = 0; t < 10; t++) { \
      const int q = QT((t + ROT) % 10), k = KT((t + ROT) % 10), v = VT((t + ROT) % 10); \
      Vhi[t] = movm(Vhi[t]); \
      Klo[t] = pack_bf16(acc[4 * k], acc[4 * k + 1]); \
      Vlo[t] = movm(pack_bf16(acc[4 * v] * rlo, acc[4 * v + 1] * rlo)); \
      Qlo[t] = pack_bf16(acc[4 * q], acc[4 * q + 1]); \
      Qhi[t] = pack_bf16(acc[4 * q + 2], acc[4 * q + 3]); }
    if (godd) { CONV_LO(8) } else { CONV_LO(0) }
    const int slot = mt * 8 + warp;
    int guard = SPIN_MAX;
    uint4 pv[5];
    const bool cA = c < 2, nA = r < 4;
    TS(0);
    mbar_wait(bar_go + fol * 8, 0);
    TS(23);
    uint32_t qe[4][2];
    float sl0[4], sl1[4], th0[4], th1[4];
#pragma unroll
    for (int hd = 0; hd < 4; hd++) {
      const int ta = 5 * (hd >> 1) + 3 * (hd & 1), ts = 5 * (hd >> 1) + 2;
      const bool mine = (hd & 1) ? !cA : cA;
      qe[hd][0] = mine ? Qlo[ts] : 0u; qe[hd][1] = mine ? Qhi[ts] : 0u;
      float sl[4], sh[4];
      mma_k24(sl, Qlo[ta], Qhi[ta], Qlo[ta + 1], Qhi[ta + 1], Klo[ta], Klo[ta + 1], qe[hd][0], qe[hd][1], Klo[ts]);
      mma_k24(sh, Qlo[ta], Qhi[ta], Qlo[ta + 1], Qhi[ta + 1], Khi[ta], Khi[ta + 1], qe[hd][0], qe[hd][1], Khi[ts]);
      th0[hd] = (in0 ? sh[2] : sl[2]) * sch0; th1[hd] = (in1 ? sh[3] : sl[3]) * sch1;
      float mh = fmaxf(th0[hd], th1[hd]);
      mh = fmaxf(mh, shx(mh, 1)); mh = fmaxf(mh, shx(mh, 2));
      th0[hd] -= mh; th1[hd] -= mh;
      sl0[hd] = sl[0]; sl1[hd] = sl[1];
    }
    mbar_wait(bar_kv + wg * 8, 0);
    TS(4);
#pragma unroll
    for (int j = 0; j < 5; j++) pv[j] = lds128(kvs + 512 * j);
    const uint32_t Kp[10] = {pv[0].x, pv[0].y, pv[2].x, pv[0].z, pv[0].w, pv[1].x, pv[1].y, pv[2].y, pv[1].z, pv[1].w};
    const uint32_t Vp[10] = {movm(pv[2].z), movm(pv[2].w), movm(pv[3].x), movm(pv[3].y), movm(pv[3].z), movm(pv[3].w), movm(pv[4].x), movm(pv[4].y), movm(pv[4].z), movm(pv[4].w)};
    const uint32_t ONES = 0x3f803f80u;
    uint32_t of[20];
#pragma unroll
    for (int hp = 0; hp < 2; hp++) {
      float o[6][4];
#pragma unroll
      for (int hh = 0; hh < 2; hh++) {
        const int hd = 2 * hp + hh, ta = 5 * hp + 3 * hh, ts = 5 * hp + 2;
        float sp[4];
        mma_k24(sp, Qlo[ta], Qhi[ta], Qlo[ta + 1], Qhi[ta + 1], Kp[ta], Kp[ta + 1], qe[hd][0], qe[hd][1], Kp[ts]);
        const float tl0 = fmaf(in0 ? sl0[hd] : sp[0], scl0, bias0), tl1 = fmaf(in1 ? sl1[hd] : sp[1], scl1, bias1);
        float ml = fmaxf(tl0, tl1);
        ml = fmaxf(ml, shx(ml, 1)); ml = fmaxf(ml, shx(ml, 2));
        if (HOLD == 1 && hd == 3 && !fol && lane == 0) mbar_arrive(bar_go + 8);
        const uint32_t Pl = pack_bf16(ex2(tl0 - ml), ex2(tl1 - ml)), Ph = pack_bf16(ex2(th0[hd]), ex2(th1[hd]));
        const uint32_t a0 = Pl & mL, a1 = Ph & ~mL, a3 = Ph & mL, ap = Pl & ~mL;
        const bool vm = hh == 0 ? nA : !nA;
        mma_k24(o[3 * hh], a0, a1, 0u, a3, Vlo[ta], Vhi[ta], ap, 0u, Vp[ta]);
        mma_k24(o[3 * hh + 1], a0, a1, 0u, a3, Vlo[ta + 1], Vhi[ta + 1], ap, 0u, Vp[ta + 1]);
        mma_k24(o[3 * hh + 2], a0, a1, 0u, a3, vm ? Vlo[ts] : ONES, vm ? Vhi[ts] : ONES, ap, 0u, vm ? Vp[ts] : ONES);
      }
      const float il = rcp(cA ? o[5][0] : o[2][0]), ih = rcp(cA ? o[5][2] : o[2][2]);
      const float jl = shx(il, 2), jh = shx(ih, 2);
      const float al = cA ? jl : il, ah = cA ? jh : ih, bl = cA ? il : jl, bh = cA ? ih : jh;
      const int t0 = 5 * hp;
      of[2 * t0]     = pack_bf16(o[0][0] * al, o[0][1] * al); of[2 * t0 + 1] = pack_bf16(o[0][2] * ah, o[0][3] * ah);
      of[2 * t0 + 2] = pack_bf16(o[1][0] * al, o[1][1] * al); of[2 * t0 + 3] = pack_bf16(o[1][2] * ah, o[1][3] * ah);
      of[2 * t0 + 4] = pack_bf16((cA ? o[2][0] : o[5][0]) * jl, (cA ? o[2][1] : o[5][1]) * jl);
      of[2 * t0 + 5] = pack_bf16((cA ? o[2][2] : o[5][2]) * jh, (cA ? o[2][3] : o[5][3]) * jh);
      of[2 * t0 + 6] = pack_bf16(o[3][0] * bl, o[3][1] * bl); of[2 * t0 + 7] = pack_bf16(o[3][2] * bh, o[3][3] * bh);
      of[2 * t0 + 8] = pack_bf16(o[4][0] * bl, o[4][1] * bl); of[2 * t0 + 9] = pack_bf16(o[4][2] * bh, o[4][3] * bh);
    }
    {
#pragma unroll
      for (int s = 0; s < 5; s++) {
        stsm4(oa + s * 256, of[4 * s], of[4 * s + 1], of[4 * s + 2], of[4 * s + 3]);
        if (s == 0 && (fol || HOLD == 2) && lane == 0) mbar_arrive(bar_go + 8 + 8 * fol);
      }
      asm volatile("fence.proxy.async.shared::cta;" ::: "memory");
      __syncwarp();
      asm volatile("{\n.reg .pred q;\nelect.sync _|q, 0xffffffff;\n@q cp.async.bulk.global.shared::cta.bulk_group [%0], [%1], 2560;\ncp.async.bulk.commit_group;\n}\n" :: "l"(odst), "r"(os) : "memory");
    }
    TS(5);
    float h[40];
#pragma unroll
    for (int s = 0; s < 5; s++) {
      const uint4 v = xr[s];
      h[8 * s] = bf_lo(v.x); h[8 * s + 1] = bf_hi(v.x); h[8 * s + 2] = bf_lo(v.y); h[8 * s + 3] = bf_hi(v.y);
      h[8 * s + 4] = bf_lo(v.z); h[8 * s + 5] = bf_hi(v.z); h[8 * s + 6] = bf_lo(v.w); h[8 * s + 7] = bf_hi(v.w);
    }
    asm volatile("cp.async.bulk.wait_group 0;" ::: "memory");
    __syncwarp();
    if (lane == 0) {
      asm volatile("red.relaxed.gpu.global.add.u32 [%0], %1;" :: "l"(ocnt), "r"(oinc) : "memory");
      mbar_arrive(bar_st + 8 * fol);
    }
    TS(22);
    mbar_wait(bar_full, 0); mbar_wait(bar_full + 8, 0); mbar_wait(bar_full + 16, 1);
    mbar_wait(bar_go + 16, 0);
    const uint64_t dwo = make_desc(D0 * 16, 5120, 512, 2);
    wgmma_fence();
#pragma unroll
    for (int s = 0; s < 5; s++) wgmma_n80_rs(h, of[4 * s], of[4 * s + 1], of[4 * s + 2], of[4 * s + 3], dwo + g * 960 + s * 64, 1);
    wgmma_commit();
    TS(6);
    const bool odd = c & 1;
    uint4* const sp = hold(&g_own[slot].st2[r + (odd ? 8 : 0)]);
    uint4* const cdp = hold(&g_x.cand[slot][g][lane & zero]);
    uint4* const kcp = hold(g_own[1].cnt + (lane & zero));
    float wr[20];
#pragma unroll
    for (int j = 0; j < 5; j++) {
      const uint4 v = lds128(sb + OFF_WR + c * 80 + j * 16);
      wr[4 * j] = __uint_as_float(v.x); wr[4 * j + 1] = __uint_as_float(v.y); wr[4 * j + 2] = __uint_as_float(v.z); wr[4 * j + 3] = __uint_as_float(v.w);
    }
    const float wsum = lds32f(sb + OFF_WR + 320);
    const uint32_t bo = bar_o + fol * 56;
    if (PRIO < 7 && fol) mbar_wait(bar_oc + 8 * PRIO, 0);
#pragma unroll
    for (int i = 0; i < 7; i++) {
      mbar_wait(bo + 8 * i, 0);
      if (i == 0) TS(1);
      const uint32_t da = D0 + OFF_O / 16 + (8 << 16) + ((i + 2) % 7) * 640, db = D0 + (320 << 16) + (i >= g ? i + 1 : i) * 960;
      wgmma_fence();
#pragma unroll
      for (int s = 0; s < 5; s++) wgmma_n80_ss(h, mk64(da + s * 16, 80u), mk64(db + s * 64, 0x80000020u), 1);
      wgmma_commit();
      wgmma_wait<1>();
      if (lane == 0 && i > 0) mbar_arrive(bo + 104 + 8 * i);
    }
    const int tok0 = P * 256 + 32 * warp + rank;
    wgmma_wait<0>();
#pragma unroll
    for (int i = 0; i < 40; i++) asm volatile("" : "+f"(h[i]) :: "memory");
    if (lane == 0) mbar_arrive(bo + 160);
    if (SPLITB) { asm volatile("{\n.reg .pred p;\nsetp.ne.u32 p, %0, 0;\n@p trap;\n}\n" :: "r"(zero) : "memory"); }
    TS(7);
    float mean, rstd, rr;
    bool pub;
    {
      float l1 = 0.f, l2 = 0.f, l3 = 0.f, h1 = 0.f, h2 = 0.f, h3 = 0.f;
#pragma unroll
      for (int j = 0; j < 10; j++) {
        l1 += h[4 * j] + h[4 * j + 1]; h1 += h[4 * j + 2] + h[4 * j + 3];
        l2 = fmaf(h[4 * j], h[4 * j], l2); l2 = fmaf(h[4 * j + 1], h[4 * j + 1], l2);
        h2 = fmaf(h[4 * j + 2], h[4 * j + 2], h2); h2 = fmaf(h[4 * j + 3], h[4 * j + 3], h2);
        l3 = fmaf(h[4 * j], wr[2 * j], l3); l3 = fmaf(h[4 * j + 1], wr[2 * j + 1], l3);
        h3 = fmaf(h[4 * j + 2], wr[2 * j], h3); h3 = fmaf(h[4 * j + 3], wr[2 * j + 1], h3);
      }
      float s1 = (odd ? h1 : l1) + shx(odd ? l1 : h1, 1), s2 = (odd ? h2 : l2) + shx(odd ? l2 : h2, 1), s3 = (odd ? h3 : l3) + shx(odd ? l3 : h3, 1);
      s1 += shx(s1, 2); s2 += shx(s2, 2); s3 += shx(s3, 2);
      uint4 p0;
      float o1 = 0.f, o2 = 0.f, o3 = 0.f, oc = 7.f;
      asm volatile("{\n.reg .pred q;\nsetp.lt.u32 q, %9, 2;\n@q atom.relaxed.gpu.global.add.v4.f32 {%0, %1, %2, %3}, [%4], {%5, %6, %7, %8};\n}\n"
                   : "+f"(o1), "+f"(o2), "+f"(o3), "+f"(oc) : "l"(sp), "f"(s1), "f"(s2), "f"(s3), "f"(1.f), "r"(c) : "memory");
      const uint32_t last = __ballot_sync(0xffffffffu, oc == 7.f);
      pub = last & 1;
      p0.x = __float_as_uint(o1 + s1); p0.y = __float_as_uint(o2 + s2); p0.z = __float_as_uint(o3 + s3);
      if (last != 0xffffffffu)
      do { p0 = ldg_pkt(sp); } while (anyw(p0.w != 0x41000000u) && --guard > 0);
      mean = __uint_as_float(p0.x) * (1.f / 640.f);
      rstd = rsq(fmaxf(fmaf(-mean, mean, __uint_as_float(p0.y) * (1.f / 640.f)), 0.f) + 1e-5f);
      rr = fmaf(-mean, wsum, __uint_as_float(p0.z)) * rstd;
    }
    TS(8);
    const int myrow = r + (odd ? 8 : 0);
    const uint32_t kk = cA ? ord_key(rr) : 0u, kmax = __reduce_max_sync(0xffffffffu, kk);
    if (pub) {
      if (kk == kmax) asm volatile("red.relaxed.gpu.global.max.u64 [%0], %1;" :: "l"(kcp), "l"(mk64(2047 - tok0 - 2 * myrow, kk)) : "memory");
      __syncwarp();
      if (lane == 0) asm volatile("red.relaxed.gpu.global.add.u32 [%0 + 8], 1;" :: "l"(kcp) : "memory");
    }
    const int crow = __reduce_min_sync(0xffffffffu, kk == kmax ? myrow : 16), L = (crow & 7) * 4 + (crow >> 3);
    if (warp == g) asm volatile("bar.arrive 3, 64;" ::: "memory");
    const uint32_t stg = sb + (fol ? OFF_O : g * 15360) + w4 * 2560;
    uint4 held;
    {
      const float nb = -mean * rstd;
      const float rl = __shfl_sync(0xffffffffu, rstd, lane & 28), rh = __shfl_sync(0xffffffffu, rstd, (lane & 28) + 1);
      const float bl = __shfl_sync(0xffffffffu, nb, lane & 28), bh = __shfl_sync(0xffffffffu, nb, (lane & 28) + 1), al = 1.f + rl, ah = 1.f + rh;
      if ((L >> 2) == r) {
        const bool chi = L & 1;
        const float rc = chi ? rh : rl, bc = chi ? bh : bl;
        uint32_t n[10];
#pragma unroll
        for (int j = 0; j < 10; j++) n[j] = pack_bf16(fmaf(chi ? h[4 * j + 2] : h[4 * j], rc, bc), fmaf(chi ? h[4 * j + 3] : h[4 * j + 1], rc, bc));
        uint4* d = cdp + c;
        stg_pkt(d, n[0], n[1], n[2], n[3]); stg_pkt(d + 4, n[4], n[5], n[6], n[7]); stg_rlx64(d + 8, n[8], n[9]);
      }
      mbar_wait(bar_oc + 56, 0);
      const uint32_t fa = stg + (lane & 15) * 160 + (lane >> 4) * 16;
#pragma unroll
      for (int s = 0; s < 5; s++)
        stsm4(fa + s * 32, pack_bf16(fmaf(h[8 * s], al, bl), fmaf(h[8 * s + 1], al, bl)), pack_bf16(fmaf(h[8 * s + 2], ah, bh), fmaf(h[8 * s + 3], ah, bh)),
              pack_bf16(fmaf(h[8 * s + 4], al, bl), fmaf(h[8 * s + 5], al, bl)), pack_bf16(fmaf(h[8 * s + 6], ah, bh), fmaf(h[8 * s + 7], ah, bh)));
      __syncwarp();
      held = lds128(stg + crow * 160 + min(lane, 9) * 16);
      if (lane < 10) stg_pkt(cdp + 12 + lane, held.x, held.y, held.z, held.w);
    }
    TS(9);
    mbar_wait(bar_ffn, 0);
    const uint32_t red = sb + OFF_RED;
    if (ffn1) {
      uint4 w1[4][5];
      {
        const int k = (lane & 7) + (lane >> 4) * 8;
        const uint32_t a1 = sb + k * 64, sw = ((lane >> 3) & 1) ^ ((lane >> 1) & 3);
#pragma unroll
        for (int s = 0; s < 5; s++)
#pragma unroll
          for (int u = 0; u < 4; u++)
            w1[u][s] = ldsm4t(a1 + (s < 4 ? warp * 4096 + s * 1024 : 32768 + warp * 1024) + (u >> 1) * (40960 + (s == 4 || warp >= 4 ? OFF_W2 - 57344 : 0)) + ((sw ^ (2 * (u & 1))) * 16));
      }
      uint32_t* const ap = hold(g_x.act + fj * 16 + (lane >> 1));
      mbar_wait(bar_win, 0);
      const uint32_t hp = sb + OFF_HN + (warp * 4 + c) * 16;
      const uint4 c0 = lds128(hp), c1 = lds128(hp + 512), c2 = lds128(hp + 1024);
      TS(10);
      float a[4][4];
#pragma unroll
      for (int u = 0; u < 4; u++) {
        a[u][0] = a[u][1] = a[u][2] = a[u][3] = 0.f;
        mma_acc(a[u], w1[u][0], c0.x, c0.y); mma_acc(a[u], w1[u][1], c0.z, c0.w); mma_acc(a[u], w1[u][2], c1.x, c1.y);
        mma_acc(a[u], w1[u][3], c1.z, c1.w); mma_acc(a[u], w1[u][4], c2.x, c2.y);
      }
      asm volatile("st.shared.v2.f32 [%0], {%1, %2};" :: "r"(red + (warp * 32 + c * 8 + r) * 8),
                   "f"(cA ? (odd ? a[0][2] : a[0][0]) : (odd ? a[1][2] : a[1][0])), "f"(cA ? (odd ? a[2][2] : a[2][0]) : (odd ? a[3][2] : a[3][0])) : "memory");
      bar_sync(1, 256);
      if (warp == 0) {
        float2 t[8];
#pragma unroll
        for (int i = 0; i < 8; i++) t[i] = lds64f(red + (i * 32 + lane) * 8);
        const float s = ((t[0].x + t[1].x) + (t[2].x + t[3].x)) + ((t[4].x + t[5].x) + (t[6].x + t[7].x));
        const float u = ((t[0].y + t[1].y) + (t[2].y + t[3].y)) + ((t[4].y + t[5].y) + (t[6].y + t[7].y));
        const float av = s * u * rcp(1.f + ex2(-1.4426950408889634f * s));
        const float an = shx(av, 1);
        if (!odd) stg_rlx32(ap, pack_bf16(av, an));
      }
      bar_sync(1, 256);
      TS(11);
    }
    char* const ob2 = (char*)(out + tok0 * 640 + g * 64);
    const int remo = 896 - 96 * g;
    {
      char* const q0 = ob2 + (lane >> 3) * 2560 + (lane & 7) * 16;
      const uint32_t s0 = stg + (lane >> 3) * 160 + (lane & 7) * 16;
#pragma unroll
      for (int s = 0; s < 4; s++) stg128_if(4 * s + (lane >> 3) != crow, q0 + s * 10240, lds128(s0 + s * 640));
      stg128_if((lane >> 1) != crow, ob2 + (lane >> 1) * 2560 + (lane & 1) * 16 + 128 + remo, lds128(stg + (lane >> 1) * 160 + (lane & 1) * 16 + 128));
    }
    mbar_wait(bar_win, 0);
    uint4 win = lds128(sb + OFF_WR + 336);
    win.z = win.y; win.y = 2047u - (win.x & 2047u); win.x = (win.y >> 8) * 16 + (win.y & 1) * 8 + ((win.y >> 5) & 7);
    stg128_if(win.x != slot && lane < 10, ob2 + crow * 2560 + lane * 16 + (lane < 8 ? 0 : remo), held);
    if (!ffn1) {
      TS(10);
      uint4 w2[6];
      const uint32_t a2 = sb + OFF_W2 + (warp * 192 + 8 * (((lane >> 3) & 1) * 4 + ((lane & 7) >> 1)) + 2 * (lane >> 4) + (lane & 1)) * 16;
#pragma unroll
      for (int s = 0; s < 6; s++) w2[s] = ldsm4t(a2 + (s >> 1) * 1024 + (s & 1) * 64);
      const uint4* p = (const uint4*)(g_x.act + warp * 96) + (r & 1) * 4 + c;
      const uint32_t* pb = (const uint32_t*)&g_x.cand[win.x][fj < 64 ? fj >> 3 : (fj - 64) >> 1][fj < 64 ? 12 + (fj & 7) : 20 + (fj & 1)] + c;
      uint32_t* const op = hold((uint32_t*)(out + win.y * 640 + fj * 8) + c);
      const float sg = shx(rcp(1.f + ex2(-1.4426950408889634f * __uint_as_float(win.z ^ ((uint32_t)((int32_t)~win.z >> 31) | 0x80000000u)))), 1);
      uint4 c0, c1, c2; uint32_t bw;
      if (ACT_NS) __nanosleep(ACT_NS);
      do {
        c0 = ldg_pkt(p); c1 = ldg_pkt(p + 8); c2 = ldg_pkt(p + 16); bw = ldg_rlx32(pb);
      } while (anyw(max(max(max(max(c0.x, c0.y), max(c0.z, c0.w)), max(max(c1.x, c1.y), max(c1.z, c1.w))), max(max(max(c2.x, c2.y), max(c2.z, c2.w)), bw)) == SENT) && --guard > 0);
      TS(11);
      float a[4] = {0.f, 0.f, 0.f, 0.f}, b[4] = {0.f, 0.f, 0.f, 0.f}, d[4] = {0.f, 0.f, 0.f, 0.f};
      mma_acc(a, w2[0], c0.x, c0.y); mma_acc(b, w2[2], c1.x, c1.y); mma_acc(d, w2[4], c2.x, c2.y);
      mma_acc(a, w2[1], c0.z, c0.w); mma_acc(b, w2[3], c1.z, c1.w); mma_acc(d, w2[5], c2.z, c2.w);
      if (c == 0) sts32f(red + (warp * 8 + r) * 4, ((a[0] + a[3]) + (b[0] + b[3])) + (d[0] + d[3]));
      bar_sync(1, 256);
      if (tid < 4) {
        float2 t[8];
#pragma unroll
        for (int i = 0; i < 8; i++) t[i] = lds64f(red + (i * 4 + tid) * 8);
        const float y0 = ((t[0].x + t[1].x) + (t[2].x + t[3].x)) + ((t[4].x + t[5].x) + (t[6].x + t[7].x));
        const float y1 = ((t[0].y + t[1].y) + (t[2].y + t[3].y)) + ((t[4].y + t[5].y) + (t[6].y + t[7].y));
        stg_rlx32(op, pack_bf16(fmaf(y0, sg, bf_lo(bw)), fmaf(y1, sg, bf_hi(bw))));
      }
    }
    TS(12);
#undef TS_T
  }
}

typedef CUresult (*EncodeFn)(CUtensorMap*, CUtensorMapDataType, cuuint32_t, void*, const cuuint64_t*, const cuuint64_t*, const cuuint32_t*,
                             const cuuint32_t*, CUtensorMapInterleave, CUtensorMapSwizzle, CUtensorMapL2promotion, CUtensorMapFloatOOBfill);

void make_map(EncodeFn enc, CUtensorMap* m, const void* base, const cuuint64_t* dims, const cuuint64_t* strides, const cuuint32_t* box,
              CUtensorMapSwizzle swz) {
  const cuuint32_t es[3] = {1, 1, 1};
  enc(m, CU_TENSOR_MAP_DATA_TYPE_BFLOAT16, 3, (void*)base, dims, strides, box, es, CU_TENSOR_MAP_INTERLEAVE_NONE, swz,
      CU_TENSOR_MAP_L2_PROMOTION_L2_128B, CU_TENSOR_MAP_FLOAT_OOB_FILL_NONE);
}

}

extern "C" void kernel_launch(void* const* d_in, const int* in_sizes, int n_in, void* d_out, int out_size) {
  const __nv_bfloat16* x = (const __nv_bfloat16*)d_in[0];
  const __nv_bfloat16* wqkv = (const __nv_bfloat16*)d_in[1];
  const __nv_bfloat16* wo = (const __nv_bfloat16*)d_in[2];
  void* fn = nullptr;
  cudaDriverEntryPointQueryResult st;
  cudaGetDriverEntryPoint("cuTensorMapEncodeTiled", &fn, cudaEnableDefault, &st);
  EncodeFn enc = (EncodeFn)fn;
  void* scp = nullptr;
  cudaGetSymbolAddress(&scp, g_scratch);
  Maps tm;
  { const cuuint64_t d[3] = {640, 1024, 2}, s[2] = {2560, 1280}; const cuuint32_t b[3] = {64, 128, 1}; make_map(enc, &tm.x, x, d, s, b, CU_TENSOR_MAP_SWIZZLE_128B); }
  { const cuuint64_t d[3] = {640, 640, 3}, s[2] = {3840, 1280}; const cuuint32_t b[3] = {64, 16, 3}; make_map(enc, &tm.w, wqkv, d, s, b, CU_TENSOR_MAP_SWIZZLE_128B); }
  { const cuuint64_t d[3] = {640, 640, 3}, s[2] = {3840, 1280}; const cuuint32_t b[3] = {16, 16, 3}; make_map(enc, &tm.wr, wqkv, d, s, b, CU_TENSOR_MAP_SWIZZLE_32B); }
  { const cuuint64_t d[3] = {640, 640, 3}, s[2] = {3840, 1280}; const cuuint32_t b[3] = {16, 16, 1}; make_map(enc, &tm.wv, wqkv, d, s, b, CU_TENSOR_MAP_SWIZZLE_32B); }
  { const cuuint64_t d[3] = {32, 640, 20}, s[2] = {1280, 64}; const cuuint32_t b[3] = {32, 80, 2}; make_map(enc, &tm.wo, wo, d, s, b, CU_TENSOR_MAP_SWIZZLE_64B); }
  { const cuuint64_t d[3] = {640, 640, 1}, s[2] = {1280, 819200}; const cuuint32_t b[3] = {16, 80, 1}; make_map(enc, &tm.wor, wo, d, s, b, CU_TENSOR_MAP_SWIZZLE_64B); }
  { const cuuint64_t d[3] = {1536, 640, 1}, s[2] = {3072, 1966080}; const cuuint32_t b[3] = {32, 128, 1};
    make_map(enc, &tm.gate, d_in[5], d, s, b, CU_TENSOR_MAP_SWIZZLE_64B); make_map(enc, &tm.up, d_in[6], d, s, b, CU_TENSOR_MAP_SWIZZLE_64B); }
  { const cuuint64_t d[3] = {640, 1536, 1}, s[2] = {1280, 1966080}; const cuuint32_t b[3] = {8, 128, 1}; make_map(enc, &tm.down, d_in[7], d, s, b, CU_TENSOR_MAP_SWIZZLE_NONE); }
  cudaFuncSetAttribute(fused_kernel, cudaFuncAttributeMaxDynamicSharedMemorySize, SMEM_BYTES);
  fused_kernel<<<128, 512, SMEM_BYTES, cudaStreamPerThread>>>(x, wqkv, wo, (const __nv_bfloat16*)d_in[4], (const __nv_bfloat16*)d_in[5],
                                                              (const __nv_bfloat16*)d_in[6], (const __nv_bfloat16*)d_in[7], (__nv_bfloat16*)d_out, (Scratch*)scp, tm);
}
```

```cpp
#include <cuda_runtime.h>
#include <cuda_bf16.h>
#include <cuda.h>
#include <stdint.h>

#define PFW_NS 50
#define PFW_N 14
#define ACT_NS 100
#define KEY_NS 0
#define AUX_NS 50
#define REG_P 72
#define REG_C 184
#define LEAD 1
#define HK_IT 2
#define F_PER 2
#define F_MAX 8
#define HOLD 2
#define AK 3
#define NSPLIT 3
#define THR_END 3
#define BOUNDED 0
#define TLIGHT 0
#define ATOM2 1
#define LAG 4
#define OV 2
#define O_UNROLL 1
#define PRIO 7
#define SPLITB 1
#define GPAD 3328
#define PROMO 2
#define PROMOX 2

namespace {

constexpr int SLOT    = 49152;
constexpr int OFF_O   = 122880;
constexpr int OFF_W2  = 4 * SLOT;
constexpr int OFF_CS  = OFF_W2 + 24576;
constexpr int OFF_RS  = OFF_CS + 3840;
constexpr int OFF_MN  = OFF_RS + 576;
constexpr int OFF_WR  = OFF_MN + 1024;
constexpr int OFF_RED = OFF_CS;
constexpr int OFF_HN  = OFF_CS + 2048;
constexpr int OFF_PT  = OFF_WR + 352;
constexpr int OFF_BAR = OFF_PT + 768;
constexpr int SMEM_BYTES = OFF_BAR + 424 + 384;
constexpr uint32_t D0 = 1024 >> 4;
constexpr int OUNR = O_UNROLL;
constexpr uint32_t SENT = 0xFFFFFFFFu;
constexpr int SPIN_MAX = 1 << 20;

struct Glob {
  uint4 cand[128][8][24];
  uint32_t act[768];
  uint32_t pad[GPAD];
};
constexpr int GLOB_PER_CTA = sizeof(Glob) / 16 / 128;
static_assert(GLOB_PER_CTA * 128 * 16 == sizeof(Glob), "glob size");
struct Own {
  uint4 halo[5][32];
  uint4 st1[32];
  uint2 cs[32];
  uint4 st2[16];
  uint4 cnt[8];
};
struct Scratch {
  Glob x;
  Own own[128];
  uint4 o[32][8][640];
  uint32_t epoch[128];
};
__device__ __align__(128) Scratch g_scratch;
#define g_x (sc->x)
#define g_own (sc->own)
#define g_o (sc->o)
#define g_epoch (sc->epoch)
#define TS(i)

__device__ __forceinline__ void mbar_init(uint32_t bar, uint32_t cnt) { asm volatile("mbarrier.init.shared::cta.b64 [%0], %1;" :: "r"(bar), "r"(cnt) : "memory"); }
__device__ __forceinline__ void mbar_expect_tx(uint32_t bar, uint32_t bytes) { asm volatile("mbarrier.arrive.expect_tx.shared::cta.b64 _, [%0], %1;" :: "r"(bar), "r"(bytes) : "memory"); }
__device__ __forceinline__ void mbar_arrive(uint32_t bar) { asm volatile("mbarrier.arrive.shared::cta.b64 _, [%0];" :: "r"(bar) : "memory"); }
__device__ __forceinline__ void mbar_arrive_cta(uint32_t bar, uint32_t cta) {
  asm volatile("{\n.reg .b32 ra;\nmapa.shared::cluster.u32 ra, %0, %1;\nmbarrier.arrive.shared::cluster.b64 _, [ra];\n}\n" :: "r"(bar), "r"(cta) : "memory");
}
__device__ __forceinline__ void mbar_wait(uint32_t bar, uint32_t parity) {
  asm volatile("{\n.reg .pred p;\nW:\nmbarrier.try_wait.parity.shared::cta.b64 p, [%0], %1;\n@!p bra.uni W;\n}\n" :: "r"(bar), "r"(parity) : "memory");
}
__device__ __forceinline__ void tma_3d(uint32_t dst, const void* tm, uint32_t bar, int c0, int c1, int c2) {
  asm volatile("cp.async.bulk.tensor.3d.shared::cluster.global.mbarrier::complete_tx::bytes [%0], [%1, {%3, %4, %5}], [%2];" :: "r"(dst), "l"(tm), "r"(bar), "r"(c0), "r"(c1), "r"(c2) : "memory");
}
__device__ __forceinline__ void tma_3d_mc(uint32_t dst, const void* tm, uint32_t bar, int c0, int c1, int c2) {
  asm volatile("cp.async.bulk.tensor.3d.shared::cluster.global.mbarrier::complete_tx::bytes.multicast::cluster [%0], [%1, {%3, %4, %5}], [%2], %6;" :: "r"(dst), "l"(tm), "r"(bar), "r"(c0), "r"(c1), "r"(c2), "h"((uint16_t)3) : "memory");
}
__device__ __forceinline__ void wgmma_fence() { asm volatile("wgmma.fence.sync.aligned;" ::: "memory"); }
__device__ __forceinline__ void wgmma_commit() { asm volatile("wgmma.commit_group.sync.aligned;" ::: "memory"); }
template <int N> __device__ __forceinline__ void wgmma_wait() { asm volatile("wgmma.wait_group.sync.aligned %0;" :: "n"(N) : "memory"); }
__device__ __forceinline__ uint64_t make_desc(uint32_t addr, uint32_t lbo, uint32_t sbo, uint32_t swz) {
  return (uint64_t)(((addr & 0x3FFFF) >> 4) | ((lbo >> 4) << 16)) | ((uint64_t)((sbo >> 4) | (swz << 30)) << 32);
}
__device__ __forceinline__ void bar_sync(int id, int n) { asm volatile("bar.sync %0, %1;" :: "r"(id), "r"(n) : "memory"); }
__device__ __forceinline__ void st_pkt(void* p, uint32_t a, uint32_t b, uint32_t c, uint32_t d) {
  asm volatile("st.relaxed.gpu.v4.u32 [%0], {%1, %2, %3, %4};" :: "l"(p), "r"(a), "r"(b), "r"(c), "r"(d) : "memory");
}
__device__ __forceinline__ uint4 ldg_pkt(const void* p) {
  uint4 v; asm volatile("ld.relaxed.gpu.global.v4.u32 {%0, %1, %2, %3}, [%4];" : "=r"(v.x), "=r"(v.y), "=r"(v.z), "=r"(v.w) : "l"(p) : "memory"); return v;
}
__device__ __forceinline__ void stg_pkt(void* p, uint32_t a, uint32_t b, uint32_t c, uint32_t d) {
  asm volatile("st.relaxed.gpu.global.v4.u32 [%0], {%1, %2, %3, %4};" :: "l"(p), "r"(a), "r"(b), "r"(c), "r"(d) : "memory");
}
__device__ __forceinline__ uint32_t ldg_rlx32(const void* p) { uint32_t v; asm volatile("ld.relaxed.gpu.global.u32 %0, [%1];" : "=r"(v) : "l"(p) : "memory"); return v; }
__device__ __forceinline__ uint2 ldg_rlx64(const void* p) { uint2 v; asm volatile("ld.relaxed.gpu.global.v2.u32 {%0, %1}, [%2];" : "=r"(v.x), "=r"(v.y) : "l"(p) : "memory"); return v; }
__device__ __forceinline__ uint32_t pin(uint32_t v) { asm volatile("" : "+r"(v)); return v; }
__device__ __forceinline__ uint64_t mk64(uint32_t lo, uint32_t hi) { return ((uint64_t)hi << 32) | lo; }
__device__ __forceinline__ uint32_t holdu(uint32_t v) { return __shfl_sync(0xffffffffu, v, threadIdx.x & 31); }
template <class T> __device__ __forceinline__ T* hold(T* p) { return (T*)__shfl_sync(0xffffffffu, (unsigned long long)p, threadIdx.x & 31); }
__device__ __forceinline__ void stg128_if(bool q, void* p, const uint4& v) {
  asm volatile("{\n.reg .pred q;\nsetp.ne.u32 q, %5, 0;\n@q st.global.v4.u32 [%0], {%1, %2, %3, %4};\n}\n" :: "l"(p), "r"(v.x), "r"(v.y), "r"(v.z), "r"(v.w), "r"((int)q) : "memory");
}
template <class T> __device__ __forceinline__ T* pin(T* p) { asm volatile("" : "+l"(p)); return p; }
__device__ __forceinline__ void stg_rlx32(void* p, uint32_t v) { asm volatile("st.relaxed.gpu.global.u32 [%0], %1;" :: "l"(p), "r"(v) : "memory"); }
__device__ __forceinline__ void stg_rlx64(void* p, uint32_t a, uint32_t b) { asm volatile("st.relaxed.gpu.global.v2.u32 [%0], {%1, %2};" :: "l"(p), "r"(a), "r"(b) : "memory"); }
__device__ __forceinline__ uint4 ldsm4(uint32_t a) { uint4 v; asm volatile("ldmatrix.sync.aligned.m8n8.x4.shared.b16 {%0, %1, %2, %3}, [%4];" : "=r"(v.x), "=r"(v.y), "=r"(v.z), "=r"(v.w) : "r"(a) : "memory"); return v; }
__device__ __forceinline__ void ldsm4_if(uint4& v, uint32_t a, int off, bool p) {
  asm volatile("{\n.reg .pred q;\nsetp.ne.u32 q, %5, 0;\n@q ldmatrix.sync.aligned.m8n8.x4.shared.b16 {%0, %1, %2, %3}, [%4];\n}\n"
               : "+r"(v.x), "+r"(v.y), "+r"(v.z), "+r"(v.w) : "r"(a + off), "r"((int)p) : "memory");
}
__device__ __forceinline__ uint4 ldsm4t(uint32_t a) { uint4 v; asm volatile("ldmatrix.sync.aligned.m8n8.x4.trans.shared.b16 {%0, %1, %2, %3}, [%4];" : "=r"(v.x), "=r"(v.y), "=r"(v.z), "=r"(v.w) : "r"(a) : "memory"); return v; }
__device__ __forceinline__ void stsm4(uint32_t a, uint32_t x, uint32_t y, uint32_t z, uint32_t w) { asm volatile("stmatrix.sync.aligned.m8n8.x4.shared.b16 [%0], {%1, %2, %3, %4};" :: "r"(a), "r"(x), "r"(y), "r"(z), "r"(w) : "memory"); }
__device__ __forceinline__ void mma_acc(float (&c)[4], const uint4& a, uint32_t b0, uint32_t b1) {
  asm("mma.sync.aligned.m16n8k16.row.col.f32.bf16.bf16.f32 {%0,%1,%2,%3}, {%4,%5,%6,%7}, {%8,%9}, {%0,%1,%2,%3};"
      : "+f"(c[0]), "+f"(c[1]), "+f"(c[2]), "+f"(c[3]) : "r"(a.x), "r"(a.y), "r"(a.z), "r"(a.w), "r"(b0), "r"(b1));
}
__device__ __forceinline__ uint4 lds128(uint32_t a) { uint4 v; asm volatile("ld.shared.v4.u32 {%0, %1, %2, %3}, [%4];" : "=r"(v.x), "=r"(v.y), "=r"(v.z), "=r"(v.w) : "r"(a) : "memory"); return v; }
__device__ __forceinline__ float2 lds64f(uint32_t a) { float2 v; asm volatile("ld.shared.v2.f32 {%0, %1}, [%2];" : "=f"(v.x), "=f"(v.y) : "r"(a)); return v; }
__device__ __forceinline__ float lds32f(uint32_t a) { float v; asm volatile("ld.shared.f32 %0, [%1];" : "=f"(v) : "r"(a)); return v; }
__device__ __forceinline__ void sts32f(uint32_t a, float v) { asm volatile("st.shared.f32 [%0], %1;" :: "r"(a), "f"(v) : "memory"); }
__device__ __forceinline__ uint32_t pack_bf16(float lo, float hi) { uint32_t r; asm("cvt.rn.bf16x2.f32 %0, %1, %2;" : "=r"(r) : "f"(hi), "f"(lo)); return r; }
__device__ __forceinline__ float bf_lo(uint32_t v) { return __uint_as_float(v << 16); }
__device__ __forceinline__ float bf_hi(uint32_t v) { return __uint_as_float(v & 0xffff0000u); }
__device__ __forceinline__ uint32_t movm(uint32_t a) { uint32_t d; asm("movmatrix.sync.aligned.m8n8.trans.b16 %0, %1;" : "=r"(d) : "r"(a)); return d; }
__device__ __forceinline__ float ex2(float x) { float y; asm("ex2.approx.ftz.f32 %0, %1;" : "=f"(y) : "f"(x)); return y; }
__device__ __forceinline__ float rsq(float x) { float y; asm("rsqrt.approx.ftz.f32 %0, %1;" : "=f"(y) : "f"(x)); return y; }
__device__ __forceinline__ float rcp(float x) { float y; asm("rcp.approx.ftz.f32 %0, %1;" : "=f"(y) : "f"(x)); return y; }
__device__ __forceinline__ bool elect() { uint32_t p; asm volatile("{\n.reg .pred q;\nelect.sync _|q, 0xffffffff;\nselp.u32 %0, 1, 0, q;\n}\n" : "=r"(p)); return p; }
__device__ __forceinline__ void pf_l2(const void* p) { asm volatile("prefetch.global.L2 [%0];" :: "l"(p)); }
__device__ __forceinline__ bool anyw(bool p) { return __any_sync(0xffffffffu, p); }
__device__ __forceinline__ float shx(float v, int m) { return __shfl_xor_sync(0xffffffffu, v, m); }
__device__ __forceinline__ void mma_k24(float (&c)[4], uint32_t a0, uint32_t a1, uint32_t a2, uint32_t a3, uint32_t b0, uint32_t b1,
                                        uint32_t e0, uint32_t e1, uint32_t f0) {
  asm("mma.sync.aligned.m16n8k16.row.col.f32.bf16.bf16.f32 {%0,%1,%2,%3}, {%4,%5,%6,%7}, {%8,%9}, {%10,%10,%10,%10};"
      : "=f"(c[0]), "=f"(c[1]), "=f"(c[2]), "=f"(c[3]) : "r"(a0), "r"(a1), "r"(a2), "r"(a3), "r"(b0), "r"(b1), "f"(0.f));
  asm("mma.sync.aligned.m16n8k8.row.col.f32.bf16.bf16.f32 {%0,%1,%2,%3}, {%4,%5}, {%6}, {%0,%1,%2,%3};"
      : "+f"(c[0]), "+f"(c[1]), "+f"(c[2]), "+f"(c[3]) : "r"(e0), "r"(e1), "r"(f0));
}
__device__ __forceinline__ uint32_t ord_key(float r) { uint32_t u = __float_as_uint(r); return u ^ ((uint32_t)((int32_t)u >> 31) | 0x80000000u); }

__device__ __forceinline__ void wgmma_n64hi_ss(float (&d)[120], uint64_t da, uint64_t db, int scale_d) {
  asm volatile("{\n.reg .pred p;\nsetp.ne.b32 p, %34, 0;\n"
    "wgmma.mma_async.sync.aligned.m64n64k16.f32.bf16.bf16 "
    "{%0, %1, %2, %3, %4, %5, %6, %7, %8, %9, %10, %11, %12, %13, %14, %15, "
    "%16, %17, %18, %19, %20, %21, %22, %23, %24, %25, %26, %27, %28, %29, %30, %31}, "
    "%32, %33, p, 1, 1, 0, 1;\n}\n"
    : "+f"(d[88]), "+f"(d[89]), "+f"(d[90]), "+f"(d[91]), "+f"(d[92]), "+f"(d[93]), "+f"(d[94]), "+f"(d[95]),
      "+f"(d[96]), "+f"(d[97]), "+f"(d[98]), "+f"(d[99]), "+f"(d[100]), "+f"(d[101]), "+f"(d[102]), "+f"(d[103]),
      "+f"(d[104]), "+f"(d[105]), "+f"(d[106]), "+f"(d[107]), "+f"(d[108]), "+f"(d[109]), "+f"(d[110]), "+f"(d[111]),
      "+f"(d[112]), "+f"(d[113]), "+f"(d[114]), "+f"(d[115]), "+f"(d[116]), "+f"(d[117]), "+f"(d[118]), "+f"(d[119])
    : "l"(da), "l"(db), "r"(scale_d));
}
__device__ __forceinline__ void wgmma_n176lo_ss(float (&d)[120], uint64_t da, uint64_t db, int scale_d) {
  asm volatile("{\n.reg .pred p;\nsetp.ne.b32 p, %90, 0;\n"
    "wgmma.mma_async.sync.aligned.m64n176k16.f32.bf16.bf16 "
    "{%0, %1, %2, %3, %4, %5, %6, %7, %8, %9, %10, %11, %12, %13, %14, %15, "
    "%16, %17, %18, %19, %20, %21, %22, %23, %24, %25, %26, %27, %28, %29, %30, %31, "
    "%32, %33, %34, %35, %36, %37, %38, %39, %40, %41, %42, %43, %44, %45, %46, %47, "
    "%48, %49, %50, %51, %52, %53, %54, %55, %56, %57, %58, %59, %60, %61, %62, %63, "
    "%64, %65, %66, %67, %68, %69, %70, %71, %72, %73, %74, %75, %76, %77, %78, %79, "
    "%80, %81, %82, %83, %84, %85, %86, %87}, "
    "%88, %89, p, 1, 1, 0, 1;\n}\n"
    : "+f"(d[0]), "+f"(d[1]), "+f"(d[2]), "+f"(d[3]), "+f"(d[4]), "+f"(d[5]), "+f"(d[6]), "+f"(d[7]),
      "+f"(d[8]), "+f"(d[9]), "+f"(d[10]), "+f"(d[11]), "+f"(d[12]), "+f"(d[13]), "+f"(d[14]), "+f"(d[15]),
      "+f"(d[16]), "+f"(d[17]), "+f"(d[18]), "+f"(d[19]), "+f"(d[20]), "+f"(d[21]), "+f"(d[22]), "+f"(d[23]),
      "+f"(d[24]), "+f"(d[25]), "+f"(d[26]), "+f"(d[27]), "+f"(d[28]), "+f"(d[29]), "+f"(d[30]), "+f"(d[31]),
      "+f"(d[32]), "+f"(d[33]), "+f"(d[34]), "+f"(d[35]), "+f"(d[36]), "+f"(d[37]), "+f"(d[38]), "+f"(d[39]),
      "+f"(d[40]), "+f"(d[41]), "+f"(d[42]), "+f"(d[43]), "+f"(d[44]), "+f"(d[45]), "+f"(d[46]), "+f"(d[47]),
      "+f"(d[48]), "+f"(d[49]), "+f"(d[50]), "+f"(d[51]), "+f"(d[52]), "+f"(d[53]), "+f"(d[54]), "+f"(d[55]),
      "+f"(d[56]), "+f"(d[57]), "+f"(d[58]), "+f"(d[59]), "+f"(d[60]), "+f"(d[61]), "+f"(d[62]), "+f"(d[63]),
      "+f"(d[64]), "+f"(d[65]), "+f"(d[66]), "+f"(d[67]), "+f"(d[68]), "+f"(d[69]), "+f"(d[70]), "+f"(d[71]),
      "+f"(d[72]), "+f"(d[73]), "+f"(d[74]), "+f"(d[75]), "+f"(d[76]), "+f"(d[77]), "+f"(d[78]), "+f"(d[79]),
      "+f"(d[80]), "+f"(d[81]), "+f"(d[82]), "+f"(d[83]), "+f"(d[84]), "+f"(d[85]), "+f"(d[86]), "+f"(d[87])
    : "l"(da), "l"(db), "r"(scale_d));
}
__device__ __forceinline__ void wgmma_n64hi_rk(float (&d)[120], uint32_t a0, uint32_t a1, uint32_t a2, uint32_t a3, uint64_t db, int scale_d) {
  asm volatile("{\n.reg .pred p;\nsetp.ne.b32 p, %37, 0;\n"
    "wgmma.mma_async.sync.aligned.m64n64k16.f32.bf16.bf16 "
    "{%0, %1, %2, %3, %4, %5, %6, %7, %8, %9, %10, %11, %12, %13, %14, %15, "
    "%16, %17, %18, %19, %20, %21, %22, %23, %24, %25, %26, %27, %28, %29, %30, %31}, "
    "{%32, %33, %34, %35}, %36, p, 1, 1, 0;\n}\n"
    : "+f"(d[88]), "+f"(d[89]), "+f"(d[90]), "+f"(d[91]), "+f"(d[92]), "+f"(d[93]), "+f"(d[94]), "+f"(d[95]),
      "+f"(d[96]), "+f"(d[97]), "+f"(d[98]), "+f"(d[99]), "+f"(d[100]), "+f"(d[101]), "+f"(d[102]), "+f"(d[103]),
      "+f"(d[104]), "+f"(d[105]), "+f"(d[106]), "+f"(d[107]), "+f"(d[108]), "+f"(d[109]), "+f"(d[110]), "+f"(d[111]),
      "+f"(d[112]), "+f"(d[113]), "+f"(d[114]), "+f"(d[115]), "+f"(d[116]), "+f"(d[117]), "+f"(d[118]), "+f"(d[119])
    : "r"(a0), "r"(a1), "r"(a2), "r"(a3), "l"(db), "r"(scale_d));
}
__device__ __forceinline__ void wgmma_n176lo_rk(float (&d)[120], uint32_t a0, uint32_t a1, uint32_t a2, uint32_t a3, uint64_t db, int scale_d) {
  asm volatile("{\n.reg .pred p;\nsetp.ne.b32 p, %93, 0;\n"
    "wgmma.mma_async.sync.aligned.m64n176k16.f32.bf16.bf16 "
    "{%0, %1, %2, %3, %4, %5, %6, %7, %8, %9, %10, %11, %12, %13, %14, %15, "
    "%16, %17, %18, %19, %20, %21, %22, %23, %24, %25, %26, %27, %28, %29, %30, %31, "
    "%32, %33, %34, %35, %36, %37, %38, %39, %40, %41, %42, %43, %44, %45, %46, %47, "
    "%48, %49, %50, %51, %52, %53, %54, %55, %56, %57, %58, %59, %60, %61, %62, %63, "
    "%64, %65, %66, %67, %68, %69, %70, %71, %72, %73, %74, %75, %76, %77, %78, %79, "
    "%80, %81, %82, %83, %84, %85, %86, %87}, "
    "{%88, %89, %90, %91}, %92, p, 1, 1, 0;\n}\n"
    : "+f"(d[0]), "+f"(d[1]), "+f"(d[2]), "+f"(d[3]), "+f"(d[4]), "+f"(d[5]), "+f"(d[6]), "+f"(d[7]),
      "+f"(d[8]), "+f"(d[9]), "+f"(d[10]), "+f"(d[11]), "+f"(d[12]), "+f"(d[13]), "+f"(d[14]), "+f"(d[15]),
      "+f"(d[16]), "+f"(d[17]), "+f"(d[18]), "+f"(d[19]), "+f"(d[20]), "+f"(d[21]), "+f"(d[22]), "+f"(d[23]),
      "+f"(d[24]), "+f"(d[25]), "+f"(d[26]), "+f"(d[27]), "+f"(d[28]), "+f"(d[29]), "+f"(d[30]), "+f"(d[31]),
      "+f"(d[32]), "+f"(d[33]), "+f"(d[34]), "+f"(d[35]), "+f"(d[36]), "+f"(d[37]), "+f"(d[38]), "+f"(d[39]),
      "+f"(d[40]), "+f"(d[41]), "+f"(d[42]), "+f"(d[43]), "+f"(d[44]), "+f"(d[45]), "+f"(d[46]), "+f"(d[47]),
      "+f"(d[48]), "+f"(d[49]), "+f"(d[50]), "+f"(d[51]), "+f"(d[52]), "+f"(d[53]), "+f"(d[54]), "+f"(d[55]),
      "+f"(d[56]), "+f"(d[57]), "+f"(d[58]), "+f"(d[59]), "+f"(d[60]), "+f"(d[61]), "+f"(d[62]), "+f"(d[63]),
      "+f"(d[64]), "+f"(d[65]), "+f"(d[66]), "+f"(d[67]), "+f"(d[68]), "+f"(d[69]), "+f"(d[70]), "+f"(d[71]),
      "+f"(d[72]), "+f"(d[73]), "+f"(d[74]), "+f"(d[75]), "+f"(d[76]), "+f"(d[77]), "+f"(d[78]), "+f"(d[79]),
      "+f"(d[80]), "+f"(d[81]), "+f"(d[82]), "+f"(d[83]), "+f"(d[84]), "+f"(d[85]), "+f"(d[86]), "+f"(d[87])
    : "r"(a0), "r"(a1), "r"(a2), "r"(a3), "l"(db), "r"(scale_d));
}
__device__ __forceinline__ void wgmma_n80_rs(float (&d)[40], uint32_t a0, uint32_t a1, uint32_t a2, uint32_t a3, uint64_t db, int scale_d) {
  asm volatile("{\n.reg .pred p;\nsetp.ne.b32 p, %45, 0;\n"
    "wgmma.mma_async.sync.aligned.m64n80k16.f32.bf16.bf16 "
    "{%0, %1, %2, %3, %4, %5, %6, %7, %8, %9, %10, %11, %12, %13, %14, %15, "
    "%16, %17, %18, %19, %20, %21, %22, %23, %24, %25, %26, %27, %28, %29, %30, %31, "
    "%32, %33, %34, %35, %36, %37, %38, %39}, "
    "{%40, %41, %42, %43}, %44, p, 1, 1, 1;\n}\n"
    : "+f"(d[0]), "+f"(d[1]), "+f"(d[2]), "+f"(d[3]), "+f"(d[4]), "+f"(d[5]), "+f"(d[6]), "+f"(d[7]),
      "+f"(d[8]), "+f"(d[9]), "+f"(d[10]), "+f"(d[11]), "+f"(d[12]), "+f"(d[13]), "+f"(d[14]), "+f"(d[15]),
      "+f"(d[16]), "+f"(d[17]), "+f"(d[18]), "+f"(d[19]), "+f"(d[20]), "+f"(d[21]), "+f"(d[22]), "+f"(d[23]),
      "+f"(d[24]), "+f"(d[25]), "+f"(d[26]), "+f"(d[27]), "+f"(d[28]), "+f"(d[29]), "+f"(d[30]), "+f"(d[31]),
      "+f"(d[32]), "+f"(d[33]), "+f"(d[34]), "+f"(d[35]), "+f"(d[36]), "+f"(d[37]), "+f"(d[38]), "+f"(d[39])
    : "r"(a0), "r"(a1), "r"(a2), "r"(a3), "l"(db), "r"(scale_d));
}
__device__ __forceinline__ void wgmma_n80_ss(float (&d)[40], uint64_t da, uint64_t db, int scale_d) {
  asm volatile("{\n.reg .pred p;\nsetp.ne.b32 p, %42, 0;\n"
    "wgmma.mma_async.sync.aligned.m64n80k16.f32.bf16.bf16 "
    "{%0, %1, %2, %3, %4, %5, %6, %7, %8, %9, %10, %11, %12, %13, %14, %15, "
    "%16, %17, %18, %19, %20, %21, %22, %23, %24, %25, %26, %27, %28, %29, %30, %31, "
    "%32, %33, %34, %35, %36, %37, %38, %39}, "
    "%40, %41, p, 1, 1, 0, 1;\n}\n"
    : "+f"(d[0]), "+f"(d[1]), "+f"(d[2]), "+f"(d[3]), "+f"(d[4]), "+f"(d[5]), "+f"(d[6]), "+f"(d[7]),
      "+f"(d[8]), "+f"(d[9]), "+f"(d[10]), "+f"(d[11]), "+f"(d[12]), "+f"(d[13]), "+f"(d[14]), "+f"(d[15]),
      "+f"(d[16]), "+f"(d[17]), "+f"(d[18]), "+f"(d[19]), "+f"(d[20]), "+f"(d[21]), "+f"(d[22]), "+f"(d[23]),
      "+f"(d[24]), "+f"(d[25]), "+f"(d[26]), "+f"(d[27]), "+f"(d[28]), "+f"(d[29]), "+f"(d[30]), "+f"(d[31]),
      "+f"(d[32]), "+f"(d[33]), "+f"(d[34]), "+f"(d[35]), "+f"(d[36]), "+f"(d[37]), "+f"(d[38]), "+f"(d[39])
    : "l"(da), "l"(db), "r"(scale_d));
}

__device__ __forceinline__ constexpr int QT(int t) { return t < 8 ? t : 16 + t; }
__device__ __forceinline__ constexpr int KT(int t) { return t < 8 ? 8 + t : 18 + t; }
__device__ __forceinline__ constexpr int VT(int t) { return t < 8 ? 16 + t : 20 + t; }

struct Maps { CUtensorMap x, w, wr, wv, wo, wor, gate, up, down; };

__global__ void __cluster_dims__(2, 1, 1) __launch_bounds__(512, 1)
fused_kernel(const __nv_bfloat16* __restrict__ x, const __nv_bfloat16* __restrict__ wqkv,
             const __nv_bfloat16* __restrict__ wo, const __nv_bfloat16* __restrict__ w_r, const __nv_bfloat16* __restrict__ w_gate,
             const __nv_bfloat16* __restrict__ w_up, const __nv_bfloat16* __restrict__ w_down, __nv_bfloat16* __restrict__ out,
             Scratch* __restrict__ sc, const __grid_constant__ Maps tm) {
  extern __shared__ __align__(1024) uint8_t smem[];
  const int tid = threadIdx.x, bid = blockIdx.x;
  if ((unsigned)(tid - 128) < 16u) pf_l2((const char*)x + (bid * 16 + tid - 128) * 1280);
  if ((unsigned)(tid - 160) < 15u) pf_l2((const char*)wqkv + (bid * 15 + tid - 160) * 128);
  const int warp = __shfl_sync(0xffffffffu, tid >> 5, 0), lane = tid & 31;
  const uint32_t sb = (uint32_t)__cvta_generic_to_shared(smem);
  const uint32_t bar_full = sb + OFF_BAR, bar_empty = bar_full + 32, bar_aux = bar_full + 64, bar_ffn = bar_full + 72, bar_win = bar_full + 80, bar_tag = bar_full + 88, bar_rst = bar_full + 96 + 296 + 24,
                 bar_o = bar_full + 96, bar_oc = bar_o + 112, bar_st = bar_o + 224, bar_go = bar_o + 248, bar_kv = bar_o + 272, bar_half = bar_o + 296;
  if (warp < 4 && elect()) {
    mbar_init(bar_half + 8 * warp, 1);
    mbar_init(bar_full + 8 * (warp ^ 2), 1);
    mbar_init(bar_empty + 8 * warp, 24);
    mbar_init(bar_aux + 8 * warp, warp == 0 ? 64 : warp == 2 ? 32 : warp == 3 ? 2 : 1);
    asm volatile("fence.mbarrier_init.release.cluster;" ::: "memory");
  }
  asm volatile("barrier.cluster.arrive.relaxed.aligned;" ::: "memory");
  if (warp >= 8 && warp < 12 && elect()) asm volatile("prefetch.tensormap [%0];" :: "l"(&tm.x + (warp - 8)) : "memory");
  const int rank = bid & 1, cl = bid >> 1;
  const int q7 = ((cl - 36) * 37) >> 8;
  const int P = cl < 4 ? 0 : cl < 36 ? (cl - 4) & 7 : cl - 35 - 7 * q7;
  const int g = (cl < 4 ? 4 + cl : cl < 36 ? (cl - 4) >> 3 : 4 + q7);
  const int mt = 2 * P + rank, cid = mt * 8 + g;
  const bool ffn1 = g >= 5;
  const int fj = ffn1 ? mt * 3 + g - 5 : (P * 5 + g) * 2 + rank;
  const int ord = ((g >> 2) ^ P) & 1;
  auto ks_of = [&](int it) { return ord == 0 || it < 2 ? it : it <= 5 ? it + 4 : it - 4; };
  const int godd = g & 1, cm = g * 80 + godd * 16, cr = g * 80 + 64 - godd * 64;
  auto load_w = [&](int ks, uint32_t a, uint32_t bar, int kk) {
    tma_3d_mc(a + 16384 + ((kk + 1) & 3) * 6144, &tm.w, bar, cm, ks * 64 + kk * 16, 0);
    tma_3d_mc(a + 41472 + kk * 2048, &tm.wr, bar, cr, ks * 64 + kk * 16, 0);
    tma_3d_mc(a + 40960 + kk * 2048, &tm.wv, bar, cm + 48, ks * 64 + kk * 16, 2);
  };
  if (warp == 0 && elect()) {
    mbar_expect_tx(bar_half, 32768);
    tma_3d(sb + 2 * SLOT, &tm.x, bar_half, 0, P * 128, rank);
    mbar_expect_tx(bar_full + 16, 16384);
  }
  asm volatile("barrier.cluster.wait.aligned;" ::: "memory");
  if (warp == 0) {
    if (elect()) {
      uint32_t bar = bar_half;
#pragma unroll 1
      for (int kk = rank; kk < 4; kk += 2) { load_w(0, sb + 2 * SLOT, bar, kk); bar = bar_full + 16; }
    }
    asm volatile("bar.arrive 4, 64;" ::: "memory");
  }

  if (warp >= 8) {
    asm volatile("setmaxnreg.dec.sync.aligned.u32 %0;" :: "n"(REG_P));
#define TS_T 0
    if (warp == 8) {
      TS(8);
      bar_sync(4, 64);
      if (elect()) {
        TS(10);
#pragma unroll 1
        for (int it = 1; it < 10; it++) {
          const int s = (it + 2) & 3, ks = ks_of(it);
          const uint32_t full = bar_full + 8 * s, a = sb + s * SLOT;
          uint32_t bar = it < NSPLIT ? bar_half + 8 * it : full;
          if (it >= 4) mbar_wait(full + 32, ((it >> 2) - 1) & 1);
          if (it >= 2 && it < THR_END) mbar_wait(bar_full + 8 * (it & 3), 0);
          if (it < NSPLIT) mbar_expect_tx(bar, 32768);
          mbar_expect_tx(full, it < NSPLIT ? 16384 : SLOT);
          tma_3d(a, &tm.x, bar, ks * 64, P * 128, rank);
#pragma unroll 1
          for (int kk = rank; kk < 4; kk += 2) { load_w(ks, a, bar, kk); bar = full; }
          TS(12 + it);
          if ((it >> 1) == 2) {
            mbar_wait(bar_rst, 0);
            asm volatile("cp.async.bulk.global.shared::cta.bulk_group [%0], [%1], %2;\ncp.async.bulk.commit_group;"
                         :: "l"(it == 4 ? (uint4*)(g_own + cid) : (uint4*)&g_x + cid * GLOB_PER_CTA), "r"(sb + OFF_CS), "r"(it == 4 ? (int)sizeof(Own) : GLOB_PER_CTA * 16) : "memory");
          }
          if (it == 6) { asm volatile("cp.async.bulk.wait_group 0;" ::: "memory"); mbar_arrive(bar_tag); }
        }
        mbar_expect_tx(bar_ffn, ffn1 ? 81920 : 24576);
        int fjn = 0;
#pragma unroll 1
        for (int it = 9; it < 17; it++) {
          if (it >= 13) { mbar_wait(bar_oc + 8 * (it - 13), 0); mbar_wait(bar_oc + 56 + 8 * (it - 13), 0); }
          else if (it >= 10) {
            const uint32_t full = bar_full + 8 * (it - 10);
            const int g0 = 3 * (it - 10), g1 = min(g0 + 3, 8);
            mbar_wait(full + 32, it < 12);
            mbar_expect_tx(full, (g1 - g0) * 12800);
#pragma unroll 1
            for (int gp = g0 + ((g0 ^ rank) & 1); gp < g1; gp += 2) {
              tma_3d_mc(sb + gp * 15360, &tm.wo, full, 0, gp * 80, g * 2);
              tma_3d_mc(sb + gp * 15360 + 10240, &tm.wor, full, 512 + g * 16, gp * 80, 0);
            }
          }
          const int j1 = ffn1 ? (it >= 13 ? 2 * it - 22 : min(it - 8, 3)) : (it >= 13 ? 12 : min((it - 8) * F_PER, F_MAX));
#pragma unroll 1
          for (; fjn < j1; fjn++) {
            const int j = fjn < 3 ? fjn + 7 : fjn - 3;
            if (ffn1) tma_3d(sb + (j < 7 ? 0 : OFF_W2 - 57344) + j * 8192, j < 5 ? &tm.gate : &tm.up, bar_ffn, fj * 32, (j < 5 ? j : j - 5) * 128, 0);
            else tma_3d(sb + OFF_W2 + fjn * 2048, &tm.down, bar_ffn, fj * 8, fjn * 128, 0);
          }
        }
        TS(11);
      }
#undef TS_T
#define TS_T 64
    } else if (warp >= 12) {
      const int l7 = lane & 7, j = warp - 12, ch = min((P >> 1) * 4 + rank * 2 + (j >> 1), 14);
      const uint32_t sxo = ((g & 3) * 32 + j * 8 + l7) * 128 + (((lane >> 3) ^ l7) * 16);
      const uint32_t swo = ch < 12 ? 16384 + (lane >> 4) * 6144 + (ch >> 2) * 2048 + (lane & 15) * 128 + ((((ch & 3) * 2 + (j & 1)) ^ l7) * 16)
                                   : 41472 + (lane >> 4) * 2048 + (ch - 12) * 512 + (lane & 15) * 32 + (((j & 1) ^ (l7 >> 2)) * 16);
      float ps = 0.f, pq = 0.f, pq1 = 0.f, pc = 0.f;
      uint32_t tag = 0;
      char* const pp = hold((lane & 1) ? (char*)&g_own[cid].cs[j * 8 + (lane >> 2)] : (char*)&g_own[cid].st1[j * 8 + (lane >> 2)]);
#pragma unroll 1
      for (int it = 1 - ord; it < 6; it = max(it + 1, 2)) {
        const int sl = (it + 2) & 3;
        if (it == 5) { mbar_wait(bar_tag, 0); tag = __float_as_uint(lds32f(sb + OFF_WR + 324)); }
        if (it < NSPLIT) mbar_wait(bar_half + 8 * it, 0);
        mbar_wait(bar_full + 8 * sl, (it >> 2) & 1);
        TS(it);
        const uint32_t a = sb + sl * SLOT;
        const uint4 v0 = ldsm4(a + sxo), v1 = ldsm4((a + sxo) ^ 64), w0 = ldsm4t(a + swo), w1 = ldsm4t(a + swo + (ch < 12 ? 12288 : 4096));
        if (lane + (int)((v0.x & v1.x & w0.x & w1.x) == 0x7fc17fc1u && (v0.x | v1.x) == 0u) < 2) mbar_arrive_cta(bar_empty + 8 * sl, lane);
        const uint32_t vv[8] = {v0.x, v0.y, v0.z, v0.w, v1.x, v1.y, v1.z, v1.w}, ww[8] = {w0.x, w0.y, w0.z, w0.w, w1.x, w1.y, w1.z, w1.w};
#pragma unroll
        for (int i = 0; i < 8; i++) {
          const float d = bf_lo(vv[i]), e = bf_hi(vv[i]);
          ps += d + e; pq = fmaf(d, d, pq); pq1 = fmaf(e, e, pq1); pc += bf_lo(ww[i]) + bf_hi(ww[i]);
        }
      }
      pq += pq1;
      ps += shx(ps, 1); pq += shx(pq, 1); pc += shx(pc, 1);
      ps += shx(ps, 2); pq += shx(pq, 2); pc += shx(pc, 2);
      if ((lane & 3) == 0) stg_pkt(pp, __float_as_uint(ps), __float_as_uint(pq), tag, 0u);
      if ((lane & 3) == 1) stg_rlx64(pp, __float_as_uint(pc), tag);
      asm volatile("bar.arrive 2, 192;" ::: "memory");
      if (warp == 12) {
        const uint4* const hp = hold(&g_own[max(cid - 16, 0)].halo[0][lane]);
        mbar_wait(bar_aux, 0);
        mbar_wait(bar_go, 0);
        uint4 v[5] = {};
        int guard = SPIN_MAX;
        if (P > 0) {
          do {
#pragma unroll
            for (int i = 0; i < 5; i++) v[i] = ldg_pkt(hp + 32 * i);
          } while (anyw(v[0].x == SENT || v[1].x == SENT || v[2].x == SENT || v[3].x == SENT || v[4].x == SENT) && --guard > 0);
        }
#pragma unroll
        for (int i = 0; i < 5; i++) *(uint4*)(smem + OFF_O + 10240 + i * 512 + lane * 16) = v[i];
        mbar_arrive(bar_kv);
      }
#undef TS_T
#define TS_T 32
    } else if (warp < 11) {
      const int l7 = lane & 7, hk = lane >> 4;
      if (warp == 10 && elect()) {
#pragma unroll 1
        for (int i = 0; i < 36; i++) mbar_init(bar_o + 8 * i, i < 14 || i == 30 ? 1 : i < 34 ? 4 : 128);
      }
      mbar_wait(bar_tag, 0);
      const uint32_t tag = __float_as_uint(lds32f(sb + OFF_WR + 324));
      bar_sync(2, 192);
      TS(0);
      int guard = SPIN_MAX;
      if (warp == 9) {
        const uint4* sp = &g_own[mt * 8].st1[lane];
        const uint4* hp = &g_own[max(mt - 2, 0) * 8 + 3].st1[24 + l7];
        uint4 a[5], b[5];
        bool bad;
        do {
          __nanosleep(AUX_NS);
          bad = false;
#pragma unroll
          for (int i = 0; i < 5; i++) {
            const uint4* q = i < 4 ? sp + i * (sizeof(Own) / 16) : hp;
            a[i] = ldg_pkt(q); b[i] = ldg_pkt(q + 4 * sizeof(Own) / 16);
          }
#pragma unroll
          for (int i = 0; i < 5; i++) bad |= a[i].z != tag || b[i].z != tag;
        } while (anyw(bad) && --guard);
        TS(1);
#pragma unroll
        for (int i = 0; i < 5; i++) {
          const float m = (__uint_as_float(a[i].x) + __uint_as_float(b[i].x)) * (1.f / 640.f);
          const float rs = rsq(fmaxf(fmaf(-m, m, (__uint_as_float(a[i].y) + __uint_as_float(b[i].y)) * (1.f / 640.f)), 0.f) + 1e-5f);
          ((float*)(smem + OFF_RS))[i < 4 ? 8 + lane + 32 * i : l7] = rs;
          const uint32_t mh = pack_bf16(-m, -m);
          const float ml = -m - bf_lo(mh);
          if (i < 4) ((uint2*)(smem + OFF_MN))[lane + 32 * i] = make_uint2(mh, pack_bf16(ml, ml));
        }
      } else {
        const uint4* cp = (const uint4*)g_own[hk * 8 + g].cs + (lane & 15);
        uint4 a[4], b[4];
        bool bad;
        do {
          __nanosleep(AUX_NS);
          bad = false;
#pragma unroll
          for (int i = 0; i < 4; i++) { a[i] = ldg_pkt(cp + i * 32 * sizeof(Own) / 16); b[i] = ldg_pkt(cp + (i * 32 + 16) * sizeof(Own) / 16); }
#pragma unroll
          for (int i = 0; i < 4; i++) bad |= a[i].y != tag || a[i].w != tag || b[i].y != tag || b[i].w != tag;
        } while (anyw(bad) && --guard);
#pragma unroll
        for (int i = 0; i < 4; i++)
          if (i < 3 || lane < 24) {
            const float c0 = __uint_as_float(a[i].x) + __uint_as_float(b[i].x), c1 = __uint_as_float(a[i].z) + __uint_as_float(b[i].z);
            const uint32_t hi = pack_bf16(c0, c1), w0 = pack_bf16(c0, c0 - bf_lo(hi)), w1 = pack_bf16(c1, c1 - bf_hi(hi));
            uint4* const d = (uint4*)(smem + OFF_CS) + 2 * (lane + 32 * i);
            d[0] = make_uint4(w0, w0, 0, 0); d[1] = make_uint4(w1, w1, 0, 0);
          }
        asm volatile("fence.proxy.async.shared::cta;" ::: "memory");
      }
      mbar_arrive(bar_aux);
      TS(2);
      const int fo = warp - 9, wq = fo ? 1 - LEAD : LEAD;
      const uint4* const fp = hold(g_own[mt * 8 + wq * 4].cnt);
      const char* src = hold((const char*)g_o[mt * 2 + wq]);
      if (elect()) {
        const uint32_t bo = bar_o + fo * 56;
#pragma unroll
        for (int i = 0; i < 7; i++) mbar_expect_tx(bo + 8 * i, 10240);
        uint32_t cv = 0, need = 4;
        mbar_wait(OV == 3 ? bar_st + 8 * fo : bar_go + 8 + 8 * fo, 0);
        uint32_t dst = sb + OFF_O + 20480;
#pragma unroll OUNR
        for (int i = 0; i < 7; i++) {
          if (i == g) { src += 10240; need <<= 4; }
          if (!(cv & need)) {
            do { cv = ldg_rlx32(fp); } while (!(cv & need) && --guard > 0);
            asm volatile("fence.proxy.async.global;" ::: "memory");
          }
          if (fo || i == 5 || (OV == 2 && i == 4)) mbar_wait(fo ? bar_oc + 8 * i : i == 4 ? bar_st : bar_st + 8, 0);
          if (i == 0) TS(6);
          asm volatile("cp.async.bulk.shared::cluster.global.mbarrier::complete_tx::bytes [%0], [%1], 10240, [%2];" :: "r"(dst), "l"(src), "r"(bo + 8 * i) : "memory");
          src += 10240; need <<= 4;
          dst += i == 4 ? -61440 : 10240;
        }
      }
#undef TS_T
#define TS_T 96
    } else {
      if ((sb & 0x3FFFF) != D0 * 16) __trap();
#pragma unroll 1
      for (int i = lane; i < 232; i += 32) { const uint32_t f = i < 208 ? SENT : 0u; ((uint4*)(smem + OFF_CS))[i] = make_uint4(f, f, f, f); }
      asm volatile("fence.proxy.async.shared::cta;" ::: "memory");
      if (elect()) mbar_arrive(bar_rst);
      mbar_wait(bar_full + 8 * ((HK_IT + 2) & 3), 0);
      TS(4);
      const uint32_t epoch = ldg_rlx32(g_epoch + cid) + 1;
      uint32_t wv[10];
#pragma unroll
      for (int i = 0; i < 10; i++) wv[i] = __ldg((const uint32_t*)w_r + lane + 32 * i);
      float s = 0.f;
#pragma unroll
      for (int i = 0; i < 10; i++) {
        s += bf_lo(wv[i]) + bf_hi(wv[i]);
        const unsigned u = i < 8 ? lane + 32 * (i - g) : lane + 32 * (i - 7) - g * 8;
        if (i < 8 ? u < 32u : u - 32u < 8u) *(float2*)(smem + OFF_WR + ((u & 3) * 10 + (u >> 2)) * 8) = make_float2(bf_lo(wv[i]), bf_hi(wv[i]));
      }
#pragma unroll
      for (int m = 1; m < 32; m <<= 1) s += shx(s, m);
      *(float2*)(smem + OFF_WR + 320) = make_float2(s, __uint_as_float(epoch * 0x9E3779B8u));
      g_epoch[cid] = epoch;
      TS(3);
      if (elect()) mbar_arrive(bar_tag);
      TS(5);
#pragma unroll 1
      for (int i = 0; i < PFW_N; i++) {
        const int m = (i + 2) >> 2, n = m == 0 ? 50 : 120, t = (m == 0 ? i : (i + 2) & 3) * 32 + lane;
        const char* b = (const char*)(m == 0 ? wo : m == 1 ? w_up : m == 2 ? w_down : w_gate);
        if (t < n) pf_l2(b + (bid * n + t) * 128);
        __nanosleep(PFW_NS);
      }
      const uint4* const kp = hold(g_own[1].cnt);
      const uint4* const cb = hold(&g_x.cand[0][lane >> 2][lane & 3]);
      bar_sync(3, 64);
      uint4 k;
      uint32_t have = SENT;
      int guard = SPIN_MAX;
      while (true) {
        k = ldg_pkt(kp);
        if (ffn1) {
          while (k.x != have && --guard > 0) {
            const uint32_t tk = 2047u - (k.x & 2047u), want = k.x;
            const uint4* q = cb + ((tk >> 8) * 16 + (tk & 1) * 8 + ((tk >> 5) & 7)) * 192;
            const uint4 c0 = ldg_pkt(q), c1 = ldg_pkt(q + 4); const uint2 c2 = ldg_rlx64(q + 8);
            k = ldg_pkt(kp);
            *(uint4*)(smem + OFF_HN + lane * 16) = c0; *(uint4*)(smem + OFF_HN + 512 + lane * 16) = c1; *(uint2*)(smem + OFF_HN + 1024 + lane * 16) = c2;
            have = anyw(c0.x == SENT || c1.x == SENT || c2.x == SENT) ? SENT : want;
          }
        } else if (KEY_NS && k.z != 128u) __nanosleep(KEY_NS);
        if (k.z == 128u || --guard <= 0) break;
      }
      *(uint2*)(smem + OFF_WR + 336) = make_uint2(k.x, k.y);
      mbar_arrive(bar_win);
      TS(7);
    }
#undef TS_T
  } else {
#define TS_T 0
    asm volatile("setmaxnreg.inc.sync.aligned.u32 %0;" :: "n"(REG_C));
    const int wg = warp >> 2, w4 = warp & 3, r = lane >> 2, c = lane & 3;
    float acc[120];
    uint4 xr[5] = {};
    const uint32_t xa = pin(sb + (warp * 16 + (lane & 15)) * 128 + ((lane >> 4) ^ (lane & 7)) * 16);
    const uint32_t zero = __shfl_sync(0xffffffffu, (uint32_t)(uintptr_t)x & 8u, 0);
    const int fol = wg != LEAD;
    const bool first = (P == 0) && (warp == 0);
    const uint32_t kvs = holdu(sb + OFF_O + fol * 10240 + w4 * 2560 + lane * 16);
    uint4* const kvd = hold(warp == 7 ? &g_own[cid].halo[0][lane] : (uint4*)(smem + (warp == 3 ? OFF_O + lane * 16 : kvs - sb + 2560)));
    uint4* const odst = hold(&g_o[mt * 2 + wg][g][w4 * 160]);
    uint4* const ocnt = hold(g_own[mt * 8 + wg * 4].cnt + (lane & zero));
    const uint32_t oinc = holdu((1u << (4 * g)) + (lane & zero));
    const bool in0 = 2 * c <= r, in1 = 2 * c + 1 <= r;
    const uint32_t mL = holdu((in0 ? 0xffffu : 0u) | (in1 ? 0xffff0000u : 0u));
    const float bias0 = __uint_as_float(holdu(first && !in0 ? 0xff800000u : 0u)), bias1 = __uint_as_float(holdu(first && !in1 ? 0xff800000u : 0u));
    const uint32_t stb = sb + OFF_RS + warp * 64, kb0 = holdu(stb + (2 * c + (in0 ? 8 : 0)) * 4), kb1 = holdu(stb + (2 * c + 1 + (in1 ? 8 : 0)) * 4);
    const uint32_t os = sb + OFF_O + (fol ? 0 : 61440) + w4 * 2560, oa = holdu(os + ((lane >> 3) & 1) * 1280 + (lane >> 4) * 128 + (lane & 7) * 16);
    float rlo, rhi, scl0, scl1, sch0, sch1;
    uint32_t m0 = 0, m1 = 0, m2 = 0, m3 = 0;
    const uint32_t mna = pin(sb + OFF_MN + (warp * 16 + r) * 8 + c * 4);
    const int itx = ord == 0 || g < 2 ? g : g < 6 ? g + 4 : g - 4, ity = (ord ? 4 : 8) + (g >> 2);
    uint32_t rel;
    asm volatile("mapa.shared::cluster.u32 %0, %1, %2;" : "=r"(rel) : "r"(bar_empty), "r"(tid & 1));
    const uint32_t xa1 = pin(xa ^ 32), xa2 = pin(xa ^ 64), xa3 = pin(xa ^ 96), xb = pin(xa ^ ((g & 3) * 32));
    const uint32_t da0 = wg * 512;
    const bool rel2 = lane < 2, rel6 = lane < 2 + 2 * (warp & 1);
    mbar_wait(bar_half, 0);
    TS(13);
    wgmma_fence();
#pragma unroll
    for (int it = 0; it < 10; it++) {
      const int s = (it + 2) & 3;
#pragma unroll
      for (int kk = 0; kk < 4; kk++) {
        if (kk == 2 && it > 0) {
          wgmma_commit();
          wgmma_wait<1>();
          const uint32_t ra = ((xr[0].x ^ xr[1].x ^ xr[2].x ^ xr[3].x ^ xr[4].x) & zero) | rel;
          if (it == 1 ? (ord ? rel2 : rel6) : it == 2 ? (ord ? rel6 : rel2) : it < 7 ? rel2 : rel6)
            asm volatile("mbarrier.arrive.shared::cluster.b64 _, [%0];" :: "r"(ra + 8 * ((it + 1) & 3)) : "memory");
        }
        if (kk == 2) {
          ldsm4_if(xr[0], xa, s * SLOT, it == itx); ldsm4_if(xr[1], xa1, s * SLOT, it == itx);
          ldsm4_if(xr[2], xa2, s * SLOT, it == itx); ldsm4_if(xr[3], xa3, s * SLOT, it == itx);
          if ((it & 6) == 4 || it >= 8) ldsm4_if(xr[4], xb, s * SLOT, it == ity);
        }
        if (kk == AK && it == 9) {
          mbar_wait(bar_aux, 0);
          TS(3);
          if (c < 2) {
            m0 = __float_as_uint(lds32f(mna)); m1 = __float_as_uint(lds32f(mna + 64)); m2 = __float_as_uint(lds32f(mna + zero)); m3 = __float_as_uint(lds32f(mna + zero + 64));
          }
          const float qs = 0.22360679774997896f * 1.4426950408889634f;
          rlo = lds32f(stb + (8 + r) * 4); rhi = lds32f(stb + (16 + r) * 4);
          scl0 = lds32f(kb0) * (rlo * qs); scl1 = lds32f(kb1) * (rlo * qs); sch0 = lds32f(kb0 + 32) * (rhi * qs); sch1 = lds32f(kb1 + 32) * (rhi * qs);
          if (!fol) bar_sync(11, 256);
        }
        if (it * 4 + kk == 40 - LAG && fol) {
          asm volatile("bar.arrive 11, 256;" ::: "memory");
          bar_sync(10, 256);
        }
        if (kk == 2 && it < NSPLIT) mbar_wait(bar_full + 8 * s, 0);
        const uint64_t da = mk64(da0 + (D0 + s * (SLOT >> 4) + kk * 2 + (1 << 16)), 0x40000040u);
        wgmma_n64hi_ss(acc, da, mk64(D0 + s * (SLOT >> 4) + 2560 + kk * 128 + (32 << 16), 0xC0000010u), (it | kk) != 0);
        wgmma_n176lo_ss(acc, da, mk64(D0 + s * (SLOT >> 4) + 1024 + ((kk + 1) & 3) * 384 + (128 << 16), 0x40000040u), (it | kk) != 0);
      }
      wgmma_commit();
      if (it < 9) {
        if (it + 1 < NSPLIT) mbar_wait(bar_half + 8 * (it + 1), 0);
        else mbar_wait(bar_full + 8 * ((it + 3) & 3), ((it + 1) >> 2) & 1);
        if (it < 8) TS(14 + it);
      }
    }
    {
      const uint64_t dc = make_desc(D0 * 16 + OFF_CS, 0, 128, 0);
      wgmma_fence();
      wgmma_n64hi_rk(acc, m0, m1, 0u, 0u, dc + 176, 1);
      wgmma_n176lo_rk(acc, m2, m3, 0u, 0u, dc, 1);
      wgmma_commit();
      if (!fol) asm volatile("bar.arrive 10, 256;" ::: "memory");
    }
    wgmma_wait<0>();
#pragma unroll
    for (int i = 0; i < 120; i++) asm volatile("" : "+f"(acc[i]) :: "memory");
    if (fol && lane == 0) mbar_arrive(bar_go);
    TS(2);
    uint32_t Qlo[10], Qhi[10], Klo[10], Khi[10], Vlo[10], Vhi[10];
#define CONV_HI(ROT) _Pragma("unroll") for (int t = 0; t < 10; t++) { \
      const int k = KT((t + ROT) % 10), v = VT((t + ROT) % 10); \
      Khi[t] = pack_bf16(acc[4 * k + 2], acc[4 * k + 3]); \
      Vhi[t] = pack_bf16(acc[4 * v + 2] * rhi, acc[4 * v + 3] * rhi); }
    if (godd) { CONV_HI(8) } else { CONV_HI(0) }
    st_pkt(kvd, Khi[0], Khi[1], Khi[3], Khi[4]);
    st_pkt(kvd + 32, Khi[5], Khi[6], Khi[8], Khi[9]);
    st_pkt(kvd + 64, Khi[2], Khi[7], Vhi[0], Vhi[1]);
    st_pkt(kvd + 96, Vhi[2], Vhi[3], Vhi[4], Vhi[5]);
    st_pkt(kvd + 128, Vhi[6], Vhi[7], Vhi[8], Vhi[9]);
    if (warp < 7) mbar_arrive(bar_kv + ((warp + 1) >> 2) * 8);
#define CONV_LO(ROT) _Pragma("unroll") for (int t = 0; t < 10; t++) { \
      const int q = QT((t + ROT) % 10), k = KT((t + ROT) % 10), v = VT((t + ROT) % 10); \
      Vhi[t] = movm(Vhi[t]); \
      Klo[t] = pack_bf16(acc[4 * k], acc[4 * k + 1]); \
      Vlo[t] = movm(pack_bf16(acc[4 * v] * rlo, acc[4 * v + 1] * rlo)); \
      Qlo[t] = pack_bf16(acc[4 * q], acc[4 * q + 1]); \
      Qhi[t] = pack_bf16(acc[4 * q + 2], acc[4 * q + 3]); }
    if (godd) { CONV_LO(8) } else { CONV_LO(0) }
    const int slot = mt * 8 + warp;
    int guard = SPIN_MAX;
    uint4 pv[5];
    const bool cA = c < 2, nA = r < 4;
    TS(0);
    mbar_wait(bar_go + fol * 8, 0);
    TS(23);
    uint32_t qe[4][2];
    float sl0[4], sl1[4], th0[4], th1[4];
#pragma unroll
    for (int hd = 0; hd < 4; hd++) {
      const int ta = 5 * (hd >> 1) + 3 * (hd & 1), ts = 5 * (hd >> 1) + 2;
      const bool mine = (hd & 1) ? !cA : cA;
      qe[hd][0] = mine ? Qlo[ts] : 0u; qe[hd][1] = mine ? Qhi[ts] : 0u;
      float sl[4], sh[4];
      mma_k24(sl, Qlo[ta], Qhi[ta], Qlo[ta + 1], Qhi[ta + 1], Klo[ta], Klo[ta + 1], qe[hd][0], qe[hd][1], Klo[ts]);
      mma_k24(sh, Qlo[ta], Qhi[ta], Qlo[ta + 1], Qhi[ta + 1], Khi[ta], Khi[ta + 1], qe[hd][0], qe[hd][1], Khi[ts]);
      th0[hd] = (in0 ? sh[2] : sl[2]) * sch0; th1[hd] = (in1 ? sh[3] : sl[3]) * sch1;
      float mh = fmaxf(th0[hd], th1[hd]);
      mh = fmaxf(mh, shx(mh, 1)); mh = fmaxf(mh, shx(mh, 2));
      th0[hd] -= mh; th1[hd] -= mh;
      sl0[hd] = sl[0]; sl1[hd] = sl[1];
    }
    mbar_wait(bar_kv + wg * 8, 0);
    TS(4);
#pragma unroll
    for (int j = 0; j < 5; j++) pv[j] = lds128(kvs + 512 * j);
    const uint32_t Kp[10] = {pv[0].x, pv[0].y, pv[2].x, pv[0].z, pv[0].w, pv[1].x, pv[1].y, pv[2].y, pv[1].z, pv[1].w};
    const uint32_t Vp[10] = {movm(pv[2].z), movm(pv[2].w), movm(pv[3].x), movm(pv[3].y), movm(pv[3].z), movm(pv[3].w), movm(pv[4].x), movm(pv[4].y), movm(pv[4].z), movm(pv[4].w)};
    const uint32_t ONES = 0x3f803f80u;
    uint32_t of[20];
#pragma unroll
    for (int hp = 0; hp < 2; hp++) {
      float o[6][4];
#pragma unroll
      for (int hh = 0; hh < 2; hh++) {
        const int hd = 2 * hp + hh, ta = 5 * hp + 3 * hh, ts = 5 * hp + 2;
        float sp[4];
        mma_k24(sp, Qlo[ta], Qhi[ta], Qlo[ta + 1], Qhi[ta + 1], Kp[ta], Kp[ta + 1], qe[hd][0], qe[hd][1], Kp[ts]);
        const float tl0 = fmaf(in0 ? sl0[hd] : sp[0], scl0, bias0), tl1 = fmaf(in1 ? sl1[hd] : sp[1], scl1, bias1);
        float ml = fmaxf(tl0, tl1);
        ml = fmaxf(ml, shx(ml, 1)); ml = fmaxf(ml, shx(ml, 2));
        if (HOLD == 1 && hd == 3 && !fol && lane == 0) mbar_arrive(bar_go + 8);
        const uint32_t Pl = pack_bf16(ex2(tl0 - ml), ex2(tl1 - ml)), Ph = pack_bf16(ex2(th0[hd]), ex2(th1[hd]));
        const uint32_t a0 = Pl & mL, a1 = Ph & ~mL, a3 = Ph & mL, ap = Pl & ~mL;
        const bool vm = hh == 0 ? nA : !nA;
        mma_k24(o[3 * hh], a0, a1, 0u, a3, Vlo[ta], Vhi[ta], ap, 0u, Vp[ta]);
        mma_k24(o[3 * hh + 1], a0, a1, 0u, a3, Vlo[ta + 1], Vhi[ta + 1], ap, 0u, Vp[ta + 1]);
        mma_k24(o[3 * hh + 2], a0, a1, 0u, a3, vm ? Vlo[ts] : ONES, vm ? Vhi[ts] : ONES, ap, 0u, vm ? Vp[ts] : ONES);
      }
      const float il = rcp(cA ? o[5][0] : o[2][0]), ih = rcp(cA ? o[5][2] : o[2][2]);
      const float jl = shx(il, 2), jh = shx(ih, 2);
      const float al = cA ? jl : il, ah = cA ? jh : ih, bl = cA ? il : jl, bh = cA ? ih : jh;
      const int t0 = 5 * hp;
      of[2 * t0]     = pack_bf16(o[0][0] * al, o[0][1] * al); of[2 * t0 + 1] = pack_bf16(o[0][2] * ah, o[0][3] * ah);
      of[2 * t0 + 2] = pack_bf16(o[1][0] * al, o[1][1] * al); of[2 * t0 + 3] = pack_bf16(o[1][2] * ah, o[1][3] * ah);
      of[2 * t0 + 4] = pack_bf16((cA ? o[2][0] : o[5][0]) * jl, (cA ? o[2][1] : o[5][1]) * jl);
      of[2 * t0 + 5] = pack_bf16((cA ? o[2][2] : o[5][2]) * jh, (cA ? o[2][3] : o[5][3]) * jh);
      of[2 * t0 + 6] = pack_bf16(o[3][0] * bl, o[3][1] * bl); of[2 * t0 + 7] = pack_bf16(o[3][2] * bh, o[3][3] * bh);
      of[2 * t0 + 8] = pack_bf16(o[4][0] * bl, o[4][1] * bl); of[2 * t0 + 9] = pack_bf16(o[4][2] * bh, o[4][3] * bh);
    }
    {
#pragma unroll
      for (int s = 0; s < 5; s++) {
        stsm4(oa + s * 256, of[4 * s], of[4 * s + 1], of[4 * s + 2], of[4 * s + 3]);
        if (s == 0 && (fol || HOLD == 2) && lane == 0) mbar_arrive(bar_go + 8 + 8 * fol);
      }
      asm volatile("fence.proxy.async.shared::cta;" ::: "memory");
      __syncwarp();
      asm volatile("{\n.reg .pred q;\nelect.sync _|q, 0xffffffff;\n@q cp.async.bulk.global.shared::cta.bulk_group [%0], [%1], 2560;\ncp.async.bulk.commit_group;\n}\n" :: "l"(odst), "r"(os) : "memory");
    }
    TS(5);
    float h[40];
#pragma unroll
    for (int s = 0; s < 5; s++) {
      const uint4 v = xr[s];
      h[8 * s] = bf_lo(v.x); h[8 * s + 1] = bf_hi(v.x); h[8 * s + 2] = bf_lo(v.y); h[8 * s + 3] = bf_hi(v.y);
      h[8 * s + 4] = bf_lo(v.z); h[8 * s + 5] = bf_hi(v.z); h[8 * s + 6] = bf_lo(v.w); h[8 * s + 7] = bf_hi(v.w);
    }
    asm volatile("cp.async.bulk.wait_group 0;" ::: "memory");
    __syncwarp();
    if (lane == 0) {
      asm volatile("red.relaxed.gpu.global.add.u32 [%0], %1;" :: "l"(ocnt), "r"(oinc) : "memory");
      mbar_arrive(bar_st + 8 * fol);
    }
    TS(22);
    mbar_wait(bar_full, 0); mbar_wait(bar_full + 8, 0); mbar_wait(bar_full + 16, 1);
    mbar_wait(bar_go + 16, 0);
    const uint64_t dwo = make_desc(D0 * 16, 5120, 512, 2);
    wgmma_fence();
#pragma unroll
    for (int s = 0; s < 5; s++) wgmma_n80_rs(h, of[4 * s], of[4 * s + 1], of[4 * s + 2], of[4 * s + 3], dwo + g * 960 + s * 64, 1);
    wgmma_commit();
    TS(6);
    const bool odd = c & 1;
    uint4* const sp = hold(&g_own[slot].st2[r + (odd ? 8 : 0)]);
    uint4* const cdp = hold(&g_x.cand[slot][g][lane & zero]);
    uint4* const kcp = hold(g_own[1].cnt + (lane & zero));
    float wr[20];
#pragma unroll
    for (int j = 0; j < 5; j++) {
      const uint4 v = lds128(sb + OFF_WR + c * 80 + j * 16);
      wr[4 * j] = __uint_as_float(v.x); wr[4 * j + 1] = __uint_as_float(v.y); wr[4 * j + 2] = __uint_as_float(v.z); wr[4 * j + 3] = __uint_as_float(v.w);
    }
    const float wsum = lds32f(sb + OFF_WR + 320);
    const uint32_t bo = bar_o + fol * 56;
    if (PRIO < 7 && fol) mbar_wait(bar_oc + 8 * PRIO, 0);
#pragma unroll
    for (int i = 0; i < 7; i++) {
      mbar_wait(bo + 8 * i, 0);
      if (i == 0) TS(1);
      const uint32_t da = D0 + OFF_O / 16 + (8 << 16) + ((i + 2) % 7) * 640, db = D0 + (320 << 16) + (i >= g ? i + 1 : i) * 960;
      wgmma_fence();
#pragma unroll
      for (int s = 0; s < 5; s++) wgmma_n80_ss(h, mk64(da + s * 16, 80u), mk64(db + s * 64, 0x80000020u), 1);
      wgmma_commit();
      wgmma_wait<1>();
      if (lane == 0 && i > 0) mbar_arrive(bo + 104 + 8 * i);
    }
    const int tok0 = P * 256 + 32 * warp + rank;
    wgmma_wait<0>();
#pragma unroll
    for (int i = 0; i < 40; i++) asm volatile("" : "+f"(h[i]) :: "memory");
    if (lane == 0) mbar_arrive(bo + 160);
    if (SPLITB) { asm volatile("{\n.reg .pred p;\nsetp.ne.u32 p, %0, 0;\n@p trap;\n}\n" :: "r"(zero) : "memory"); }
    TS(7);
    float mean, rstd, rr;
    bool pub;
    {
      float l1 = 0.f, l2 = 0.f, l3 = 0.f, h1 = 0.f, h2 = 0.f, h3 = 0.f;
#pragma unroll
      for (int j = 0; j < 10; j++) {
        l1 += h[4 * j] + h[4 * j + 1]; h1 += h[4 * j + 2] + h[4 * j + 3];
        l2 = fmaf(h[4 * j], h[4 * j], l2); l2 = fmaf(h[4 * j + 1], h[4 * j + 1], l2);
        h2 = fmaf(h[4 * j + 2], h[4 * j + 2], h2); h2 = fmaf(h[4 * j + 3], h[4 * j + 3], h2);
        l3 = fmaf(h[4 * j], wr[2 * j], l3); l3 = fmaf(h[4 * j + 1], wr[2 * j + 1], l3);
        h3 = fmaf(h[4 * j + 2], wr[2 * j], h3); h3 = fmaf(h[4 * j + 3], wr[2 * j + 1], h3);
      }
      float s1 = (odd ? h1 : l1) + shx(odd ? l1 : h1, 1), s2 = (odd ? h2 : l2) + shx(odd ? l2 : h2, 1), s3 = (odd ? h3 : l3) + shx(odd ? l3 : h3, 1);
      s1 += shx(s1, 2); s2 += shx(s2, 2); s3 += shx(s3, 2);
      uint4 p0;
      float o1 = 0.f, o2 = 0.f, o3 = 0.f, oc = 7.f;
      asm volatile("{\n.reg .pred q;\nsetp.lt.u32 q, %9, 2;\n@q atom.relaxed.gpu.global.add.v4.f32 {%0, %1, %2, %3}, [%4], {%5, %6, %7, %8};\n}\n"
                   : "+f"(o1), "+f"(o2), "+f"(o3), "+f"(oc) : "l"(sp), "f"(s1), "f"(s2), "f"(s3), "f"(1.f), "r"(c) : "memory");
      const uint32_t last = __ballot_sync(0xffffffffu, oc == 7.f);
      pub = last & 1;
      p0.x = __float_as_uint(o1 + s1); p0.y = __float_as_uint(o2 + s2); p0.z = __float_as_uint(o3 + s3);
      if (last != 0xffffffffu)
      do { p0 = ldg_pkt(sp); } while (anyw(p0.w != 0x41000000u) && --guard > 0);
      mean = __uint_as_float(p0.x) * (1.f / 640.f);
      rstd = rsq(fmaxf(fmaf(-mean, mean, __uint_as_float(p0.y) * (1.f / 640.f)), 0.f) + 1e-5f);
      rr = fmaf(-mean, wsum, __uint_as_float(p0.z)) * rstd;
    }
    TS(8);
    const int myrow = r + (odd ? 8 : 0);
    const uint32_t kk = cA ? ord_key(rr) : 0u, kmax = __reduce_max_sync(0xffffffffu, kk);
    if (pub) {
      if (kk == kmax) asm volatile("red.relaxed.gpu.global.max.u64 [%0], %1;" :: "l"(kcp), "l"(mk64(2047 - tok0 - 2 * myrow, kk)) : "memory");
      __syncwarp();
      if (lane == 0) asm volatile("red.relaxed.gpu.global.add.u32 [%0 + 8], 1;" :: "l"(kcp) : "memory");
    }
    const int crow = __reduce_min_sync(0xffffffffu, kk == kmax ? myrow : 16), L = (crow & 7) * 4 + (crow >> 3);
    if (warp == g) asm volatile("bar.arrive 3, 64;" ::: "memory");
    const uint32_t stg = sb + (fol ? OFF_O : g * 15360) + w4 * 2560;
    uint4 held;
    {
      const float nb = -mean * rstd;
      const float rl = __shfl_sync(0xffffffffu, rstd, lane & 28), rh = __shfl_sync(0xffffffffu, rstd, (lane & 28) + 1);
      const float bl = __shfl_sync(0xffffffffu, nb, lane & 28), bh = __shfl_sync(0xffffffffu, nb, (lane & 28) + 1), al = 1.f + rl, ah = 1.f + rh;
      if ((L >> 2) == r) {
        const bool chi = L & 1;
        const float rc = chi ? rh : rl, bc = chi ? bh : bl;
        uint32_t n[10];
#pragma unroll
        for (int j = 0; j < 10; j++) n[j] = pack_bf16(fmaf(chi ? h[4 * j + 2] : h[4 * j], rc, bc), fmaf(chi ? h[4 * j + 3] : h[4 * j + 1], rc, bc));
        uint4* d = cdp + c;
        stg_pkt(d, n[0], n[1], n[2], n[3]); stg_pkt(d + 4, n[4], n[5], n[6], n[7]); stg_rlx64(d + 8, n[8], n[9]);
      }
      mbar_wait(bar_oc + 56, 0);
      const uint32_t fa = stg + (lane & 15) * 160 + (lane >> 4) * 16;
#pragma unroll
      for (int s = 0; s < 5; s++)
        stsm4(fa + s * 32, pack_bf16(fmaf(h[8 * s], al, bl), fmaf(h[8 * s + 1], al, bl)), pack_bf16(fmaf(h[8 * s + 2], ah, bh), fmaf(h[8 * s + 3], ah, bh)),
              pack_bf16(fmaf(h[8 * s + 4], al, bl), fmaf(h[8 * s + 5], al, bl)), pack_bf16(fmaf(h[8 * s + 6], ah, bh), fmaf(h[8 * s + 7], ah, bh)));
      __syncwarp();
      held = lds128(stg + crow * 160 + min(lane, 9) * 16);
      if (lane < 10) stg_pkt(cdp + 12 + lane, held.x, held.y, held.z, held.w);
    }
    TS(9);
    mbar_wait(bar_ffn, 0);
    const uint32_t red = sb + OFF_RED;
    if (ffn1) {
      uint4 w1[4][5];
      {
        const int k = (lane & 7) + (lane >> 4) * 8;
        const uint32_t a1 = sb + k * 64, sw = ((lane >> 3) & 1) ^ ((lane >> 1) & 3);
#pragma unroll
        for (int s = 0; s < 5; s++)
#pragma unroll
          for (int u = 0; u < 4; u++)
            w1[u][s] = ldsm4t(a1 + (s < 4 ? warp * 4096 + s * 1024 : 32768 + warp * 1024) + (u >> 1) * (40960 + (s == 4 || warp >= 4 ? OFF_W2 - 57344 : 0)) + ((sw ^ (2 * (u & 1))) * 16));
      }
      uint32_t* const ap = hold(g_x.act + fj * 16 + (lane >> 1));
      mbar_wait(bar_win, 0);
      const uint32_t hp = sb + OFF_HN + (warp * 4 + c) * 16;
      const uint4 c0 = lds128(hp), c1 = lds128(hp + 512), c2 = lds128(hp + 1024);
      TS(10);
      float a[4][4];
#pragma unroll
      for (int u = 0; u < 4; u++) {
        a[u][0] = a[u][1] = a[u][2] = a[u][3] = 0.f;
        mma_acc(a[u], w1[u][0], c0.x, c0.y); mma_acc(a[u], w1[u][1], c0.z, c0.w); mma_acc(a[u], w1[u][2], c1.x, c1.y);
        mma_acc(a[u], w1[u][3], c1.z, c1.w); mma_acc(a[u], w1[u][4], c2.x, c2.y);
      }
      asm volatile("st.shared.v2.f32 [%0], {%1, %2};" :: "r"(red + (warp * 32 + c * 8 + r) * 8),
                   "f"(cA ? (odd ? a[0][2] : a[0][0]) : (odd ? a[1][2] : a[1][0])), "f"(cA ? (odd ? a[2][2] : a[2][0]) : (odd ? a[3][2] : a[3][0])) : "memory");
      bar_sync(1, 256);
      if (warp == 0) {
        float2 t[8];
#pragma unroll
        for (int i = 0; i < 8; i++) t[i] = lds64f(red + (i * 32 + lane) * 8);
        const float s = ((t[0].x + t[1].x) + (t[2].x + t[3].x)) + ((t[4].x + t[5].x) + (t[6].x + t[7].x));
        const float u = ((t[0].y + t[1].y) + (t[2].y + t[3].y)) + ((t[4].y + t[5].y) + (t[6].y + t[7].y));
        const float av = s * u * rcp(1.f + ex2(-1.4426950408889634f * s));
        const float an = shx(av, 1);
        if (!odd) stg_rlx32(ap, pack_bf16(av, an));
      }
      bar_sync(1, 256);
      TS(11);
    }
    char* const ob2 = (char*)(out + tok0 * 640 + g * 64);
    const int remo = 896 - 96 * g;
    {
      char* const q0 = ob2 + (lane >> 3) * 2560 + (lane & 7) * 16;
      const uint32_t s0 = stg + (lane >> 3) * 160 + (lane & 7) * 16;
#pragma unroll
      for (int s = 0; s < 4; s++) stg128_if(4 * s + (lane >> 3) != crow, q0 + s * 10240, lds128(s0 + s * 640));
      stg128_if((lane >> 1) != crow, ob2 + (lane >> 1) * 2560 + (lane & 1) * 16 + 128 + remo, lds128(stg + (lane >> 1) * 160 + (lane & 1) * 16 + 128));
    }
    mbar_wait(bar_win, 0);
    uint4 win = lds128(sb + OFF_WR + 336);
    win.z = win.y; win.y = 2047u - (win.x & 2047u); win.x = (win.y >> 8) * 16 + (win.y & 1) * 8 + ((win.y >> 5) & 7);
    stg128_if(win.x != slot && lane < 10, ob2 + crow * 2560 + lane * 16 + (lane < 8 ? 0 : remo), held);
    if (!ffn1) {
      TS(10);
      uint4 w2[6];
      const uint32_t a2 = sb + OFF_W2 + (warp * 192 + 8 * (((lane >> 3) & 1) * 4 + ((lane & 7) >> 1)) + 2 * (lane >> 4) + (lane & 1)) * 16;
#pragma unroll
      for (int s = 0; s < 6; s++) w2[s] = ldsm4t(a2 + (s >> 1) * 1024 + (s & 1) * 64);
      const uint4* p = (const uint4*)(g_x.act + warp * 96) + (r & 1) * 4 + c;
      const uint32_t* pb = (const uint32_t*)&g_x.cand[win.x][fj < 64 ? fj >> 3 : (fj - 64) >> 1][fj < 64 ? 12 + (fj & 7) : 20 + (fj & 1)] + c;
      uint32_t* const op = hold((uint32_t*)(out + win.y * 640 + fj * 8) + c);
      const float sg = shx(rcp(1.f + ex2(-1.4426950408889634f * __uint_as_float(win.z ^ ((uint32_t)((int32_t)~win.z >> 31) | 0x80000000u)))), 1);
      uint4 c0, c1, c2; uint32_t bw;
      if (ACT_NS) __nanosleep(ACT_NS);
      do {
        c0 = ldg_pkt(p); c1 = ldg_pkt(p + 8); c2 = ldg_pkt(p + 16); bw = ldg_rlx32(pb);
      } while (anyw(max(max(max(max(c0.x, c0.y), max(c0.z, c0.w)), max(max(c1.x, c1.y), max(c1.z, c1.w))), max(max(max(c2.x, c2.y), max(c2.z, c2.w)), bw)) == SENT) && --guard > 0);
      TS(11);
      float a[4] = {0.f, 0.f, 0.f, 0.f}, b[4] = {0.f, 0.f, 0.f, 0.f}, d[4] = {0.f, 0.f, 0.f, 0.f};
      mma_acc(a, w2[0], c0.x, c0.y); mma_acc(b, w2[2], c1.x, c1.y); mma_acc(d, w2[4], c2.x, c2.y);
      mma_acc(a, w2[1], c0.z, c0.w); mma_acc(b, w2[3], c1.z, c1.w); mma_acc(d, w2[5], c2.z, c2.w);
      if (c == 0) sts32f(red + (warp * 8 + r) * 4, ((a[0] + a[3]) + (b[0] + b[3])) + (d[0] + d[3]));
      bar_sync(1, 256);
      if (tid < 4) {
        float2 t[8];
#pragma unroll
        for (int i = 0; i < 8; i++) t[i] = lds64f(red + (i * 4 + tid) * 8);
        const float y0 = ((t[0].x + t[1].x) + (t[2].x + t[3].x)) + ((t[4].x + t[5].x) + (t[6].x + t[7].x));
        const float y1 = ((t[0].y + t[1].y) + (t[2].y + t[3].y)) + ((t[4].y + t[5].y) + (t[6].y + t[7].y));
        stg_rlx32(op, pack_bf16(fmaf(y0, sg, bf_lo(bw)), fmaf(y1, sg, bf_hi(bw))));
      }
    }
    TS(12);
#undef TS_T
  }
}

typedef CUresult (*EncodeFn)(CUtensorMap*, CUtensorMapDataType, cuuint32_t, void*, const cuuint64_t*, const cuuint64_t*, const cuuint32_t*,
                             const cuuint32_t*, CUtensorMapInterleave, CUtensorMapSwizzle, CUtensorMapL2promotion, CUtensorMapFloatOOBfill);

void make_map(EncodeFn enc, CUtensorMap* m, const void* base, const cuuint64_t* dims, const cuuint64_t* strides, const cuuint32_t* box,
              CUtensorMapSwizzle swz, int promo = PROMO) {
  const cuuint32_t es[3] = {1, 1, 1};
  enc(m, CU_TENSOR_MAP_DATA_TYPE_BFLOAT16, 3, (void*)base, dims, strides, box, es, CU_TENSOR_MAP_INTERLEAVE_NONE, swz,
      (CUtensorMapL2promotion)promo, CU_TENSOR_MAP_FLOAT_OOB_FILL_NONE);
}

}

extern "C" void kernel_launch(void* const* d_in, const int* in_sizes, int n_in, void* d_out, int out_size) {
  const __nv_bfloat16* x = (const __nv_bfloat16*)d_in[0];
  const __nv_bfloat16* wqkv = (const __nv_bfloat16*)d_in[1];
  const __nv_bfloat16* wo = (const __nv_bfloat16*)d_in[2];
  void* fn = nullptr;
  cudaDriverEntryPointQueryResult st;
  cudaGetDriverEntryPoint("cuTensorMapEncodeTiled", &fn, cudaEnableDefault, &st);
  EncodeFn enc = (EncodeFn)fn;
  void* scp = nullptr;
  cudaGetSymbolAddress(&scp, g_scratch);
  Maps tm;
  { const cuuint64_t d[3] = {640, 1024, 2}, s[2] = {2560, 1280}; const cuuint32_t b[3] = {64, 128, 1}; make_map(enc, &tm.x, x, d, s, b, CU_TENSOR_MAP_SWIZZLE_128B, PROMOX); }
  { const cuuint64_t d[3] = {640, 640, 3}, s[2] = {3840, 1280}; const cuuint32_t b[3] = {64, 16, 3}; make_map(enc, &tm.w, wqkv, d, s, b, CU_TENSOR_MAP_SWIZZLE_128B); }
  { const cuuint64_t d[3] = {640, 640, 3}, s[2] = {3840, 1280}; const cuuint32_t b[3] = {16, 16, 3}; make_map(enc, &tm.wr, wqkv, d, s, b, CU_TENSOR_MAP_SWIZZLE_32B); }
  { const cuuint64_t d[3] = {640, 640, 3}, s[2] = {3840, 1280}; const cuuint32_t b[3] = {16, 16, 1}; make_map(enc, &tm.wv, wqkv, d, s, b, CU_TENSOR_MAP_SWIZZLE_32B); }
  { const cuuint64_t d[3] = {32, 640, 20}, s[2] = {1280, 64}; const cuuint32_t b[3] = {32, 80, 2}; make_map(enc, &tm.wo, wo, d, s, b, CU_TENSOR_MAP_SWIZZLE_64B); }
  { const cuuint64_t d[3] = {640, 640, 1}, s[2] = {1280, 819200}; const cuuint32_t b[3] = {16, 80, 1}; make_map(enc, &tm.wor, wo, d, s, b, CU_TENSOR_MAP_SWIZZLE_64B); }
  { const cuuint64_t d[3] = {1536, 640, 1}, s[2] = {3072, 1966080}; const cuuint32_t b[3] = {32, 128, 1};
    make_map(enc, &tm.gate, d_in[5], d, s, b, CU_TENSOR_MAP_SWIZZLE_64B); make_map(enc, &tm.up, d_in[6], d, s, b, CU_TENSOR_MAP_SWIZZLE_64B); }
  { const cuuint64_t d[3] = {640, 1536, 1}, s[2] = {1280, 1966080}; const cuuint32_t b[3] = {8, 128, 1}; make_map(enc, &tm.down, d_in[7], d, s, b, CU_TENSOR_MAP_SWIZZLE_NONE); }
  cudaFuncSetAttribute(fused_kernel, cudaFuncAttributeMaxDynamicSharedMemorySize, SMEM_BYTES);
  fused_kernel<<<128, 512, SMEM_BYTES, cudaStreamPerThread>>>(x, wqkv, wo, (const __nv_bfloat16*)d_in[4], (const __nv_bfloat16*)d_in[5],
                                                              (const __nv_bfloat16*)d_in[6], (const __nv_bfloat16*)d_in[7], (__nv_bfloat16*)d_out, (Scratch*)scp, tm);
}
```

```cpp
#include <cuda_runtime.h>
#include <cuda_bf16.h>
#include <cuda.h>
#include <stdint.h>

#define PFW_NS 50
#define PFW_N 14
#define ACT_NS 100
#define KEY_NS 0
#define AUX_NS 50
#define REG_P 64
#define REG_C 192
#define LEAD 1
#define HK_IT 2
#define F_PER 2
#define F_MAX 8
#define HOLD 2
#define AK 3
#define NSPLIT 3
#define THR_END 3
#define BOUNDED 0
#define TLIGHT 0
#define ATOM2 1
#define LAG 4
#define OV 2
#define O_UNROLL 1
#define PRIO 7
#define SPLITB 1
#define GPAD 3328
#define PROMO 2
#define PROMOX 2

namespace {

constexpr int SLOT    = 49152;
constexpr int OFF_O   = 122880;
constexpr int OFF_W2  = 4 * SLOT;
constexpr int OFF_CS  = OFF_W2 + 24576;
constexpr int OFF_RS  = OFF_CS + 3840;
constexpr int OFF_MN  = OFF_RS + 576;
constexpr int OFF_WR  = OFF_MN + 1024;
constexpr int OFF_RED = OFF_CS;
constexpr int OFF_HN  = OFF_CS + 2048;
constexpr int OFF_PT  = OFF_WR + 352;
constexpr int OFF_BAR = OFF_PT + 768;
constexpr int SMEM_BYTES = OFF_BAR + 424 + 384;
constexpr uint32_t D0 = 1024 >> 4;
constexpr int OUNR = O_UNROLL;
constexpr uint32_t SENT = 0xFFFFFFFFu;
constexpr int SPIN_MAX = 1 << 20;

struct Glob {
  uint4 cand[128][8][24];
  uint32_t act[768];
  uint32_t pad[GPAD];
};
constexpr int GLOB_PER_CTA = sizeof(Glob) / 16 / 128;
static_assert(GLOB_PER_CTA * 128 * 16 == sizeof(Glob), "glob size");
struct Own {
  uint4 halo[5][32];
  uint4 st1[32];
  uint2 cs[32];
  uint4 st2[16];
  uint4 cnt[8];
};
struct Scratch {
  Glob x;
  Own own[128];
  uint4 o[32][8][640];
  uint32_t epoch[128];
};
__device__ __align__(128) Scratch g_scratch;
#define g_x (sc->x)
#define g_own (sc->own)
#define g_o (sc->o)
#define g_epoch (sc->epoch)
#define TS(i)

__device__ __forceinline__ void mbar_init(uint32_t bar, uint32_t cnt) { asm volatile("mbarrier.init.shared::cta.b64 [%0], %1;" :: "r"(bar), "r"(cnt) : "memory"); }
__device__ __forceinline__ void mbar_expect_tx(uint32_t bar, uint32_t bytes) { asm volatile("mbarrier.arrive.expect_tx.shared::cta.b64 _, [%0], %1;" :: "r"(bar), "r"(bytes) : "memory"); }
__device__ __forceinline__ void mbar_arrive(uint32_t bar) { asm volatile("mbarrier.arrive.shared::cta.b64 _, [%0];" :: "r"(bar) : "memory"); }
__device__ __forceinline__ void mbar_arrive_cta(uint32_t bar, uint32_t cta) {
  asm volatile("{\n.reg .b32 ra;\nmapa.shared::cluster.u32 ra, %0, %1;\nmbarrier.arrive.shared::cluster.b64 _, [ra];\n}\n" :: "r"(bar), "r"(cta) : "memory");
}
__device__ __forceinline__ void mbar_wait(uint32_t bar, uint32_t parity) {
  asm volatile("{\n.reg .pred p;\nW:\nmbarrier.try_wait.parity.shared::cta.b64 p, [%0], %1;\n@!p bra.uni W;\n}\n" :: "r"(bar), "r"(parity) : "memory");
}
__device__ __forceinline__ void tma_3d(uint32_t dst, const void* tm, uint32_t bar, int c0, int c1, int c2) {
  asm volatile("cp.async.bulk.tensor.3d.shared::cluster.global.mbarrier::complete_tx::bytes [%0], [%1, {%3, %4, %5}], [%2];" :: "r"(dst), "l"(tm), "r"(bar), "r"(c0), "r"(c1), "r"(c2) : "memory");
}
__device__ __forceinline__ void tma_3d_mc(uint32_t dst, const void* tm, uint32_t bar, int c0, int c1, int c2) {
  asm volatile("cp.async.bulk.tensor.3d.shared::cluster.global.mbarrier::complete_tx::bytes.multicast::cluster [%0], [%1, {%3, %4, %5}], [%2], %6;" :: "r"(dst), "l"(tm), "r"(bar), "r"(c0), "r"(c1), "r"(c2), "h"((uint16_t)3) : "memory");
}
__device__ __forceinline__ void wgmma_fence() { asm volatile("wgmma.fence.sync.aligned;" ::: "memory"); }
__device__ __forceinline__ void wgmma_commit() { asm volatile("wgmma.commit_group.sync.aligned;" ::: "memory"); }
template <int N> __device__ __forceinline__ void wgmma_wait() { asm volatile("wgmma.wait_group.sync.aligned %0;" :: "n"(N) : "memory"); }
__device__ __forceinline__ uint64_t make_desc(uint32_t addr, uint32_t lbo, uint32_t sbo, uint32_t swz) {
  return (uint64_t)(((addr & 0x3FFFF) >> 4) | ((lbo >> 4) << 16)) | ((uint64_t)((sbo >> 4) | (swz << 30)) << 32);
}
__device__ __forceinline__ void bar_sync(int id, int n) { asm volatile("bar.sync %0, %1;" :: "r"(id), "r"(n) : "memory"); }
__device__ __forceinline__ uint4 ldg_pkt(const void* p) {
  uint4 v; asm volatile("ld.relaxed.gpu.global.v4.u32 {%0, %1, %2, %3}, [%4];" : "=r"(v.x), "=r"(v.y), "=r"(v.z), "=r"(v.w) : "l"(p) : "memory"); return v;
}
__device__ __forceinline__ void stg_pkt(void* p, uint32_t a, uint32_t b, uint32_t c, uint32_t d) {
  asm volatile("st.relaxed.gpu.global.v4.u32 [%0], {%1, %2, %3, %4};" :: "l"(p), "r"(a), "r"(b), "r"(c), "r"(d) : "memory");
}
__device__ __forceinline__ uint32_t ldg_rlx32(const void* p) { uint32_t v; asm volatile("ld.relaxed.gpu.global.u32 %0, [%1];" : "=r"(v) : "l"(p) : "memory"); return v; }
__device__ __forceinline__ uint2 ldg_rlx64(const void* p) { uint2 v; asm volatile("ld.relaxed.gpu.global.v2.u32 {%0, %1}, [%2];" : "=r"(v.x), "=r"(v.y) : "l"(p) : "memory"); return v; }
__device__ __forceinline__ uint32_t pin(uint32_t v) { asm volatile("" : "+r"(v)); return v; }
__device__ __forceinline__ uint64_t mk64(uint32_t lo, uint32_t hi) { return ((uint64_t)hi << 32) | lo; }
__device__ __forceinline__ uint32_t holdu(uint32_t v) { return __shfl_sync(0xffffffffu, v, threadIdx.x & 31); }
template <class T> __device__ __forceinline__ T* hold(T* p) { return (T*)__shfl_sync(0xffffffffu, (unsigned long long)p, threadIdx.x & 31); }
__device__ __forceinline__ void stg128_if(bool q, void* p, const uint4& v) {
  asm volatile("{\n.reg .pred q;\nsetp.ne.u32 q, %5, 0;\n@q st.global.v4.u32 [%0], {%1, %2, %3, %4};\n}\n" :: "l"(p), "r"(v.x), "r"(v.y), "r"(v.z), "r"(v.w), "r"((int)q) : "memory");
}
template <class T> __device__ __forceinline__ T* pin(T* p) { asm volatile("" : "+l"(p)); return p; }
__device__ __forceinline__ void stg_rlx32(void* p, uint32_t v) { asm volatile("st.relaxed.gpu.global.u32 [%0], %1;" :: "l"(p), "r"(v) : "memory"); }
__device__ __forceinline__ void stg_rlx64(void* p, uint32_t a, uint32_t b) { asm volatile("st.relaxed.gpu.global.v2.u32 [%0], {%1, %2};" :: "l"(p), "r"(a), "r"(b) : "memory"); }
__device__ __forceinline__ uint4 ldsm4(uint32_t a) { uint4 v; asm volatile("ldmatrix.sync.aligned.m8n8.x4.shared.b16 {%0, %1, %2, %3}, [%4];" : "=r"(v.x), "=r"(v.y), "=r"(v.z), "=r"(v.w) : "r"(a) : "memory"); return v; }
__device__ __forceinline__ void ldsm4_if(uint4& v, uint32_t a, int off, bool p) {
  asm volatile("{\n.reg .pred q;\nsetp.ne.u32 q, %5, 0;\n@q ldmatrix.sync.aligned.m8n8.x4.shared.b16 {%0, %1, %2, %3}, [%4];\n}\n"
               : "+r"(v.x), "+r"(v.y), "+r"(v.z), "+r"(v.w) : "r"(a + off), "r"((int)p) : "memory");
}
__device__ __forceinline__ uint4 ldsm4t(uint32_t a) { uint4 v; asm volatile("ldmatrix.sync.aligned.m8n8.x4.trans.shared.b16 {%0, %1, %2, %3}, [%4];" : "=r"(v.x), "=r"(v.y), "=r"(v.z), "=r"(v.w) : "r"(a) : "memory"); return v; }
__device__ __forceinline__ void stsm4(uint32_t a, uint32_t x, uint32_t y, uint32_t z, uint32_t w) { asm volatile("stmatrix.sync.aligned.m8n8.x4.shared.b16 [%0], {%1, %2, %3, %4};" :: "r"(a), "r"(x), "r"(y), "r"(z), "r"(w) : "memory"); }
__device__ __forceinline__ void mma_acc(float (&c)[4], const uint4& a, uint32_t b0, uint32_t b1) {
  asm("mma.sync.aligned.m16n8k16.row.col.f32.bf16.bf16.f32 {%0,%1,%2,%3}, {%4,%5,%6,%7}, {%8,%9}, {%0,%1,%2,%3};"
      : "+f"(c[0]), "+f"(c[1]), "+f"(c[2]), "+f"(c[3]) : "r"(a.x), "r"(a.y), "r"(a.z), "r"(a.w), "r"(b0), "r"(b1));
}
__device__ __forceinline__ uint4 lds128(uint32_t a) { uint4 v; asm volatile("ld.shared.v4.u32 {%0, %1, %2, %3}, [%4];" : "=r"(v.x), "=r"(v.y), "=r"(v.z), "=r"(v.w) : "r"(a) : "memory"); return v; }
__device__ __forceinline__ float2 lds64f(uint32_t a) { float2 v; asm volatile("ld.shared.v2.f32 {%0, %1}, [%2];" : "=f"(v.x), "=f"(v.y) : "r"(a)); return v; }
__device__ __forceinline__ float lds32f(uint32_t a) { float v; asm volatile("ld.shared.f32 %0, [%1];" : "=f"(v) : "r"(a)); return v; }
__device__ __forceinline__ void sts32f(uint32_t a, float v) { asm volatile("st.shared.f32 [%0], %1;" :: "r"(a), "f"(v) : "memory"); }
__device__ __forceinline__ uint32_t pack_bf16(float lo, float hi) { uint32_t r; asm("cvt.rn.bf16x2.f32 %0, %1, %2;" : "=r"(r) : "f"(hi), "f"(lo)); return r; }
__device__ __forceinline__ float bf_lo(uint32_t v) { return __uint_as_float(v << 16); }
__device__ __forceinline__ float bf_hi(uint32_t v) { return __uint_as_float(v & 0xffff0000u); }
__device__ __forceinline__ uint32_t movm(uint32_t a) { uint32_t d; asm("movmatrix.sync.aligned.m8n8.trans.b16 %0, %1;" : "=r"(d) : "r"(a)); return d; }
__device__ __forceinline__ float ex2(float x) { float y; asm("ex2.approx.ftz.f32 %0, %1;" : "=f"(y) : "f"(x)); return y; }
__device__ __forceinline__ float rsq(float x) { float y; asm("rsqrt.approx.ftz.f32 %0, %1;" : "=f"(y) : "f"(x)); return y; }
__device__ __forceinline__ float rcp(float x) { float y; asm("rcp.approx.ftz.f32 %0, %1;" : "=f"(y) : "f"(x)); return y; }
__device__ __forceinline__ bool elect() { uint32_t p; asm volatile("{\n.reg .pred q;\nelect.sync _|q, 0xffffffff;\nselp.u32 %0, 1, 0, q;\n}\n" : "=r"(p)); return p; }
__device__ __forceinline__ void pf_l2(const void* p) { asm volatile("prefetch.global.L2 [%0];" :: "l"(p)); }
__device__ __forceinline__ bool anyw(bool p) { return __any_sync(0xffffffffu, p); }
__device__ __forceinline__ float shx(float v, int m) { return __shfl_xor_sync(0xffffffffu, v, m); }
__device__ __forceinline__ void mma_k24(float (&c)[4], uint32_t a0, uint32_t a1, uint32_t a2, uint32_t a3, uint32_t b0, uint32_t b1,
                                        uint32_t e0, uint32_t e1, uint32_t f0) {
  asm("mma.sync.aligned.m16n8k16.row.col.f32.bf16.bf16.f32 {%0,%1,%2,%3}, {%4,%5,%6,%7}, {%8,%9}, {%10,%10,%10,%10};"
      : "=f"(c[0]), "=f"(c[1]), "=f"(c[2]), "=f"(c[3]) : "r"(a0), "r"(a1), "r"(a2), "r"(a3), "r"(b0), "r"(b1), "f"(0.f));
  asm("mma.sync.aligned.m16n8k8.row.col.f32.bf16.bf16.f32 {%0,%1,%2,%3}, {%4,%5}, {%6}, {%0,%1,%2,%3};"
      : "+f"(c[0]), "+f"(c[1]), "+f"(c[2]), "+f"(c[3]) : "r"(e0), "r"(e1), "r"(f0));
}
__device__ __forceinline__ uint32_t ord_key(float r) { uint32_t u = __float_as_uint(r); return u ^ ((uint32_t)((int32_t)u >> 31) | 0x80000000u); }

__device__ __forceinline__ void wgmma_n64hi_ss(float (&d)[120], uint64_t da, uint64_t db, int scale_d) {
  asm volatile("{\n.reg .pred p;\nsetp.ne.b32 p, %34, 0;\n"
    "wgmma.mma_async.sync.aligned.m64n64k16.f32.bf16.bf16 "
    "{%0, %1, %2, %3, %4, %5, %6, %7, %8, %9, %10, %11, %12, %13, %14, %15, "
    "%16, %17, %18, %19, %20, %21, %22, %23, %24, %25, %26, %27, %28, %29, %30, %31}, "
    "%32, %33, p, 1, 1, 0, 1;\n}\n"
    : "+f"(d[88]), "+f"(d[89]), "+f"(d[90]), "+f"(d[91]), "+f"(d[92]), "+f"(d[93]), "+f"(d[94]), "+f"(d[95]),
      "+f"(d[96]), "+f"(d[97]), "+f"(d[98]), "+f"(d[99]), "+f"(d[100]), "+f"(d[101]), "+f"(d[102]), "+f"(d[103]),
      "+f"(d[104]), "+f"(d[105]), "+f"(d[106]), "+f"(d[107]), "+f"(d[108]), "+f"(d[109]), "+f"(d[110]), "+f"(d[111]),
      "+f"(d[112]), "+f"(d[113]), "+f"(d[114]), "+f"(d[115]), "+f"(d[116]), "+f"(d[117]), "+f"(d[118]), "+f"(d[119])
    : "l"(da), "l"(db), "r"(scale_d));
}
__device__ __forceinline__ void wgmma_n176lo_ss(float (&d)[120], uint64_t da, uint64_t db, int scale_d) {
  asm volatile("{\n.reg .pred p;\nsetp.ne.b32 p, %90, 0;\n"
    "wgmma.mma_async.sync.aligned.m64n176k16.f32.bf16.bf16 "
    "{%0, %1, %2, %3, %4, %5, %6, %7, %8, %9, %10, %11, %12, %13, %14, %15, "
    "%16, %17, %18, %19, %20, %21, %22, %23, %24, %25, %26, %27, %28, %29, %30, %31, "
    "%32, %33, %34, %35, %36, %37, %38, %39, %40, %41, %42, %43, %44, %45, %46, %47, "
    "%48, %49, %50, %51, %52, %53, %54, %55, %56, %57, %58, %59, %60, %61, %62, %63, "
    "%64, %65, %66, %67, %68, %69, %70, %71, %72, %73, %74, %75, %76, %77, %78, %79, "
    "%80, %81, %82, %83, %84, %85, %86, %87}, "
    "%88, %89, p, 1, 1, 0, 1;\n}\n"
    : "+f"(d[0]), "+f"(d[1]), "+f"(d[2]), "+f"(d[3]), "+f"(d[4]), "+f"(d[5]), "+f"(d[6]), "+f"(d[7]),
      "+f"(d[8]), "+f"(d[9]), "+f"(d[10]), "+f"(d[11]), "+f"(d[12]), "+f"(d[13]), "+f"(d[14]), "+f"(d[15]),
      "+f"(d[16]), "+f"(d[17]), "+f"(d[18]), "+f"(d[19]), "+f"(d[20]), "+f"(d[21]), "+f"(d[22]), "+f"(d[23]),
      "+f"(d[24]), "+f"(d[25]), "+f"(d[26]), "+f"(d[27]), "+f"(d[28]), "+f"(d[29]), "+f"(d[30]), "+f"(d[31]),
      "+f"(d[32]), "+f"(d[33]), "+f"(d[34]), "+f"(d[35]), "+f"(d[36]), "+f"(d[37]), "+f"(d[38]), "+f"(d[39]),
      "+f"(d[40]), "+f"(d[41]), "+f"(d[42]), "+f"(d[43]), "+f"(d[44]), "+f"(d[45]), "+f"(d[46]), "+f"(d[47]),
      "+f"(d[48]), "+f"(d[49]), "+f"(d[50]), "+f"(d[51]), "+f"(d[52]), "+f"(d[53]), "+f"(d[54]), "+f"(d[55]),
      "+f"(d[56]), "+f"(d[57]), "+f"(d[58]), "+f"(d[59]), "+f"(d[60]), "+f"(d[61]), "+f"(d[62]), "+f"(d[63]),
      "+f"(d[64]), "+f"(d[65]), "+f"(d[66]), "+f"(d[67]), "+f"(d[68]), "+f"(d[69]), "+f"(d[70]), "+f"(d[71]),
      "+f"(d[72]), "+f"(d[73]), "+f"(d[74]), "+f"(d[75]), "+f"(d[76]), "+f"(d[77]), "+f"(d[78]), "+f"(d[79]),
      "+f"(d[80]), "+f"(d[81]), "+f"(d[82]), "+f"(d[83]), "+f"(d[84]), "+f"(d[85]), "+f"(d[86]), "+f"(d[87])
    : "l"(da), "l"(db), "r"(scale_d));
}
__device__ __forceinline__ void wgmma_n64hi_rk(float (&d)[120], uint32_t a0, uint32_t a1, uint32_t a2, uint32_t a3, uint64_t db, int scale_d) {
  asm volatile("{\n.reg .pred p;\nsetp.ne.b32 p, %37, 0;\n"
    "wgmma.mma_async.sync.aligned.m64n64k16.f32.bf16.bf16 "
    "{%0, %1, %2, %3, %4, %5, %6, %7, %8, %9, %10, %11, %12, %13, %14, %15, "
    "%16, %17, %18, %19, %20, %21, %22, %23, %24, %25, %26, %27, %28, %29, %30, %31}, "
    "{%32, %33, %34, %35}, %36, p, 1, 1, 0;\n}\n"
    : "+f"(d[88]), "+f"(d[89]), "+f"(d[90]), "+f"(d[91]), "+f"(d[92]), "+f"(d[93]), "+f"(d[94]), "+f"(d[95]),
      "+f"(d[96]), "+f"(d[97]), "+f"(d[98]), "+f"(d[99]), "+f"(d[100]), "+f"(d[101]), "+f"(d[102]), "+f"(d[103]),
      "+f"(d[104]), "+f"(d[105]), "+f"(d[106]), "+f"(d[107]), "+f"(d[108]), "+f"(d[109]), "+f"(d[110]), "+f"(d[111]),
      "+f"(d[112]), "+f"(d[113]), "+f"(d[114]), "+f"(d[115]), "+f"(d[116]), "+f"(d[117]), "+f"(d[118]), "+f"(d[119])
    : "r"(a0), "r"(a1), "r"(a2), "r"(a3), "l"(db), "r"(scale_d));
}
__device__ __forceinline__ void wgmma_n176lo_rk(float (&d)[120], uint32_t a0, uint32_t a1, uint32_t a2, uint32_t a3, uint64_t db, int scale_d) {
  asm volatile("{\n.reg .pred p;\nsetp.ne.b32 p, %93, 0;\n"
    "wgmma.mma_async.sync.aligned.m64n176k16.f32.bf16.bf16 "
    "{%0, %1, %2, %3, %4, %5, %6, %7, %8, %9, %10, %11, %12, %13, %14, %15, "
    "%16, %17, %18, %19, %20, %21, %22, %23, %24, %25, %26, %27, %28, %29, %30, %31, "
    "%32, %33, %34, %35, %36, %37, %38, %39, %40, %41, %42, %43, %44, %45, %46, %47, "
    "%48, %49, %50, %51, %52, %53, %54, %55, %56, %57, %58, %59, %60, %61, %62, %63, "
    "%64, %65, %66, %67, %68, %69, %70, %71, %72, %73, %74, %75, %76, %77, %78, %79, "
    "%80, %81, %82, %83, %84, %85, %86, %87}, "
    "{%88, %89, %90, %91}, %92, p, 1, 1, 0;\n}\n"
    : "+f"(d[0]), "+f"(d[1]), "+f"(d[2]), "+f"(d[3]), "+f"(d[4]), "+f"(d[5]), "+f"(d[6]), "+f"(d[7]),
      "+f"(d[8]), "+f"(d[9]), "+f"(d[10]), "+f"(d[11]), "+f"(d[12]), "+f"(d[13]), "+f"(d[14]), "+f"(d[15]),
      "+f"(d[16]), "+f"(d[17]), "+f"(d[18]), "+f"(d[19]), "+f"(d[20]), "+f"(d[21]), "+f"(d[22]), "+f"(d[23]),
      "+f"(d[24]), "+f"(d[25]), "+f"(d[26]), "+f"(d[27]), "+f"(d[28]), "+f"(d[29]), "+f"(d[30]), "+f"(d[31]),
      "+f"(d[32]), "+f"(d[33]), "+f"(d[34]), "+f"(d[35]), "+f"(d[36]), "+f"(d[37]), "+f"(d[38]), "+f"(d[39]),
      "+f"(d[40]), "+f"(d[41]), "+f"(d[42]), "+f"(d[43]), "+f"(d[44]), "+f"(d[45]), "+f"(d[46]), "+f"(d[47]),
      "+f"(d[48]), "+f"(d[49]), "+f"(d[50]), "+f"(d[51]), "+f"(d[52]), "+f"(d[53]), "+f"(d[54]), "+f"(d[55]),
      "+f"(d[56]), "+f"(d[57]), "+f"(d[58]), "+f"(d[59]), "+f"(d[60]), "+f"(d[61]), "+f"(d[62]), "+f"(d[63]),
      "+f"(d[64]), "+f"(d[65]), "+f"(d[66]), "+f"(d[67]), "+f"(d[68]), "+f"(d[69]), "+f"(d[70]), "+f"(d[71]),
      "+f"(d[72]), "+f"(d[73]), "+f"(d[74]), "+f"(d[75]), "+f"(d[76]), "+f"(d[77]), "+f"(d[78]), "+f"(d[79]),
      "+f"(d[80]), "+f"(d[81]), "+f"(d[82]), "+f"(d[83]), "+f"(d[84]), "+f"(d[85]), "+f"(d[86]), "+f"(d[87])
    : "r"(a0), "r"(a1), "r"(a2), "r"(a3), "l"(db), "r"(scale_d));
}
__device__ __forceinline__ void wgmma_n80_rs(float (&d)[40], uint32_t a0, uint32_t a1, uint32_t a2, uint32_t a3, uint64_t db, int scale_d) {
  asm volatile("{\n.reg .pred p;\nsetp.ne.b32 p, %45, 0;\n"
    "wgmma.mma_async.sync.aligned.m64n80k16.f32.bf16.bf16 "
    "{%0, %1, %2, %3, %4, %5, %6, %7, %8, %9, %10, %11, %12, %13, %14, %15, "
    "%16, %17, %18, %19, %20, %21, %22, %23, %24, %25, %26, %27, %28, %29, %30, %31, "
    "%32, %33, %34, %35, %36, %37, %38, %39}, "
    "{%40, %41, %42, %43}, %44, p, 1, 1, 1;\n}\n"
    : "+f"(d[0]), "+f"(d[1]), "+f"(d[2]), "+f"(d[3]), "+f"(d[4]), "+f"(d[5]), "+f"(d[6]), "+f"(d[7]),
      "+f"(d[8]), "+f"(d[9]), "+f"(d[10]), "+f"(d[11]), "+f"(d[12]), "+f"(d[13]), "+f"(d[14]), "+f"(d[15]),
      "+f"(d[16]), "+f"(d[17]), "+f"(d[18]), "+f"(d[19]), "+f"(d[20]), "+f"(d[21]), "+f"(d[22]), "+f"(d[23]),
      "+f"(d[24]), "+f"(d[25]), "+f"(d[26]), "+f"(d[27]), "+f"(d[28]), "+f"(d[29]), "+f"(d[30]), "+f"(d[31]),
      "+f"(d[32]), "+f"(d[33]), "+f"(d[34]), "+f"(d[35]), "+f"(d[36]), "+f"(d[37]), "+f"(d[38]), "+f"(d[39])
    : "r"(a0), "r"(a1), "r"(a2), "r"(a3), "l"(db), "r"(scale_d));
}
__device__ __forceinline__ void wgmma_n80_ss(float (&d)[40], uint64_t da, uint64_t db, int scale_d) {
  asm volatile("{\n.reg .pred p;\nsetp.ne.b32 p, %42, 0;\n"
    "wgmma.mma_async.sync.aligned.m64n80k16.f32.bf16.bf16 "
    "{%0, %1, %2, %3, %4, %5, %6, %7, %8, %9, %10, %11, %12, %13, %14, %15, "
    "%16, %17, %18, %19, %20, %21, %22, %23, %24, %25, %26, %27, %28, %29, %30, %31, "
    "%32, %33, %34, %35, %36, %37, %38, %39}, "
    "%40, %41, p, 1, 1, 0, 1;\n}\n"
    : "+f"(d[0]), "+f"(d[1]), "+f"(d[2]), "+f"(d[3]), "+f"(d[4]), "+f"(d[5]), "+f"(d[6]), "+f"(d[7]),
      "+f"(d[8]), "+f"(d[9]), "+f"(d[10]), "+f"(d[11]), "+f"(d[12]), "+f"(d[13]), "+f"(d[14]), "+f"(d[15]),
      "+f"(d[16]), "+f"(d[17]), "+f"(d[18]), "+f"(d[19]), "+f"(d[20]), "+f"(d[21]), "+f"(d[22]), "+f"(d[23]),
      "+f"(d[24]), "+f"(d[25]), "+f"(d[26]), "+f"(d[27]), "+f"(d[28]), "+f"(d[29]), "+f"(d[30]), "+f"(d[31]),
      "+f"(d[32]), "+f"(d[33]), "+f"(d[34]), "+f"(d[35]), "+f"(d[36]), "+f"(d[37]), "+f"(d[38]), "+f"(d[39])
    : "l"(da), "l"(db), "r"(scale_d));
}

__device__ __forceinline__ constexpr int QT(int t) { return t < 8 ? t : 16 + t; }
__device__ __forceinline__ constexpr int KT(int t) { return t < 8 ? 8 + t : 18 + t; }
__device__ __forceinline__ constexpr int VT(int t) { return t < 8 ? 16 + t : 20 + t; }

struct Maps { CUtensorMap x, w, wr, wv, wo, wor, gate, up, down; };

__global__ void __cluster_dims__(2, 1, 1) __launch_bounds__(512, 1)
fused_kernel(const __nv_bfloat16* __restrict__ x, const __nv_bfloat16* __restrict__ wqkv,
             const __nv_bfloat16* __restrict__ wo, const __nv_bfloat16* __restrict__ w_r, const __nv_bfloat16* __restrict__ w_gate,
             const __nv_bfloat16* __restrict__ w_up, const __nv_bfloat16* __restrict__ w_down, __nv_bfloat16* __restrict__ out,
             Scratch* __restrict__ sc, const __grid_constant__ Maps tm) {
  extern __shared__ __align__(1024) uint8_t smem[];
  const int tid = threadIdx.x, bid = blockIdx.x;
  if ((unsigned)(tid - 128) < 16u) pf_l2((const char*)x + (bid * 16 + tid - 128) * 1280);
  if ((unsigned)(tid - 160) < 15u) pf_l2((const char*)wqkv + (bid * 15 + tid - 160) * 128);
  const int warp = __shfl_sync(0xffffffffu, tid >> 5, 0), lane = tid & 31;
  const uint32_t sb = (uint32_t)__cvta_generic_to_shared(smem);
  const uint32_t bar_full = sb + OFF_BAR, bar_empty = bar_full + 32, bar_aux = bar_full + 64, bar_ffn = bar_full + 72, bar_win = bar_full + 80, bar_tag = bar_full + 88, bar_rst = bar_full + 96 + 296 + 24,
                 bar_o = bar_full + 96, bar_oc = bar_o + 112, bar_st = bar_o + 224, bar_go = bar_o + 248, bar_kv = bar_o + 272, bar_half = bar_o + 296;
  if (warp < 4 && elect()) {
    mbar_init(bar_half + 8 * warp, 1);
    mbar_init(bar_full + 8 * (warp ^ 2), 1);
    mbar_init(bar_empty + 8 * warp, 24);
    mbar_init(bar_aux + 8 * warp, warp == 0 ? 64 : warp == 2 ? 32 : warp == 3 ? 2 : 1);
    asm volatile("fence.mbarrier_init.release.cluster;" ::: "memory");
  }
  asm volatile("barrier.cluster.arrive.relaxed.aligned;" ::: "memory");
  if (warp >= 8 && warp < 12 && elect()) asm volatile("prefetch.tensormap [%0];" :: "l"(&tm.x + (warp - 8)) : "memory");
  const int rank = bid & 1, cl = bid >> 1;
  const int q7 = ((cl - 36) * 37) >> 8;
  const int P = cl < 4 ? 0 : cl < 36 ? (cl - 4) & 7 : cl - 35 - 7 * q7;
  const int g = (cl < 4 ? 4 + cl : cl < 36 ? (cl - 4) >> 3 : 4 + q7);
  const int mt = 2 * P + rank, cid = mt * 8 + g;
  const bool ffn1 = g >= 5;
  const int fj = ffn1 ? mt * 3 + g - 5 : (P * 5 + g) * 2 + rank;
  const int ord = ((g >> 2) ^ P) & 1;
  auto ks_of = [&](int it) { return ord == 0 || it < 2 ? it : it <= 5 ? it + 4 : it - 4; };
  const int godd = g & 1, cm = g * 80 + godd * 16, cr = g * 80 + 64 - godd * 64;
  auto load_w = [&](int ks, uint32_t a, uint32_t bar, int kk) {
    tma_3d_mc(a + 16384 + ((kk + 1) & 3) * 6144, &tm.w, bar, cm, ks * 64 + kk * 16, 0);
    tma_3d_mc(a + 41472 + kk * 2048, &tm.wr, bar, cr, ks * 64 + kk * 16, 0);
    tma_3d_mc(a + 40960 + kk * 2048, &tm.wv, bar, cm + 48, ks * 64 + kk * 16, 2);
  };
  if (warp == 0 && elect()) {
    mbar_expect_tx(bar_half, 32768);
    tma_3d(sb + 2 * SLOT, &tm.x, bar_half, 0, P * 128, rank);
    mbar_expect_tx(bar_full + 16, 16384);
  }
  asm volatile("barrier.cluster.wait.aligned;" ::: "memory");
  if (warp == 0) {
    if (elect()) {
      uint32_t bar = bar_half;
#pragma unroll 1
      for (int kk = rank; kk < 4; kk += 2) { load_w(0, sb + 2 * SLOT, bar, kk); bar = bar_full + 16; }
    }
    asm volatile("bar.arrive 4, 64;" ::: "memory");
  }

  if (warp >= 8) {
    asm volatile("setmaxnreg.dec.sync.aligned.u32 %0;" :: "n"(REG_P));
#define TS_T 0
    if (warp == 8) {
      TS(8);
      bar_sync(4, 64);
      if (elect()) {
        TS(10);
#pragma unroll 1
        for (int it = 1; it < 10; it++) {
          const int s = (it + 2) & 3, ks = ks_of(it);
          const uint32_t full = bar_full + 8 * s, a = sb + s * SLOT;
          uint32_t bar = it < NSPLIT ? bar_half + 8 * it : full;
          if (it >= 4) mbar_wait(full + 32, ((it >> 2) - 1) & 1);
          if (it >= 2 && it < THR_END) mbar_wait(bar_full + 8 * (it & 3), 0);
          if (it < NSPLIT) mbar_expect_tx(bar, 32768);
          mbar_expect_tx(full, it < NSPLIT ? 16384 : SLOT);
          tma_3d(a, &tm.x, bar, ks * 64, P * 128, rank);
#pragma unroll 1
          for (int kk = rank; kk < 4; kk += 2) { load_w(ks, a, bar, kk); bar = full; }
          TS(12 + it);
          if ((it >> 1) == 2) {
            mbar_wait(bar_rst, 0);
            asm volatile("cp.async.bulk.global.shared::cta.bulk_group [%0], [%1], %2;\ncp.async.bulk.commit_group;"
                         :: "l"(it == 4 ? (uint4*)(g_own + cid) : (uint4*)&g_x + cid * GLOB_PER_CTA), "r"(sb + OFF_CS), "r"(it == 4 ? (int)sizeof(Own) : GLOB_PER_CTA * 16) : "memory");
          }
          if (it == 6) { asm volatile("cp.async.bulk.wait_group 0;" ::: "memory"); mbar_arrive(bar_tag); }
        }
        mbar_expect_tx(bar_ffn, ffn1 ? 81920 : 24576);
        int fjn = 0;
#pragma unroll 1
        for (int it = 9; it < 17; it++) {
          if (it >= 13) { mbar_wait(bar_oc + 8 * (it - 13), 0); mbar_wait(bar_oc + 56 + 8 * (it - 13), 0); }
          else if (it >= 10) {
            const uint32_t full = bar_full + 8 * (it - 10);
            const int g0 = 3 * (it - 10), g1 = min(g0 + 3, 8);
            mbar_wait(full + 32, it < 12);
            mbar_expect_tx(full, (g1 - g0) * 12800);
#pragma unroll 1
            for (int gp = g0 + ((g0 ^ rank) & 1); gp < g1; gp += 2) {
              tma_3d_mc(sb + gp * 15360, &tm.wo, full, 0, gp * 80, g * 2);
              tma_3d_mc(sb + gp * 15360 + 10240, &tm.wor, full, 512 + g * 16, gp * 80, 0);
            }
          }
          const int j1 = ffn1 ? (it >= 13 ? 2 * it - 22 : min(it - 8, 3)) : (it >= 13 ? 12 : min((it - 8) * F_PER, F_MAX));
#pragma unroll 1
          for (; fjn < j1; fjn++) {
            const int j = fjn < 3 ? fjn + 7 : fjn - 3;
            if (ffn1) tma_3d(sb + (j < 7 ? 0 : OFF_W2 - 57344) + j * 8192, j < 5 ? &tm.gate : &tm.up, bar_ffn, fj * 32, (j < 5 ? j : j - 5) * 128, 0);
            else tma_3d(sb + OFF_W2 + fjn * 2048, &tm.down, bar_ffn, fj * 8, fjn * 128, 0);
          }
        }
        TS(11);
      }
#undef TS_T
#define TS_T 64
    } else if (warp >= 12) {
      const int l7 = lane & 7, j = warp - 12, ch = min((P >> 1) * 4 + rank * 2 + (j >> 1), 14);
      const uint32_t sxo = ((g & 3) * 32 + j * 8 + l7) * 128 + (((lane >> 3) ^ l7) * 16);
      const uint32_t swo = ch < 12 ? 16384 + (lane >> 4) * 6144 + (ch >> 2) * 2048 + (lane & 15) * 128 + ((((ch & 3) * 2 + (j & 1)) ^ l7) * 16)
                                   : 41472 + (lane >> 4) * 2048 + (ch - 12) * 512 + (lane & 15) * 32 + (((j & 1) ^ (l7 >> 2)) * 16);
      float ps = 0.f, pq = 0.f, pq1 = 0.f, pc = 0.f;
      uint32_t tag = 0;
      char* const pp = hold((lane & 1) ? (char*)&g_own[cid].cs[j * 8 + (lane >> 2)] : (char*)&g_own[cid].st1[j * 8 + (lane >> 2)]);
#pragma unroll 1
      for (int it = 1 - ord; it < 6; it = max(it + 1, 2)) {
        const int sl = (it + 2) & 3;
        if (it == 5) { mbar_wait(bar_tag, 0); tag = __float_as_uint(lds32f(sb + OFF_WR + 324)); }
        if (it < NSPLIT) mbar_wait(bar_half + 8 * it, 0);
        mbar_wait(bar_full + 8 * sl, (it >> 2) & 1);
        TS(it);
        const uint32_t a = sb + sl * SLOT;
        const uint4 v0 = ldsm4(a + sxo), v1 = ldsm4((a + sxo) ^ 64), w0 = ldsm4t(a + swo), w1 = ldsm4t(a + swo + (ch < 12 ? 12288 : 4096));
        if (lane + (int)((v0.x & v1.x & w0.x & w1.x) == 0x7fc17fc1u && (v0.x | v1.x) == 0u) < 2) mbar_arrive_cta(bar_empty + 8 * sl, lane);
        const uint32_t vv[8] = {v0.x, v0.y, v0.z, v0.w, v1.x, v1.y, v1.z, v1.w}, ww[8] = {w0.x, w0.y, w0.z, w0.w, w1.x, w1.y, w1.z, w1.w};
#pragma unroll
        for (int i = 0; i < 8; i++) {
          const float d = bf_lo(vv[i]), e = bf_hi(vv[i]);
          ps += d + e; pq = fmaf(d, d, pq); pq1 = fmaf(e, e, pq1); pc += bf_lo(ww[i]) + bf_hi(ww[i]);
        }
      }
      pq += pq1;
      ps += shx(ps, 1); pq += shx(pq, 1); pc += shx(pc, 1);
      ps += shx(ps, 2); pq += shx(pq, 2); pc += shx(pc, 2);
      if ((lane & 3) == 0) stg_pkt(pp, __float_as_uint(ps), __float_as_uint(pq), tag, 0u);
      if ((lane & 3) == 1) stg_rlx64(pp, __float_as_uint(pc), tag);
      asm volatile("bar.arrive 2, 192;" ::: "memory");
      if (warp == 12) {
        const uint4* const hp = hold(&g_own[max(cid - 16, 0)].halo[0][lane]);
        mbar_wait(bar_aux, 0);
        mbar_wait(bar_go, 0);
        uint4 v[5] = {};
        int guard = SPIN_MAX;
        if (P > 0) {
          do {
#pragma unroll
            for (int i = 0; i < 5; i++) v[i] = ldg_pkt(hp + 32 * i);
          } while (anyw(v[0].x == SENT || v[1].x == SENT || v[2].x == SENT || v[3].x == SENT || v[4].x == SENT) && --guard > 0);
        }
#pragma unroll
        for (int i = 0; i < 5; i++) stsm4(sb + OFF_O + 10240 + i * 512 + lane * 16, v[i].x, v[i].y, v[i].z, v[i].w);
        mbar_arrive(bar_kv);
      }
#undef TS_T
#define TS_T 32
    } else if (warp < 11) {
      const int l7 = lane & 7, hk = lane >> 4;
      if (warp == 10 && elect()) {
#pragma unroll 1
        for (int i = 0; i < 36; i++) mbar_init(bar_o + 8 * i, i < 14 || i == 30 ? 1 : i < 34 ? 4 : 128);
      }
      mbar_wait(bar_tag, 0);
      const uint32_t tag = __float_as_uint(lds32f(sb + OFF_WR + 324));
      bar_sync(2, 192);
      TS(0);
      int guard = SPIN_MAX;
      if (warp == 9) {
        const uint4* sp = &g_own[mt * 8].st1[lane];
        const uint4* hp = &g_own[max(mt - 2, 0) * 8 + 3].st1[24 + l7];
        uint4 a[5], b[5];
        bool bad;
        do {
          __nanosleep(AUX_NS);
          bad = false;
#pragma unroll
          for (int i = 0; i < 5; i++) {
            const uint4* q = i < 4 ? sp + i * (sizeof(Own) / 16) : hp;
            a[i] = ldg_pkt(q); b[i] = ldg_pkt(q + 4 * sizeof(Own) / 16);
          }
#pragma unroll
          for (int i = 0; i < 5; i++) bad |= a[i].z != tag || b[i].z != tag;
        } while (anyw(bad) && --guard);
        TS(1);
#pragma unroll
        for (int i = 0; i < 5; i++) {
          const float m = (__uint_as_float(a[i].x) + __uint_as_float(b[i].x)) * (1.f / 640.f);
          const float rs = rsq(fmaxf(fmaf(-m, m, (__uint_as_float(a[i].y) + __uint_as_float(b[i].y)) * (1.f / 640.f)), 0.f) + 1e-5f);
          ((float*)(smem + OFF_RS))[i < 4 ? 8 + lane + 32 * i : l7] = rs;
          const uint32_t mh = pack_bf16(-m, -m);
          const float ml = -m - bf_lo(mh);
          if (i < 4) ((uint2*)(smem + OFF_MN))[lane + 32 * i] = make_uint2(mh, pack_bf16(ml, ml));
        }
      } else {
        const uint4* cp = (const uint4*)g_own[hk * 8 + g].cs + (lane & 15);
        uint4 a[4], b[4];
        bool bad;
        do {
          __nanosleep(AUX_NS);
          bad = false;
#pragma unroll
          for (int i = 0; i < 4; i++) { a[i] = ldg_pkt(cp + i * 32 * sizeof(Own) / 16); b[i] = ldg_pkt(cp + (i * 32 + 16) * sizeof(Own) / 16); }
#pragma unroll
          for (int i = 0; i < 4; i++) bad |= a[i].y != tag || a[i].w != tag || b[i].y != tag || b[i].w != tag;
        } while (anyw(bad) && --guard);
#pragma unroll
        for (int i = 0; i < 4; i++)
          if (i < 3 || lane < 24) {
            const float c0 = __uint_as_float(a[i].x) + __uint_as_float(b[i].x), c1 = __uint_as_float(a[i].z) + __uint_as_float(b[i].z);
            const uint32_t hi = pack_bf16(c0, c1), w0 = pack_bf16(c0, c0 - bf_lo(hi)), w1 = pack_bf16(c1, c1 - bf_hi(hi));
            uint4* const d = (uint4*)(smem + OFF_CS) + 2 * (lane + 32 * i);
            d[0] = make_uint4(w0, w0, 0, 0); d[1] = make_uint4(w1, w1, 0, 0);
          }
        asm volatile("fence.proxy.async.shared::cta;" ::: "memory");
      }
      mbar_arrive(bar_aux);
      TS(2);
      const int fo = warp - 9, wq = fo ? 1 - LEAD : LEAD;
      const uint4* const fp = hold(g_own[mt * 8 + wq * 4].cnt);
      const char* src = hold((const char*)g_o[mt * 2 + wq]);
      if (elect()) {
        const uint32_t bo = bar_o + fo * 56;
#pragma unroll
        for (int i = 0; i < 7; i++) mbar_expect_tx(bo + 8 * i, 10240);
        uint32_t cv = 0, need = 4;
        mbar_wait(OV == 3 ? bar_st + 8 * fo : bar_go + 8 + 8 * fo, 0);
        uint32_t dst = sb + OFF_O + 20480;
#pragma unroll OUNR
        for (int i = 0; i < 7; i++) {
          if (i == g) { src += 10240; need <<= 4; }
          if (!(cv & need)) {
            do { cv = ldg_rlx32(fp); } while (!(cv & need) && --guard > 0);
            asm volatile("fence.proxy.async.global;" ::: "memory");
          }
          if (fo || i == 5 || (OV == 2 && i == 4)) mbar_wait(fo ? bar_oc + 8 * i : i == 4 ? bar_st : bar_st + 8, 0);
          if (i == 0) TS(6);
          asm volatile("cp.async.bulk.shared::cluster.global.mbarrier::complete_tx::bytes [%0], [%1], 10240, [%2];" :: "r"(dst), "l"(src), "r"(bo + 8 * i) : "memory");
          src += 10240; need <<= 4;
          dst += i == 4 ? -61440 : 10240;
        }
      }
#undef TS_T
#define TS_T 96
    } else {
      if ((sb & 0x3FFFF) != D0 * 16) __trap();
#pragma unroll 1
      for (int i = lane; i < 232; i += 32) { const uint32_t f = i < 208 ? SENT : 0u; ((uint4*)(smem + OFF_CS))[i] = make_uint4(f, f, f, f); }
      asm volatile("fence.proxy.async.shared::cta;" ::: "memory");
      if (elect()) mbar_arrive(bar_rst);
      mbar_wait(bar_full + 8 * ((HK_IT + 2) & 3), 0);
      TS(4);
      const uint32_t epoch = ldg_rlx32(g_epoch + cid) + 1;
      uint32_t wv[10];
#pragma unroll
      for (int i = 0; i < 10; i++) wv[i] = __ldg((const uint32_t*)w_r + lane + 32 * i);
      float s = 0.f;
#pragma unroll
      for (int i = 0; i < 10; i++) {
        s += bf_lo(wv[i]) + bf_hi(wv[i]);
        const unsigned u = i < 8 ? lane + 32 * (i - g) : lane + 32 * (i - 7) - g * 8;
        if (i < 8 ? u < 32u : u - 32u < 8u) *(float2*)(smem + OFF_WR + ((u & 3) * 10 + (u >> 2)) * 8) = make_float2(bf_lo(wv[i]), bf_hi(wv[i]));
      }
#pragma unroll
      for (int m = 1; m < 32; m <<= 1) s += shx(s, m);
      *(float2*)(smem + OFF_WR + 320) = make_float2(s, __uint_as_float(epoch * 0x9E3779B8u));
      g_epoch[cid] = epoch;
      TS(3);
      if (elect()) mbar_arrive(bar_tag);
      TS(5);
#pragma unroll 1
      for (int i = 0; i < PFW_N; i++) {
        const int m = (i + 2) >> 2, n = m == 0 ? 50 : 120, t = (m == 0 ? i : (i + 2) & 3) * 32 + lane;
        const char* b = (const char*)(m == 0 ? wo : m == 1 ? w_up : m == 2 ? w_down : w_gate);
        if (t < n) pf_l2(b + (bid * n + t) * 128);
        __nanosleep(PFW_NS);
      }
      const uint4* const kp = hold(g_own[1].cnt);
      const uint4* const cb = hold(&g_x.cand[0][lane >> 2][lane & 3]);
      bar_sync(3, 64);
      uint4 k;
      uint32_t have = SENT;
      int guard = SPIN_MAX;
      while (true) {
        k = ldg_pkt(kp);
        if (ffn1) {
          while (k.x != have && --guard > 0) {
            const uint32_t tk = 2047u - (k.x & 2047u), want = k.x;
            const uint4* q = cb + ((tk >> 8) * 16 + (tk & 1) * 8 + ((tk >> 5) & 7)) * 192;
            const uint4 c0 = ldg_pkt(q), c1 = ldg_pkt(q + 4); const uint2 c2 = ldg_rlx64(q + 8);
            k = ldg_pkt(kp);
            *(uint4*)(smem + OFF_HN + lane * 16) = c0; *(uint4*)(smem + OFF_HN + 512 + lane * 16) = c1; *(uint2*)(smem + OFF_HN + 1024 + lane * 16) = c2;
            have = anyw(c0.x == SENT || c1.x == SENT || c2.x == SENT) ? SENT : want;
          }
        } else if (KEY_NS && k.z != 128u) __nanosleep(KEY_NS);
        if (k.z == 128u || --guard <= 0) break;
      }
      *(uint2*)(smem + OFF_WR + 336) = make_uint2(k.x, k.y);
      mbar_arrive(bar_win);
      TS(7);
    }
#undef TS_T
  } else {
#define TS_T 0
    asm volatile("setmaxnreg.inc.sync.aligned.u32 %0;" :: "n"(REG_C));
    const int wg = warp >> 2, w4 = warp & 3, r = lane >> 2, c = lane & 3;
    float acc[120];
    uint4 xr[5] = {};
    const uint32_t xa = pin(sb + (warp * 16 + (lane & 15)) * 128 + ((lane >> 4) ^ (lane & 7)) * 16);
    const uint32_t zero = __shfl_sync(0xffffffffu, (uint32_t)(uintptr_t)x & 8u, 0);
    const int fol = wg != LEAD;
    const bool first = (P == 0) && (warp == 0);
    const uint32_t kvs = holdu(sb + OFF_O + fol * 10240 + w4 * 2560 + lane * 16);
    const uint32_t kvd = warp == 3 ? kvs - 17920 : kvs + 2560;
    uint4* const kvg = hold(&g_own[cid].halo[0][lane]);
    uint4* const odst = hold(&g_o[mt * 2 + wg][g][w4 * 160]);
    uint4* const ocnt = hold(g_own[mt * 8 + wg * 4].cnt + (lane & zero));
    const uint32_t oinc = holdu((1u << (4 * g)) + (lane & zero));
    const bool in0 = 2 * c <= r, in1 = 2 * c + 1 <= r;
    const uint32_t mL = holdu((in0 ? 0xffffu : 0u) | (in1 ? 0xffff0000u : 0u));
    const float bias0 = __uint_as_float(holdu(first && !in0 ? 0xff800000u : 0u)), bias1 = __uint_as_float(holdu(first && !in1 ? 0xff800000u : 0u));
    const uint32_t stb = sb + OFF_RS + warp * 64, kb0 = holdu(stb + (2 * c + (in0 ? 8 : 0)) * 4), kb1 = holdu(stb + (2 * c + 1 + (in1 ? 8 : 0)) * 4);
    const uint32_t os = sb + OFF_O + (fol ? 0 : 61440) + w4 * 2560, oa = holdu(os + ((lane >> 3) & 1) * 1280 + (lane >> 4) * 128 + (lane & 7) * 16);
    float rlo, rhi, scl0, scl1, sch0, sch1;
    uint32_t m0 = 0, m1 = 0, m2 = 0, m3 = 0;
    const uint32_t mna = pin(sb + OFF_MN + (warp * 16 + r) * 8 + c * 4);
    const int itx = ord == 0 || g < 2 ? g : g < 6 ? g + 4 : g - 4, ity = (ord ? 4 : 8) + (g >> 2);
    uint32_t rel;
    asm volatile("mapa.shared::cluster.u32 %0, %1, %2;" : "=r"(rel) : "r"(bar_empty), "r"(tid & 1));
    const uint32_t xa1 = pin(xa ^ 32), xa2 = pin(xa ^ 64), xa3 = pin(xa ^ 96), xb = pin(xa ^ ((g & 3) * 32));
    const uint32_t da0 = wg * 512;
    const bool rel2 = lane < 2, rel6 = lane < 2 + 2 * (warp & 1);
    mbar_wait(bar_half, 0);
    TS(13);
    wgmma_fence();
#pragma unroll
    for (int it = 0; it < 10; it++) {
      const int s = (it + 2) & 3;
#pragma unroll
      for (int kk = 0; kk < 4; kk++) {
        if (kk == 2 && it > 0) {
          wgmma_commit();
          wgmma_wait<1>();
          const uint32_t ra = ((xr[0].x ^ xr[1].x ^ xr[2].x ^ xr[3].x ^ xr[4].x) & zero) | rel;
          if (it == 1 ? (ord ? rel2 : rel6) : it == 2 ? (ord ? rel6 : rel2) : it < 7 ? rel2 : rel6)
            asm volatile("mbarrier.arrive.shared::cluster.b64 _, [%0];" :: "r"(ra + 8 * ((it + 1) & 3)) : "memory");
        }
        if (kk == 2) {
          ldsm4_if(xr[0], xa, s * SLOT, it == itx); ldsm4_if(xr[1], xa1, s * SLOT, it == itx);
          ldsm4_if(xr[2], xa2, s * SLOT, it == itx); ldsm4_if(xr[3], xa3, s * SLOT, it == itx);
          if ((it & 6) == 4 || it >= 8) ldsm4_if(xr[4], xb, s * SLOT, it == ity);
        }
        if (kk == AK && it == 9) {
          mbar_wait(bar_aux, 0);
          TS(3);
          if (c < 2) {
            m0 = __float_as_uint(lds32f(mna)); m1 = __float_as_uint(lds32f(mna + 64)); m2 = __float_as_uint(lds32f(mna + zero)); m3 = __float_as_uint(lds32f(mna + zero + 64));
          }
          const float qs = 0.22360679774997896f * 1.4426950408889634f;
          rlo = lds32f(stb + (8 + r) * 4); rhi = lds32f(stb + (16 + r) * 4);
          scl0 = lds32f(kb0) * (rlo * qs); scl1 = lds32f(kb1) * (rlo * qs); sch0 = lds32f(kb0 + 32) * (rhi * qs); sch1 = lds32f(kb1 + 32) * (rhi * qs);
          if (!fol) bar_sync(11, 256);
        }
        if (it * 4 + kk == 40 - LAG && fol) {
          asm volatile("bar.arrive 11, 256;" ::: "memory");
          bar_sync(10, 256);
        }
        if (kk == 2 && it < NSPLIT) mbar_wait(bar_full + 8 * s, 0);
        const uint64_t da = mk64(da0 + (D0 + s * (SLOT >> 4) + kk * 2 + (1 << 16)), 0x40000040u);
        wgmma_n64hi_ss(acc, da, mk64(D0 + s * (SLOT >> 4) + 2560 + kk * 128 + (32 << 16), 0xC0000010u), (it | kk) != 0);
        wgmma_n176lo_ss(acc, da, mk64(D0 + s * (SLOT >> 4) + 1024 + ((kk + 1) & 3) * 384 + (128 << 16), 0x40000040u), (it | kk) != 0);
      }
      wgmma_commit();
      if (it < 9) {
        if (it + 1 < NSPLIT) mbar_wait(bar_half + 8 * (it + 1), 0);
        else mbar_wait(bar_full + 8 * ((it + 3) & 3), ((it + 1) >> 2) & 1);
        if (it < 8) TS(14 + it);
      }
    }
    {
      const uint64_t dc = make_desc(D0 * 16 + OFF_CS, 0, 128, 0);
      wgmma_fence();
      wgmma_n64hi_rk(acc, m0, m1, 0u, 0u, dc + 176, 1);
      wgmma_n176lo_rk(acc, m2, m3, 0u, 0u, dc, 1);
      wgmma_commit();
      if (!fol) asm volatile("bar.arrive 10, 256;" ::: "memory");
    }
    wgmma_wait<0>();
#pragma unroll
    for (int i = 0; i < 120; i++) asm volatile("" : "+f"(acc[i]) :: "memory");
    if (fol && lane == 0) mbar_arrive(bar_go);
    TS(2);
    uint32_t Qlo[10], Qhi[10], Klo[10], Khi[10], Vlo[10], Vhi[10];
#define CONV_HI(ROT) _Pragma("unroll") for (int t = 0; t < 10; t++) { \
      const int k = KT((t + ROT) % 10), v = VT((t + ROT) % 10); \
      Khi[t] = pack_bf16(acc[4 * k + 2], acc[4 * k + 3]); \
      Vhi[t] = pack_bf16(acc[4 * v + 2] * rhi, acc[4 * v + 3] * rhi); }
    if (godd) { CONV_HI(8) } else { CONV_HI(0) }
    if (warp == 7) {
      stg_pkt(kvg, Khi[0], Khi[1], Khi[3], Khi[4]); stg_pkt(kvg + 32, Khi[5], Khi[6], Khi[8], Khi[9]); stg_pkt(kvg + 64, Khi[2], Khi[7], Vhi[0], Vhi[1]);
      stg_pkt(kvg + 96, Vhi[2], Vhi[3], Vhi[4], Vhi[5]); stg_pkt(kvg + 128, Vhi[6], Vhi[7], Vhi[8], Vhi[9]);
    } else {
      stsm4(kvd, Khi[0], Khi[1], Khi[3], Khi[4]); stsm4(kvd + 512, Khi[5], Khi[6], Khi[8], Khi[9]); stsm4(kvd + 1024, Khi[2], Khi[7], Vhi[0], Vhi[1]);
      stsm4(kvd + 1536, Vhi[2], Vhi[3], Vhi[4], Vhi[5]); stsm4(kvd + 2048, Vhi[6], Vhi[7], Vhi[8], Vhi[9]);
      mbar_arrive(bar_kv + ((warp + 1) >> 2) * 8);
    }
#define CONV_LO(ROT) _Pragma("unroll") for (int t = 0; t < 10; t++) { \
      const int q = QT((t + ROT) % 10), k = KT((t + ROT) % 10), v = VT((t + ROT) % 10); \
      Vhi[t] = movm(Vhi[t]); \
      Klo[t] = pack_bf16(acc[4 * k], acc[4 * k + 1]); \
      Vlo[t] = movm(pack_bf16(acc[4 * v] * rlo, acc[4 * v + 1] * rlo)); \
      Qlo[t] = pack_bf16(acc[4 * q], acc[4 * q + 1]); \
      Qhi[t] = pack_bf16(acc[4 * q + 2], acc[4 * q + 3]); }
    if (godd) { CONV_LO(8) } else { CONV_LO(0) }
    const int slot = mt * 8 + warp;
    int guard = SPIN_MAX;
    const bool cA = c < 2, nA = r < 4;
    TS(0);
    mbar_wait(bar_go + fol * 8, 0);
    TS(23);
    uint32_t qe[4][2];
    float sl0[4], sl1[4], th0[4], th1[4];
#pragma unroll
    for (int hd = 0; hd < 4; hd++) {
      const int ta = 5 * (hd >> 1) + 3 * (hd & 1), ts = 5 * (hd >> 1) + 2;
      const bool mine = (hd & 1) ? !cA : cA;
      qe[hd][0] = mine ? Qlo[ts] : 0u; qe[hd][1] = mine ? Qhi[ts] : 0u;
      float sl[4], sh[4];
      mma_k24(sl, Qlo[ta], Qhi[ta], Qlo[ta + 1], Qhi[ta + 1], Klo[ta], Klo[ta + 1], qe[hd][0], qe[hd][1], Klo[ts]);
      mma_k24(sh, Qlo[ta], Qhi[ta], Qlo[ta + 1], Qhi[ta + 1], Khi[ta], Khi[ta + 1], qe[hd][0], qe[hd][1], Khi[ts]);
      th0[hd] = (in0 ? sh[2] : sl[2]) * sch0; th1[hd] = (in1 ? sh[3] : sl[3]) * sch1;
      float mh = fmaxf(th0[hd], th1[hd]);
      mh = fmaxf(mh, shx(mh, 1)); mh = fmaxf(mh, shx(mh, 2));
      th0[hd] -= mh; th1[hd] -= mh;
      sl0[hd] = sl[0]; sl1[hd] = sl[1];
    }
    mbar_wait(bar_kv + wg * 8, 0);
    TS(4);
    const uint4 k0 = ldsm4(kvs), k1 = ldsm4(kvs + 512), k2 = ldsm4(kvs + 1024), v0 = ldsm4t(kvs + 1024), v1 = ldsm4t(kvs + 1536), v2 = ldsm4t(kvs + 2048);
    const uint32_t Kp[10] = {k0.x, k0.y, k2.x, k0.z, k0.w, k1.x, k1.y, k2.y, k1.z, k1.w};
    const uint32_t Vp[10] = {v0.z, v0.w, v1.x, v1.y, v1.z, v1.w, v2.x, v2.y, v2.z, v2.w};
    const uint32_t ONES = 0x3f803f80u;
    uint32_t of[20];
#pragma unroll
    for (int hp = 0; hp < 2; hp++) {
      float o[6][4];
#pragma unroll
      for (int hh = 0; hh < 2; hh++) {
        const int hd = 2 * hp + hh, ta = 5 * hp + 3 * hh, ts = 5 * hp + 2;
        float sp[4];
        mma_k24(sp, Qlo[ta], Qhi[ta], Qlo[ta + 1], Qhi[ta + 1], Kp[ta], Kp[ta + 1], qe[hd][0], qe[hd][1], Kp[ts]);
        const float tl0 = fmaf(in0 ? sl0[hd] : sp[0], scl0, bias0), tl1 = fmaf(in1 ? sl1[hd] : sp[1], scl1, bias1);
        float ml = fmaxf(tl0, tl1);
        ml = fmaxf(ml, shx(ml, 1)); ml = fmaxf(ml, shx(ml, 2));
        if (HOLD == 1 && hd == 3 && !fol && lane == 0) mbar_arrive(bar_go + 8);
        const uint32_t Pl = pack_bf16(ex2(tl0 - ml), ex2(tl1 - ml)), Ph = pack_bf16(ex2(th0[hd]), ex2(th1[hd]));
        const uint32_t a0 = Pl & mL, a1 = Ph & ~mL, a3 = Ph & mL, ap = Pl & ~mL;
        const uint32_t z0 = Ph & zero, z1 = ~Ph & zero;
        const bool vm = hh == 0 ? nA : !nA;
        mma_k24(o[3 * hh], a0, a1, z0, a3, Vlo[ta], Vhi[ta], ap, z1, Vp[ta]);
        mma_k24(o[3 * hh + 1], a0, a1, z0, a3, Vlo[ta + 1], Vhi[ta + 1], ap, z1, Vp[ta + 1]);
        mma_k24(o[3 * hh + 2], a0, a1, z0, a3, vm ? Vlo[ts] : ONES, vm ? Vhi[ts] : ONES, ap, z1, vm ? Vp[ts] : ONES);
      }
      const float il = rcp(cA ? o[5][0] : o[2][0]), ih = rcp(cA ? o[5][2] : o[2][2]);
      const float jl = shx(il, 2), jh = shx(ih, 2);
      const float al = cA ? jl : il, ah = cA ? jh : ih, bl = cA ? il : jl, bh = cA ? ih : jh;
      const int t0 = 5 * hp;
      of[2 * t0]     = pack_bf16(o[0][0] * al, o[0][1] * al); of[2 * t0 + 1] = pack_bf16(o[0][2] * ah, o[0][3] * ah);
      of[2 * t0 + 2] = pack_bf16(o[1][0] * al, o[1][1] * al); of[2 * t0 + 3] = pack_bf16(o[1][2] * ah, o[1][3] * ah);
      of[2 * t0 + 4] = pack_bf16((cA ? o[2][0] : o[5][0]) * jl, (cA ? o[2][1] : o[5][1]) * jl);
      of[2 * t0 + 5] = pack_bf16((cA ? o[2][2] : o[5][2]) * jh, (cA ? o[2][3] : o[5][3]) * jh);
      of[2 * t0 + 6] = pack_bf16(o[3][0] * bl, o[3][1] * bl); of[2 * t0 + 7] = pack_bf16(o[3][2] * bh, o[3][3] * bh);
      of[2 * t0 + 8] = pack_bf16(o[4][0] * bl, o[4][1] * bl); of[2 * t0 + 9] = pack_bf16(o[4][2] * bh, o[4][3] * bh);
    }
    {
#pragma unroll
      for (int s = 0; s < 5; s++) {
        stsm4(oa + s * 256, of[4 * s], of[4 * s + 1], of[4 * s + 2], of[4 * s + 3]);
        if (s == 0 && (fol || HOLD == 2) && lane == 0) mbar_arrive(bar_go + 8 + 8 * fol);
      }
      asm volatile("fence.proxy.async.shared::cta;" ::: "memory");
      __syncwarp();
      asm volatile("{\n.reg .pred q;\nelect.sync _|q, 0xffffffff;\n@q cp.async.bulk.global.shared::cta.bulk_group [%0], [%1], 2560;\ncp.async.bulk.commit_group;\n}\n" :: "l"(odst), "r"(os) : "memory");
    }
    TS(5);
    float h[40];
#pragma unroll
    for (int s = 0; s < 5; s++) {
      const uint4 v = xr[s];
      h[8 * s] = bf_lo(v.x); h[8 * s + 1] = bf_hi(v.x); h[8 * s + 2] = bf_lo(v.y); h[8 * s + 3] = bf_hi(v.y);
      h[8 * s + 4] = bf_lo(v.z); h[8 * s + 5] = bf_hi(v.z); h[8 * s + 6] = bf_lo(v.w); h[8 * s + 7] = bf_hi(v.w);
    }
    asm volatile("cp.async.bulk.wait_group 0;" ::: "memory");
    __syncwarp();
    if (lane == 0) {
      asm volatile("red.relaxed.gpu.global.add.u32 [%0], %1;" :: "l"(ocnt), "r"(oinc) : "memory");
      mbar_arrive(bar_st + 8 * fol);
    }
    TS(22);
    mbar_wait(bar_full, 0); mbar_wait(bar_full + 8, 0); mbar_wait(bar_full + 16, 1);
    mbar_wait(bar_go + 16, 0);
    const uint64_t dwo = make_desc(D0 * 16, 5120, 512, 2);
    wgmma_fence();
#pragma unroll
    for (int s = 0; s < 5; s++) wgmma_n80_rs(h, of[4 * s], of[4 * s + 1], of[4 * s + 2], of[4 * s + 3], dwo + g * 960 + s * 64, 1);
    wgmma_commit();
    TS(6);
    const bool odd = c & 1;
    uint4* const sp = hold(&g_own[slot].st2[r + (odd ? 8 : 0)]);
    uint4* const cdp = hold(&g_x.cand[slot][g][lane & zero]);
    uint4* const kcp = hold(g_own[1].cnt + (lane & zero));
    float wr[20];
#pragma unroll
    for (int j = 0; j < 5; j++) {
      const uint4 v = lds128(sb + OFF_WR + c * 80 + j * 16);
      wr[4 * j] = __uint_as_float(v.x); wr[4 * j + 1] = __uint_as_float(v.y); wr[4 * j + 2] = __uint_as_float(v.z); wr[4 * j + 3] = __uint_as_float(v.w);
    }
    const float wsum = lds32f(sb + OFF_WR + 320);
    const uint32_t bo = bar_o + fol * 56;
    if (PRIO < 7 && fol) mbar_wait(bar_oc + 8 * PRIO, 0);
#pragma unroll
    for (int i = 0; i < 7; i++) {
      mbar_wait(bo + 8 * i, 0);
      if (i == 0) TS(1);
      const uint32_t da = D0 + OFF_O / 16 + (8 << 16) + ((i + 2) % 7) * 640, db = D0 + (320 << 16) + (i >= g ? i + 1 : i) * 960;
      wgmma_fence();
#pragma unroll
      for (int s = 0; s < 5; s++) wgmma_n80_ss(h, mk64(da + s * 16, 80u), mk64(db + s * 64, 0x80000020u), 1);
      wgmma_commit();
      wgmma_wait<1>();
      if (lane == 0 && i > 0) mbar_arrive(bo + 104 + 8 * i);
    }
    const int tok0 = P * 256 + 32 * warp + rank;
    wgmma_wait<0>();
#pragma unroll
    for (int i = 0; i < 40; i++) asm volatile("" : "+f"(h[i]) :: "memory");
    if (lane == 0) mbar_arrive(bo + 160);
    if (SPLITB) { asm volatile("{\n.reg .pred p;\nsetp.ne.u32 p, %0, 0;\n@p trap;\n}\n" :: "r"(zero) : "memory"); }
    TS(7);
    float mean, rstd, rr;
    bool pub;
    {
      float l1 = 0.f, l2 = 0.f, l3 = 0.f, h1 = 0.f, h2 = 0.f, h3 = 0.f;
#pragma unroll
      for (int j = 0; j < 10; j++) {
        l1 += h[4 * j] + h[4 * j + 1]; h1 += h[4 * j + 2] + h[4 * j + 3];
        l2 = fmaf(h[4 * j], h[4 * j], l2); l2 = fmaf(h[4 * j + 1], h[4 * j + 1], l2);
        h2 = fmaf(h[4 * j + 2], h[4 * j + 2], h2); h2 = fmaf(h[4 * j + 3], h[4 * j + 3], h2);
        l3 = fmaf(h[4 * j], wr[2 * j], l3); l3 = fmaf(h[4 * j + 1], wr[2 * j + 1], l3);
        h3 = fmaf(h[4 * j + 2], wr[2 * j], h3); h3 = fmaf(h[4 * j + 3], wr[2 * j + 1], h3);
      }
      float s1 = (odd ? h1 : l1) + shx(odd ? l1 : h1, 1), s2 = (odd ? h2 : l2) + shx(odd ? l2 : h2, 1), s3 = (odd ? h3 : l3) + shx(odd ? l3 : h3, 1);
      s1 += shx(s1, 2); s2 += shx(s2, 2); s3 += shx(s3, 2);
      uint4 p0;
      float o1 = 0.f, o2 = 0.f, o3 = 0.f, oc = 7.f;
      asm volatile("{\n.reg .pred q;\nsetp.lt.u32 q, %9, 2;\n@q atom.relaxed.gpu.global.add.v4.f32 {%0, %1, %2, %3}, [%4], {%5, %6, %7, %8};\n}\n"
                   : "+f"(o1), "+f"(o2), "+f"(o3), "+f"(oc) : "l"(sp), "f"(s1), "f"(s2), "f"(s3), "f"(1.f), "r"(c) : "memory");
      const uint32_t last = __ballot_sync(0xffffffffu, oc == 7.f);
      pub = last & 1;
      p0.x = __float_as_uint(o1 + s1); p0.y = __float_as_uint(o2 + s2); p0.z = __float_as_uint(o3 + s3);
      if (last != 0xffffffffu)
      do { p0 = ldg_pkt(sp); } while (anyw(p0.w != 0x41000000u) && --guard > 0);
      mean = __uint_as_float(p0.x) * (1.f / 640.f);
      rstd = rsq(fmaxf(fmaf(-mean, mean, __uint_as_float(p0.y) * (1.f / 640.f)), 0.f) + 1e-5f);
      rr = fmaf(-mean, wsum, __uint_as_float(p0.z)) * rstd;
    }
    TS(8);
    const int myrow = r + (odd ? 8 : 0);
    const uint32_t kk = cA ? ord_key(rr) : 0u, kmax = __reduce_max_sync(0xffffffffu, kk);
    if (pub) {
      if (kk == kmax) asm volatile("red.relaxed.gpu.global.max.u64 [%0], %1;" :: "l"(kcp), "l"(mk64(2047 - tok0 - 2 * myrow, kk)) : "memory");
      __syncwarp();
      if (lane == 0) asm volatile("red.relaxed.gpu.global.add.u32 [%0 + 8], 1;" :: "l"(kcp) : "memory");
    }
    const int crow = __reduce_min_sync(0xffffffffu, kk == kmax ? myrow : 16), L = (crow & 7) * 4 + (crow >> 3);
    if (warp == g) asm volatile("bar.arrive 3, 64;" ::: "memory");
    const uint32_t stg = sb + (fol ? OFF_O : g * 15360) + w4 * 2560;
    uint4 held;
    {
      const float nb = -mean * rstd;
      const float rl = __shfl_sync(0xffffffffu, rstd, lane & 28), rh = __shfl_sync(0xffffffffu, rstd, (lane & 28) + 1);
      const float bl = __shfl_sync(0xffffffffu, nb, lane & 28), bh = __shfl_sync(0xffffffffu, nb, (lane & 28) + 1), al = 1.f + rl, ah = 1.f + rh;
      if ((L >> 2) == r) {
        const bool chi = L & 1;
        const float rc = chi ? rh : rl, bc = chi ? bh : bl;
        uint32_t n[10];
#pragma unroll
        for (int j = 0; j < 10; j++) n[j] = pack_bf16(fmaf(chi ? h[4 * j + 2] : h[4 * j], rc, bc), fmaf(chi ? h[4 * j + 3] : h[4 * j + 1], rc, bc));
        uint4* d = cdp + c;
        stg_pkt(d, n[0], n[1], n[2], n[3]); stg_pkt(d + 4, n[4], n[5], n[6], n[7]); stg_rlx64(d + 8, n[8], n[9]);
      }
      mbar_wait(bar_oc + 56, 0);
      const uint32_t fa = stg + (lane & 15) * 160 + (lane >> 4) * 16;
#pragma unroll
      for (int s = 0; s < 5; s++)
        stsm4(fa + s * 32, pack_bf16(fmaf(h[8 * s], al, bl), fmaf(h[8 * s + 1], al, bl)), pack_bf16(fmaf(h[8 * s + 2], ah, bh), fmaf(h[8 * s + 3], ah, bh)),
              pack_bf16(fmaf(h[8 * s + 4], al, bl), fmaf(h[8 * s + 5], al, bl)), pack_bf16(fmaf(h[8 * s + 6], ah, bh), fmaf(h[8 * s + 7], ah, bh)));
      __syncwarp();
      held = lds128(stg + crow * 160 + min(lane, 9) * 16);
      if (lane < 10) stg_pkt(cdp + 12 + lane, held.x, held.y, held.z, held.w);
    }
    TS(9);
    mbar_wait(bar_ffn, 0);
    const uint32_t red = sb + OFF_RED;
    if (ffn1) {
      uint4 w1[4][5];
      {
        const int k = (lane & 7) + (lane >> 4) * 8;
        const uint32_t a1 = sb + k * 64, sw = ((lane >> 3) & 1) ^ ((lane >> 1) & 3);
#pragma unroll
        for (int s = 0; s < 5; s++)
#pragma unroll
          for (int u = 0; u < 4; u++)
            w1[u][s] = ldsm4t(a1 + (s < 4 ? warp * 4096 + s * 1024 : 32768 + warp * 1024) + (u >> 1) * (40960 + (s == 4 || warp >= 4 ? OFF_W2 - 57344 : 0)) + ((sw ^ (2 * (u & 1))) * 16));
      }
      uint32_t* const ap = hold(g_x.act + fj * 16 + (lane >> 1));
      mbar_wait(bar_win, 0);
      const uint32_t hp = sb + OFF_HN + (warp * 4 + c) * 16;
      const uint4 c0 = lds128(hp), c1 = lds128(hp + 512), c2 = lds128(hp + 1024);
      TS(10);
      float a[4][4];
#pragma unroll
      for (int u = 0; u < 4; u++) {
        a[u][0] = a[u][1] = a[u][2] = a[u][3] = 0.f;
        mma_acc(a[u], w1[u][0], c0.x, c0.y); mma_acc(a[u], w1[u][1], c0.z, c0.w); mma_acc(a[u], w1[u][2], c1.x, c1.y);
        mma_acc(a[u], w1[u][3], c1.z, c1.w); mma_acc(a[u], w1[u][4], c2.x, c2.y);
      }
      asm volatile("st.shared.v2.f32 [%0], {%1, %2};" :: "r"(red + (warp * 32 + c * 8 + r) * 8),
                   "f"(cA ? (odd ? a[0][2] : a[0][0]) : (odd ? a[1][2] : a[1][0])), "f"(cA ? (odd ? a[2][2] : a[2][0]) : (odd ? a[3][2] : a[3][0])) : "memory");
      bar_sync(1, 256);
      if (warp == 0) {
        float2 t[8];
#pragma unroll
        for (int i = 0; i < 8; i++) t[i] = lds64f(red + (i * 32 + lane) * 8);
        const float s = ((t[0].x + t[1].x) + (t[2].x + t[3].x)) + ((t[4].x + t[5].x) + (t[6].x + t[7].x));
        const float u = ((t[0].y + t[1].y) + (t[2].y + t[3].y)) + ((t[4].y + t[5].y) + (t[6].y + t[7].y));
        const float av = s * u * rcp(1.f + ex2(-1.4426950408889634f * s));
        const float an = shx(av, 1);
        if (!odd) stg_rlx32(ap, pack_bf16(av, an));
      }
      bar_sync(1, 256);
      TS(11);
    }
    char* const ob2 = (char*)(out + tok0 * 640 + g * 64);
    const int remo = 896 - 96 * g;
    {
      char* const q0 = ob2 + (lane >> 3) * 2560 + (lane & 7) * 16;
      const uint32_t s0 = stg + (lane >> 3) * 160 + (lane & 7) * 16;
#pragma unroll
      for (int s = 0; s < 4; s++) stg128_if(4 * s + (lane >> 3) != crow, q0 + s * 10240, lds128(s0 + s * 640));
      stg128_if((lane >> 1) != crow, ob2 + (lane >> 1) * 2560 + (lane & 1) * 16 + 128 + remo, lds128(stg + (lane >> 1) * 160 + (lane & 1) * 16 + 128));
    }
    mbar_wait(bar_win, 0);
    uint4 win = lds128(sb + OFF_WR + 336);
    win.z = win.y; win.y = 2047u - (win.x & 2047u); win.x = (win.y >> 8) * 16 + (win.y & 1) * 8 + ((win.y >> 5) & 7);
    stg128_if(win.x != slot && lane < 10, ob2 + crow * 2560 + lane * 16 + (lane < 8 ? 0 : remo), held);
    if (!ffn1) {
      TS(10);
      uint4 w2[6];
      const uint32_t a2 = sb + OFF_W2 + (warp * 192 + 8 * (((lane >> 3) & 1) * 4 + ((lane & 7) >> 1)) + 2 * (lane >> 4) + (lane & 1)) * 16;
#pragma unroll
      for (int s = 0; s < 6; s++) w2[s] = ldsm4t(a2 + (s >> 1) * 1024 + (s & 1) * 64);
      const uint4* p = (const uint4*)(g_x.act + warp * 96) + (r & 1) * 4 + c;
      const uint32_t* pb = (const uint32_t*)&g_x.cand[win.x][fj < 64 ? fj >> 3 : (fj - 64) >> 1][fj < 64 ? 12 + (fj & 7) : 20 + (fj & 1)] + c;
      uint32_t* const op = hold((uint32_t*)(out + win.y * 640 + fj * 8) + c);
      const float sg = shx(rcp(1.f + ex2(-1.4426950408889634f * __uint_as_float(win.z ^ ((uint32_t)((int32_t)~win.z >> 31) | 0x80000000u)))), 1);
      uint4 c0, c1, c2; uint32_t bw;
      if (ACT_NS) __nanosleep(ACT_NS);
      do {
        c0 = ldg_pkt(p); c1 = ldg_pkt(p + 8); c2 = ldg_pkt(p + 16); bw = ldg_rlx32(pb);
      } while (anyw(max(max(max(max(c0.x, c0.y), max(c0.z, c0.w)), max(max(c1.x, c1.y), max(c1.z, c1.w))), max(max(max(c2.x, c2.y), max(c2.z, c2.w)), bw)) == SENT) && --guard > 0);
      TS(11);
      float a[4] = {0.f, 0.f, 0.f, 0.f}, b[4] = {0.f, 0.f, 0.f, 0.f}, d[4] = {0.f, 0.f, 0.f, 0.f};
      mma_acc(a, w2[0], c0.x, c0.y); mma_acc(b, w2[2], c1.x, c1.y); mma_acc(d, w2[4], c2.x, c2.y);
      mma_acc(a, w2[1], c0.z, c0.w); mma_acc(b, w2[3], c1.z, c1.w); mma_acc(d, w2[5], c2.z, c2.w);
      if (c == 0) sts32f(red + (warp * 8 + r) * 4, ((a[0] + a[3]) + (b[0] + b[3])) + (d[0] + d[3]));
      bar_sync(1, 256);
      if (tid < 4) {
        float2 t[8];
#pragma unroll
        for (int i = 0; i < 8; i++) t[i] = lds64f(red + (i * 4 + tid) * 8);
        const float y0 = ((t[0].x + t[1].x) + (t[2].x + t[3].x)) + ((t[4].x + t[5].x) + (t[6].x + t[7].x));
        const float y1 = ((t[0].y + t[1].y) + (t[2].y + t[3].y)) + ((t[4].y + t[5].y) + (t[6].y + t[7].y));
        stg_rlx32(op, pack_bf16(fmaf(y0, sg, bf_lo(bw)), fmaf(y1, sg, bf_hi(bw))));
      }
    }
    TS(12);
#undef TS_T
  }
}

typedef CUresult (*EncodeFn)(CUtensorMap*, CUtensorMapDataType, cuuint32_t, void*, const cuuint64_t*, const cuuint64_t*, const cuuint32_t*,
                             const cuuint32_t*, CUtensorMapInterleave, CUtensorMapSwizzle, CUtensorMapL2promotion, CUtensorMapFloatOOBfill);

void make_map(EncodeFn enc, CUtensorMap* m, const void* base, const cuuint64_t* dims, const cuuint64_t* strides, const cuuint32_t* box,
              CUtensorMapSwizzle swz, int promo = PROMO) {
  const cuuint32_t es[3] = {1, 1, 1};
  enc(m, CU_TENSOR_MAP_DATA_TYPE_BFLOAT16, 3, (void*)base, dims, strides, box, es, CU_TENSOR_MAP_INTERLEAVE_NONE, swz,
      (CUtensorMapL2promotion)promo, CU_TENSOR_MAP_FLOAT_OOB_FILL_NONE);
}

}

extern "C" void kernel_launch(void* const* d_in, const int* in_sizes, int n_in, void* d_out, int out_size) {
  const __nv_bfloat16* x = (const __nv_bfloat16*)d_in[0];
  const __nv_bfloat16* wqkv = (const __nv_bfloat16*)d_in[1];
  const __nv_bfloat16* wo = (const __nv_bfloat16*)d_in[2];
  void* fn = nullptr;
  cudaDriverEntryPointQueryResult st;
  cudaGetDriverEntryPoint("cuTensorMapEncodeTiled", &fn, cudaEnableDefault, &st);
  EncodeFn enc = (EncodeFn)fn;
  void* scp = nullptr;
  cudaGetSymbolAddress(&scp, g_scratch);
  Maps tm;
  { const cuuint64_t d[3] = {640, 1024, 2}, s[2] = {2560, 1280}; const cuuint32_t b[3] = {64, 128, 1}; make_map(enc, &tm.x, x, d, s, b, CU_TENSOR_MAP_SWIZZLE_128B, PROMOX); }
  { const cuuint64_t d[3] = {640, 640, 3}, s[2] = {3840, 1280}; const cuuint32_t b[3] = {64, 16, 3}; make_map(enc, &tm.w, wqkv, d, s, b, CU_TENSOR_MAP_SWIZZLE_128B); }
  { const cuuint64_t d[3] = {640, 640, 3}, s[2] = {3840, 1280}; const cuuint32_t b[3] = {16, 16, 3}; make_map(enc, &tm.wr, wqkv, d, s, b, CU_TENSOR_MAP_SWIZZLE_32B); }
  { const cuuint64_t d[3] = {640, 640, 3}, s[2] = {3840, 1280}; const cuuint32_t b[3] = {16, 16, 1}; make_map(enc, &tm.wv, wqkv, d, s, b, CU_TENSOR_MAP_SWIZZLE_32B); }
  { const cuuint64_t d[3] = {32, 640, 20}, s[2] = {1280, 64}; const cuuint32_t b[3] = {32, 80, 2}; make_map(enc, &tm.wo, wo, d, s, b, CU_TENSOR_MAP_SWIZZLE_64B); }
  { const cuuint64_t d[3] = {640, 640, 1}, s[2] = {1280, 819200}; const cuuint32_t b[3] = {16, 80, 1}; make_map(enc, &tm.wor, wo, d, s, b, CU_TENSOR_MAP_SWIZZLE_64B); }
  { const cuuint64_t d[3] = {1536, 640, 1}, s[2] = {3072, 1966080}; const cuuint32_t b[3] = {32, 128, 1};
    make_map(enc, &tm.gate, d_in[5], d, s, b, CU_TENSOR_MAP_SWIZZLE_64B); make_map(enc, &tm.up, d_in[6], d, s, b, CU_TENSOR_MAP_SWIZZLE_64B); }
  { const cuuint64_t d[3] = {640, 1536, 1}, s[2] = {1280, 1966080}; const cuuint32_t b[3] = {8, 128, 1}; make_map(enc, &tm.down, d_in[7], d, s, b, CU_TENSOR_MAP_SWIZZLE_NONE); }
  cudaFuncSetAttribute(fused_kernel, cudaFuncAttributeMaxDynamicSharedMemorySize, SMEM_BYTES);
  fused_kernel<<<128, 512, SMEM_BYTES, cudaStreamPerThread>>>(x, wqkv, wo, (const __nv_bfloat16*)d_in[4], (const __nv_bfloat16*)d_in[5],
                                                              (const __nv_bfloat16*)d_in[6], (const __nv_bfloat16*)d_in[7], (__nv_bfloat16*)d_out, (Scratch*)scp, tm);
}
```

```cpp
#include <cuda_runtime.h>
#include <cuda_bf16.h>
#include <cuda.h>
#include <stdint.h>

#define PFW_NS 50
#define PFW_N 14
#define ACT_NS 100
#define KEY_NS 0
#define AUX_NS 50
#define REG_P 64
#define REG_C 192
#define LEAD 1
#define HK_IT 2
#define F_PER 2
#define F_MAX 8
#define HOLD 2
#define AK 3
#define NSPLIT 3
#define THR_END 3
#define BOUNDED 0
#define TLIGHT 0
#define ATOM2 1
#define LAG 4
#define OV 2
#define O_UNROLL 1
#define PRIO 7
#define SPLITB 1
#define GPAD 3328
#define PROMO 2
#define PROMOX 2
#define OWN1 1

namespace {

constexpr int SLOT    = 49152;
constexpr int OFF_O   = 122880;
constexpr int OFF_W2  = 4 * SLOT;
constexpr int OFF_CS  = OFF_W2 + 24576;
constexpr int OFF_RS  = OFF_CS + 3840;
constexpr int OFF_MN  = OFF_RS + 576;
constexpr int OFF_WR  = OFF_MN + 1024;
constexpr int OFF_RED = OFF_CS;
constexpr int OFF_HN  = OFF_CS + 2048;
constexpr int OFF_PT  = OFF_WR + 352;
constexpr int OFF_BAR = OFF_PT + 768;
constexpr int SMEM_BYTES = OFF_BAR + 424 + 384;
constexpr uint32_t D0 = 1024 >> 4;
constexpr int OUNR = O_UNROLL;
constexpr uint32_t SENT = 0xFFFFFFFFu;
constexpr int SPIN_MAX = 1 << 20;

struct Glob {
  uint4 cand[128][8][24];
  uint32_t act[768];
  uint32_t pad[GPAD];
};
constexpr int GLOB_PER_CTA = sizeof(Glob) / 16 / 128;
static_assert(GLOB_PER_CTA * 128 * 16 == sizeof(Glob), "glob size");
struct Own {
  uint4 halo[5][32];
  uint4 st1[32];
  uint2 cs[32];
  uint4 st2[16];
  uint4 cnt[8];
};
struct Scratch {
  Glob x;
  Own own[128];
  uint4 o[32][8][640];
  uint32_t epoch[128];
};
__device__ __align__(128) Scratch g_scratch;
#define g_x (sc->x)
#define g_own (sc->own)
#define g_o (sc->o)
#define g_epoch (sc->epoch)
#define TS(i)

__device__ __forceinline__ void mbar_init(uint32_t bar, uint32_t cnt) { asm volatile("mbarrier.init.shared::cta.b64 [%0], %1;" :: "r"(bar), "r"(cnt) : "memory"); }
__device__ __forceinline__ void mbar_expect_tx(uint32_t bar, uint32_t bytes) { asm volatile("mbarrier.arrive.expect_tx.shared::cta.b64 _, [%0], %1;" :: "r"(bar), "r"(bytes) : "memory"); }
__device__ __forceinline__ void mbar_arrive(uint32_t bar) { asm volatile("mbarrier.arrive.shared::cta.b64 _, [%0];" :: "r"(bar) : "memory"); }
__device__ __forceinline__ void mbar_arrive_cta(uint32_t bar, uint32_t cta) {
  asm volatile("{\n.reg .b32 ra;\nmapa.shared::cluster.u32 ra, %0, %1;\nmbarrier.arrive.shared::cluster.b64 _, [ra];\n}\n" :: "r"(bar), "r"(cta) : "memory");
}
__device__ __forceinline__ void mbar_wait(uint32_t bar, uint32_t parity) {
  asm volatile("{\n.reg .pred p;\nW:\nmbarrier.try_wait.parity.shared::cta.b64 p, [%0], %1;\n@!p bra.uni W;\n}\n" :: "r"(bar), "r"(parity) : "memory");
}
__device__ __forceinline__ void tma_3d(uint32_t dst, const void* tm, uint32_t bar, int c0, int c1, int c2) {
  asm volatile("cp.async.bulk.tensor.3d.shared::cluster.global.mbarrier::complete_tx::bytes [%0], [%1, {%3, %4, %5}], [%2];" :: "r"(dst), "l"(tm), "r"(bar), "r"(c0), "r"(c1), "r"(c2) : "memory");
}
__device__ __forceinline__ void tma_3d_mc(uint32_t dst, const void* tm, uint32_t bar, int c0, int c1, int c2) {
  asm volatile("cp.async.bulk.tensor.3d.shared::cluster.global.mbarrier::complete_tx::bytes.multicast::cluster [%0], [%1, {%3, %4, %5}], [%2], %6;" :: "r"(dst), "l"(tm), "r"(bar), "r"(c0), "r"(c1), "r"(c2), "h"((uint16_t)3) : "memory");
}
__device__ __forceinline__ void wgmma_fence() { asm volatile("wgmma.fence.sync.aligned;" ::: "memory"); }
__device__ __forceinline__ void wgmma_commit() { asm volatile("wgmma.commit_group.sync.aligned;" ::: "memory"); }
template <int N> __device__ __forceinline__ void wgmma_wait() { asm volatile("wgmma.wait_group.sync.aligned %0;" :: "n"(N) : "memory"); }
__device__ __forceinline__ uint64_t make_desc(uint32_t addr, uint32_t lbo, uint32_t sbo, uint32_t swz) {
  return (uint64_t)(((addr & 0x3FFFF) >> 4) | ((lbo >> 4) << 16)) | ((uint64_t)((sbo >> 4) | (swz << 30)) << 32);
}
__device__ __forceinline__ void bar_sync(int id, int n) { asm volatile("bar.sync %0, %1;" :: "r"(id), "r"(n) : "memory"); }
__device__ __forceinline__ uint4 ldg_pkt(const void* p) {
  uint4 v; asm volatile("ld.relaxed.gpu.global.v4.u32 {%0, %1, %2, %3}, [%4];" : "=r"(v.x), "=r"(v.y), "=r"(v.z), "=r"(v.w) : "l"(p) : "memory"); return v;
}
__device__ __forceinline__ void stg_pkt(void* p, uint32_t a, uint32_t b, uint32_t c, uint32_t d) {
  asm volatile("st.relaxed.gpu.global.v4.u32 [%0], {%1, %2, %3, %4};" :: "l"(p), "r"(a), "r"(b), "r"(c), "r"(d) : "memory");
}
__device__ __forceinline__ uint32_t ldg_rlx32(const void* p) { uint32_t v; asm volatile("ld.relaxed.gpu.global.u32 %0, [%1];" : "=r"(v) : "l"(p) : "memory"); return v; }
__device__ __forceinline__ uint2 ldg_rlx64(const void* p) { uint2 v; asm volatile("ld.relaxed.gpu.global.v2.u32 {%0, %1}, [%2];" : "=r"(v.x), "=r"(v.y) : "l"(p) : "memory"); return v; }
__device__ __forceinline__ uint32_t pin(uint32_t v) { asm volatile("" : "+r"(v)); return v; }
__device__ __forceinline__ uint64_t mk64(uint32_t lo, uint32_t hi) { return ((uint64_t)hi << 32) | lo; }
__device__ __forceinline__ uint32_t holdu(uint32_t v) { return __shfl_sync(0xffffffffu, v, threadIdx.x & 31); }
template <class T> __device__ __forceinline__ T* hold(T* p) { return (T*)__shfl_sync(0xffffffffu, (unsigned long long)p, threadIdx.x & 31); }
__device__ __forceinline__ void stg128_if(bool q, void* p, const uint4& v) {
  asm volatile("{\n.reg .pred q;\nsetp.ne.u32 q, %5, 0;\n@q st.global.v4.u32 [%0], {%1, %2, %3, %4};\n}\n" :: "l"(p), "r"(v.x), "r"(v.y), "r"(v.z), "r"(v.w), "r"((int)q) : "memory");
}
template <class T> __device__ __forceinline__ T* pin(T* p) { asm volatile("" : "+l"(p)); return p; }
__device__ __forceinline__ void stg_rlx32(void* p, uint32_t v) { asm volatile("st.relaxed.gpu.global.u32 [%0], %1;" :: "l"(p), "r"(v) : "memory"); }
__device__ __forceinline__ void stg_rlx64(void* p, uint32_t a, uint32_t b) { asm volatile("st.relaxed.gpu.global.v2.u32 [%0], {%1, %2};" :: "l"(p), "r"(a), "r"(b) : "memory"); }
__device__ __forceinline__ uint4 ldsm4(uint32_t a) { uint4 v; asm volatile("ldmatrix.sync.aligned.m8n8.x4.shared.b16 {%0, %1, %2, %3}, [%4];" : "=r"(v.x), "=r"(v.y), "=r"(v.z), "=r"(v.w) : "r"(a) : "memory"); return v; }
__device__ __forceinline__ void ldsm4_if(uint4& v, uint32_t a, int off, bool p) {
  asm volatile("{\n.reg .pred q;\nsetp.ne.u32 q, %5, 0;\n@q ldmatrix.sync.aligned.m8n8.x4.shared.b16 {%0, %1, %2, %3}, [%4];\n}\n"
               : "+r"(v.x), "+r"(v.y), "+r"(v.z), "+r"(v.w) : "r"(a + off), "r"((int)p) : "memory");
}
__device__ __forceinline__ uint4 ldsm4t(uint32_t a) { uint4 v; asm volatile("ldmatrix.sync.aligned.m8n8.x4.trans.shared.b16 {%0, %1, %2, %3}, [%4];" : "=r"(v.x), "=r"(v.y), "=r"(v.z), "=r"(v.w) : "r"(a) : "memory"); return v; }
__device__ __forceinline__ void stsm4(uint32_t a, uint32_t x, uint32_t y, uint32_t z, uint32_t w) { asm volatile("stmatrix.sync.aligned.m8n8.x4.shared.b16 [%0], {%1, %2, %3, %4};" :: "r"(a), "r"(x), "r"(y), "r"(z), "r"(w) : "memory"); }
__device__ __forceinline__ void mma_acc(float (&c)[4], const uint4& a, uint32_t b0, uint32_t b1) {
  asm("mma.sync.aligned.m16n8k16.row.col.f32.bf16.bf16.f32 {%0,%1,%2,%3}, {%4,%5,%6,%7}, {%8,%9}, {%0,%1,%2,%3};"
      : "+f"(c[0]), "+f"(c[1]), "+f"(c[2]), "+f"(c[3]) : "r"(a.x), "r"(a.y), "r"(a.z), "r"(a.w), "r"(b0), "r"(b1));
}
__device__ __forceinline__ uint4 lds128(uint32_t a) { uint4 v; asm volatile("ld.shared.v4.u32 {%0, %1, %2, %3}, [%4];" : "=r"(v.x), "=r"(v.y), "=r"(v.z), "=r"(v.w) : "r"(a) : "memory"); return v; }
__device__ __forceinline__ float2 lds64f(uint32_t a) { float2 v; asm volatile("ld.shared.v2.f32 {%0, %1}, [%2];" : "=f"(v.x), "=f"(v.y) : "r"(a)); return v; }
__device__ __forceinline__ float lds32f(uint32_t a) { float v; asm volatile("ld.shared.f32 %0, [%1];" : "=f"(v) : "r"(a)); return v; }
__device__ __forceinline__ void sts32f(uint32_t a, float v) { asm volatile("st.shared.f32 [%0], %1;" :: "r"(a), "f"(v) : "memory"); }
__device__ __forceinline__ uint32_t pack_bf16(float lo, float hi) { uint32_t r; asm("cvt.rn.bf16x2.f32 %0, %1, %2;" : "=r"(r) : "f"(hi), "f"(lo)); return r; }
__device__ __forceinline__ float bf_lo(uint32_t v) { return __uint_as_float(v << 16); }
__device__ __forceinline__ float bf_hi(uint32_t v) { return __uint_as_float(v & 0xffff0000u); }
__device__ __forceinline__ uint32_t movm(uint32_t a) { uint32_t d; asm("movmatrix.sync.aligned.m8n8.trans.b16 %0, %1;" : "=r"(d) : "r"(a)); return d; }
__device__ __forceinline__ float ex2(float x) { float y; asm("ex2.approx.ftz.f32 %0, %1;" : "=f"(y) : "f"(x)); return y; }
__device__ __forceinline__ float rsq(float x) { float y; asm("rsqrt.approx.ftz.f32 %0, %1;" : "=f"(y) : "f"(x)); return y; }
__device__ __forceinline__ float rcp(float x) { float y; asm("rcp.approx.ftz.f32 %0, %1;" : "=f"(y) : "f"(x)); return y; }
__device__ __forceinline__ bool elect() { uint32_t p; asm volatile("{\n.reg .pred q;\nelect.sync _|q, 0xffffffff;\nselp.u32 %0, 1, 0, q;\n}\n" : "=r"(p)); return p; }
__device__ __forceinline__ void pf_l2(const void* p) { asm volatile("prefetch.global.L2 [%0];" :: "l"(p)); }
__device__ __forceinline__ bool anyw(bool p) { return __any_sync(0xffffffffu, p); }
__device__ __forceinline__ float shx(float v, int m) { return __shfl_xor_sync(0xffffffffu, v, m); }
__device__ __forceinline__ void mma_k24(float (&c)[4], uint32_t a0, uint32_t a1, uint32_t a2, uint32_t a3, uint32_t b0, uint32_t b1,
                                        uint32_t e0, uint32_t e1, uint32_t f0) {
  asm("mma.sync.aligned.m16n8k16.row.col.f32.bf16.bf16.f32 {%0,%1,%2,%3}, {%4,%5,%6,%7}, {%8,%9}, {%10,%10,%10,%10};"
      : "=f"(c[0]), "=f"(c[1]), "=f"(c[2]), "=f"(c[3]) : "r"(a0), "r"(a1), "r"(a2), "r"(a3), "r"(b0), "r"(b1), "f"(0.f));
  asm("mma.sync.aligned.m16n8k8.row.col.f32.bf16.bf16.f32 {%0,%1,%2,%3}, {%4,%5}, {%6}, {%0,%1,%2,%3};"
      : "+f"(c[0]), "+f"(c[1]), "+f"(c[2]), "+f"(c[3]) : "r"(e0), "r"(e1), "r"(f0));
}
__device__ __forceinline__ uint32_t ord_key(float r) { uint32_t u = __float_as_uint(r); return u ^ ((uint32_t)((int32_t)u >> 31) | 0x80000000u); }

__device__ __forceinline__ void wgmma_n64hi_ss(float (&d)[120], uint64_t da, uint64_t db, int scale_d) {
  asm volatile("{\n.reg .pred p;\nsetp.ne.b32 p, %34, 0;\n"
    "wgmma.mma_async.sync.aligned.m64n64k16.f32.bf16.bf16 "
    "{%0, %1, %2, %3, %4, %5, %6, %7, %8, %9, %10, %11, %12, %13, %14, %15, "
    "%16, %17, %18, %19, %20, %21, %22, %23, %24, %25, %26, %27, %28, %29, %30, %31}, "
    "%32, %33, p, 1, 1, 0, 1;\n}\n"
    : "+f"(d[88]), "+f"(d[89]), "+f"(d[90]), "+f"(d[91]), "+f"(d[92]), "+f"(d[93]), "+f"(d[94]), "+f"(d[95]),
      "+f"(d[96]), "+f"(d[97]), "+f"(d[98]), "+f"(d[99]), "+f"(d[100]), "+f"(d[101]), "+f"(d[102]), "+f"(d[103]),
      "+f"(d[104]), "+f"(d[105]), "+f"(d[106]), "+f"(d[107]), "+f"(d[108]), "+f"(d[109]), "+f"(d[110]), "+f"(d[111]),
      "+f"(d[112]), "+f"(d[113]), "+f"(d[114]), "+f"(d[115]), "+f"(d[116]), "+f"(d[117]), "+f"(d[118]), "+f"(d[119])
    : "l"(da), "l"(db), "r"(scale_d));
}
__device__ __forceinline__ void wgmma_n176lo_ss(float (&d)[120], uint64_t da, uint64_t db, int scale_d) {
  asm volatile("{\n.reg .pred p;\nsetp.ne.b32 p, %90, 0;\n"
    "wgmma.mma_async.sync.aligned.m64n176k16.f32.bf16.bf16 "
    "{%0, %1, %2, %3, %4, %5, %6, %7, %8, %9, %10, %11, %12, %13, %14, %15, "
    "%16, %17, %18, %19, %20, %21, %22, %23, %24, %25, %26, %27, %28, %29, %30, %31, "
    "%32, %33, %34, %35, %36, %37, %38, %39, %40, %41, %42, %43, %44, %45, %46, %47, "
    "%48, %49, %50, %51, %52, %53, %54, %55, %56, %57, %58, %59, %60, %61, %62, %63, "
    "%64, %65, %66, %67, %68, %69, %70, %71, %72, %73, %74, %75, %76, %77, %78, %79, "
    "%80, %81, %82, %83, %84, %85, %86, %87}, "
    "%88, %89, p, 1, 1, 0, 1;\n}\n"
    : "+f"(d[0]), "+f"(d[1]), "+f"(d[2]), "+f"(d[3]), "+f"(d[4]), "+f"(d[5]), "+f"(d[6]), "+f"(d[7]),
      "+f"(d[8]), "+f"(d[9]), "+f"(d[10]), "+f"(d[11]), "+f"(d[12]), "+f"(d[13]), "+f"(d[14]), "+f"(d[15]),
      "+f"(d[16]), "+f"(d[17]), "+f"(d[18]), "+f"(d[19]), "+f"(d[20]), "+f"(d[21]), "+f"(d[22]), "+f"(d[23]),
      "+f"(d[24]), "+f"(d[25]), "+f"(d[26]), "+f"(d[27]), "+f"(d[28]), "+f"(d[29]), "+f"(d[30]), "+f"(d[31]),
      "+f"(d[32]), "+f"(d[33]), "+f"(d[34]), "+f"(d[35]), "+f"(d[36]), "+f"(d[37]), "+f"(d[38]), "+f"(d[39]),
      "+f"(d[40]), "+f"(d[41]), "+f"(d[42]), "+f"(d[43]), "+f"(d[44]), "+f"(d[45]), "+f"(d[46]), "+f"(d[47]),
      "+f"(d[48]), "+f"(d[49]), "+f"(d[50]), "+f"(d[51]), "+f"(d[52]), "+f"(d[53]), "+f"(d[54]), "+f"(d[55]),
      "+f"(d[56]), "+f"(d[57]), "+f"(d[58]), "+f"(d[59]), "+f"(d[60]), "+f"(d[61]), "+f"(d[62]), "+f"(d[63]),
      "+f"(d[64]), "+f"(d[65]), "+f"(d[66]), "+f"(d[67]), "+f"(d[68]), "+f"(d[69]), "+f"(d[70]), "+f"(d[71]),
      "+f"(d[72]), "+f"(d[73]), "+f"(d[74]), "+f"(d[75]), "+f"(d[76]), "+f"(d[77]), "+f"(d[78]), "+f"(d[79]),
      "+f"(d[80]), "+f"(d[81]), "+f"(d[82]), "+f"(d[83]), "+f"(d[84]), "+f"(d[85]), "+f"(d[86]), "+f"(d[87])
    : "l"(da), "l"(db), "r"(scale_d));
}
__device__ __forceinline__ void wgmma_n64hi_rk(float (&d)[120], uint32_t a0, uint32_t a1, uint32_t a2, uint32_t a3, uint64_t db, int scale_d) {
  asm volatile("{\n.reg .pred p;\nsetp.ne.b32 p, %37, 0;\n"
    "wgmma.mma_async.sync.aligned.m64n64k16.f32.bf16.bf16 "
    "{%0, %1, %2, %3, %4, %5, %6, %7, %8, %9, %10, %11, %12, %13, %14, %15, "
    "%16, %17, %18, %19, %20, %21, %22, %23, %24, %25, %26, %27, %28, %29, %30, %31}, "
    "{%32, %33, %34, %35}, %36, p, 1, 1, 0;\n}\n"
    : "+f"(d[88]), "+f"(d[89]), "+f"(d[90]), "+f"(d[91]), "+f"(d[92]), "+f"(d[93]), "+f"(d[94]), "+f"(d[95]),
      "+f"(d[96]), "+f"(d[97]), "+f"(d[98]), "+f"(d[99]), "+f"(d[100]), "+f"(d[101]), "+f"(d[102]), "+f"(d[103]),
      "+f"(d[104]), "+f"(d[105]), "+f"(d[106]), "+f"(d[107]), "+f"(d[108]), "+f"(d[109]), "+f"(d[110]), "+f"(d[111]),
      "+f"(d[112]), "+f"(d[113]), "+f"(d[114]), "+f"(d[115]), "+f"(d[116]), "+f"(d[117]), "+f"(d[118]), "+f"(d[119])
    : "r"(a0), "r"(a1), "r"(a2), "r"(a3), "l"(db), "r"(scale_d));
}
__device__ __forceinline__ void wgmma_n176lo_rk(float (&d)[120], uint32_t a0, uint32_t a1, uint32_t a2, uint32_t a3, uint64_t db, int scale_d) {
  asm volatile("{\n.reg .pred p;\nsetp.ne.b32 p, %93, 0;\n"
    "wgmma.mma_async.sync.aligned.m64n176k16.f32.bf16.bf16 "
    "{%0, %1, %2, %3, %4, %5, %6, %7, %8, %9, %10, %11, %12, %13, %14, %15, "
    "%16, %17, %18, %19, %20, %21, %22, %23, %24, %25, %26, %27, %28, %29, %30, %31, "
    "%32, %33, %34, %35, %36, %37, %38, %39, %40, %41, %42, %43, %44, %45, %46, %47, "
    "%48, %49, %50, %51, %52, %53, %54, %55, %56, %57, %58, %59, %60, %61, %62, %63, "
    "%64, %65, %66, %67, %68, %69, %70, %71, %72, %73, %74, %75, %76, %77, %78, %79, "
    "%80, %81, %82, %83, %84, %85, %86, %87}, "
    "{%88, %89, %90, %91}, %92, p, 1, 1, 0;\n}\n"
    : "+f"(d[0]), "+f"(d[1]), "+f"(d[2]), "+f"(d[3]), "+f"(d[4]), "+f"(d[5]), "+f"(d[6]), "+f"(d[7]),
      "+f"(d[8]), "+f"(d[9]), "+f"(d[10]), "+f"(d[11]), "+f"(d[12]), "+f"(d[13]), "+f"(d[14]), "+f"(d[15]),
      "+f"(d[16]), "+f"(d[17]), "+f"(d[18]), "+f"(d[19]), "+f"(d[20]), "+f"(d[21]), "+f"(d[22]), "+f"(d[23]),
      "+f"(d[24]), "+f"(d[25]), "+f"(d[26]), "+f"(d[27]), "+f"(d[28]), "+f"(d[29]), "+f"(d[30]), "+f"(d[31]),
      "+f"(d[32]), "+f"(d[33]), "+f"(d[34]), "+f"(d[35]), "+f"(d[36]), "+f"(d[37]), "+f"(d[38]), "+f"(d[39]),
      "+f"(d[40]), "+f"(d[41]), "+f"(d[42]), "+f"(d[43]), "+f"(d[44]), "+f"(d[45]), "+f"(d[46]), "+f"(d[47]),
      "+f"(d[48]), "+f"(d[49]), "+f"(d[50]), "+f"(d[51]), "+f"(d[52]), "+f"(d[53]), "+f"(d[54]), "+f"(d[55]),
      "+f"(d[56]), "+f"(d[57]), "+f"(d[58]), "+f"(d[59]), "+f"(d[60]), "+f"(d[61]), "+f"(d[62]), "+f"(d[63]),
      "+f"(d[64]), "+f"(d[65]), "+f"(d[66]), "+f"(d[67]), "+f"(d[68]), "+f"(d[69]), "+f"(d[70]), "+f"(d[71]),
      "+f"(d[72]), "+f"(d[73]), "+f"(d[74]), "+f"(d[75]), "+f"(d[76]), "+f"(d[77]), "+f"(d[78]), "+f"(d[79]),
      "+f"(d[80]), "+f"(d[81]), "+f"(d[82]), "+f"(d[83]), "+f"(d[84]), "+f"(d[85]), "+f"(d[86]), "+f"(d[87])
    : "r"(a0), "r"(a1), "r"(a2), "r"(a3), "l"(db), "r"(scale_d));
}
__device__ __forceinline__ void wgmma_n80_rs(float (&d)[40], uint32_t a0, uint32_t a1, uint32_t a2, uint32_t a3, uint64_t db, int scale_d) {
  asm volatile("{\n.reg .pred p;\nsetp.ne.b32 p, %45, 0;\n"
    "wgmma.mma_async.sync.aligned.m64n80k16.f32.bf16.bf16 "
    "{%0, %1, %2, %3, %4, %5, %6, %7, %8, %9, %10, %11, %12, %13, %14, %15, "
    "%16, %17, %18, %19, %20, %21, %22, %23, %24, %25, %26, %27, %28, %29, %30, %31, "
    "%32, %33, %34, %35, %36, %37, %38, %39}, "
    "{%40, %41, %42, %43}, %44, p, 1, 1, 1;\n}\n"
    : "+f"(d[0]), "+f"(d[1]), "+f"(d[2]), "+f"(d[3]), "+f"(d[4]), "+f"(d[5]), "+f"(d[6]), "+f"(d[7]),
      "+f"(d[8]), "+f"(d[9]), "+f"(d[10]), "+f"(d[11]), "+f"(d[12]), "+f"(d[13]), "+f"(d[14]), "+f"(d[15]),
      "+f"(d[16]), "+f"(d[17]), "+f"(d[18]), "+f"(d[19]), "+f"(d[20]), "+f"(d[21]), "+f"(d[22]), "+f"(d[23]),
      "+f"(d[24]), "+f"(d[25]), "+f"(d[26]), "+f"(d[27]), "+f"(d[28]), "+f"(d[29]), "+f"(d[30]), "+f"(d[31]),
      "+f"(d[32]), "+f"(d[33]), "+f"(d[34]), "+f"(d[35]), "+f"(d[36]), "+f"(d[37]), "+f"(d[38]), "+f"(d[39])
    : "r"(a0), "r"(a1), "r"(a2), "r"(a3), "l"(db), "r"(scale_d));
}
__device__ __forceinline__ void wgmma_n80_ss(float (&d)[40], uint64_t da, uint64_t db, int scale_d) {
  asm volatile("{\n.reg .pred p;\nsetp.ne.b32 p, %42, 0;\n"
    "wgmma.mma_async.sync.aligned.m64n80k16.f32.bf16.bf16 "
    "{%0, %1, %2, %3, %4, %5, %6, %7, %8, %9, %10, %11, %12, %13, %14, %15, "
    "%16, %17, %18, %19, %20, %21, %22, %23, %24, %25, %26, %27, %28, %29, %30, %31, "
    "%32, %33, %34, %35, %36, %37, %38, %39}, "
    "%40, %41, p, 1, 1, 0, 1;\n}\n"
    : "+f"(d[0]), "+f"(d[1]), "+f"(d[2]), "+f"(d[3]), "+f"(d[4]), "+f"(d[5]), "+f"(d[6]), "+f"(d[7]),
      "+f"(d[8]), "+f"(d[9]), "+f"(d[10]), "+f"(d[11]), "+f"(d[12]), "+f"(d[13]), "+f"(d[14]), "+f"(d[15]),
      "+f"(d[16]), "+f"(d[17]), "+f"(d[18]), "+f"(d[19]), "+f"(d[20]), "+f"(d[21]), "+f"(d[22]), "+f"(d[23]),
      "+f"(d[24]), "+f"(d[25]), "+f"(d[26]), "+f"(d[27]), "+f"(d[28]), "+f"(d[29]), "+f"(d[30]), "+f"(d[31]),
      "+f"(d[32]), "+f"(d[33]), "+f"(d[34]), "+f"(d[35]), "+f"(d[36]), "+f"(d[37]), "+f"(d[38]), "+f"(d[39])
    : "l"(da), "l"(db), "r"(scale_d));
}

__device__ __forceinline__ constexpr int QT(int t) { return t < 8 ? t : 16 + t; }
__device__ __forceinline__ constexpr int KT(int t) { return t < 8 ? 8 + t : 18 + t; }
__device__ __forceinline__ constexpr int VT(int t) { return t < 8 ? 16 + t : 20 + t; }

struct Maps { CUtensorMap x, w, wr, wv, wo, wor, gate, up, down; };

__global__ void __cluster_dims__(2, 1, 1) __launch_bounds__(512, 1)
fused_kernel(const __nv_bfloat16* __restrict__ x, const __nv_bfloat16* __restrict__ wqkv,
             const __nv_bfloat16* __restrict__ wo, const __nv_bfloat16* __restrict__ w_r, const __nv_bfloat16* __restrict__ w_gate,
             const __nv_bfloat16* __restrict__ w_up, const __nv_bfloat16* __restrict__ w_down, __nv_bfloat16* __restrict__ out,
             Scratch* __restrict__ sc, const __grid_constant__ Maps tm) {
  extern __shared__ __align__(1024) uint8_t smem[];
  const int tid = threadIdx.x, bid = blockIdx.x;
  if ((unsigned)(tid - 128) < 16u) pf_l2((const char*)x + (bid * 16 + tid - 128) * 1280);
  if ((unsigned)(tid - 160) < 15u) pf_l2((const char*)wqkv + (bid * 15 + tid - 160) * 128);
  const int warp = __shfl_sync(0xffffffffu, tid >> 5, 0), lane = tid & 31;
  const uint32_t sb = (uint32_t)__cvta_generic_to_shared(smem);
  const uint32_t bar_full = sb + OFF_BAR, bar_empty = bar_full + 32, bar_aux = bar_full + 64, bar_ffn = bar_full + 72, bar_win = bar_full + 80, bar_tag = bar_full + 88, bar_rst = bar_full + 96 + 296 + 24,
                 bar_o = bar_full + 96, bar_oc = bar_o + 112, bar_st = bar_o + 224, bar_go = bar_o + 248, bar_kv = bar_o + 272, bar_half = bar_o + 296;
  if (warp < 4 && elect()) {
    mbar_init(bar_half + 8 * warp, 1);
    mbar_init(bar_full + 8 * (warp ^ 2), 1);
    mbar_init(bar_empty + 8 * warp, 24);
    mbar_init(bar_aux + 8 * warp, warp == 0 ? 64 : warp == 2 ? 32 : warp == 3 ? 2 : 1);
    asm volatile("fence.mbarrier_init.release.cluster;" ::: "memory");
  }
  asm volatile("barrier.cluster.arrive.relaxed.aligned;" ::: "memory");
  if (warp >= 8 && warp < 12 && elect()) asm volatile("prefetch.tensormap [%0];" :: "l"(&tm.x + (warp - 8)) : "memory");
  const int rank = bid & 1, cl = bid >> 1;
  const int q7 = ((cl - 36) * 37) >> 8;
  const int P = cl < 4 ? 0 : cl < 36 ? (cl - 4) & 7 : cl - 35 - 7 * q7;
  const int g = (cl < 4 ? 4 + cl : cl < 36 ? (cl - 4) >> 3 : 4 + q7);
  const int mt = 2 * P + rank, cid = mt * 8 + g;
  const bool ffn1 = g >= 5;
  const int fj = ffn1 ? mt * 3 + g - 5 : (P * 5 + g) * 2 + rank;
  const int ord = ((g >> 2) ^ P) & 1;
  auto ks_of = [&](int it) { return ord == 0 || it < 2 ? it : it <= 5 ? it + 4 : it - 4; };
  const int godd = g & 1, cm = g * 80 + godd * 16, cr = g * 80 + 64 - godd * 64;
  auto load_w = [&](int ks, uint32_t a, uint32_t bar, int kk) {
    tma_3d_mc(a + 16384 + ((kk + 1) & 3) * 6144, &tm.w, bar, cm, ks * 64 + kk * 16, 0);
    tma_3d_mc(a + 41472 + kk * 2048, &tm.wr, bar, cr, ks * 64 + kk * 16, 0);
    tma_3d_mc(a + 40960 + kk * 2048, &tm.wv, bar, cm + 48, ks * 64 + kk * 16, 2);
  };
  if (warp == 0 && elect()) {
    mbar_expect_tx(bar_half, 32768);
    tma_3d(sb + 2 * SLOT, &tm.x, bar_half, 0, P * 128, rank);
    mbar_expect_tx(bar_full + 16, 16384);
  }
  asm volatile("barrier.cluster.wait.aligned;" ::: "memory");
  if (warp == 0) {
    if (elect()) {
      uint32_t bar = bar_half;
#pragma unroll 1
      for (int kk = rank; kk < 4; kk += 2) { load_w(0, sb + 2 * SLOT, bar, kk); bar = bar_full + 16; }
    }
    asm volatile("bar.arrive 4, 64;" ::: "memory");
  }

  if (warp >= 8) {
    asm volatile("setmaxnreg.dec.sync.aligned.u32 %0;" :: "n"(REG_P));
#define TS_T 0
    if (warp == 8) {
      TS(8);
      bar_sync(4, 64);
      if (elect()) {
        TS(10);
#pragma unroll 1
        for (int it = 1; it < 10; it++) {
          const int s = (it + 2) & 3, ks = ks_of(it);
          const uint32_t full = bar_full + 8 * s, a = sb + s * SLOT;
          uint32_t bar = it < NSPLIT ? bar_half + 8 * it : full;
          if (it >= 4) mbar_wait(full + 32, ((it >> 2) - 1) & 1);
          if (it >= 2 && it < THR_END) mbar_wait(bar_full + 8 * (it & 3), 0);
          if (it < NSPLIT) mbar_expect_tx(bar, 32768);
          mbar_expect_tx(full, it < NSPLIT ? 16384 : SLOT);
          tma_3d(a, &tm.x, bar, ks * 64, P * 128, rank);
#pragma unroll 1
          for (int kk = rank; kk < 4; kk += 2) { load_w(ks, a, bar, kk); bar = full; }
          TS(12 + it);
          if ((it >> 1) == 2) {
            mbar_wait(bar_rst, 0);
            asm volatile("cp.async.bulk.global.shared::cta.bulk_group [%0], [%1], %2;\ncp.async.bulk.commit_group;"
                         :: "l"(it == 4 ? (uint4*)(g_own + cid) : (uint4*)&g_x + cid * GLOB_PER_CTA), "r"(sb + OFF_CS), "r"(it == 4 ? (int)sizeof(Own) : GLOB_PER_CTA * 16) : "memory");
          }
          if (it == 6) { asm volatile("cp.async.bulk.wait_group 0;" ::: "memory"); mbar_arrive(bar_tag); }
        }
        mbar_expect_tx(bar_ffn, ffn1 ? 81920 : 24576);
        int fjn = 0;
#pragma unroll 1
        for (int it = 9; it < 17; it++) {
          if (it >= 13) { mbar_wait(bar_oc + 8 * (it - 13), 0); mbar_wait(bar_oc + 56 + 8 * (it - 13), 0); }
          else if (it >= 10) {
            const uint32_t full = bar_full + 8 * (it - 10);
            const int g0 = 3 * (it - 10), g1 = min(g0 + 3, 8);
            mbar_wait(full + 32, it < 12);
            mbar_expect_tx(full, (g1 - g0) * 12800);
#pragma unroll 1
            for (int gp = g0 + ((g0 ^ rank) & 1); gp < g1; gp += 2) {
              tma_3d_mc(sb + gp * 15360, &tm.wo, full, 0, gp * 80, g * 2);
              tma_3d_mc(sb + gp * 15360 + 10240, &tm.wor, full, 512 + g * 16, gp * 80, 0);
            }
          }
          const int j1 = ffn1 ? (it >= 13 ? 2 * it - 22 : min(it - 8, 3)) : (it >= 13 ? 12 : min((it - 8) * F_PER, F_MAX));
#pragma unroll 1
          for (; fjn < j1; fjn++) {
            const int j = fjn < 3 ? fjn + 7 : fjn - 3;
            if (ffn1) tma_3d(sb + (j < 7 ? 0 : OFF_W2 - 57344) + j * 8192, j < 5 ? &tm.gate : &tm.up, bar_ffn, fj * 32, (j < 5 ? j : j - 5) * 128, 0);
            else tma_3d(sb + OFF_W2 + fjn * 2048, &tm.down, bar_ffn, fj * 8, fjn * 128, 0);
          }
        }
        TS(11);
      }
#undef TS_T
#define TS_T 64
    } else if (warp >= 12) {
      const int l7 = lane & 7, j = warp - 12, ch = min((P >> 1) * 4 + rank * 2 + (j >> 1), 14);
      const uint32_t sxo = ((g & 3) * 32 + j * 8 + l7) * 128 + (((lane >> 3) ^ l7) * 16);
      const uint32_t swo = ch < 12 ? 16384 + (lane >> 4) * 6144 + (ch >> 2) * 2048 + (lane & 15) * 128 + ((((ch & 3) * 2 + (j & 1)) ^ l7) * 16)
                                   : 41472 + (lane >> 4) * 2048 + (ch - 12) * 512 + (lane & 15) * 32 + (((j & 1) ^ (l7 >> 2)) * 16);
      float ps = 0.f, pq = 0.f, pq1 = 0.f, pc = 0.f;
      uint32_t tag = 0;
      char* const pp = hold((lane & 1) ? (char*)&g_own[cid].cs[j * 8 + (lane >> 2)] : (char*)&g_own[cid].st1[j * 8 + (lane >> 2)]);
#pragma unroll 1
      for (int it = 1 - ord; it < 6; it = max(it + 1, 2)) {
        const int sl = (it + 2) & 3;
        if (it == 5) { mbar_wait(bar_tag, 0); tag = __float_as_uint(lds32f(sb + OFF_WR + 324)); }
        if (it < NSPLIT) mbar_wait(bar_half + 8 * it, 0);
        mbar_wait(bar_full + 8 * sl, (it >> 2) & 1);
        TS(it);
        const uint32_t a = sb + sl * SLOT;
        const uint4 v0 = ldsm4(a + sxo), v1 = ldsm4((a + sxo) ^ 64), w0 = ldsm4t(a + swo), w1 = ldsm4t(a + swo + (ch < 12 ? 12288 : 4096));
        if (lane + (int)((v0.x & v1.x & w0.x & w1.x) == 0x7fc17fc1u && (v0.x | v1.x) == 0u) < 2) mbar_arrive_cta(bar_empty + 8 * sl, lane);
        const uint32_t vv[8] = {v0.x, v0.y, v0.z, v0.w, v1.x, v1.y, v1.z, v1.w}, ww[8] = {w0.x, w0.y, w0.z, w0.w, w1.x, w1.y, w1.z, w1.w};
#pragma unroll
        for (int i = 0; i < 8; i++) {
          const float d = bf_lo(vv[i]), e = bf_hi(vv[i]);
          ps += d + e; pq = fmaf(d, d, pq); pq1 = fmaf(e, e, pq1); pc += bf_lo(ww[i]) + bf_hi(ww[i]);
        }
      }
      pq += pq1;
      ps += shx(ps, 1); pq += shx(pq, 1); pc += shx(pc, 1);
      ps += shx(ps, 2); pq += shx(pq, 2); pc += shx(pc, 2);
      if ((lane & 3) == 0) stg_pkt(pp, __float_as_uint(ps), __float_as_uint(pq), tag, 0u);
      if ((lane & 3) == 1) stg_rlx64(pp, __float_as_uint(pc), tag);
      asm volatile("bar.arrive 2, 192;" ::: "memory");
      if (warp == 12) {
        const uint4* const hp = hold(&g_own[max(cid - 16, 0)].halo[0][lane]);
        mbar_wait(bar_aux, 0);
        mbar_wait(bar_go, 0);
        uint4 v[5] = {};
        int guard = SPIN_MAX;
        if (P > 0) {
          do {
#pragma unroll
            for (int i = 0; i < 5; i++) v[i] = ldg_pkt(hp + 32 * i);
          } while (anyw(v[0].x == SENT || v[1].x == SENT || v[2].x == SENT || v[3].x == SENT || v[4].x == SENT) && --guard > 0);
        }
#pragma unroll
        for (int i = 0; i < 5; i++) stsm4(sb + OFF_O + 10240 + i * 512 + lane * 16, v[i].x, v[i].y, v[i].z, v[i].w);
        mbar_arrive(bar_kv);
      }
#undef TS_T
#define TS_T 32
    } else if (warp < 11) {
      const int l7 = lane & 7, hk = lane >> 4;
      if (warp == 10 && elect()) {
#pragma unroll 1
        for (int i = 0; i < 36; i++) mbar_init(bar_o + 8 * i, i < 14 || i == 30 ? 1 : i < 34 ? 4 : 128);
      }
      mbar_wait(bar_tag, 0);
      const uint32_t tag = __float_as_uint(lds32f(sb + OFF_WR + 324));
      bar_sync(2, 192);
      TS(0);
      int guard = SPIN_MAX;
      if (warp == 9) {
        const uint4* sp = &g_own[mt * 8].st1[lane];
        const uint4* hp = &g_own[max(mt - 2, 0) * 8 + 3].st1[24 + l7];
        uint4 a[5], b[5];
        bool bad;
        do {
          __nanosleep(AUX_NS);
          bad = false;
#pragma unroll
          for (int i = 0; i < 5; i++) {
            const uint4* q = i < 4 ? sp + i * (sizeof(Own) / 16) : hp;
            a[i] = ldg_pkt(q); b[i] = ldg_pkt(q + 4 * sizeof(Own) / 16);
          }
#pragma unroll
          for (int i = 0; i < 5; i++) bad |= a[i].z != tag || b[i].z != tag;
        } while (anyw(bad) && --guard);
        TS(1);
#pragma unroll
        for (int i = 0; i < 5; i++) {
          const float m = (__uint_as_float(a[i].x) + __uint_as_float(b[i].x)) * (1.f / 640.f);
          const float rs = rsq(fmaxf(fmaf(-m, m, (__uint_as_float(a[i].y) + __uint_as_float(b[i].y)) * (1.f / 640.f)), 0.f) + 1e-5f);
          ((float*)(smem + OFF_RS))[i < 4 ? 8 + lane + 32 * i : l7] = rs;
          const uint32_t mh = pack_bf16(-m, -m);
          const float ml = -m - bf_lo(mh);
          if (i < 4) ((uint2*)(smem + OFF_MN))[lane + 32 * i] = make_uint2(mh, pack_bf16(ml, ml));
        }
      } else {
        const uint4* cp = (const uint4*)g_own[hk * 8 + g].cs + (lane & 15);
        uint4 a[4], b[4];
        bool bad;
        do {
          __nanosleep(AUX_NS);
          bad = false;
#pragma unroll
          for (int i = 0; i < 4; i++) { a[i] = ldg_pkt(cp + i * 32 * sizeof(Own) / 16); b[i] = ldg_pkt(cp + (i * 32 + 16) * sizeof(Own) / 16); }
#pragma unroll
          for (int i = 0; i < 4; i++) bad |= a[i].y != tag || a[i].w != tag || b[i].y != tag || b[i].w != tag;
        } while (anyw(bad) && --guard);
#pragma unroll
        for (int i = 0; i < 4; i++)
          if (i < 3 || lane < 24) {
            const float c0 = __uint_as_float(a[i].x) + __uint_as_float(b[i].x), c1 = __uint_as_float(a[i].z) + __uint_as_float(b[i].z);
            const uint32_t hi = pack_bf16(c0, c1), w0 = pack_bf16(c0, c0 - bf_lo(hi)), w1 = pack_bf16(c1, c1 - bf_hi(hi));
            uint4* const d = (uint4*)(smem + OFF_CS) + 2 * (lane + 32 * i);
            d[0] = make_uint4(w0, w0, 0, 0); d[1] = make_uint4(w1, w1, 0, 0);
          }
        asm volatile("fence.proxy.async.shared::cta;" ::: "memory");
      }
      mbar_arrive(bar_aux);
      TS(2);
      const int fo = warp - 9, wq = fo ? 1 - LEAD : LEAD;
      const uint4* const fp = hold(g_own[mt * 8 + wq * 4].cnt);
      const char* src = hold((const char*)g_o[mt * 2 + wq]);
      if (elect()) {
        const uint32_t bo = bar_o + fo * 56;
#pragma unroll
        for (int i = 0; i < 7; i++) mbar_expect_tx(bo + 8 * i, 10240);
        uint32_t cv = 0, need = 4;
        mbar_wait(OV == 3 ? bar_st + 8 * fo : bar_go + 8 + 8 * fo, 0);
        uint32_t dst = sb + OFF_O + 20480;
#pragma unroll OUNR
        for (int i = 0; i < 7; i++) {
          if (i == g) { src += 10240; need <<= 4; }
          if (!(cv & need)) {
            do { cv = ldg_rlx32(fp); } while (!(cv & need) && --guard > 0);
            asm volatile("fence.proxy.async.global;" ::: "memory");
          }
          if (fo || i == 5 || (OV == 2 && i == 4)) mbar_wait(fo ? bar_oc + 8 * i : i == 4 ? bar_st : bar_st + 8, 0);
          if (i == 0) TS(6);
          asm volatile("cp.async.bulk.shared::cluster.global.mbarrier::complete_tx::bytes [%0], [%1], 10240, [%2];" :: "r"(dst), "l"(src), "r"(bo + 8 * i) : "memory");
          src += 10240; need <<= 4;
          dst += i == 4 ? -61440 : 10240;
        }
      }
#undef TS_T
#define TS_T 96
    } else {
      if ((sb & 0x3FFFF) != D0 * 16) __trap();
#pragma unroll 1
      for (int i = lane; i < 232; i += 32) { const uint32_t f = i < 208 ? SENT : 0u; ((uint4*)(smem + OFF_CS))[i] = make_uint4(f, f, f, f); }
      asm volatile("fence.proxy.async.shared::cta;" ::: "memory");
      if (elect()) mbar_arrive(bar_rst);
      mbar_wait(bar_full + 8 * ((HK_IT + 2) & 3), 0);
      TS(4);
      const uint32_t epoch = ldg_rlx32(g_epoch + cid) + 1;
      uint32_t wv[10];
#pragma unroll
      for (int i = 0; i < 10; i++) wv[i] = __ldg((const uint32_t*)w_r + lane + 32 * i);
      float s = 0.f;
#pragma unroll
      for (int i = 0; i < 10; i++) {
        s += bf_lo(wv[i]) + bf_hi(wv[i]);
        const unsigned u = i < 8 ? lane + 32 * (i - g) : lane + 32 * (i - 7) - g * 8;
        if (i < 8 ? u < 32u : u - 32u < 8u) *(float2*)(smem + OFF_WR + ((u & 3) * 10 + (u >> 2)) * 8) = make_float2(bf_lo(wv[i]), bf_hi(wv[i]));
      }
#pragma unroll
      for (int m = 1; m < 32; m <<= 1) s += shx(s, m);
      *(float2*)(smem + OFF_WR + 320) = make_float2(s, __uint_as_float(epoch * 0x9E3779B8u));
      g_epoch[cid] = epoch;
      TS(3);
      if (elect()) mbar_arrive(bar_tag);
      TS(5);
#pragma unroll 1
      for (int i = 0; i < PFW_N; i++) {
        const int m = (i + 2) >> 2, n = m == 0 ? 50 : 120, t = (m == 0 ? i : (i + 2) & 3) * 32 + lane;
        const char* b = (const char*)(m == 0 ? wo : m == 1 ? w_up : m == 2 ? w_down : w_gate);
        if (t < n) pf_l2(b + (bid * n + t) * 128);
        __nanosleep(PFW_NS);
      }
      const uint4* const kp = hold(g_own[1].cnt);
      const uint4* const cb = hold(&g_x.cand[0][lane >> 2][lane & 3]);
      bar_sync(3, 64);
      uint4 k;
      uint32_t have = SENT;
      int guard = SPIN_MAX;
      while (true) {
        k = ldg_pkt(kp);
        if (ffn1) {
          while (k.x != have && --guard > 0) {
            const uint32_t tk = 2047u - (k.x & 2047u), want = k.x;
            const uint4* q = cb + ((tk >> 8) * 16 + (tk & 1) * 8 + ((tk >> 5) & 7)) * 192;
            const uint4 c0 = ldg_pkt(q), c1 = ldg_pkt(q + 4); const uint2 c2 = ldg_rlx64(q + 8);
            k = ldg_pkt(kp);
            *(uint4*)(smem + OFF_HN + lane * 16) = c0; *(uint4*)(smem + OFF_HN + 512 + lane * 16) = c1; *(uint2*)(smem + OFF_HN + 1024 + lane * 16) = c2;
            have = anyw(c0.x == SENT || c1.x == SENT || c2.x == SENT) ? SENT : want;
          }
        } else if (KEY_NS && k.z != 128u) __nanosleep(KEY_NS);
        if (k.z == 128u || --guard <= 0) break;
      }
      *(uint2*)(smem + OFF_WR + 336) = make_uint2(k.x, k.y);
      mbar_arrive(bar_win);
      TS(7);
    }
#undef TS_T
  } else {
#define TS_T 0
    asm volatile("setmaxnreg.inc.sync.aligned.u32 %0;" :: "n"(REG_C));
    const int wg = warp >> 2, w4 = warp & 3, r = lane >> 2, c = lane & 3;
    float acc[120];
    uint4 xr[5] = {};
    const uint32_t xa = pin(sb + (warp * 16 + (lane & 15)) * 128 + ((lane >> 4) ^ (lane & 7)) * 16);
    const uint32_t zero = __shfl_sync(0xffffffffu, (uint32_t)(uintptr_t)x & 8u, 0);
    const int fol = wg != LEAD;
    const bool first = (P == 0) && (warp == 0);
    const uint32_t kvs = holdu(sb + OFF_O + fol * 10240 + w4 * 2560 + lane * 16);
    const uint32_t kvd = warp == 3 ? kvs - 17920 : kvs + 2560;
    uint4* const kvg = hold(&g_own[cid].halo[0][lane]);
    uint4* const odst = hold(&g_o[mt * 2 + wg][g][w4 * 160]);
    uint4* const ocnt = hold(g_own[mt * 8 + wg * 4].cnt + (lane & zero));
    const uint32_t oinc = holdu((1u << (4 * g)) + (lane & zero));
    const bool in0 = 2 * c <= r, in1 = 2 * c + 1 <= r;
    const uint32_t mL = holdu((in0 ? 0xffffu : 0u) | (in1 ? 0xffff0000u : 0u));
    const float bias0 = __uint_as_float(holdu(first && !in0 ? 0xff800000u : 0u)), bias1 = __uint_as_float(holdu(first && !in1 ? 0xff800000u : 0u));
    const uint32_t stb = sb + OFF_RS + warp * 64, kb0 = holdu(stb + (2 * c + (in0 ? 8 : 0)) * 4), kb1 = holdu(stb + (2 * c + 1 + (in1 ? 8 : 0)) * 4);
    const uint32_t os = sb + OFF_O + (fol ? 0 : 61440) + w4 * 2560, oa = holdu(os + ((lane >> 3) & 1) * 1280 + (lane >> 4) * 128 + (lane & 7) * 16);
    float rlo, rhi, scl0, scl1, sch0, sch1;
    uint32_t m0 = 0, m1 = 0, m2 = 0, m3 = 0;
    const uint32_t mna = pin(sb + OFF_MN + (warp * 16 + r) * 8 + c * 4);
    const int itx = ord == 0 || g < 2 ? g : g < 6 ? g + 4 : g - 4, ity = (ord ? 4 : 8) + (g >> 2);
    uint32_t rel;
    asm volatile("mapa.shared::cluster.u32 %0, %1, %2;" : "=r"(rel) : "r"(bar_empty), "r"(tid & 1));
    const uint32_t xa1 = pin(xa ^ 32), xa2 = pin(xa ^ 64), xa3 = pin(xa ^ 96), xb = pin(xa ^ ((g & 3) * 32));
    const uint32_t da0 = wg * 512;
    const bool rel2 = lane < 2, rel6 = lane < 2 + 2 * (warp & 1);
    mbar_wait(bar_half, 0);
    TS(13);
    wgmma_fence();
#pragma unroll
    for (int it = 0; it < 10; it++) {
      const int s = (it + 2) & 3;
#pragma unroll
      for (int kk = 0; kk < 4; kk++) {
        if (kk == 2 && it > 0) {
          wgmma_commit();
          wgmma_wait<1>();
          const uint32_t ra = ((xr[0].x ^ xr[1].x ^ xr[2].x ^ xr[3].x ^ xr[4].x) & zero) | rel;
          if (it == 1 ? (ord ? rel2 : rel6) : it == 2 ? (ord ? rel6 : rel2) : it < 7 ? rel2 : rel6)
            asm volatile("mbarrier.arrive.shared::cluster.b64 _, [%0];" :: "r"(ra + 8 * ((it + 1) & 3)) : "memory");
        }
        if (kk == 2) {
          ldsm4_if(xr[0], xa, s * SLOT, it == itx); ldsm4_if(xr[1], xa1, s * SLOT, it == itx);
          ldsm4_if(xr[2], xa2, s * SLOT, it == itx); ldsm4_if(xr[3], xa3, s * SLOT, it == itx);
          if ((it & 6) == 4 || it >= 8) ldsm4_if(xr[4], xb, s * SLOT, it == ity);
        }
        if (kk == AK && it == 9) {
          mbar_wait(bar_aux, 0);
          TS(3);
          if (c < 2) {
            m0 = __float_as_uint(lds32f(mna)); m1 = __float_as_uint(lds32f(mna + 64)); m2 = __float_as_uint(lds32f(mna + zero)); m3 = __float_as_uint(lds32f(mna + zero + 64));
          }
          const float qs = 0.22360679774997896f * 1.4426950408889634f;
          rlo = lds32f(stb + (8 + r) * 4); rhi = lds32f(stb + (16 + r) * 4);
          scl0 = lds32f(kb0) * (rlo * qs); scl1 = lds32f(kb1) * (rlo * qs); sch0 = lds32f(kb0 + 32) * (rhi * qs); sch1 = lds32f(kb1 + 32) * (rhi * qs);
          if (!fol) bar_sync(11, 256);
        }
        if (it * 4 + kk == 40 - LAG && fol) {
          asm volatile("bar.arrive 11, 256;" ::: "memory");
          bar_sync(10, 256);
        }
        if (kk == 2 && it < NSPLIT) mbar_wait(bar_full + 8 * s, 0);
        const uint64_t da = mk64(da0 + (D0 + s * (SLOT >> 4) + kk * 2 + (1 << 16)), 0x40000040u);
        wgmma_n64hi_ss(acc, da, mk64(D0 + s * (SLOT >> 4) + 2560 + kk * 128 + (32 << 16), 0xC0000010u), (it | kk) != 0);
        wgmma_n176lo_ss(acc, da, mk64(D0 + s * (SLOT >> 4) + 1024 + ((kk + 1) & 3) * 384 + (128 << 16), 0x40000040u), (it | kk) != 0);
      }
      wgmma_commit();
      if (it < 9) {
        if (it + 1 < NSPLIT) mbar_wait(bar_half + 8 * (it + 1), 0);
        else mbar_wait(bar_full + 8 * ((it + 3) & 3), ((it + 1) >> 2) & 1);
        if (it < 8) TS(14 + it);
      }
    }
    {
      const uint64_t dc = make_desc(D0 * 16 + OFF_CS, 0, 128, 0);
      wgmma_fence();
      wgmma_n64hi_rk(acc, m0, m1, 0u, 0u, dc + 176, 1);
      wgmma_n176lo_rk(acc, m2, m3, 0u, 0u, dc, 1);
      wgmma_commit();
      if (!fol) asm volatile("bar.arrive 10, 256;" ::: "memory");
    }
    wgmma_wait<0>();
#pragma unroll
    for (int i = 0; i < 120; i++) asm volatile("" : "+f"(acc[i]) :: "memory");
    if (fol && lane == 0) mbar_arrive(bar_go);
    TS(2);
    uint32_t Qlo[10], Qhi[10], Klo[10], Khi[10], Vlo[10], Vhi[10];
#define CONV_HI(ROT) _Pragma("unroll") for (int t = 0; t < 10; t++) { \
      const int k = KT((t + ROT) % 10), v = VT((t + ROT) % 10); \
      Khi[t] = pack_bf16(acc[4 * k + 2], acc[4 * k + 3]); \
      Vhi[t] = pack_bf16(acc[4 * v + 2] * rhi, acc[4 * v + 3] * rhi); }
    if (godd) { CONV_HI(8) } else { CONV_HI(0) }
    if (warp == 7) {
      stg_pkt(kvg, Khi[0], Khi[1], Khi[3], Khi[4]); stg_pkt(kvg + 32, Khi[5], Khi[6], Khi[8], Khi[9]); stg_pkt(kvg + 64, Khi[2], Khi[7], Vhi[0], Vhi[1]);
      stg_pkt(kvg + 96, Vhi[2], Vhi[3], Vhi[4], Vhi[5]); stg_pkt(kvg + 128, Vhi[6], Vhi[7], Vhi[8], Vhi[9]);
    } else {
      stsm4(kvd, Khi[0], Khi[1], Khi[3], Khi[4]); stsm4(kvd + 512, Khi[5], Khi[6], Khi[8], Khi[9]); stsm4(kvd + 1024, Khi[2], Khi[7], Vhi[0], Vhi[1]);
      stsm4(kvd + 1536, Vhi[2], Vhi[3], Vhi[4], Vhi[5]); stsm4(kvd + 2048, Vhi[6], Vhi[7], Vhi[8], Vhi[9]);
      mbar_arrive(bar_kv + ((warp + 1) >> 2) * 8);
    }
#define CONV_LO(ROT) _Pragma("unroll") for (int t = 0; t < 10; t++) { \
      const int q = QT((t + ROT) % 10), k = KT((t + ROT) % 10), v = VT((t + ROT) % 10); \
      Vhi[t] = movm(Vhi[t]); \
      Klo[t] = pack_bf16(acc[4 * k], acc[4 * k + 1]); \
      Vlo[t] = movm(pack_bf16(acc[4 * v] * rlo, acc[4 * v + 1] * rlo)); \
      Qlo[t] = pack_bf16(acc[4 * q], acc[4 * q + 1]); \
      Qhi[t] = pack_bf16(acc[4 * q + 2], acc[4 * q + 3]); }
    if (godd) { CONV_LO(8) } else { CONV_LO(0) }
    const int slot = mt * 8 + warp;
    int guard = SPIN_MAX;
    const bool cA = c < 2, nA = r < 4;
    TS(0);
    mbar_wait(bar_go + fol * 8, 0);
    TS(23);
    uint32_t qe[4][2];
    float sl0[4], sl1[4], th0[4], th1[4];
#pragma unroll
    for (int hd = 0; hd < 4; hd++) {
      const int ta = 5 * (hd >> 1) + 3 * (hd & 1), ts = 5 * (hd >> 1) + 2;
      const bool mine = (hd & 1) ? !cA : cA;
      qe[hd][0] = mine ? Qlo[ts] : 0u; qe[hd][1] = mine ? Qhi[ts] : 0u;
      float sl[4], sh[4];
      mma_k24(sl, Qlo[ta], Qhi[ta], Qlo[ta + 1], Qhi[ta + 1], Klo[ta], Klo[ta + 1], qe[hd][0], qe[hd][1], Klo[ts]);
      mma_k24(sh, Qlo[ta], Qhi[ta], Qlo[ta + 1], Qhi[ta + 1], Khi[ta], Khi[ta + 1], qe[hd][0], qe[hd][1], Khi[ts]);
      th0[hd] = (in0 ? sh[2] : sl[2]) * sch0; th1[hd] = (in1 ? sh[3] : sl[3]) * sch1;
      float mh = fmaxf(th0[hd], th1[hd]);
      mh = fmaxf(mh, shx(mh, 1)); mh = fmaxf(mh, shx(mh, 2));
      th0[hd] -= mh; th1[hd] -= mh;
      sl0[hd] = sl[0]; sl1[hd] = sl[1];
    }
    mbar_wait(bar_kv + wg * 8, 0);
    TS(4);
    const uint4 k0 = ldsm4(kvs), k1 = ldsm4(kvs + 512), k2 = ldsm4(kvs + 1024), v0 = ldsm4t(kvs + 1024), v1 = ldsm4t(kvs + 1536), v2 = ldsm4t(kvs + 2048);
    const uint32_t Kp[10] = {k0.x, k0.y, k2.x, k0.z, k0.w, k1.x, k1.y, k2.y, k1.z, k1.w};
    const uint32_t Vp[10] = {v0.z, v0.w, v1.x, v1.y, v1.z, v1.w, v2.x, v2.y, v2.z, v2.w};
    const uint32_t ONES = 0x3f803f80u;
    uint32_t of[20];
#pragma unroll
    for (int hp = 0; hp < 2; hp++) {
      float o[6][4];
#pragma unroll
      for (int hh = 0; hh < 2; hh++) {
        const int hd = 2 * hp + hh, ta = 5 * hp + 3 * hh, ts = 5 * hp + 2;
        float sp[4];
        mma_k24(sp, Qlo[ta], Qhi[ta], Qlo[ta + 1], Qhi[ta + 1], Kp[ta], Kp[ta + 1], qe[hd][0], qe[hd][1], Kp[ts]);
        const float tl0 = fmaf(in0 ? sl0[hd] : sp[0], scl0, bias0), tl1 = fmaf(in1 ? sl1[hd] : sp[1], scl1, bias1);
        float ml = fmaxf(tl0, tl1);
        ml = fmaxf(ml, shx(ml, 1)); ml = fmaxf(ml, shx(ml, 2));
        if (HOLD == 1 && hd == 3 && !fol && lane == 0) mbar_arrive(bar_go + 8);
        const uint32_t Pl = pack_bf16(ex2(tl0 - ml), ex2(tl1 - ml)), Ph = pack_bf16(ex2(th0[hd]), ex2(th1[hd]));
        const uint32_t a0 = Pl & mL, a1 = Ph & ~mL, a3 = Ph & mL, ap = Pl & ~mL;
        const uint32_t z0 = Ph & zero, z1 = ~Ph & zero;
        const bool vm = hh == 0 ? nA : !nA;
        mma_k24(o[3 * hh], a0, a1, z0, a3, Vlo[ta], Vhi[ta], ap, z1, Vp[ta]);
        mma_k24(o[3 * hh + 1], a0, a1, z0, a3, Vlo[ta + 1], Vhi[ta + 1], ap, z1, Vp[ta + 1]);
        mma_k24(o[3 * hh + 2], a0, a1, z0, a3, vm ? Vlo[ts] : ONES, vm ? Vhi[ts] : ONES, ap, z1, vm ? Vp[ts] : ONES);
      }
      const float il = rcp(cA ? o[5][0] : o[2][0]), ih = rcp(cA ? o[5][2] : o[2][2]);
      const float jl = shx(il, 2), jh = shx(ih, 2);
      const float al = cA ? jl : il, ah = cA ? jh : ih, bl = cA ? il : jl, bh = cA ? ih : jh;
      const int t0 = 5 * hp;
      of[2 * t0]     = pack_bf16(o[0][0] * al, o[0][1] * al); of[2 * t0 + 1] = pack_bf16(o[0][2] * ah, o[0][3] * ah);
      of[2 * t0 + 2] = pack_bf16(o[1][0] * al, o[1][1] * al); of[2 * t0 + 3] = pack_bf16(o[1][2] * ah, o[1][3] * ah);
      of[2 * t0 + 4] = pack_bf16((cA ? o[2][0] : o[5][0]) * jl, (cA ? o[2][1] : o[5][1]) * jl);
      of[2 * t0 + 5] = pack_bf16((cA ? o[2][2] : o[5][2]) * jh, (cA ? o[2][3] : o[5][3]) * jh);
      of[2 * t0 + 6] = pack_bf16(o[3][0] * bl, o[3][1] * bl); of[2 * t0 + 7] = pack_bf16(o[3][2] * bh, o[3][3] * bh);
      of[2 * t0 + 8] = pack_bf16(o[4][0] * bl, o[4][1] * bl); of[2 * t0 + 9] = pack_bf16(o[4][2] * bh, o[4][3] * bh);
    }
    {
#pragma unroll
      for (int s = 0; s < 5; s++) {
        stsm4(oa + s * 256, of[4 * s], of[4 * s + 1], of[4 * s + 2], of[4 * s + 3]);
        if (s == 0 && (fol || HOLD == 2) && lane == 0) mbar_arrive(bar_go + 8 + 8 * fol);
      }
      asm volatile("fence.proxy.async.shared::cta;" ::: "memory");
      __syncwarp();
      asm volatile("{\n.reg .pred q;\nelect.sync _|q, 0xffffffff;\n@q cp.async.bulk.global.shared::cta.bulk_group [%0], [%1], 2560;\ncp.async.bulk.commit_group;\n}\n" :: "l"(odst), "r"(os) : "memory");
    }
    TS(5);
    auto publish = [&]() {
      asm volatile("cp.async.bulk.wait_group 0;" ::: "memory");
      __syncwarp();
      if (lane == 0) {
        asm volatile("red.relaxed.gpu.global.add.u32 [%0], %1;" :: "l"(ocnt), "r"(oinc) : "memory");
        mbar_arrive(bar_st + 8 * fol);
      }
      TS(22);
    };
    if (!(OWN1 && fol)) publish();
    float h[40];
#pragma unroll
    for (int s = 0; s < 5; s++) {
      const uint4 v = xr[s];
      h[8 * s] = bf_lo(v.x); h[8 * s + 1] = bf_hi(v.x); h[8 * s + 2] = bf_lo(v.y); h[8 * s + 3] = bf_hi(v.y);
      h[8 * s + 4] = bf_lo(v.z); h[8 * s + 5] = bf_hi(v.z); h[8 * s + 6] = bf_lo(v.w); h[8 * s + 7] = bf_hi(v.w);
    }
    mbar_wait(bar_full, 0); mbar_wait(bar_full + 8, 0); mbar_wait(bar_full + 16, 1);
    mbar_wait(bar_go + 16, 0);
    const uint64_t dwo = make_desc(D0 * 16, 5120, 512, 2);
    wgmma_fence();
#pragma unroll
    for (int s = 0; s < 5; s++) wgmma_n80_rs(h, of[4 * s], of[4 * s + 1], of[4 * s + 2], of[4 * s + 3], dwo + g * 960 + s * 64, 1);
    wgmma_commit();
    if (OWN1 && fol) publish();
    TS(6);
    const bool odd = c & 1;
    uint4* const sp = hold(&g_own[slot].st2[r + (odd ? 8 : 0)]);
    uint4* const cdp = hold(&g_x.cand[slot][g][lane & zero]);
    uint4* const kcp = hold(g_own[1].cnt + (lane & zero));
    float wr[20];
#pragma unroll
    for (int j = 0; j < 5; j++) {
      const uint4 v = lds128(sb + OFF_WR + c * 80 + j * 16);
      wr[4 * j] = __uint_as_float(v.x); wr[4 * j + 1] = __uint_as_float(v.y); wr[4 * j + 2] = __uint_as_float(v.z); wr[4 * j + 3] = __uint_as_float(v.w);
    }
    const float wsum = lds32f(sb + OFF_WR + 320);
    const uint32_t bo = bar_o + fol * 56;
    if (PRIO < 7 && fol) mbar_wait(bar_oc + 8 * PRIO, 0);
#pragma unroll
    for (int i = 0; i < 7; i++) {
      mbar_wait(bo + 8 * i, 0);
      if (i == 0) TS(1);
      const uint32_t da = D0 + OFF_O / 16 + (8 << 16) + ((i + 2) % 7) * 640, db = D0 + (320 << 16) + (i >= g ? i + 1 : i) * 960;
      wgmma_fence();
#pragma unroll
      for (int s = 0; s < 5; s++) wgmma_n80_ss(h, mk64(da + s * 16, 80u), mk64(db + s * 64, 0x80000020u), 1);
      wgmma_commit();
      wgmma_wait<1>();
      if (lane == 0 && i > 0) mbar_arrive(bo + 104 + 8 * i);
    }
    const int tok0 = P * 256 + 32 * warp + rank;
    wgmma_wait<0>();
#pragma unroll
    for (int i = 0; i < 40; i++) asm volatile("" : "+f"(h[i]) :: "memory");
    if (lane == 0) mbar_arrive(bo + 160);
    if (SPLITB) { asm volatile("{\n.reg .pred p;\nsetp.ne.u32 p, %0, 0;\n@p trap;\n}\n" :: "r"(zero) : "memory"); }
    TS(7);
    float mean, rstd, rr;
    bool pub;
    {
      float l1 = 0.f, l2 = 0.f, l3 = 0.f, h1 = 0.f, h2 = 0.f, h3 = 0.f;
#pragma unroll
      for (int j = 0; j < 10; j++) {
        l1 += h[4 * j] + h[4 * j + 1]; h1 += h[4 * j + 2] + h[4 * j + 3];
        l2 = fmaf(h[4 * j], h[4 * j], l2); l2 = fmaf(h[4 * j + 1], h[4 * j + 1], l2);
        h2 = fmaf(h[4 * j + 2], h[4 * j + 2], h2); h2 = fmaf(h[4 * j + 3], h[4 * j + 3], h2);
        l3 = fmaf(h[4 * j], wr[2 * j], l3); l3 = fmaf(h[4 * j + 1], wr[2 * j + 1], l3);
        h3 = fmaf(h[4 * j + 2], wr[2 * j], h3); h3 = fmaf(h[4 * j + 3], wr[2 * j + 1], h3);
      }
      float s1 = (odd ? h1 : l1) + shx(odd ? l1 : h1, 1), s2 = (odd ? h2 : l2) + shx(odd ? l2 : h2, 1), s3 = (odd ? h3 : l3) + shx(odd ? l3 : h3, 1);
      s1 += shx(s1, 2); s2 += shx(s2, 2); s3 += shx(s3, 2);
      uint4 p0;
      float o1 = 0.f, o2 = 0.f, o3 = 0.f, oc = 7.f;
      asm volatile("{\n.reg .pred q;\nsetp.lt.u32 q, %9, 2;\n@q atom.relaxed.gpu.global.add.v4.f32 {%0, %1, %2, %3}, [%4], {%5, %6, %7, %8};\n}\n"
                   : "+f"(o1), "+f"(o2), "+f"(o3), "+f"(oc) : "l"(sp), "f"(s1), "f"(s2), "f"(s3), "f"(1.f), "r"(c) : "memory");
      const uint32_t last = __ballot_sync(0xffffffffu, oc == 7.f);
      pub = last & 1;
      p0.x = __float_as_uint(o1 + s1); p0.y = __float_as_uint(o2 + s2); p0.z = __float_as_uint(o3 + s3);
      if (last != 0xffffffffu)
      do { p0 = ldg_pkt(sp); } while (anyw(p0.w != 0x41000000u) && --guard > 0);
      mean = __uint_as_float(p0.x) * (1.f / 640.f);
      rstd = rsq(fmaxf(fmaf(-mean, mean, __uint_as_float(p0.y) * (1.f / 640.f)), 0.f) + 1e-5f);
      rr = fmaf(-mean, wsum, __uint_as_float(p0.z)) * rstd;
    }
    TS(8);
    const int myrow = r + (odd ? 8 : 0);
    const uint32_t kk = cA ? ord_key(rr) : 0u, kmax = __reduce_max_sync(0xffffffffu, kk);
    if (pub) {
      if (kk == kmax) asm volatile("red.relaxed.gpu.global.max.u64 [%0], %1;" :: "l"(kcp), "l"(mk64(2047 - tok0 - 2 * myrow, kk)) : "memory");
      __syncwarp();
      if (lane == 0) asm volatile("red.relaxed.gpu.global.add.u32 [%0 + 8], 1;" :: "l"(kcp) : "memory");
    }
    const int crow = __reduce_min_sync(0xffffffffu, kk == kmax ? myrow : 16), L = (crow & 7) * 4 + (crow >> 3);
    if (warp == g) asm volatile("bar.arrive 3, 64;" ::: "memory");
    const uint32_t stg = sb + (fol ? OFF_O : g * 15360) + w4 * 2560;
    uint4 held;
    {
      const float nb = -mean * rstd;
      const float rl = __shfl_sync(0xffffffffu, rstd, lane & 28), rh = __shfl_sync(0xffffffffu, rstd, (lane & 28) + 1);
      const float bl = __shfl_sync(0xffffffffu, nb, lane & 28), bh = __shfl_sync(0xffffffffu, nb, (lane & 28) + 1), al = 1.f + rl, ah = 1.f + rh;
      if ((L >> 2) == r) {
        const bool chi = L & 1;
        const float rc = chi ? rh : rl, bc = chi ? bh : bl;
        uint32_t n[10];
#pragma unroll
        for (int j = 0; j < 10; j++) n[j] = pack_bf16(fmaf(chi ? h[4 * j + 2] : h[4 * j], rc, bc), fmaf(chi ? h[4 * j + 3] : h[4 * j + 1], rc, bc));
        uint4* d = cdp + c;
        stg_pkt(d, n[0], n[1], n[2], n[3]); stg_pkt(d + 4, n[4], n[5], n[6], n[7]); stg_rlx64(d + 8, n[8], n[9]);
      }
      mbar_wait(bar_oc + 56, 0);
      const uint32_t fa = stg + (lane & 15) * 160 + (lane >> 4) * 16;
#pragma unroll
      for (int s = 0; s < 5; s++)
        stsm4(fa + s * 32, pack_bf16(fmaf(h[8 * s], al, bl), fmaf(h[8 * s + 1], al, bl)), pack_bf16(fmaf(h[8 * s + 2], ah, bh), fmaf(h[8 * s + 3], ah, bh)),
              pack_bf16(fmaf(h[8 * s + 4], al, bl), fmaf(h[8 * s + 5], al, bl)), pack_bf16(fmaf(h[8 * s + 6], ah, bh), fmaf(h[8 * s + 7], ah, bh)));
      __syncwarp();
      held = lds128(stg + crow * 160 + min(lane, 9) * 16);
      if (lane < 10) stg_pkt(cdp + 12 + lane, held.x, held.y, held.z, held.w);
    }
    TS(9);
    mbar_wait(bar_ffn, 0);
    const uint32_t red = sb + OFF_RED;
    if (ffn1) {
      uint4 w1[4][5];
      {
        const int k = (lane & 7) + (lane >> 4) * 8;
        const uint32_t a1 = sb + k * 64, sw = ((lane >> 3) & 1) ^ ((lane >> 1) & 3);
#pragma unroll
        for (int s = 0; s < 5; s++)
#pragma unroll
          for (int u = 0; u < 4; u++)
            w1[u][s] = ldsm4t(a1 + (s < 4 ? warp * 4096 + s * 1024 : 32768 + warp * 1024) + (u >> 1) * (40960 + (s == 4 || warp >= 4 ? OFF_W2 - 57344 : 0)) + ((sw ^ (2 * (u & 1))) * 16));
      }
      uint32_t* const ap = hold(g_x.act + fj * 16 + (lane >> 1));
      mbar_wait(bar_win, 0);
      const uint32_t hp = sb + OFF_HN + (warp * 4 + c) * 16;
      const uint4 c0 = lds128(hp), c1 = lds128(hp + 512), c2 = lds128(hp + 1024);
      TS(10);
      float a[4][4];
#pragma unroll
      for (int u = 0; u < 4; u++) {
        a[u][0] = a[u][1] = a[u][2] = a[u][3] = 0.f;
        mma_acc(a[u], w1[u][0], c0.x, c0.y); mma_acc(a[u], w1[u][1], c0.z, c0.w); mma_acc(a[u], w1[u][2], c1.x, c1.y);
        mma_acc(a[u], w1[u][3], c1.z, c1.w); mma_acc(a[u], w1[u][4], c2.x, c2.y);
      }
      asm volatile("st.shared.v2.f32 [%0], {%1, %2};" :: "r"(red + (warp * 32 + c * 8 + r) * 8),
                   "f"(cA ? (odd ? a[0][2] : a[0][0]) : (odd ? a[1][2] : a[1][0])), "f"(cA ? (odd ? a[2][2] : a[2][0]) : (odd ? a[3][2] : a[3][0])) : "memory");
      bar_sync(1, 256);
      if (warp == 0) {
        float2 t[8];
#pragma unroll
        for (int i = 0; i < 8; i++) t[i] = lds64f(red + (i * 32 + lane) * 8);
        const float s = ((t[0].x + t[1].x) + (t[2].x + t[3].x)) + ((t[4].x + t[5].x) + (t[6].x + t[7].x));
        const float u = ((t[0].y + t[1].y) + (t[2].y + t[3].y)) + ((t[4].y + t[5].y) + (t[6].y + t[7].y));
        const float av = s * u * rcp(1.f + ex2(-1.4426950408889634f * s));
        const float an = shx(av, 1);
        if (!odd) stg_rlx32(ap, pack_bf16(av, an));
      }
      bar_sync(1, 256);
      TS(11);
    }
    char* const ob2 = (char*)(out + tok0 * 640 + g * 64);
    const int remo = 896 - 96 * g;
    {
      char* const q0 = ob2 + (lane >> 3) * 2560 + (lane & 7) * 16;
      const uint32_t s0 = stg + (lane >> 3) * 160 + (lane & 7) * 16;
#pragma unroll
      for (int s = 0; s < 4; s++) stg128_if(4 * s + (lane >> 3) != crow, q0 + s * 10240, lds128(s0 + s * 640));
      stg128_if((lane >> 1) != crow, ob2 + (lane >> 1) * 2560 + (lane & 1) * 16 + 128 + remo, lds128(stg + (lane >> 1) * 160 + (lane & 1) * 16 + 128));
    }
    mbar_wait(bar_win, 0);
    uint4 win = lds128(sb + OFF_WR + 336);
    win.z = win.y; win.y = 2047u - (win.x & 2047u); win.x = (win.y >> 8) * 16 + (win.y & 1) * 8 + ((win.y >> 5) & 7);
    stg128_if(win.x != slot && lane < 10, ob2 + crow * 2560 + lane * 16 + (lane < 8 ? 0 : remo), held);
    if (!ffn1) {
      TS(10);
      uint4 w2[6];
      const uint32_t a2 = sb + OFF_W2 + (warp * 192 + 8 * (((lane >> 3) & 1) * 4 + ((lane & 7) >> 1)) + 2 * (lane >> 4) + (lane & 1)) * 16;
#pragma unroll
      for (int s = 0; s < 6; s++) w2[s] = ldsm4t(a2 + (s >> 1) * 1024 + (s & 1) * 64);
      const uint4* p = (const uint4*)(g_x.act + warp * 96) + (r & 1) * 4 + c;
      const uint32_t* pb = (const uint32_t*)&g_x.cand[win.x][fj < 64 ? fj >> 3 : (fj - 64) >> 1][fj < 64 ? 12 + (fj & 7) : 20 + (fj & 1)] + c;
      uint32_t* const op = hold((uint32_t*)(out + win.y * 640 + fj * 8) + c);
      const float sg = shx(rcp(1.f + ex2(-1.4426950408889634f * __uint_as_float(win.z ^ ((uint32_t)((int32_t)~win.z >> 31) | 0x80000000u)))), 1);
      uint4 c0, c1, c2; uint32_t bw;
      if (ACT_NS) __nanosleep(ACT_NS);
      do {
        c0 = ldg_pkt(p); c1 = ldg_pkt(p + 8); c2 = ldg_pkt(p + 16); bw = ldg_rlx32(pb);
      } while (anyw(max(max(max(max(c0.x, c0.y), max(c0.z, c0.w)), max(max(c1.x, c1.y), max(c1.z, c1.w))), max(max(max(c2.x, c2.y), max(c2.z, c2.w)), bw)) == SENT) && --guard > 0);
      TS(11);
      float a[4] = {0.f, 0.f, 0.f, 0.f}, b[4] = {0.f, 0.f, 0.f, 0.f}, d[4] = {0.f, 0.f, 0.f, 0.f};
      mma_acc(a, w2[0], c0.x, c0.y); mma_acc(b, w2[2], c1.x, c1.y); mma_acc(d, w2[4], c2.x, c2.y);
      mma_acc(a, w2[1], c0.z, c0.w); mma_acc(b, w2[3], c1.z, c1.w); mma_acc(d, w2[5], c2.z, c2.w);
      if (c == 0) sts32f(red + (warp * 8 + r) * 4, ((a[0] + a[3]) + (b[0] + b[3])) + (d[0] + d[3]));
      bar_sync(1, 256);
      if (tid < 4) {
        float2 t[8];
#pragma unroll
        for (int i = 0; i < 8; i++) t[i] = lds64f(red + (i * 4 + tid) * 8);
        const float y0 = ((t[0].x + t[1].x) + (t[2].x + t[3].x)) + ((t[4].x + t[5].x) + (t[6].x + t[7].x));
        const float y1 = ((t[0].y + t[1].y) + (t[2].y + t[3].y)) + ((t[4].y + t[5].y) + (t[6].y + t[7].y));
        stg_rlx32(op, pack_bf16(fmaf(y0, sg, bf_lo(bw)), fmaf(y1, sg, bf_hi(bw))));
      }
    }
    TS(12);
#undef TS_T
  }
}

typedef CUresult (*EncodeFn)(CUtensorMap*, CUtensorMapDataType, cuuint32_t, void*, const cuuint64_t*, const cuuint64_t*, const cuuint32_t*,
                             const cuuint32_t*, CUtensorMapInterleave, CUtensorMapSwizzle, CUtensorMapL2promotion, CUtensorMapFloatOOBfill);

void make_map(EncodeFn enc, CUtensorMap* m, const void* base, const cuuint64_t* dims, const cuuint64_t* strides, const cuuint32_t* box,
              CUtensorMapSwizzle swz, int promo = PROMO) {
  const cuuint32_t es[3] = {1, 1, 1};
  enc(m, CU_TENSOR_MAP_DATA_TYPE_BFLOAT16, 3, (void*)base, dims, strides, box, es, CU_TENSOR_MAP_INTERLEAVE_NONE, swz,
      (CUtensorMapL2promotion)promo, CU_TENSOR_MAP_FLOAT_OOB_FILL_NONE);
}

}

extern "C" void kernel_launch(void* const* d_in, const int* in_sizes, int n_in, void* d_out, int out_size) {
  const __nv_bfloat16* x = (const __nv_bfloat16*)d_in[0];
  const __nv_bfloat16* wqkv = (const __nv_bfloat16*)d_in[1];
  const __nv_bfloat16* wo = (const __nv_bfloat16*)d_in[2];
  void* fn = nullptr;
  cudaDriverEntryPointQueryResult st;
  cudaGetDriverEntryPoint("cuTensorMapEncodeTiled", &fn, cudaEnableDefault, &st);
  EncodeFn enc = (EncodeFn)fn;
  void* scp = nullptr;
  cudaGetSymbolAddress(&scp, g_scratch);
  Maps tm;
  { const cuuint64_t d[3] = {640, 1024, 2}, s[2] = {2560, 1280}; const cuuint32_t b[3] = {64, 128, 1}; make_map(enc, &tm.x, x, d, s, b, CU_TENSOR_MAP_SWIZZLE_128B, PROMOX); }
  { const cuuint64_t d[3] = {640, 640, 3}, s[2] = {3840, 1280}; const cuuint32_t b[3] = {64, 16, 3}; make_map(enc, &tm.w, wqkv, d, s, b, CU_TENSOR_MAP_SWIZZLE_128B); }
  { const cuuint64_t d[3] = {640, 640, 3}, s[2] = {3840, 1280}; const cuuint32_t b[3] = {16, 16, 3}; make_map(enc, &tm.wr, wqkv, d, s, b, CU_TENSOR_MAP_SWIZZLE_32B); }
  { const cuuint64_t d[3] = {640, 640, 3}, s[2] = {3840, 1280}; const cuuint32_t b[3] = {16, 16, 1}; make_map(enc, &tm.wv, wqkv, d, s, b, CU_TENSOR_MAP_SWIZZLE_32B); }
  { const cuuint64_t d[3] = {32, 640, 20}, s[2] = {1280, 64}; const cuuint32_t b[3] = {32, 80, 2}; make_map(enc, &tm.wo, wo, d, s, b, CU_TENSOR_MAP_SWIZZLE_64B); }
  { const cuuint64_t d[3] = {640, 640, 1}, s[2] = {1280, 819200}; const cuuint32_t b[3] = {16, 80, 1}; make_map(enc, &tm.wor, wo, d, s, b, CU_TENSOR_MAP_SWIZZLE_64B); }
  { const cuuint64_t d[3] = {1536, 640, 1}, s[2] = {3072, 1966080}; const cuuint32_t b[3] = {32, 128, 1};
    make_map(enc, &tm.gate, d_in[5], d, s, b, CU_TENSOR_MAP_SWIZZLE_64B); make_map(enc, &tm.up, d_in[6], d, s, b, CU_TENSOR_MAP_SWIZZLE_64B); }
  { const cuuint64_t d[3] = {640, 1536, 1}, s[2] = {1280, 1966080}; const cuuint32_t b[3] = {8, 128, 1}; make_map(enc, &tm.down, d_in[7], d, s, b, CU_TENSOR_MAP_SWIZZLE_NONE); }
  cudaFuncSetAttribute(fused_kernel, cudaFuncAttributeMaxDynamicSharedMemorySize, SMEM_BYTES);
  fused_kernel<<<128, 512, SMEM_BYTES, cudaStreamPerThread>>>(x, wqkv, wo, (const __nv_bfloat16*)d_in[4], (const __nv_bfloat16*)d_in[5],
                                                              (const __nv_bfloat16*)d_in[6], (const __nv_bfloat16*)d_in[7], (__nv_bfloat16*)d_out, (Scratch*)scp, tm);
}
```
